```python
import torch

def _softmax(x, axis=-1):
    return torch.softmax(x, dim=axis)
def _gelu(x):
    return torch.nn.functional.gelu(x, approximate="tanh")
def _silu(x):
    return torch.nn.functional.silu(x)
def _sigmoid(x):
    return torch.sigmoid(x)
def _layernorm(x, axis=-1, eps=1e-5):
    m = x.mean(dim=axis, keepdim=True)
    v = x.var(dim=axis, keepdim=True, unbiased=False)
    return (x - m) / torch.sqrt(v + eps)
def _scatter_add(tgt, idx, src, axis=0):
    return tgt.clone().index_add_(axis, idx, src)
def _segment_sum(src, seg, n):
    out = torch.zeros((n,) + src.shape[1:], dtype=src.dtype)
    return out.index_add_(0, seg, src)
def _pad(x, pw):
    flat = tuple(v for pair in reversed(pw) for v in pair)
    return torch.nn.functional.pad(x, flat)

kernel_name = 'standalone__seq2seq_rnn_t_joint__speech'

def setup_inputs():

    _w = (lambda a: (lambda t: t.to(torch.bfloat16) if t.is_floating_point() else t)(torch.as_tensor(a)))
    B, T, D, K = 2, 16000, 256, 31
    U = 8
    sc = (1.0 / (K * D)) ** 0.5
    sd = (1.0 / D) ** 0.5
    return {
        "x": _w((lambda *s: torch.randn(*s, dtype=torch.bfloat16) * 0.2)(B, T, D) * 0.5),
        "w1": _w((lambda *s: torch.randn(*s, dtype=torch.bfloat16) * 3.2)(K, D, D) * sc),
        "w2": _w((lambda *s: torch.randn(*s, dtype=torch.bfloat16) * 3.2)(K, D, D) * sc),
        "g": _w((lambda *s: torch.randn(*s, dtype=torch.bfloat16) * 3.2)(B, U, D) * 0.5),
        "w_f": _w((lambda *s: torch.randn(*s, dtype=torch.bfloat16) * 3.2)(D, D) * sd),
        "w_g": _w((lambda *s: torch.randn(*s, dtype=torch.bfloat16) * 3.2)(D, D) * sd),
        "w_o": _w((lambda *s: torch.randn(*s, dtype=torch.bfloat16) * 3.2)(D, D) * sd),
    }

def reference(x, w1, w2, g, w_f, w_g, w_o):
    B, T, D = x.shape
    K = w1.shape[0]
    pad = K // 2
    xp = _pad(x, ((0,0),(pad,pad),(0,0)))
    h = torch.zeros_like(x)
    for i in range(K):
        h = h + torch.einsum("btc,cd->btd", xp[:, i:i+T, :], w1[i])
    h = _gelu(h)[:, ::2, :]
    T1 = h.shape[1]
    hp = _pad(h, ((0,0),(pad,pad),(0,0)))
    f = torch.zeros_like(h)
    for i in range(K):
        f = f + torch.einsum("btc,cd->btd", hp[:, i:i+T1, :], w2[i])
    f = _gelu(f)[:, ::2, :]
    fe = torch.einsum("btd,de->bte", f, w_f)
    ge = torch.einsum("bud,de->bue", g, w_g)
    j = torch.tanh(fe[:, :, None, :] + ge[:, None, :, :])
    return torch.einsum("btud,dv->btuv", j, w_o)
```

```cpp
#include <cuda_runtime.h>
#include <cuda_bf16.h>
#include <cuda.h>
#include <stdint.h>
#include <string.h>
#include <type_traits>

#define ALIAS 1
#define W_SHIFT 1
namespace {

constexpr int NB1 = 168;
constexpr int NB2 = 84;

__device__ __align__(1024) __nv_bfloat16 g_X1[8 * 64 * 2 * NB1 * 64];
__device__ __align__(1024) __nv_bfloat16 g_W2[8 * 64 * 4 * 64 * 64];
__device__ __align__(1024) __nv_bfloat16 g_Y1[2 * NB1 * 4 * 64 * 64];
__device__ __align__(1024) __nv_bfloat16 g_X2[8 * 64 * 2 * NB2 * 64];
__device__ __align__(1024) __nv_bfloat16 g_Y2[2 * NB2 * 4 * 64 * 64];
__device__ __align__(1024) float g_ge[16 * 256];

__device__ __forceinline__ uint32_t s2u(const void* p) { return (uint32_t)__cvta_generic_to_shared(p); }
__device__ __forceinline__ void mbar_init(uint32_t b, int c) {
  asm volatile("mbarrier.init.shared::cta.b64 [%0], %1;" ::"r"(b), "r"(c) : "memory");
}
__device__ __forceinline__ void mbar_expect(uint32_t b, int bytes) {
  asm volatile("mbarrier.arrive.expect_tx.shared::cta.b64 _, [%0], %1;" ::"r"(b), "r"(bytes) : "memory");
}
__device__ __forceinline__ void mbar_arrive(uint32_t b) {
  asm volatile("mbarrier.arrive.shared::cta.b64 _, [%0];" ::"r"(b) : "memory");
}
__device__ __forceinline__ void mbar_arrive_cta(uint32_t b, uint32_t cta) {
  asm volatile("{\n.reg .b32 r;\nmapa.shared::cluster.u32 r, %0, %1;\nmbarrier.arrive.shared::cluster.b64 _, [r];\n}" ::"r"(b), "r"(cta) : "memory");
}
__device__ __forceinline__ void mbar_wait(uint32_t b, int ph) {
  asm volatile(
      "{\n.reg .pred p;\n.reg .u32 n;\n"
      "mov.u32 n, 0;\n"
      "MBW_LOOP:\n"
      "mbarrier.try_wait.parity.shared::cta.b64 p, [%0], %1;\n"
      "@p bra MBW_DONE;\n"
      "add.u32 n, n, 1;\n"
      "setp.lt.u32 p, n, 1048576;\n"
      "@p bra MBW_LOOP;\n"
      "MBW_DONE:\n}" ::"r"(b), "r"(ph) : "memory");
}
__device__ __forceinline__ void fence_bar_init() { asm volatile("fence.mbarrier_init.release.cluster;" ::: "memory"); }
__device__ __forceinline__ void fence_async() { asm volatile("fence.proxy.async.shared::cta;" ::: "memory"); }
__device__ __forceinline__ void bar_sync(int id, int n) { asm volatile("bar.sync %0, %1;" ::"r"(id), "r"(n) : "memory"); }
__device__ __forceinline__ void bar_arrive(int id, int n) { asm volatile("bar.arrive %0, %1;" ::"r"(id), "r"(n) : "memory"); }
__device__ __forceinline__ void pdl_wait() { asm volatile("griddepcontrol.wait;" ::: "memory"); }
__device__ __forceinline__ void pdl_launch() { asm volatile("griddepcontrol.launch_dependents;" ::: "memory"); }
__device__ __forceinline__ void prefetch_map(const CUtensorMap* m) {
  asm volatile("prefetch.tensormap [%0];" ::"l"(m) : "memory");
}
template <int P> __device__ __forceinline__ uint64_t policy() {
  uint64_t p;
  asm("createpolicy.fractional.L2::evict_first.b64 %0, 1.0;" : "=l"(p));
  return p;
}
template <int P> __device__ __forceinline__ void tma_ld3(uint32_t dst, const CUtensorMap* m, uint32_t bar, int c0, int c1, int c2) {
  if constexpr (P == 0)
    asm volatile("cp.async.bulk.tensor.3d.shared::cluster.global.mbarrier::complete_tx::bytes [%0], [%1, {%3, %4, %5}], [%2];"
                 ::"r"(dst), "l"(m), "r"(bar), "r"(c0), "r"(c1), "r"(c2) : "memory");
  else
    asm volatile("cp.async.bulk.tensor.3d.shared::cluster.global.mbarrier::complete_tx::bytes.L2::cache_hint [%0], [%1, {%3, %4, %5}], [%2], %6;"
                 ::"r"(dst), "l"(m), "r"(bar), "r"(c0), "r"(c1), "r"(c2), "l"(policy<P>()) : "memory");
}
template <int P> __device__ __forceinline__ void tma_ld3mc(uint32_t dst, const CUtensorMap* m, uint32_t bar, int c0, int c1, int c2) {
  if constexpr (P == 0)
    asm volatile("cp.async.bulk.tensor.3d.shared::cluster.global.mbarrier::complete_tx::bytes.multicast::cluster [%0], [%1, {%3, %4, %5}], [%2], %6;"
                 ::"r"(dst), "l"(m), "r"(bar), "r"(c0), "r"(c1), "r"(c2), "h"((uint16_t)3) : "memory");
  else
    asm volatile("cp.async.bulk.tensor.3d.shared::cluster.global.mbarrier::complete_tx::bytes.multicast::cluster.L2::cache_hint [%0], [%1, {%3, %4, %5}], [%2], %6, %7;"
                 ::"r"(dst), "l"(m), "r"(bar), "r"(c0), "r"(c1), "r"(c2), "h"((uint16_t)3), "l"(policy<P>()) : "memory");
}
template <int P> __device__ __forceinline__ void tma_ld4(uint32_t dst, const CUtensorMap* m, uint32_t bar, int c0, int c1, int c2, int c3) {
  if constexpr (P == 0)
    asm volatile("cp.async.bulk.tensor.4d.shared::cluster.global.mbarrier::complete_tx::bytes [%0], [%1, {%3, %4, %5, %6}], [%2];"
                 ::"r"(dst), "l"(m), "r"(bar), "r"(c0), "r"(c1), "r"(c2), "r"(c3) : "memory");
  else
    asm volatile("cp.async.bulk.tensor.4d.shared::cluster.global.mbarrier::complete_tx::bytes.L2::cache_hint [%0], [%1, {%3, %4, %5, %6}], [%2], %7;"
                 ::"r"(dst), "l"(m), "r"(bar), "r"(c0), "r"(c1), "r"(c2), "r"(c3), "l"(policy<P>()) : "memory");
}
template <int P> __device__ __forceinline__ void tma_ld4mc(uint32_t dst, const CUtensorMap* m, uint32_t bar, int c0, int c1, int c2, int c3) {
  if constexpr (P == 0)
    asm volatile("cp.async.bulk.tensor.4d.shared::cluster.global.mbarrier::complete_tx::bytes.multicast::cluster [%0], [%1, {%3, %4, %5, %6}], [%2], %7;"
                 ::"r"(dst), "l"(m), "r"(bar), "r"(c0), "r"(c1), "r"(c2), "r"(c3), "h"((uint16_t)3) : "memory");
  else
    asm volatile("cp.async.bulk.tensor.4d.shared::cluster.global.mbarrier::complete_tx::bytes.multicast::cluster.L2::cache_hint [%0], [%1, {%3, %4, %5, %6}], [%2], %7, %8;"
                 ::"r"(dst), "l"(m), "r"(bar), "r"(c0), "r"(c1), "r"(c2), "r"(c3), "h"((uint16_t)3), "l"(policy<P>()) : "memory");
}
template <int P> __device__ __forceinline__ void tma_ld5(uint32_t dst, const CUtensorMap* m, uint32_t bar, int c0, int c1, int c2, int c3, int c4) {
  if constexpr (P == 0)
    asm volatile("cp.async.bulk.tensor.5d.shared::cluster.global.mbarrier::complete_tx::bytes [%0], [%1, {%3, %4, %5, %6, %7}], [%2];"
                 ::"r"(dst), "l"(m), "r"(bar), "r"(c0), "r"(c1), "r"(c2), "r"(c3), "r"(c4) : "memory");
  else
    asm volatile("cp.async.bulk.tensor.5d.shared::cluster.global.mbarrier::complete_tx::bytes.L2::cache_hint [%0], [%1, {%3, %4, %5, %6, %7}], [%2], %8;"
                 ::"r"(dst), "l"(m), "r"(bar), "r"(c0), "r"(c1), "r"(c2), "r"(c3), "r"(c4), "l"(policy<P>()) : "memory");
}
template <int P> __device__ __forceinline__ void tma_st3(const CUtensorMap* m, uint32_t src, int c0, int c1, int c2) {
  if constexpr (P == 0)
    asm volatile("cp.async.bulk.tensor.3d.global.shared::cta.bulk_group [%0, {%2, %3, %4}], [%1];" ::"l"(m), "r"(src), "r"(c0), "r"(c1), "r"(c2) : "memory");
  else
    asm volatile("cp.async.bulk.tensor.3d.global.shared::cta.bulk_group.L2::cache_hint [%0, {%2, %3, %4}], [%1], %5;" ::"l"(m), "r"(src), "r"(c0), "r"(c1), "r"(c2), "l"(policy<P>()) : "memory");
}
template <int P> __device__ __forceinline__ void tma_st4(const CUtensorMap* m, uint32_t src, int c0, int c1, int c2, int c3) {
  if constexpr (P == 0)
    asm volatile("cp.async.bulk.tensor.4d.global.shared::cta.bulk_group [%0, {%2, %3, %4, %5}], [%1];" ::"l"(m), "r"(src), "r"(c0), "r"(c1), "r"(c2), "r"(c3) : "memory");
  else
    asm volatile("cp.async.bulk.tensor.4d.global.shared::cta.bulk_group.L2::cache_hint [%0, {%2, %3, %4, %5}], [%1], %6;" ::"l"(m), "r"(src), "r"(c0), "r"(c1), "r"(c2), "r"(c3), "l"(policy<P>()) : "memory");
}
template <int P> __device__ __forceinline__ void tma_st5(const CUtensorMap* m, uint32_t src, int c0, int c1, int c2, int c3, int c4) {
  if constexpr (P == 0)
    asm volatile("cp.async.bulk.tensor.5d.global.shared::cta.bulk_group [%0, {%2, %3, %4, %5, %6}], [%1];" ::"l"(m), "r"(src), "r"(c0), "r"(c1), "r"(c2), "r"(c3), "r"(c4) : "memory");
  else
    asm volatile("cp.async.bulk.tensor.5d.global.shared::cta.bulk_group.L2::cache_hint [%0, {%2, %3, %4, %5, %6}], [%1], %7;" ::"l"(m), "r"(src), "r"(c0), "r"(c1), "r"(c2), "r"(c3), "r"(c4), "l"(policy<P>()) : "memory");
}
__device__ __forceinline__ void bulk_commit() { asm volatile("cp.async.bulk.commit_group;" ::: "memory"); }
template <int N> __device__ __forceinline__ void bulk_wait_read() { asm volatile("cp.async.bulk.wait_group.read %0;" ::"n"(N) : "memory"); }
__device__ __forceinline__ void wg_fence() { asm volatile("wgmma.fence.sync.aligned;" ::: "memory"); }
__device__ __forceinline__ void wg_commit() { asm volatile("wgmma.commit_group.sync.aligned;" ::: "memory"); }
template <int N> __device__ __forceinline__ void wg_wait() { asm volatile("wgmma.wait_group.sync.aligned %0;" ::"n"(N) : "memory"); }
template <int R> __device__ __forceinline__ void reg_fence(float (&d)[R]) {
#pragma unroll
  for (int i = 0; i < R; i++) asm volatile("" : "+f"(d[i])::"memory");
}
template <int R> __device__ __forceinline__ void reg_fence(uint32_t (&d)[R]) {
#pragma unroll
  for (int i = 0; i < R; i++) asm volatile("" : "+r"(d[i])::"memory");
}
__device__ __forceinline__ void stsm4(uint32_t a, uint32_t r0, uint32_t r1, uint32_t r2, uint32_t r3) {
  asm volatile("stmatrix.sync.aligned.m8n8.x4.shared.b16 [%0], {%1, %2, %3, %4};" ::"r"(a), "r"(r0), "r"(r1), "r"(r2), "r"(r3) : "memory");
}
__device__ __forceinline__ void stsm4t(uint32_t a, uint32_t r0, uint32_t r1, uint32_t r2, uint32_t r3) {
  asm volatile("stmatrix.sync.aligned.m8n8.x4.trans.shared.b16 [%0], {%1, %2, %3, %4};" ::"r"(a), "r"(r0), "r"(r1), "r"(r2), "r"(r3) : "memory");
}
__device__ __forceinline__ void ldsm4(uint32_t a, uint32_t& r0, uint32_t& r1, uint32_t& r2, uint32_t& r3) {
  asm volatile("ldmatrix.sync.aligned.m8n8.x4.shared.b16 {%0, %1, %2, %3}, [%4];" : "=r"(r0), "=r"(r1), "=r"(r2), "=r"(r3) : "r"(a) : "memory");
}
__device__ __forceinline__ void ldsm4t(uint32_t a, uint32_t& r0, uint32_t& r1, uint32_t& r2, uint32_t& r3) {
  asm volatile("ldmatrix.sync.aligned.m8n8.x4.trans.shared.b16 {%0, %1, %2, %3}, [%4];" : "=r"(r0), "=r"(r1), "=r"(r2), "=r"(r3) : "r"(a) : "memory");
}
__device__ __forceinline__ void ldg128(const uint4* p, uint32_t& a, uint32_t& b, uint32_t& c, uint32_t& d) {
  asm volatile("ld.global.nc.v4.u32 {%0, %1, %2, %3}, [%4];" : "=r"(a), "=r"(b), "=r"(c), "=r"(d) : "l"(p));
}
__device__ __forceinline__ uint32_t pack2(float lo, float hi) {
  uint32_t r;
  asm("cvt.rn.bf16x2.f32 %0, %1, %2;" : "=r"(r) : "f"(hi), "f"(lo));
  return r;
}
__device__ __forceinline__ float tanh_f32(float x) {
  float y;
  asm("tanh.approx.f32 %0, %1;" : "=f"(y) : "f"(x));
  return y;
}
__device__ __forceinline__ float gelu(float hx) {
  const float u = hx * fmaf(hx * hx, 8.0f * 0.044715f * 0.7978845608028654f, 2.0f * 0.7978845608028654f);
  return fmaf(hx, tanh_f32(u), hx);
}
__device__ __forceinline__ uint64_t mk_desc4(uint32_t addr4, uint32_t lbo, uint32_t sbo, uint32_t swz) {
  const uint32_t lo = addr4 + ((lbo >> 4) << 16), hi = (sbo >> 4) | (swz << 30);
  uint64_t d;
  asm("mov.b64 %0, {%1, %2};" : "=l"(d) : "r"(lo), "r"(hi));
  return d;
}
#define mk_desc(base, off, lbo, sbo, swz) mk_desc4((((base) & 0x3FFFF) >> 4) + ((off) >> 4), lbo, sbo, swz)

template <int SA, int SB, int TA, int TB>
__device__ __forceinline__ void wgmma_ss_32(float (&d)[16], uint64_t da, uint64_t db, int sd) {
  asm volatile("{\n.reg .pred p;\nsetp.ne.b32 p, %18, 0;\n"
      "wgmma.mma_async.sync.aligned.m64n32k16.f32.bf16.bf16 {"
      "%0, %1, %2, %3, %4, %5, %6, %7, %8, %9, %10, %11, %12, %13, %14, %15"
      "}, %16, %17, p, %19, %20, %21, %22;\n}\n"
      : "+f"(d[0]), "+f"(d[1]), "+f"(d[2]), "+f"(d[3]), "+f"(d[4]), "+f"(d[5]), "+f"(d[6]), "+f"(d[7]), "+f"(d[8]),
        "+f"(d[9]), "+f"(d[10]), "+f"(d[11]), "+f"(d[12]), "+f"(d[13]), "+f"(d[14]), "+f"(d[15])
      : "l"(da), "l"(db), "r"(sd), "n"(SA), "n"(SB), "n"(TA), "n"(TB));
}
template <int SA, int SB, int TA, int TB>
__device__ __forceinline__ void wgmma_ss_48(float (&d)[24], uint64_t da, uint64_t db, int sd) {
  asm volatile("{\n.reg .pred p;\nsetp.ne.b32 p, %26, 0;\n"
      "wgmma.mma_async.sync.aligned.m64n48k16.f32.bf16.bf16 {"
      "%0, %1, %2, %3, %4, %5, %6, %7, %8, %9, %10, %11, %12, %13, %14, %15, %16, %17, %18, %19, %20, %21, %22, %23"
      "}, %24, %25, p, %27, %28, %29, %30;\n}\n"
      : "+f"(d[0]), "+f"(d[1]), "+f"(d[2]), "+f"(d[3]), "+f"(d[4]), "+f"(d[5]), "+f"(d[6]), "+f"(d[7]), "+f"(d[8]),
        "+f"(d[9]), "+f"(d[10]), "+f"(d[11]), "+f"(d[12]), "+f"(d[13]), "+f"(d[14]), "+f"(d[15]), "+f"(d[16]),
        "+f"(d[17]), "+f"(d[18]), "+f"(d[19]), "+f"(d[20]), "+f"(d[21]), "+f"(d[22]), "+f"(d[23])
      : "l"(da), "l"(db), "r"(sd), "n"(SA), "n"(SB), "n"(TA), "n"(TB));
}
template <int SA, int SB, int TA, int TB>
__device__ __forceinline__ void wgmma_ss_128(float (&d)[64], uint64_t da, uint64_t db, int sd) {
  asm volatile("{\n.reg .pred p;\nsetp.ne.b32 p, %66, 0;\n"
      "wgmma.mma_async.sync.aligned.m64n128k16.f32.bf16.bf16 {"
      "%0, %1, %2, %3, %4, %5, %6, %7, %8, %9, %10, %11, %12, %13, %14, %15, %16, %17, %18, %19, %20, %21, %22, %23, "
      "%24, %25, %26, %27, %28, %29, %30, %31, %32, %33, %34, %35, %36, %37, %38, %39, %40, %41, %42, %43, %44, %45, "
      "%46, %47, %48, %49, %50, %51, %52, %53, %54, %55, %56, %57, %58, %59, %60, %61, %62, %63"
      "}, %64, %65, p, %67, %68, %69, %70;\n}\n"
      : "+f"(d[0]), "+f"(d[1]), "+f"(d[2]), "+f"(d[3]), "+f"(d[4]), "+f"(d[5]), "+f"(d[6]), "+f"(d[7]), "+f"(d[8]),
        "+f"(d[9]), "+f"(d[10]), "+f"(d[11]), "+f"(d[12]), "+f"(d[13]), "+f"(d[14]), "+f"(d[15]), "+f"(d[16]),
        "+f"(d[17]), "+f"(d[18]), "+f"(d[19]), "+f"(d[20]), "+f"(d[21]), "+f"(d[22]), "+f"(d[23]), "+f"(d[24]),
        "+f"(d[25]), "+f"(d[26]), "+f"(d[27]), "+f"(d[28]), "+f"(d[29]), "+f"(d[30]), "+f"(d[31]), "+f"(d[32]),
        "+f"(d[33]), "+f"(d[34]), "+f"(d[35]), "+f"(d[36]), "+f"(d[37]), "+f"(d[38]), "+f"(d[39]), "+f"(d[40]),
        "+f"(d[41]), "+f"(d[42]), "+f"(d[43]), "+f"(d[44]), "+f"(d[45]), "+f"(d[46]), "+f"(d[47]), "+f"(d[48]),
        "+f"(d[49]), "+f"(d[50]), "+f"(d[51]), "+f"(d[52]), "+f"(d[53]), "+f"(d[54]), "+f"(d[55]), "+f"(d[56]),
        "+f"(d[57]), "+f"(d[58]), "+f"(d[59]), "+f"(d[60]), "+f"(d[61]), "+f"(d[62]), "+f"(d[63])
      : "l"(da), "l"(db), "r"(sd), "n"(SA), "n"(SB), "n"(TA), "n"(TB));
}
template <int SA, int SB, int TA, int TB>
__device__ __forceinline__ void wgmma_ss_168(float (&d)[84], uint64_t da, uint64_t db, int sd) {
  asm volatile("{\n.reg .pred p;\nsetp.ne.b32 p, %86, 0;\n"
      "wgmma.mma_async.sync.aligned.m64n168k16.f32.bf16.bf16 {"
      "%0, %1, %2, %3, %4, %5, %6, %7, %8, %9, %10, %11, %12, %13, %14, %15, %16, %17, %18, %19, %20, %21, %22, %23, "
      "%24, %25, %26, %27, %28, %29, %30, %31, %32, %33, %34, %35, %36, %37, %38, %39, %40, %41, %42, %43, %44, %45, "
      "%46, %47, %48, %49, %50, %51, %52, %53, %54, %55, %56, %57, %58, %59, %60, %61, %62, %63, %64, %65, %66, %67, "
      "%68, %69, %70, %71, %72, %73, %74, %75, %76, %77, %78, %79, %80, %81, %82, %83"
      "}, %84, %85, p, %87, %88, %89, %90;\n}\n"
      : "+f"(d[0]), "+f"(d[1]), "+f"(d[2]), "+f"(d[3]), "+f"(d[4]), "+f"(d[5]), "+f"(d[6]), "+f"(d[7]), "+f"(d[8]),
        "+f"(d[9]), "+f"(d[10]), "+f"(d[11]), "+f"(d[12]), "+f"(d[13]), "+f"(d[14]), "+f"(d[15]), "+f"(d[16]),
        "+f"(d[17]), "+f"(d[18]), "+f"(d[19]), "+f"(d[20]), "+f"(d[21]), "+f"(d[22]), "+f"(d[23]), "+f"(d[24]),
        "+f"(d[25]), "+f"(d[26]), "+f"(d[27]), "+f"(d[28]), "+f"(d[29]), "+f"(d[30]), "+f"(d[31]), "+f"(d[32]),
        "+f"(d[33]), "+f"(d[34]), "+f"(d[35]), "+f"(d[36]), "+f"(d[37]), "+f"(d[38]), "+f"(d[39]), "+f"(d[40]),
        "+f"(d[41]), "+f"(d[42]), "+f"(d[43]), "+f"(d[44]), "+f"(d[45]), "+f"(d[46]), "+f"(d[47]), "+f"(d[48]),
        "+f"(d[49]), "+f"(d[50]), "+f"(d[51]), "+f"(d[52]), "+f"(d[53]), "+f"(d[54]), "+f"(d[55]), "+f"(d[56]),
        "+f"(d[57]), "+f"(d[58]), "+f"(d[59]), "+f"(d[60]), "+f"(d[61]), "+f"(d[62]), "+f"(d[63]), "+f"(d[64]),
        "+f"(d[65]), "+f"(d[66]), "+f"(d[67]), "+f"(d[68]), "+f"(d[69]), "+f"(d[70]), "+f"(d[71]), "+f"(d[72]),
        "+f"(d[73]), "+f"(d[74]), "+f"(d[75]), "+f"(d[76]), "+f"(d[77]), "+f"(d[78]), "+f"(d[79]), "+f"(d[80]),
        "+f"(d[81]), "+f"(d[82]), "+f"(d[83])
      : "l"(da), "l"(db), "r"(sd), "n"(SA), "n"(SB), "n"(TA), "n"(TB));
}
template <int SA, int SB, int TB>
__device__ __forceinline__ void wgmma_rs_32(float (&d)[16], uint32_t a0, uint32_t a1, uint32_t a2, uint32_t a3, uint64_t db, int sd) {
  asm volatile("{\n.reg .pred p;\nsetp.ne.b32 p, %21, 0;\n"
      "wgmma.mma_async.sync.aligned.m64n32k16.f32.bf16.bf16 {"
      "%0, %1, %2, %3, %4, %5, %6, %7, %8, %9, %10, %11, %12, %13, %14, %15"
      "}, {%16, %17, %18, %19}, %20, p, %22, %23, %24;\n}\n"
      : "+f"(d[0]), "+f"(d[1]), "+f"(d[2]), "+f"(d[3]), "+f"(d[4]), "+f"(d[5]), "+f"(d[6]), "+f"(d[7]), "+f"(d[8]),
        "+f"(d[9]), "+f"(d[10]), "+f"(d[11]), "+f"(d[12]), "+f"(d[13]), "+f"(d[14]), "+f"(d[15])
      : "r"(a0), "r"(a1), "r"(a2), "r"(a3), "l"(db), "r"(sd), "n"(SA), "n"(SB), "n"(TB));
}
template <int SA, int SB, int TB>
__device__ __forceinline__ void wgmma_rs_64(float (&d)[32], uint32_t a0, uint32_t a1, uint32_t a2, uint32_t a3, uint64_t db, int sd) {
  asm volatile("{\n.reg .pred p;\nsetp.ne.b32 p, %37, 0;\n"
      "wgmma.mma_async.sync.aligned.m64n64k16.f32.bf16.bf16 {"
      "%0, %1, %2, %3, %4, %5, %6, %7, %8, %9, %10, %11, %12, %13, %14, %15, %16, %17, %18, %19, %20, %21, %22, %23, "
      "%24, %25, %26, %27, %28, %29, %30, %31"
      "}, {%32, %33, %34, %35}, %36, p, %38, %39, %40;\n}\n"
      : "+f"(d[0]), "+f"(d[1]), "+f"(d[2]), "+f"(d[3]), "+f"(d[4]), "+f"(d[5]), "+f"(d[6]), "+f"(d[7]), "+f"(d[8]),
        "+f"(d[9]), "+f"(d[10]), "+f"(d[11]), "+f"(d[12]), "+f"(d[13]), "+f"(d[14]), "+f"(d[15]), "+f"(d[16]),
        "+f"(d[17]), "+f"(d[18]), "+f"(d[19]), "+f"(d[20]), "+f"(d[21]), "+f"(d[22]), "+f"(d[23]), "+f"(d[24]),
        "+f"(d[25]), "+f"(d[26]), "+f"(d[27]), "+f"(d[28]), "+f"(d[29]), "+f"(d[30]), "+f"(d[31])
      : "r"(a0), "r"(a1), "r"(a2), "r"(a3), "l"(db), "r"(sd), "n"(SA), "n"(SB), "n"(TB));
}
template <int SA, int SB, int TB>
__device__ __forceinline__ void wgmma_rs_128(float (&d)[64], uint32_t a0, uint32_t a1, uint32_t a2, uint32_t a3, uint64_t db, int sd) {
  asm volatile("{\n.reg .pred p;\nsetp.ne.b32 p, %69, 0;\n"
      "wgmma.mma_async.sync.aligned.m64n128k16.f32.bf16.bf16 {"
      "%0, %1, %2, %3, %4, %5, %6, %7, %8, %9, %10, %11, %12, %13, %14, %15, %16, %17, %18, %19, %20, %21, %22, %23, "
      "%24, %25, %26, %27, %28, %29, %30, %31, %32, %33, %34, %35, %36, %37, %38, %39, %40, %41, %42, %43, %44, %45, "
      "%46, %47, %48, %49, %50, %51, %52, %53, %54, %55, %56, %57, %58, %59, %60, %61, %62, %63"
      "}, {%64, %65, %66, %67}, %68, p, %70, %71, %72;\n}\n"
      : "+f"(d[0]), "+f"(d[1]), "+f"(d[2]), "+f"(d[3]), "+f"(d[4]), "+f"(d[5]), "+f"(d[6]), "+f"(d[7]), "+f"(d[8]),
        "+f"(d[9]), "+f"(d[10]), "+f"(d[11]), "+f"(d[12]), "+f"(d[13]), "+f"(d[14]), "+f"(d[15]), "+f"(d[16]),
        "+f"(d[17]), "+f"(d[18]), "+f"(d[19]), "+f"(d[20]), "+f"(d[21]), "+f"(d[22]), "+f"(d[23]), "+f"(d[24]),
        "+f"(d[25]), "+f"(d[26]), "+f"(d[27]), "+f"(d[28]), "+f"(d[29]), "+f"(d[30]), "+f"(d[31]), "+f"(d[32]),
        "+f"(d[33]), "+f"(d[34]), "+f"(d[35]), "+f"(d[36]), "+f"(d[37]), "+f"(d[38]), "+f"(d[39]), "+f"(d[40]),
        "+f"(d[41]), "+f"(d[42]), "+f"(d[43]), "+f"(d[44]), "+f"(d[45]), "+f"(d[46]), "+f"(d[47]), "+f"(d[48]),
        "+f"(d[49]), "+f"(d[50]), "+f"(d[51]), "+f"(d[52]), "+f"(d[53]), "+f"(d[54]), "+f"(d[55]), "+f"(d[56]),
        "+f"(d[57]), "+f"(d[58]), "+f"(d[59]), "+f"(d[60]), "+f"(d[61]), "+f"(d[62]), "+f"(d[63])
      : "r"(a0), "r"(a1), "r"(a2), "r"(a3), "l"(db), "r"(sd), "n"(SA), "n"(SB), "n"(TB));
}
template <int SA, int SB, int TB>
__device__ __forceinline__ void wgmma_rs_168(float (&d)[84], uint32_t a0, uint32_t a1, uint32_t a2, uint32_t a3, uint64_t db, int sd) {
  asm volatile("{\n.reg .pred p;\nsetp.ne.b32 p, %89, 0;\n"
      "wgmma.mma_async.sync.aligned.m64n168k16.f32.bf16.bf16 {"
      "%0, %1, %2, %3, %4, %5, %6, %7, %8, %9, %10, %11, %12, %13, %14, %15, %16, %17, %18, %19, %20, %21, %22, %23, "
      "%24, %25, %26, %27, %28, %29, %30, %31, %32, %33, %34, %35, %36, %37, %38, %39, %40, %41, %42, %43, %44, %45, "
      "%46, %47, %48, %49, %50, %51, %52, %53, %54, %55, %56, %57, %58, %59, %60, %61, %62, %63, %64, %65, %66, %67, "
      "%68, %69, %70, %71, %72, %73, %74, %75, %76, %77, %78, %79, %80, %81, %82, %83"
      "}, {%84, %85, %86, %87}, %88, p, %90, %91, %92;\n}\n"
      : "+f"(d[0]), "+f"(d[1]), "+f"(d[2]), "+f"(d[3]), "+f"(d[4]), "+f"(d[5]), "+f"(d[6]), "+f"(d[7]), "+f"(d[8]),
        "+f"(d[9]), "+f"(d[10]), "+f"(d[11]), "+f"(d[12]), "+f"(d[13]), "+f"(d[14]), "+f"(d[15]), "+f"(d[16]),
        "+f"(d[17]), "+f"(d[18]), "+f"(d[19]), "+f"(d[20]), "+f"(d[21]), "+f"(d[22]), "+f"(d[23]), "+f"(d[24]),
        "+f"(d[25]), "+f"(d[26]), "+f"(d[27]), "+f"(d[28]), "+f"(d[29]), "+f"(d[30]), "+f"(d[31]), "+f"(d[32]),
        "+f"(d[33]), "+f"(d[34]), "+f"(d[35]), "+f"(d[36]), "+f"(d[37]), "+f"(d[38]), "+f"(d[39]), "+f"(d[40]),
        "+f"(d[41]), "+f"(d[42]), "+f"(d[43]), "+f"(d[44]), "+f"(d[45]), "+f"(d[46]), "+f"(d[47]), "+f"(d[48]),
        "+f"(d[49]), "+f"(d[50]), "+f"(d[51]), "+f"(d[52]), "+f"(d[53]), "+f"(d[54]), "+f"(d[55]), "+f"(d[56]),
        "+f"(d[57]), "+f"(d[58]), "+f"(d[59]), "+f"(d[60]), "+f"(d[61]), "+f"(d[62]), "+f"(d[63]), "+f"(d[64]),
        "+f"(d[65]), "+f"(d[66]), "+f"(d[67]), "+f"(d[68]), "+f"(d[69]), "+f"(d[70]), "+f"(d[71]), "+f"(d[72]),
        "+f"(d[73]), "+f"(d[74]), "+f"(d[75]), "+f"(d[76]), "+f"(d[77]), "+f"(d[78]), "+f"(d[79]), "+f"(d[80]),
        "+f"(d[81]), "+f"(d[82]), "+f"(d[83])
      : "r"(a0), "r"(a1), "r"(a2), "r"(a3), "l"(db), "r"(sd), "n"(SA), "n"(SB), "n"(TB));
}
template <int SA, int SB, int TB>
__device__ __forceinline__ void wgmma_rs_256(float (&d)[128], uint32_t a0, uint32_t a1, uint32_t a2, uint32_t a3, uint64_t db, int sd) {
  asm volatile("{\n.reg .pred p;\nsetp.ne.b32 p, %133, 0;\n"
      "wgmma.mma_async.sync.aligned.m64n256k16.f32.bf16.bf16 {"
      "%0, %1, %2, %3, %4, %5, %6, %7, %8, %9, %10, %11, %12, %13, %14, %15, %16, %17, %18, %19, %20, %21, %22, %23, "
      "%24, %25, %26, %27, %28, %29, %30, %31, %32, %33, %34, %35, %36, %37, %38, %39, %40, %41, %42, %43, %44, %45, "
      "%46, %47, %48, %49, %50, %51, %52, %53, %54, %55, %56, %57, %58, %59, %60, %61, %62, %63, %64, %65, %66, %67, "
      "%68, %69, %70, %71, %72, %73, %74, %75, %76, %77, %78, %79, %80, %81, %82, %83, %84, %85, %86, %87, %88, %89, "
      "%90, %91, %92, %93, %94, %95, %96, %97, %98, %99, %100, %101, %102, %103, %104, %105, %106, %107, %108, %109, "
      "%110, %111, %112, %113, %114, %115, %116, %117, %118, %119, %120, %121, %122, %123, %124, %125, %126, %127"
      "}, {%128, %129, %130, %131}, %132, p, %134, %135, %136;\n}\n"
      : "+f"(d[0]), "+f"(d[1]), "+f"(d[2]), "+f"(d[3]), "+f"(d[4]), "+f"(d[5]), "+f"(d[6]), "+f"(d[7]), "+f"(d[8]),
        "+f"(d[9]), "+f"(d[10]), "+f"(d[11]), "+f"(d[12]), "+f"(d[13]), "+f"(d[14]), "+f"(d[15]), "+f"(d[16]),
        "+f"(d[17]), "+f"(d[18]), "+f"(d[19]), "+f"(d[20]), "+f"(d[21]), "+f"(d[22]), "+f"(d[23]), "+f"(d[24]),
        "+f"(d[25]), "+f"(d[26]), "+f"(d[27]), "+f"(d[28]), "+f"(d[29]), "+f"(d[30]), "+f"(d[31]), "+f"(d[32]),
        "+f"(d[33]), "+f"(d[34]), "+f"(d[35]), "+f"(d[36]), "+f"(d[37]), "+f"(d[38]), "+f"(d[39]), "+f"(d[40]),
        "+f"(d[41]), "+f"(d[42]), "+f"(d[43]), "+f"(d[44]), "+f"(d[45]), "+f"(d[46]), "+f"(d[47]), "+f"(d[48]),
        "+f"(d[49]), "+f"(d[50]), "+f"(d[51]), "+f"(d[52]), "+f"(d[53]), "+f"(d[54]), "+f"(d[55]), "+f"(d[56]),
        "+f"(d[57]), "+f"(d[58]), "+f"(d[59]), "+f"(d[60]), "+f"(d[61]), "+f"(d[62]), "+f"(d[63]), "+f"(d[64]),
        "+f"(d[65]), "+f"(d[66]), "+f"(d[67]), "+f"(d[68]), "+f"(d[69]), "+f"(d[70]), "+f"(d[71]), "+f"(d[72]),
        "+f"(d[73]), "+f"(d[74]), "+f"(d[75]), "+f"(d[76]), "+f"(d[77]), "+f"(d[78]), "+f"(d[79]), "+f"(d[80]),
        "+f"(d[81]), "+f"(d[82]), "+f"(d[83]), "+f"(d[84]), "+f"(d[85]), "+f"(d[86]), "+f"(d[87]), "+f"(d[88]),
        "+f"(d[89]), "+f"(d[90]), "+f"(d[91]), "+f"(d[92]), "+f"(d[93]), "+f"(d[94]), "+f"(d[95]), "+f"(d[96]),
        "+f"(d[97]), "+f"(d[98]), "+f"(d[99]), "+f"(d[100]), "+f"(d[101]), "+f"(d[102]), "+f"(d[103]), "+f"(d[104]),
        "+f"(d[105]), "+f"(d[106]), "+f"(d[107]), "+f"(d[108]), "+f"(d[109]), "+f"(d[110]), "+f"(d[111]),
        "+f"(d[112]), "+f"(d[113]), "+f"(d[114]), "+f"(d[115]), "+f"(d[116]), "+f"(d[117]), "+f"(d[118]),
        "+f"(d[119]), "+f"(d[120]), "+f"(d[121]), "+f"(d[122]), "+f"(d[123]), "+f"(d[124]), "+f"(d[125]),
        "+f"(d[126]), "+f"(d[127])
      : "r"(a0), "r"(a1), "r"(a2), "r"(a3), "l"(db), "r"(sd), "n"(SA), "n"(SB), "n"(TB));
}

__device__ const __align__(128) uint32_t c_img[3584] = {
    0x00003c80, 0x00003c80, 0x00003c80, 0x00003c80, 0x00003c80, 0x00003c80, 0x00003c80, 0x00003c80, 0x00003c80, 0x00003c80,
    0x00003c80, 0x00003c80, 0x00003c80, 0x00003c80, 0x00003c80, 0x00003c80, 0x00003c80, 0x00003c80, 0x00003c80, 0x00003c80,
    0x00003c80, 0x00003c80, 0x00003c80, 0x00003c80, 0x00003c80, 0x00003c80, 0x00003c80, 0x00003c80, 0x00003c80, 0x00003c80,
    0x00003c80, 0x00003c80, 0x3c463c22, 0x3c623bf1, 0x3c753b95, 0x3c7f3ac9, 0x3ac93c7f, 0x3b953c75, 0x3bf13c62, 0x3c223c46,
    0x3c22bc46, 0x3bf1bc62, 0x3b95bc75, 0x3ac9bc7f, 0x3c7fbac9, 0x3c75bb95, 0x3c62bbf1, 0x3c46bc22, 0xbc46bc22, 0xbc62bbf1,
    0xbc75bb95, 0xbc7fbac9, 0xbac9bc7f, 0xbb95bc75, 0xbbf1bc62, 0xbc22bc46, 0xbc223c46, 0xbbf13c62, 0xbb953c75, 0xbac93c7f,
    0xbc7f3ac9, 0xbc753b95, 0xbc623bf1, 0xbc463c22, 0xbb48bc7b, 0xbc0ebc55, 0xbc55bc0e, 0xbc7bbb48, 0xbc7b3b48, 0xbc553c0e,
    0xbc0e3c55, 0xbb483c7b, 0x3b483c7b, 0x3c0e3c55, 0x3c553c0e, 0x3c7b3b48, 0x3c7bbb48, 0x3c55bc0e, 0x3c0ebc55, 0x3b48bc7b,
    0xbb48bc7b, 0xbc0ebc55, 0xbc55bc0e, 0xbc7bbb48, 0xbc7b3b48, 0xbc553c0e, 0xbc0e3c55, 0xbb483c7b, 0x3b483c7b, 0x3c0e3c55,
    0x3c553c0e, 0x3c7b3b48, 0x3c7bbb48, 0x3c55bc0e, 0x3c0ebc55, 0x3b48bc7b, 0x3c623bf1, 0x3c7fbac9, 0x3c46bc22, 0x3b95bc75,
    0xbc753b95, 0xbc223c46, 0xbac93c7f, 0x3bf13c62, 0x3bf1bc62, 0xbac9bc7f, 0xbc22bc46, 0xbc75bb95, 0x3b953c75, 0x3c463c22,
    0x3c7f3ac9, 0x3c62bbf1, 0xbc62bbf1, 0xbc7f3ac9, 0xbc463c22, 0xbb953c75, 0x3c75bb95, 0x3c22bc46, 0x3ac9bc7f, 0xbbf1bc62,
    0xbbf13c62, 0x3ac93c7f, 0x3c223c46, 0x3c753b95, 0xbb95bc75, 0xbc46bc22, 0xbc7fbac9, 0xbc623bf1, 0x3bc43c6d, 0x3c6d3bc4,
    0x3c6dbbc4, 0x3bc4bc6d, 0xbbc4bc6d, 0xbc6dbbc4, 0xbc6d3bc4, 0xbbc43c6d, 0x3bc43c6d, 0x3c6d3bc4, 0x3c6dbbc4, 0x3bc4bc6d,
    0xbbc4bc6d, 0xbc6dbbc4, 0xbc6d3bc4, 0xbbc43c6d, 0x3bc43c6d, 0x3c6d3bc4, 0x3c6dbbc4, 0x3bc4bc6d, 0xbbc4bc6d, 0xbc6dbbc4,
    0xbc6d3bc4, 0xbbc43c6d, 0x3bc43c6d, 0x3c6d3bc4, 0x3c6dbbc4, 0x3bc4bc6d, 0xbbc4bc6d, 0xbc6dbbc4, 0xbc6d3bc4, 0xbbc43c6d,
    0x3c753b95, 0x3c46bc22, 0xbac9bc7f, 0xbc62bbf1, 0xbbf1bc62, 0xbc7fbac9, 0xbc223c46, 0x3b953c75, 0x3b95bc75, 0xbc22bc46,
    0xbc7f3ac9, 0xbbf13c62, 0xbc623bf1, 0xbac93c7f, 0x3c463c22, 0x3c75bb95, 0xbc75bb95, 0xbc463c22, 0x3ac93c7f, 0x3c623bf1,
    0x3bf13c62, 0x3c7f3ac9, 0x3c22bc46, 0xbb95bc75, 0xbb953c75, 0x3c223c46, 0x3c7fbac9, 0x3bf1bc62, 0x3c62bbf1, 0x3ac9bc7f,
    0xbc46bc22, 0xbc753b95, 0xbc0ebc55, 0xbc7b3b48, 0xbb483c7b, 0x3c553c0e, 0x3c55bc0e, 0xbb48bc7b, 0xbc7bbb48, 0xbc0e3c55,
    0x3c0e3c55, 0x3c7bbb48, 0x3b48bc7b, 0xbc55bc0e, 0xbc553c0e, 0x3b483c7b, 0x3c7b3b48, 0x3c0ebc55, 0xbc0ebc55, 0xbc7b3b48,
    0xbb483c7b, 0x3c553c0e, 0x3c55bc0e, 0xbb48bc7b, 0xbc7bbb48, 0xbc0e3c55, 0x3c0e3c55, 0x3c7bbb48, 0x3b48bc7b, 0xbc55bc0e,
    0xbc553c0e, 0x3b483c7b, 0x3c7b3b48, 0x3c0ebc55, 0x3c7f3ac9, 0x3b95bc75, 0xbc62bbf1, 0xbc223c46, 0x3c46bc22, 0xbbf1bc62,
    0xbc753b95, 0x3ac93c7f, 0x3ac9bc7f, 0xbc75bb95, 0xbbf13c62, 0x3c463c22, 0xbc22bc46, 0xbc623bf1, 0x3b953c75, 0x3c7fbac9,
    0xbc7fbac9, 0xbb953c75, 0x3c623bf1, 0x3c22bc46, 0xbc463c22, 0x3bf13c62, 0x3c75bb95, 0xbac9bc7f, 0xbac93c7f, 0x3c753b95,
    0x3bf1bc62, 0xbc46bc22, 0x3c223c46, 0x3c62bbf1, 0xbb95bc75, 0xbc7f3ac9, 0x3a493c80, 0x3b163c7d, 0x3b793c78, 0x3bac3c71,
    0x3bdb3c67, 0x3c043c5c, 0x3c183c4e, 0x3c2c3c3e, 0x3c3e3c2c, 0x3c4e3c18, 0x3c5c3c04, 0x3c673bdb, 0x3c713bac, 0x3c783b79,
    0x3c7d3b16, 0x3c803a49, 0x3c80ba49, 0x3c7dbb16, 0x3c78bb79, 0x3c71bbac, 0x3c67bbdb, 0x3c5cbc04, 0x3c4ebc18, 0x3c3ebc2c,
    0x3c2cbc3e, 0x3c18bc4e, 0x3c04bc5c, 0x3bdbbc67, 0x3bacbc71, 0x3b79bc78, 0x3b16bc7d, 0x3a49bc80, 0x3c783b79, 0x3c80ba49,
    0x3c71bbac, 0x3c4ebc18, 0x3b163c7d, 0x3bdb3c67, 0x3c2c3c3e, 0x3c5c3c04, 0xbc04bc5c, 0xbc3ebc2c, 0xbc67bbdb, 0xbc7dbb16,
    0x3c18bc4e, 0x3bacbc71, 0x3a49bc80, 0xbb79bc78, 0xbb793c78, 0x3a493c80, 0x3bac3c71, 0x3c183c4e, 0xbc7d3b16, 0xbc673bdb,
    0xbc3e3c2c, 0xbc043c5c, 0x3c5cbc04, 0x3c2cbc3e, 0x3bdbbc67, 0x3b16bc7d, 0x3c4e3c18, 0x3c713bac, 0x3c803a49, 0x3c78bb79,
    0xbc5cbc04, 0xbc80ba49, 0xbc673bdb, 0xbc183c4e, 0xbb163c7d, 0x3bac3c71, 0x3c3e3c2c, 0x3c783b79, 0x3b793c78, 0x3c2c3c3e,
    0x3c713bac, 0x3c7dbb16, 0x3c4ebc18, 0x3bdbbc67, 0xba49bc80, 0xbc04bc5c, 0xbc043c5c, 0xba493c80, 0x3bdb3c67, 0x3c4e3c18,
    0x3c7d3b16, 0x3c71bbac, 0x3c2cbc3e, 0x3b79bc78, 0x3c78bb79, 0x3c3ebc2c, 0x3bacbc71, 0xbb16bc7d, 0xbc18bc4e, 0xbc67bbdb,
    0xbc803a49, 0xbc5c3c04, 0x3c3ebc2c, 0x3b16bc7d, 0xbc04bc5c, 0xbc71bbac, 0xbbdb3c67, 0x3b793c78, 0x3c4e3c18, 0x3c80ba49,
    0x3a49bc80, 0xbc18bc4e, 0xbc78bb79, 0xbc673bdb, 0x3bac3c71, 0x3c5c3c04, 0x3c7dbb16, 0x3c2cbc3e, 0x3c2c3c3e, 0x3c7d3b16,
    0x3c5cbc04, 0x3bacbc71, 0xbc67bbdb, 0xbc783b79, 0xbc183c4e, 0x3a493c80, 0x3c803a49, 0x3c4ebc18, 0x3b79bc78, 0xbbdbbc67,
    0xbc713bac, 0xbc043c5c, 0x3b163c7d, 0x3c3e3c2c, 0x3c67bbdb, 0x3b79bc78, 0xbc18bc4e, 0xbc80ba49, 0xbc2c3c3e, 0x3b163c7d,
    0x3c5c3c04, 0x3c71bbac, 0x3bacbc71, 0xbc04bc5c, 0xbc7dbb16, 0xbc3e3c2c, 0x3a493c80, 0x3c4e3c18, 0x3c78bb79, 0x3bdbbc67,
    0x3bdb3c67, 0x3c783b79, 0x3c4ebc18, 0x3a49bc80, 0xbc3ebc2c, 0xbc7d3b16, 0xbc043c5c, 0x3bac3c71, 0x3c713bac, 0x3c5cbc04,
    0x3b16bc7d, 0xbc2cbc3e, 0xbc803a49, 0xbc183c4e, 0x3b793c78, 0x3c673bdb, 0xbb16bc7d, 0xbc71bbac, 0xbc3e3c2c, 0x3b793c78,
    0xbc5c3c04, 0x3a493c80, 0x3c673bdb, 0x3c4ebc18, 0xbc183c4e, 0x3bdb3c67, 0x3c803a49, 0x3c04bc5c, 0x3c783b79, 0x3c2cbc3e,
    0xbbacbc71, 0xbc7dbb16, 0xbc7d3b16, 0xbbac3c71, 0x3c2c3c3e, 0x3c78bb79, 0x3c043c5c, 0x3c80ba49, 0x3bdbbc67, 0xbc18bc4e,
    0x3c4e3c18, 0x3c67bbdb, 0x3a49bc80, 0xbc5cbc04, 0x3b79bc78, 0xbc3ebc2c, 0xbc713bac, 0xbb163c7d, 0xbb163c7d, 0x3c673bdb,
    0x3c2cbc3e, 0xbc04bc5c, 0xbc783b79, 0xba493c80, 0x3c713bac, 0x3c18bc4e, 0x3c4ebc18, 0xbbacbc71, 0xbc803a49, 0xbb793c78,
    0x3c5c3c04, 0x3c3ebc2c, 0xbbdbbc67, 0xbc7d3b16, 0xbc7dbb16, 0xbbdb3c67, 0x3c3e3c2c, 0x3c5cbc04, 0xbb79bc78, 0xbc80ba49,
    0xbbac3c71, 0x3c4e3c18, 0x3c183c4e, 0x3c71bbac, 0xba49bc80, 0xbc78bb79, 0xbc043c5c, 0x3c2c3c3e, 0x3c67bbdb, 0xbb16bc7d,
    0xbc67bbdb, 0xbc043c5c, 0x3c4e3c18, 0x3c2cbc3e, 0xbc80ba49, 0xbb163c7d, 0x3c783b79, 0x3bacbc71, 0xbc713bac, 0x3b793c78,
    0x3c7dbb16, 0xba49bc80, 0xbc3e3c2c, 0x3c183c4e, 0x3c5cbc04, 0xbbdbbc67, 0xbbdb3c67, 0x3c5c3c04, 0x3c18bc4e, 0xbc3ebc2c,
    0xba493c80, 0x3c7d3b16, 0x3b79bc78, 0xbc71bbac, 0x3bac3c71, 0x3c78bb79, 0xbb16bc7d, 0xbc803a49, 0x3c2c3c3e, 0x3c4ebc18,
    0xbc04bc5c, 0xbc673bdb, 0x3c353c35, 0x3c35bc35, 0xbc35bc35, 0xbc353c35, 0x3c353c35, 0x3c35bc35, 0xbc35bc35, 0xbc353c35,
    0x3c353c35, 0x3c35bc35, 0xbc35bc35, 0xbc353c35, 0x3c353c35, 0x3c35bc35, 0xbc35bc35, 0xbc353c35, 0x3c353c35, 0x3c35bc35,
    0xbc35bc35, 0xbc353c35, 0x3c353c35, 0x3c35bc35, 0xbc35bc35, 0xbc353c35, 0x3c353c35, 0x3c35bc35, 0xbc35bc35, 0xbc353c35,
    0x3c353c35, 0x3c35bc35, 0xbc35bc35, 0xbc353c35, 0x3c7fbac9, 0xbb95bc75, 0xbc623bf1, 0x3c223c46, 0x3c463c22, 0x3bf1bc62,
    0xbc75bb95, 0xbac93c7f, 0xbac9bc7f, 0xbc753b95, 0x3bf13c62, 0x3c46bc22, 0x3c22bc46, 0xbc62bbf1, 0xbb953c75, 0x3c7f3ac9,
    0xbc7f3ac9, 0x3b953c75, 0x3c62bbf1, 0xbc22bc46, 0xbc46bc22, 0xbbf13c62, 0x3c753b95, 0x3ac9bc7f, 0x3ac93c7f, 0x3c75bb95,
    0xbbf1bc62, 0xbc463c22, 0xbc223c46, 0x3c623bf1, 0x3b95bc75, 0xbc7fbac9, 0xbc55bc0e, 0xbb483c7b, 0x3c7bbb48, 0xbc0ebc55,
    0xbc0e3c55, 0x3c7b3b48, 0xbb48bc7b, 0xbc553c0e, 0x3c553c0e, 0x3b48bc7b, 0xbc7b3b48, 0x3c0e3c55, 0x3c0ebc55, 0xbc7bbb48,
    0x3b483c7b, 0x3c55bc0e, 0xbc55bc0e, 0xbb483c7b, 0x3c7bbb48, 0xbc0ebc55, 0xbc0e3c55, 0x3c7b3b48, 0xbb48bc7b, 0xbc553c0e,
    0x3c553c0e, 0x3b48bc7b, 0xbc7b3b48, 0x3c0e3c55, 0x3c0ebc55, 0xbc7bbb48, 0x3b483c7b, 0x3c55bc0e, 0x3c75bb95, 0xbc46bc22,
    0xbac93c7f, 0x3c62bbf1, 0xbbf13c62, 0x3c7fbac9, 0xbc22bc46, 0xbb953c75, 0xbb95bc75, 0xbc223c46, 0x3c7f3ac9, 0xbbf1bc62,
    0x3c623bf1, 0xbac9bc7f, 0xbc463c22, 0x3c753b95, 0xbc753b95, 0x3c463c22, 0x3ac9bc7f, 0xbc623bf1, 0x3bf1bc62, 0xbc7f3ac9,
    0x3c223c46, 0x3b95bc75, 0x3b953c75, 0x3c22bc46, 0xbc7fbac9, 0x3bf13c62, 0xbc62bbf1, 0x3ac93c7f, 0x3c46bc22, 0xbc75bb95,
    0x3c6d3bc4, 0xbbc4bc6d, 0xbbc43c6d, 0x3c6dbbc4, 0xbc6dbbc4, 0x3bc43c6d, 0x3bc4bc6d, 0xbc6d3bc4, 0x3c6d3bc4, 0xbbc4bc6d,
    0xbbc43c6d, 0x3c6dbbc4, 0xbc6dbbc4, 0x3bc43c6d, 0x3bc4bc6d, 0xbc6d3bc4, 0x3c6d3bc4, 0xbbc4bc6d, 0xbbc43c6d, 0x3c6dbbc4,
    0xbc6dbbc4, 0x3bc43c6d, 0x3bc4bc6d, 0xbc6d3bc4, 0x3c6d3bc4, 0xbbc4bc6d, 0xbbc43c6d, 0x3c6dbbc4, 0xbc6dbbc4, 0x3bc43c6d,
    0x3bc4bc6d, 0xbc6d3bc4, 0x3c62bbf1, 0xbc7fbac9, 0x3c463c22, 0xbb95bc75, 0xbc75bb95, 0x3c223c46, 0xbac9bc7f, 0xbbf13c62,
    0xbbf1bc62, 0xbac93c7f, 0x3c22bc46, 0xbc753b95, 0xbb953c75, 0x3c46bc22, 0xbc7f3ac9, 0x3c623bf1, 0xbc623bf1, 0x3c7f3ac9,
    0xbc46bc22, 0x3b953c75, 0x3c753b95, 0xbc22bc46, 0x3ac93c7f, 0x3bf1bc62, 0x3bf13c62, 0x3ac9bc7f, 0xbc223c46, 0x3c75bb95,
    0x3b95bc75, 0xbc463c22, 0x3c7fbac9, 0xbc62bbf1, 0xbc7bbb48, 0x3c553c0e, 0xbc0ebc55, 0x3b483c7b, 0x3b48bc7b, 0xbc0e3c55,
    0x3c55bc0e, 0xbc7b3b48, 0x3c7b3b48, 0xbc55bc0e, 0x3c0e3c55, 0xbb48bc7b, 0xbb483c7b, 0x3c0ebc55, 0xbc553c0e, 0x3c7bbb48,
    0xbc7bbb48, 0x3c553c0e, 0xbc0ebc55, 0x3b483c7b, 0x3b48bc7b, 0xbc0e3c55, 0x3c55bc0e, 0xbc7b3b48, 0x3c7b3b48, 0xbc55bc0e,
    0x3c0e3c55, 0xbb48bc7b, 0xbb483c7b, 0x3c0ebc55, 0xbc553c0e, 0x3c7bbb48, 0x3c46bc22, 0xbc623bf1, 0x3c75bb95, 0xbc7f3ac9,
    0x3ac9bc7f, 0xbb953c75, 0x3bf1bc62, 0xbc223c46, 0xbc22bc46, 0x3bf13c62, 0xbb95bc75, 0x3ac93c7f, 0xbc7fbac9, 0x3c753b95,
    0xbc62bbf1, 0x3c463c22, 0xbc463c22, 0x3c62bbf1, 0xbc753b95, 0x3c7fbac9, 0xbac93c7f, 0x3b95bc75, 0xbbf13c62, 0x3c22bc46,
    0x3c223c46, 0xbbf1bc62, 0x3b953c75, 0xbac9bc7f, 0x3c7f3ac9, 0xbc75bb95, 0x3c623bf1, 0xbc46bc22, 0x3c3e3c2c, 0x3c18bc4e,
    0xbc5cbc04, 0xbbdb3c67, 0x3c713bac, 0x3b79bc78, 0xbc7dbb16, 0xba493c80, 0x3c80ba49, 0xbb16bc7d, 0xbc783b79, 0x3bac3c71,
    0x3c67bbdb, 0xbc04bc5c, 0xbc4e3c18, 0x3c2c3c3e, 0x3c2cbc3e, 0xbc4ebc18, 0xbc043c5c, 0x3c673bdb, 0x3bacbc71, 0xbc78bb79,
    0xbb163c7d, 0x3c803a49, 0xba49bc80, 0xbc7d3b16, 0x3b793c78, 0x3c71bbac, 0xbbdbbc67, 0xbc5c3c04, 0x3c183c4e, 0x3c3ebc2c,
    0x3c5cbc04, 0xbc3ebc2c, 0xbbdb3c67, 0x3c7d3b16, 0x3c4e3c18, 0x3bacbc71, 0xbc80ba49, 0x3b793c78, 0xbc78bb79, 0x3a493c80,
    0x3c71bbac, 0xbc18bc4e, 0xbb16bc7d, 0xbc673bdb, 0x3c2c3c3e, 0x3c04bc5c, 0x3c043c5c, 0x3c2cbc3e, 0xbc67bbdb, 0xbb163c7d,
    0xbc183c4e, 0x3c713bac, 0x3a49bc80, 0xbc783b79, 0x3b79bc78, 0xbc803a49, 0x3bac3c71, 0x3c4ebc18, 0x3c7dbb16, 0xbbdbbc67,
    0xbc3e3c2c, 0x3c5c3c04, 0xbc783b79, 0x3c2c3c3e, 0x3bacbc71, 0xbc7d3b16, 0x3c183c4e, 0x3bdbbc67, 0xbc803a49, 0x3c043c5c,
    0x3c5c3c04, 0x3a49bc80, 0xbc673bdb, 0x3c4e3c18, 0x3b16bc7d, 0xbc713bac, 0x3c3e3c2c, 0x3b79bc78, 0x3b793c78, 0x3c3ebc2c,
    0xbc71bbac, 0x3b163c7d, 0x3c4ebc18, 0xbc67bbdb, 0x3a493c80, 0x3c5cbc04, 0x3c04bc5c, 0xbc80ba49, 0x3bdb3c67, 0x3c18bc4e,
    0xbc7dbb16, 0x3bac3c71, 0x3c2cbc3e, 0xbc78bb79, 0x3a49bc80, 0xbc4e3c18, 0x3c783b79, 0xbbdbbc67, 0x3bac3c71, 0x3c04bc5c,
    0xbc7d3b16, 0x3c3e3c2c, 0xbc2cbc3e, 0xbb163c7d, 0x3c5cbc04, 0xbc71bbac, 0x3c673bdb, 0xbb79bc78, 0xbc183c4e, 0x3c80ba49,
    0x3c803a49, 0xbc18bc4e, 0xbb793c78, 0x3c67bbdb, 0xbc713bac, 0x3c5c3c04, 0xbb16bc7d, 0xbc2c3c3e, 0x3c3ebc2c, 0xbc7dbb16,
    0x3c043c5c, 0x3bacbc71, 0xbbdb3c67, 0x3c78bb79, 0xbc4ebc18, 0x3a493c80, 0x3bacbc71, 0xbc5c3c04, 0x3c7d3b16, 0xbc2cbc3e,
    0x3a493c80, 0x3c18bc4e, 0xbc783b79, 0x3c673bdb, 0xbbdbbc67, 0xbb793c78, 0x3c4ebc18, 0xbc80ba49, 0x3c3e3c2c, 0xbb16bc7d,
    0xbc043c5c, 0x3c71bbac, 0x3c713bac, 0xbc04bc5c, 0xbb163c7d, 0x3c3ebc2c, 0xbc803a49, 0x3c4e3c18, 0xbb79bc78, 0xbbdb3c67,
    0x3c67bbdb, 0xbc78bb79, 0x3c183c4e, 0x3a49bc80, 0xbc2c3c3e, 0x3c7dbb16, 0xbc5cbc04, 0x3bac3c71, 0xbc4ebc18, 0x3bdb3c67,
    0x3a49bc80, 0xbc043c5c, 0xbb793c78, 0x3c2cbc3e, 0xbc713bac, 0x3c7d3b16, 0x3b163c7d, 0x3bacbc71, 0xbc3e3c2c, 0x3c78bb79,
    0x3c5cbc04, 0xbc803a49, 0x3c673bdb, 0xbc18bc4e, 0xbc183c4e, 0x3c67bbdb, 0xbc80ba49, 0x3c5c3c04, 0x3c783b79, 0xbc3ebc2c,
    0x3bac3c71, 0x3b16bc7d, 0x3c7dbb16, 0xbc71bbac, 0x3c2c3c3e, 0xbb79bc78, 0xbc04bc5c, 0x3a493c80, 0x3bdbbc67, 0xbc4e3c18,
    0x3c183c4e, 0xbbacbc71, 0x3a493c80, 0x3b79bc78, 0xbc043c5c, 0x3c3ebc2c, 0xbc673bdb, 0x3c7dbb16, 0x3b16bc7d, 0xbbdb3c67,
    0x3c2cbc3e, 0xbc5c3c04, 0x3c78bb79, 0xbc80ba49, 0x3c713bac, 0xbc4ebc18, 0xbc4e3c18, 0x3c71bbac, 0xbc803a49, 0x3c783b79,
    0xbc5cbc04, 0x3c2c3c3e, 0xbbdbbc67, 0x3b163c7d, 0x3c7d3b16, 0xbc67bbdb, 0x3c3e3c2c, 0xbc04bc5c, 0x3b793c78, 0x3a49bc80,
    0xbbac3c71, 0x3c18bc4e, 0xbc713bac, 0x3c78bb79, 0xbc7d3b16, 0x3c80ba49, 0xbc3e3c2c, 0x3c4ebc18, 0xbc5c3c04, 0x3c67bbdb,
    0xbbdb3c67, 0x3c04bc5c, 0xbc183c4e, 0x3c2cbc3e, 0xba493c80, 0x3b16bc7d, 0xbb793c78, 0x3bacbc71, 0x3bac3c71, 0xbb79bc78,
    0x3b163c7d, 0xba49bc80, 0x3c2c3c3e, 0xbc18bc4e, 0x3c043c5c, 0xbbdbbc67, 0x3c673bdb, 0xbc5cbc04, 0x3c4e3c18, 0xbc3ebc2c,
    0x3c803a49, 0xbc7dbb16, 0x3c783b79, 0xbc71bbac, 0x3c800000, 0xbc800000, 0x3c800000, 0xbc800000, 0x3c800000, 0xbc800000,
    0x3c800000, 0xbc800000, 0x3c800000, 0xbc800000, 0x3c800000, 0xbc800000, 0x3c800000, 0xbc800000, 0x3c800000, 0xbc800000,
    0x3c800000, 0xbc800000, 0x3c800000, 0xbc800000, 0x3c800000, 0xbc800000, 0x3c800000, 0xbc800000, 0x3c800000, 0xbc800000,
    0x3c800000, 0xbc800000, 0x3c800000, 0xbc800000, 0x3c800000, 0xbc800000, 0x3c22bc46, 0xbbf13c62, 0x3b95bc75, 0xbac93c7f,
    0x3c7fbac9, 0xbc753b95, 0x3c62bbf1, 0xbc463c22, 0xbc46bc22, 0x3c623bf1, 0xbc75bb95, 0x3c7f3ac9, 0xbac9bc7f, 0x3b953c75,
    0xbbf1bc62, 0x3c223c46, 0xbc223c46, 0x3bf1bc62, 0xbb953c75, 0x3ac9bc7f, 0xbc7f3ac9, 0x3c75bb95, 0xbc623bf1, 0x3c46bc22,
    0x3c463c22, 0xbc62bbf1, 0x3c753b95, 0xbc7fbac9, 0x3ac93c7f, 0xbb95bc75, 0x3bf13c62, 0xbc22bc46, 0xbc7b3b48, 0x3c55bc0e,
    0xbc0e3c55, 0x3b48bc7b, 0x3b483c7b, 0xbc0ebc55, 0x3c553c0e, 0xbc7bbb48, 0x3c7bbb48, 0xbc553c0e, 0x3c0ebc55, 0xbb483c7b,
    0xbb48bc7b, 0x3c0e3c55, 0xbc55bc0e, 0x3c7b3b48, 0xbc7b3b48, 0x3c55bc0e, 0xbc0e3c55, 0x3b48bc7b, 0x3b483c7b, 0xbc0ebc55,
    0x3c553c0e, 0xbc7bbb48, 0x3c7bbb48, 0xbc553c0e, 0x3c0ebc55, 0xbb483c7b, 0xbb48bc7b, 0x3c0e3c55, 0xbc55bc0e, 0x3c7b3b48,
    0x3bf1bc62, 0x3ac93c7f, 0xbc22bc46, 0x3c753b95, 0x3b953c75, 0xbc46bc22, 0x3c7f3ac9, 0xbc623bf1, 0xbc62bbf1, 0x3c7fbac9,
    0xbc463c22, 0x3b95bc75, 0x3c75bb95, 0xbc223c46, 0x3ac9bc7f, 0x3bf13c62, 0xbbf13c62, 0xbac9bc7f, 0x3c223c46, 0xbc75bb95,
    0xbb95bc75, 0x3c463c22, 0xbc7fbac9, 0x3c62bbf1, 0x3c623bf1, 0xbc7f3ac9, 0x3c46bc22, 0xbb953c75, 0xbc753b95, 0x3c22bc46,
    0xbac93c7f, 0xbbf1bc62, 0x3c6dbbc4, 0xbbc43c6d, 0xbbc4bc6d, 0x3c6d3bc4, 0xbc6d3bc4, 0x3bc4bc6d, 0x3bc43c6d, 0xbc6dbbc4,
    0x3c6dbbc4, 0xbbc43c6d, 0xbbc4bc6d, 0x3c6d3bc4, 0xbc6d3bc4, 0x3bc4bc6d, 0x3bc43c6d, 0xbc6dbbc4, 0x3c6dbbc4, 0xbbc43c6d,
    0xbbc4bc6d, 0x3c6d3bc4, 0xbc6d3bc4, 0x3bc4bc6d, 0x3bc43c6d, 0xbc6dbbc4, 0x3c6dbbc4, 0xbbc43c6d, 0xbbc4bc6d, 0x3c6d3bc4,
    0xbc6d3bc4, 0x3bc4bc6d, 0x3bc43c6d, 0xbc6dbbc4, 0x3b95bc75, 0x3c223c46, 0xbc7f3ac9, 0x3bf1bc62, 0xbc623bf1, 0x3ac9bc7f,
    0x3c463c22, 0xbc753b95, 0xbc75bb95, 0x3c46bc22, 0x3ac93c7f, 0xbc62bbf1, 0x3bf13c62, 0xbc7fbac9, 0x3c22bc46, 0x3b953c75,
    0xbb953c75, 0xbc22bc46, 0x3c7fbac9, 0xbbf13c62, 0x3c62bbf1, 0xbac93c7f, 0xbc46bc22, 0x3c75bb95, 0x3c753b95, 0xbc463c22,
    0xbac9bc7f, 0x3c623bf1, 0xbbf1bc62, 0x3c7f3ac9, 0xbc223c46, 0xbb95bc75, 0xbc553c0e, 0xbb48bc7b, 0x3c7b3b48, 0xbc0e3c55,
    0xbc0ebc55, 0x3c7bbb48, 0xbb483c7b, 0xbc55bc0e, 0x3c55bc0e, 0x3b483c7b, 0xbc7bbb48, 0x3c0ebc55, 0x3c0e3c55, 0xbc7b3b48,
    0x3b48bc7b, 0x3c553c0e, 0xbc553c0e, 0xbb48bc7b, 0x3c7b3b48, 0xbc0e3c55, 0xbc0ebc55, 0x3c7bbb48, 0xbb483c7b, 0xbc55bc0e,
    0x3c55bc0e, 0x3b483c7b, 0xbc7bbb48, 0x3c0ebc55, 0x3c0e3c55, 0xbc7b3b48, 0x3b48bc7b, 0x3c553c0e, 0x3ac9bc7f, 0x3c753b95,
    0xbbf13c62, 0xbc46bc22, 0xbc22bc46, 0x3c62bbf1, 0x3b953c75, 0xbc7f3ac9, 0xbc7fbac9, 0x3b95bc75, 0x3c623bf1, 0xbc223c46,
    0xbc463c22, 0xbbf1bc62, 0x3c75bb95, 0x3ac93c7f, 0xbac93c7f, 0xbc75bb95, 0x3bf1bc62, 0x3c463c22, 0x3c223c46, 0xbc623bf1,
    0xbb95bc75, 0x3c7fbac9, 0x3c7f3ac9, 0xbb953c75, 0xbc62bbf1, 0x3c22bc46, 0x3c46bc22, 0x3bf13c62, 0xbc753b95, 0xbac9bc7f,
    0x3c80ba49, 0xbc7d3b16, 0x3c78bb79, 0xbc713bac, 0x3c67bbdb, 0xbc5c3c04, 0x3c4ebc18, 0xbc3e3c2c, 0x3c2cbc3e, 0xbc183c4e,
    0x3c04bc5c, 0xbbdb3c67, 0x3bacbc71, 0xbb793c78, 0x3b16bc7d, 0xba493c80, 0xba49bc80, 0x3b163c7d, 0xbb79bc78, 0x3bac3c71,
    0xbbdbbc67, 0x3c043c5c, 0xbc18bc4e, 0x3c2c3c3e, 0xbc3ebc2c, 0x3c4e3c18, 0xbc5cbc04, 0x3c673bdb, 0xbc71bbac, 0x3c783b79,
    0xbc7dbb16, 0x3c803a49, 0x3b79bc78, 0x3a493c80, 0xbbacbc71, 0x3c183c4e, 0x3c7dbb16, 0xbc673bdb, 0x3c3ebc2c, 0xbc043c5c,
    0xbc5c3c04, 0x3c2cbc3e, 0xbbdb3c67, 0x3b16bc7d, 0xbc4ebc18, 0x3c713bac, 0xbc80ba49, 0x3c78bb79, 0x3c783b79, 0xbc803a49,
    0x3c71bbac, 0xbc4e3c18, 0x3b163c7d, 0xbbdbbc67, 0x3c2c3c3e, 0xbc5cbc04, 0xbc04bc5c, 0x3c3e3c2c, 0xbc67bbdb, 0x3c7d3b16,
    0x3c18bc4e, 0xbbac3c71, 0x3a49bc80, 0x3b793c78, 0xbc043c5c, 0x3a49bc80, 0x3bdb3c67, 0xbc4ebc18, 0x3c7d3b16, 0xbc713bac,
    0x3c2cbc3e, 0xbb793c78, 0x3c78bb79, 0xbc3e3c2c, 0x3bacbc71, 0x3b163c7d, 0xbc18bc4e, 0x3c673bdb, 0xbc803a49, 0x3c5cbc04,
    0x3c5c3c04, 0xbc80ba49, 0x3c67bbdb, 0xbc183c4e, 0x3b16bc7d, 0x3bac3c71, 0xbc3ebc2c, 0x3c783b79, 0xbb79bc78, 0x3c2c3c3e,
    0xbc71bbac, 0x3c7dbb16, 0xbc4e3c18, 0x3bdbbc67, 0x3a493c80, 0xbc04bc5c, 0xbc2cbc3e, 0x3c7d3b16, 0xbc5c3c04, 0x3bacbc71,
    0x3c673bdb, 0xbc783b79, 0x3c18bc4e, 0x3a493c80, 0xbc80ba49, 0x3c4ebc18, 0xbb793c78, 0xbbdbbc67, 0x3c71bbac, 0xbc043c5c,
    0xbb16bc7d, 0x3c3e3c2c, 0x3c3ebc2c, 0xbb163c7d, 0xbc04bc5c, 0x3c713bac, 0xbbdb3c67, 0xbb79bc78, 0x3c4e3c18, 0xbc803a49,
    0x3a49bc80, 0x3c183c4e, 0xbc78bb79, 0x3c67bbdb, 0x3bac3c71, 0xbc5cbc04, 0x3c7dbb16, 0xbc2c3c3e, 0xbbdbbc67, 0x3c783b79,
    0xbc4e3c18, 0x3a49bc80, 0x3c3e3c2c, 0xbc7d3b16, 0x3c04bc5c, 0x3bac3c71, 0xbc71bbac, 0x3c5cbc04, 0xbb163c7d, 0xbc2cbc3e,
    0x3c80ba49, 0xbc183c4e, 0xbb79bc78, 0x3c673bdb, 0x3c67bbdb, 0xbb793c78, 0xbc18bc4e, 0x3c803a49, 0xbc2c3c3e, 0xbb16bc7d,
    0x3c5c3c04, 0xbc713bac, 0x3bacbc71, 0x3c043c5c, 0xbc7dbb16, 0x3c3ebc2c, 0x3a493c80, 0xbc4ebc18, 0x3c78bb79, 0xbbdb3c67,
    0xbc7d3b16, 0x3bacbc71, 0x3c2c3c3e, 0xbc783b79, 0x3c043c5c, 0xbc803a49, 0x3bdbbc67, 0x3c183c4e, 0x3c4e3c18, 0xbc673bdb,
    0x3a49bc80, 0x3c5c3c04, 0x3b79bc78, 0x3c3e3c2c, 0xbc713bac, 0x3b16bc7d, 0x3b163c7d, 0xbc71bbac, 0x3c3ebc2c, 0x3b793c78,
    0x3c5cbc04, 0x3a493c80, 0xbc67bbdb, 0x3c4ebc18, 0x3c18bc4e, 0x3bdb3c67, 0xbc80ba49, 0x3c04bc5c, 0xbc78bb79, 0x3c2cbc3e,
    0x3bac3c71, 0xbc7dbb16, 0x3c7d3b16, 0xbbdb3c67, 0xbc3ebc2c, 0x3c5cbc04, 0x3b793c78, 0xbc80ba49, 0x3bacbc71, 0x3c4e3c18,
    0xbc18bc4e, 0x3c71bbac, 0x3a493c80, 0xbc78bb79, 0x3c04bc5c, 0x3c2c3c3e, 0xbc673bdb, 0xbb16bc7d, 0xbb163c7d, 0xbc67bbdb,
    0x3c2cbc3e, 0x3c043c5c, 0xbc783b79, 0x3a49bc80, 0x3c713bac, 0xbc183c4e, 0x3c4ebc18, 0x3bac3c71, 0xbc803a49, 0x3b79bc78,
    0x3c5c3c04, 0xbc3e3c2c, 0xbbdbbc67, 0x3c7dbb16, 0xbbdb3c67, 0xbc5cbc04, 0x3c18bc4e, 0x3c3e3c2c, 0xba493c80, 0xbc7dbb16,
    0x3b79bc78, 0x3c713bac, 0x3bac3c71, 0xbc783b79, 0xbb16bc7d, 0x3c80ba49, 0x3c2c3c3e, 0xbc4e3c18, 0xbc04bc5c, 0x3c67bbdb,
    0x3c673bdb, 0xbc043c5c, 0xbc4ebc18, 0x3c2cbc3e, 0x3c803a49, 0xbb163c7d, 0xbc78bb79, 0x3bacbc71, 0x3c71bbac, 0x3b793c78,
    0xbc7d3b16, 0xba49bc80, 0x3c3ebc2c, 0x3c183c4e, 0xbc5c3c04, 0xbbdbbc67, 0x3f803f80, 0x3f7d3f7f, 0x3f783f7b, 0x3f713f75,
    0x3f673f6d, 0x3f5c3f62, 0x3f4e3f55, 0x3f3e3f46, 0x3f2c3f35, 0x3f183f22, 0x3f043f0e, 0x3edb3ef1, 0x3eac3ec4, 0x3e793e95,
    0x3e163e48, 0x3d493dc9, 0xbd490000, 0xbe16bdc9, 0xbe79be48, 0xbeacbe95, 0xbedbbec4, 0xbf04bef1, 0xbf18bf0e, 0xbf2cbf22,
    0xbf3ebf35, 0xbf4ebf46, 0xbf5cbf55, 0xbf67bf62, 0xbf71bf6d, 0xbf78bf75, 0xbf7dbf7b, 0xbf80bf7f, 0x3edb3ec4, 0x3f043ef1,
    0x3f183f0e, 0x3f2c3f22, 0x3d490000, 0x3e163dc9, 0x3e793e48, 0x3eac3e95, 0x3f713f6d, 0x3f783f75, 0x3f7d3f7b, 0x3f803f7f,
    0x3f3e3f35, 0x3f4e3f46, 0x3f5c3f55, 0x3f673f62, 0x3f673f6d, 0x3f5c3f62, 0x3f4e3f55, 0x3f3e3f46, 0x3f803f80, 0x3f7d3f7f,
    0x3f783f7b, 0x3f713f75, 0x3eac3ec4, 0x3e793e95, 0x3e163e48, 0x3d493dc9, 0x3f2c3f35, 0x3f183f22, 0x3f043f0e, 0x3edb3ef1,
    0xbf4ebf35, 0xbf71bf62, 0xbf80bf7b, 0xbf78bf7f, 0xbf5cbf6d, 0xbf2cbf46, 0xbedbbf0e, 0xbe16be95, 0x3f7d3f80, 0x3f673f75,
    0x3f3e3f55, 0x3f043f22, 0x3e793ec4, 0xbd493dc9, 0xbeacbe48, 0xbf18bef1, 0x3f183f35, 0x3eac3ef1, 0x3d493e48, 0xbe79bdc9,
    0xbf04bec4, 0xbf3ebf22, 0xbf67bf55, 0xbf7dbf75, 0x3e160000, 0x3edb3e95, 0x3f2c3f0e, 0x3f5c3f46, 0x3f783f6d, 0x3f803f7f,
    0x3f713f7b, 0x3f4e3f62, 0xbf04bec4, 0xbf3ebf22, 0xbf67bf55, 0xbf7dbf75, 0x3f183f35, 0x3eac3ef1, 0x3d493e48, 0xbe79bdc9,
    0x3f783f6d, 0x3f803f7f, 0x3f713f7b, 0x3f4e3f62, 0x3e160000, 0x3edb3e95, 0x3f2c3f0e, 0x3f5c3f46, 0x3f5c3f6d, 0x3f2c3f46,
    0x3edb3f0e, 0x3e163e95, 0x3f4e3f35, 0x3f713f62, 0x3f803f7b, 0x3f783f7f, 0xbe79bec4, 0x3d49bdc9, 0x3eac3e48, 0x3f183ef1,
    0xbf7dbf80, 0xbf67bf75, 0xbf3ebf55, 0xbf04bf22, 0xbe790000, 0xbf2cbef1, 0xbf71bf55, 0xbf7dbf7f, 0xbf4ebf6d, 0xbedbbf22,
    0x3d49be48, 0x3f043e95, 0x3f5c3f35, 0x3f803f75, 0x3f673f7b, 0x3f183f46, 0x3e163ec4, 0xbeacbdc9, 0xbf3ebf0e, 0xbf78bf62,
    0x3f783f80, 0x3f3e3f62, 0x3eac3f0e, 0xbe163dc9, 0xbf18bec4, 0xbf67bf46, 0xbf80bf7b, 0xbf5cbf75, 0xbf04bf35, 0xbd49be95,
    0x3edb3e48, 0x3f4e3f22, 0x3f7d3f6d, 0x3f713f7f, 0x3f2c3f55, 0x3e793ef1, 0xbf18bec4, 0xbf67bf46, 0xbf80bf7b, 0xbf5cbf75,
    0x3f783f80, 0x3f3e3f62, 0x3eac3f0e, 0xbe163dc9, 0x3f7d3f6d, 0x3f713f7f, 0x3f2c3f55, 0x3e793ef1, 0xbf04bf35, 0xbd49be95,
    0x3edb3e48, 0x3f4e3f22, 0x3f4e3f6d, 0x3edb3f22, 0xbd493e48, 0xbf04be95, 0x3e790000, 0x3f2c3ef1, 0x3f713f55, 0x3f7d3f7f,
    0xbe16bec4, 0x3eac3dc9, 0x3f3e3f0e, 0x3f783f62, 0xbf5cbf35, 0xbf80bf75, 0xbf67bf7b, 0xbf18bf46, 0xbedbbf35, 0x3e79bdc9,
    0x3f4e3f0e, 0x3f803f75, 0x3f3e3f6d, 0x3e163ef1, 0xbf04be48, 0xbf71bf46, 0x3eac0000, 0x3f5c3f22, 0x3f7d3f7b, 0x3f2c3f62,
    0x3d493ec4, 0xbf18be95, 0xbf78bf55, 0xbf67bf7f, 0x3f673f35, 0x3f783f7f, 0x3f183f55, 0xbd493e95, 0xbf2cbec4, 0xbf7dbf62,
    0xbf5cbf7b, 0xbeacbf22, 0x3f713f80, 0x3f043f46, 0xbe163e48, 0xbf3ebef1, 0xbf80bf6d, 0xbf4ebf75, 0xbe79bf0e, 0x3edb3dc9,
    0x3f2c3ec4, 0x3f7d3f62, 0x3f5c3f7b, 0x3eac3f22, 0xbf67bf35, 0xbf78bf7f, 0xbf18bf55, 0x3d49be95, 0x3f803f6d, 0x3f4e3f75,
    0x3e793f0e, 0xbedbbdc9, 0xbf71bf80, 0xbf04bf46, 0x3e16be48, 0x3f3e3ef1, 0x3f3e3f6d, 0x3e163ef1, 0xbf04be48, 0xbf71bf46,
    0xbedbbf35, 0x3e79bdc9, 0x3f4e3f0e, 0x3f803f75, 0x3d493ec4, 0xbf18be95, 0xbf78bf55, 0xbf67bf7f, 0x3eac0000, 0x3f5c3f22,
    0x3f7d3f7b, 0x3f2c3f62, 0x3f673f80, 0x3e793f22, 0xbf18be48, 0xbf80bf62, 0xbf2cbf6d, 0x3e16be95, 0x3f5c3f0e, 0x3f713f7f,
    0x3eac3f35, 0xbf04bdc9, 0xbf7dbf55, 0xbf3ebf75, 0x3d49bec4, 0x3f4e3ef1, 0x3f783f7b, 0x3edb3f46, 0xbedb0000, 0xbf78bf46,
    0xbf4ebf7b, 0xbd49bef1, 0x3f3e3ec4, 0x3f7d3f75, 0x3f043f55, 0xbeac3dc9, 0xbf71bf35, 0xbf5cbf7f, 0xbe16bf0e, 0x3f2c3e95,
    0x3f803f6d, 0x3f183f62, 0xbe793e48, 0xbf67bf22, 0xbf3ebec4, 0xbf7dbf75, 0xbf04bf55, 0x3eacbdc9, 0x3edb0000, 0x3f783f46,
    0x3f4e3f7b, 0x3d493ef1, 0xbf80bf6d, 0xbf18bf62, 0x3e79be48, 0x3f673f22, 0x3f713f35, 0x3f5c3f7f, 0x3e163f0e, 0xbf2cbe95,
    0xbf2cbf6d, 0x3e16be95, 0x3f5c3f0e, 0x3f713f7f, 0x3f673f80, 0x3e793f22, 0xbf18be48, 0xbf80bf62, 0x3d49bec4, 0x3f4e3ef1,
    0x3f783f7b, 0x3edb3f46, 0x3eac3f35, 0xbf04bdc9, 0xbf7dbf55, 0xbf3ebf75, 0xbf78bf35, 0xbf2cbf75, 0x3eacbe48, 0x3f7d3f46,
    0x3f183f6d, 0xbedb3dc9, 0xbf80bf55, 0xbf04bf62, 0x3f5c3f80, 0xbd493ef1, 0xbf67bf0e, 0xbf4ebf7f, 0x3e16bec4, 0x3f713f22,
    0x3f3e3f7b, 0xbe793e95, 0x3e793f35, 0xbf3ebe95, 0xbf71bf7b, 0xbe16bf22, 0x3f4e3ec4, 0x3f673f7f, 0x3d493f0e, 0xbf5cbef1,
    0x3f040000, 0x3f803f62, 0x3edb3f55, 0xbf18bdc9, 0xbf7dbf6d, 0xbeacbf46, 0x3f2c3e48, 0x3f783f75, 0x3f4e3ec4, 0x3f673f7f,
    0x3d493f0e, 0xbf5cbef1, 0x3e793f35, 0xbf3ebe95, 0xbf71bf7b, 0xbe16bf22, 0xbf7dbf6d, 0xbeacbf46, 0x3f2c3e48, 0x3f783f75,
    0x3f040000, 0x3f803f62, 0x3edb3f55, 0xbf18bdc9, 0xbf18bf6d, 0x3edbbdc9, 0x3f803f55, 0x3f043f62, 0x3f783f35, 0x3f2c3f75,
    0xbeac3e48, 0xbf7dbf46, 0xbe163ec4, 0xbf71bf22, 0xbf3ebf7b, 0x3e79be95, 0xbf5cbf80, 0x3d49bef1, 0x3f673f0e, 0x3f4e3f7f,
    0xbf180000, 0xbf71bf75, 0x3d49bf0e, 0x3f783f22, 0x3f043f6d, 0xbf2cbdc9, 0xbf67bf7b, 0x3e16bef1, 0x3f7d3f35, 0x3edb3f62,
    0xbf3ebe48, 0xbf5cbf7f, 0x3e79bec4, 0x3f803f46, 0x3eac3f55, 0xbf4ebe95, 0x3f4e3f80, 0xbeac3e95, 0xbf80bf55, 0xbe79bf46,
    0x3f5c3ec4, 0x3f3e3f7f, 0xbedb3e48, 0xbf7dbf62, 0xbe16bf35, 0x3f673ef1, 0x3f2c3f7b, 0xbf043dc9, 0xbf78bf6d, 0xbd49bf22,
    0x3f713f0e, 0x3f183f75, 0x3f5c3ec4, 0x3f3e3f7f, 0xbedb3e48, 0xbf7dbf62, 0x3f4e3f80, 0xbeac3e95, 0xbf80bf55, 0xbe79bf46,
    0xbf78bf6d, 0xbd49bf22, 0x3f713f0e, 0x3f183f75, 0xbe16bf35, 0x3f673ef1, 0x3f2c3f7b, 0xbf043dc9, 0xbf04bf6d, 0x3f2c3dc9,
    0x3f673f7b, 0xbe163ef1, 0x3f180000, 0x3f713f75, 0xbd493f0e, 0xbf78bf22, 0xbe793ec4, 0xbf80bf46, 0xbeacbf55, 0x3f4e3e95,
    0xbf7dbf35, 0xbedbbf62, 0x3f3e3e48, 0x3f5c3f7f, 0xbd49bf35, 0x3f7d3f22, 0x3e793f55, 0xbf71bef1, 0xbedbbf6d, 0x3f5c3e95,
    0x3f183f7b, 0xbf3ebdc9, 0x3f2c0000, 0x3f4e3f7f, 0xbf043e48, 0xbf67bf75, 0x3eacbec4, 0x3f783f62, 0xbe163f0e, 0xbf80bf46,
    0x3f803f35, 0x3e163f46, 0xbf78bf0e, 0xbeacbf62, 0x3f673ec4, 0x3f043f75, 0xbf4ebe48, 0xbf2cbf7f, 0x3f3e3f80, 0xbf183dc9,
    0xbf5cbf7b, 0x3edbbe95, 0x3f713f6d, 0xbe793ef1, 0xbf7dbf55, 0x3d49bf22, 0xbf67bec4, 0xbf04bf75, 0x3f4e3e48, 0x3f2c3f7f,
    0xbf80bf35, 0xbe16bf46, 0x3f783f0e, 0x3eac3f62, 0xbf71bf6d, 0x3e79bef1, 0x3f7d3f55, 0xbd493f22, 0xbf3ebf80, 0x3f18bdc9,
    0x3f5c3f7b, 0xbedb3e95, 0xbedbbf6d, 0x3f5c3e95, 0x3f183f7b, 0xbf3ebdc9, 0xbd49bf35, 0x3f7d3f22, 0x3e793f55, 0xbf71bef1,
    0x3eacbec4, 0x3f783f62, 0xbe163f0e, 0xbf80bf46, 0x3f2c0000, 0x3f4e3f7f, 0xbf043e48, 0xbf67bf75, 0x3f2c3f80, 0xbf4ebdc9,
    0xbf04bf7b, 0x3f673e95, 0x3eac3f6d, 0xbf78bef1, 0xbe16bf55, 0x3f803f22, 0xbd493f35, 0xbf7dbf46, 0x3e79bf0e, 0x3f713f62,
    0xbedb3ec4, 0xbf5cbf75, 0x3f18be48, 0x3f3e3f7f, 0xbf3e0000, 0xbf18bf7f, 0x3f5c3e48, 0x3edb3f75, 0xbf71bec4, 0xbe79bf62,
    0x3f7d3f0e, 0x3d493f46, 0xbf80bf35, 0x3e16bf22, 0x3f783f55, 0xbeac3ef1, 0xbf67bf6d, 0x3f04be95, 0x3f4e3f7b, 0xbf2c3dc9,
    0x3f713ec4, 0x3e793f62, 0xbf7dbf0e, 0xbd49bf46, 0x3f3e0000, 0x3f183f7f, 0xbf5cbe48, 0xbedbbf75, 0x3f673f6d, 0xbf043e95,
    0xbf4ebf7b, 0x3f2cbdc9, 0x3f803f35, 0xbe163f22, 0xbf78bf55, 0x3eacbef1, 0x3eac3f6d, 0xbf78bef1, 0xbe16bf55, 0x3f803f22,
    0x3f2c3f80, 0xbf4ebdc9, 0xbf04bf7b, 0x3f673e95, 0xbedb3ec4, 0xbf5cbf75, 0x3f18be48, 0x3f3e3f7f, 0xbd493f35, 0xbf7dbf46,
    0x3e79bf0e, 0x3f713f62, 0xbf7dbf35, 0x3edbbef1, 0x3f3e3f7b, 0xbf5cbdc9, 0xbe79bf6d, 0x3f803f22, 0xbeac3f0e, 0xbf4ebf75,
    0x3f183f80, 0xbf71be95, 0xbd49bf55, 0x3f783f46, 0xbf043ec4, 0xbf2cbf7f, 0x3f673e48, 0x3e163f62, 0xbe163f35, 0xbf67bf62,
    0x3f2cbe48, 0x3f043f7f, 0xbf78bec4, 0x3d49bf46, 0x3f713f55, 0xbf183e95, 0x3f4e0000, 0x3eac3f75, 0xbf80bf0e, 0x3e79bf22,
    0x3f5c3f6d, 0xbf3e3dc9, 0xbedbbf7b, 0x3f7d3ef1, 0xbf78bec4, 0x3d49bf46, 0x3f713f55, 0xbf183e95, 0xbe163f35, 0xbf67bf62,
    0x3f2cbe48, 0x3f043f7f, 0x3f5c3f6d, 0xbf3e3dc9, 0xbedbbf7b, 0x3f7d3ef1, 0x3f4e0000, 0x3eac3f75, 0xbf80bf0e, 0x3e79bf22,
    0x3e793f6d, 0xbf80bf22, 0x3eacbf0e, 0x3f4e3f75, 0x3f7d3f35, 0xbedb3ef1, 0xbf3ebf7b, 0x3f5c3dc9, 0x3f04bec4, 0x3f2c3f7f,
    0xbf67be48, 0xbe16bf62, 0xbf18bf80, 0x3f713e95, 0x3d493f55, 0xbf78bf46, 0xbf5c0000, 0xbd49bf62, 0x3f673f55, 0xbf4e3dc9,
    0xbe16bf6d, 0x3f713f46, 0xbf3e3e48, 0xbe79bf75, 0x3f783f35, 0xbf2c3e95, 0xbeacbf7b, 0x3f7d3f22, 0xbf183ec4, 0xbedbbf7f,
    0x3f803f0e, 0xbf043ef1, 0x3f043f80, 0xbf80bef1, 0x3edbbf0e, 0x3f183f7f, 0xbf7dbec4, 0x3eacbf22, 0x3f2c3f7b, 0xbf78be95,
    0x3e79bf35, 0x3f3e3f75, 0xbf71be48, 0x3e16bf46, 0x3f4e3f6d, 0xbf67bdc9, 0x3d49bf55, 0x3f5c3f62, 0xbf7dbec4, 0x3eacbf22,
    0x3f2c3f7b, 0xbf78be95, 0x3f043f80, 0xbf80bef1, 0x3edbbf0e, 0x3f183f7f, 0x3f4e3f6d, 0xbf67bdc9, 0x3d49bf55, 0x3f5c3f62,
    0x3e79bf35, 0x3f3e3f75, 0xbf71be48, 0x3e16bf46, 0x3e163f6d, 0xbf71bf46, 0x3f3ebe48, 0x3e793f75, 0x3f5c0000, 0x3d493f62,
    0xbf67bf55, 0x3f4ebdc9, 0x3f18bec4, 0x3edb3f7f, 0xbf80bf0e, 0x3f04bef1, 0xbf78bf35, 0x3f2cbe95, 0x3eac3f7b, 0xbf7dbf22,
    0x3eacbf35, 0x3f043f7f, 0xbf7dbf0e, 0x3f3ebe95, 0x3d493f6d, 0xbf4ebf62, 0x3f783e48, 0xbedb3f22, 0x3f670000, 0xbe793f46,
    0xbf18bf7b, 0x3f803ef1, 0xbf2c3ec4, 0xbe16bf75, 0x3f5c3f55, 0xbf71bdc9, 0x3f713f35, 0xbf5c3dc9, 0x3e16bf55, 0x3f2c3f75,
    0xbf80bec4, 0x3f18bef1, 0x3e793f7b, 0xbf67bf46, 0x3edb3f80, 0xbf78bf22, 0x3f4ebe48, 0xbd493f62, 0xbf3ebf6d, 0x3f7d3e95,
    0xbf043f0e, 0xbeacbf7f, 0x3f803ec4, 0xbf183ef1, 0xbe79bf7b, 0x3f673f46, 0xbf71bf35, 0x3f5cbdc9, 0xbe163f55, 0xbf2cbf75,
    0x3f3e3f6d, 0xbf7dbe95, 0x3f04bf0e, 0x3eac3f7f, 0xbedbbf80, 0x3f783f22, 0xbf4e3e48, 0x3d49bf62, 0x3d493f6d, 0xbf4ebf62,
    0x3f783e48, 0xbedb3f22, 0x3eacbf35, 0x3f043f7f, 0xbf7dbf0e, 0x3f3ebe95, 0xbf2c3ec4, 0xbe16bf75, 0x3f5c3f55, 0xbf71bdc9,
    0x3f670000, 0xbe793f46, 0xbf18bf7b, 0x3f803ef1, 0x3eac3f80, 0xbf5cbf46, 0x3f7d3e48, 0xbf2c3ef1, 0x3d49bf6d, 0x3f183f75,
    0xbf78bf0e, 0x3f67bdc9, 0xbedb3f35, 0xbe79bf7f, 0x3f4e3f55, 0xbf80be95, 0x3f3ebec4, 0xbe163f62, 0xbf04bf7b, 0x3f713f22,
    0xbf710000, 0x3f04bf22, 0x3e163f7b, 0xbf3ebf62, 0x3f803ec4, 0xbf4e3e95, 0x3e79bf55, 0x3edb3f7f, 0xbf67bf35, 0x3f783dc9,
    0xbf183f0e, 0xbd49bf75, 0x3f2c3f6d, 0xbf7dbef1, 0x3f5cbe48, 0xbeac3f46, 0xbf80bec4, 0x3f4ebe95, 0xbe793f55, 0xbedbbf7f,
    0x3f710000, 0xbf043f22, 0xbe16bf7b, 0x3f3e3f62, 0xbf2cbf6d, 0x3f7d3ef1, 0xbf5c3e48, 0x3eacbf46, 0x3f673f35, 0xbf78bdc9,
    0x3f18bf0e, 0x3d493f75, 0x3d49bf6d, 0x3f183f75, 0xbf78bf0e, 0x3f67bdc9, 0x3eac3f80, 0xbf5cbf46, 0x3f7d3e48, 0xbf2c3ef1,
    0x3f3ebec4, 0xbe163f62, 0xbf04bf7b, 0x3f713f22, 0xbedb3f35, 0xbe79bf7f, 0x3f4e3f55, 0xbf80be95, 0xbf5cbf35, 0x3f803e95,
    0xbf673e48, 0x3f18bf22, 0xbe163f6d, 0xbeacbf7f, 0x3f3e3f55, 0xbf78bef1, 0x3e793f80, 0xbf2cbf62, 0x3f713f0e, 0xbf7dbdc9,
    0x3f4ebec4, 0xbedb3f46, 0xbd49bf7b, 0x3f043f75, 0xbf043f35, 0x3d49bf75, 0x3edb3f7b, 0xbf4ebf46, 0x3f7d3ec4, 0xbf713dc9,
    0x3f2cbf0e, 0xbe793f62, 0x3f780000, 0xbf3e3ef1, 0x3eacbf55, 0x3e163f7f, 0xbf18bf6d, 0x3f673f22, 0xbf80be48, 0x3f5cbe95,
    0x3f7d3ec4, 0xbf713dc9, 0x3f2cbf0e, 0xbe793f62, 0xbf043f35, 0x3d49bf75, 0x3edb3f7b, 0xbf4ebf46, 0xbf18bf6d, 0x3f673f22,
    0xbf80be48, 0x3f5cbe95, 0x3f780000, 0xbf3e3ef1, 0x3eacbf55, 0x3e163f7f, 0x3e16bf6d, 0x3eac3f7f, 0xbf3ebf55, 0x3f783ef1,
    0x3f5c3f35, 0xbf80be95, 0x3f67be48, 0xbf183f22, 0xbf4e3ec4, 0x3edbbf46, 0x3d493f7b, 0xbf04bf75, 0xbe79bf80, 0x3f2c3f62,
    0xbf71bf0e, 0x3f7d3dc9, 0xbf7d0000, 0x3f67be95, 0xbf3e3f0e, 0x3f04bf46, 0xbe793f6d, 0xbd49bf7f, 0x3eac3f7b, 0xbf18bf62,
    0x3f4e3f35, 0xbf71bef1, 0x3f803e48, 0xbf783dc9, 0x3f5cbec4, 0xbf2c3f22, 0x3edbbf55, 0xbe163f75, 0x3e163f80, 0xbedbbf75,
    0x3f2c3f55, 0xbf5cbf22, 0x3f783ec4, 0xbf80bdc9, 0x3f71be48, 0xbf4e3ef1, 0x3f18bf35, 0xbeac3f62, 0x3d49bf7b, 0x3e793f7f,
    0xbf04bf6d, 0x3f3e3f46, 0xbf67bf0e, 0x3f7d3e95, 0x3f783ec4, 0xbf80bdc9, 0x3f71be48, 0xbf4e3ef1, 0x3e163f80, 0xbedbbf75,
    0x3f2c3f55, 0xbf5cbf22, 0xbf04bf6d, 0x3f3e3f46, 0xbf67bf0e, 0x3f7d3e95, 0x3f18bf35, 0xbeac3f62, 0x3d49bf7b, 0x3e793f7f,
    0x3e79bf6d, 0x3d493f7f, 0xbeacbf7b, 0x3f183f62, 0x3f7d0000, 0xbf673e95, 0x3f3ebf0e, 0xbf043f46, 0xbf5c3ec4, 0x3f2cbf22,
    0xbedb3f55, 0x3e16bf75, 0xbf4ebf35, 0x3f713ef1, 0xbf80be48, 0x3f78bdc9, 0x3f2cbf35, 0xbf183f46, 0x3f04bf55, 0xbedb3f62,
    0x3eacbf6d, 0xbe793f75, 0x3e16bf7b, 0xbd493f7f, 0x3f800000, 0xbf7d3dc9, 0x3f78be48, 0xbf713e95, 0x3f67bec4, 0xbf5c3ef1,
    0x3f4ebf0e, 0xbf3e3f22, 0x3f3e3f35, 0xbf4ebf22, 0x3f5c3f0e, 0xbf67bef1, 0x3f713ec4, 0xbf78be95, 0x3f7d3e48, 0xbf80bdc9,
    0x3d493f80, 0xbe16bf7f, 0x3e793f7b, 0xbeacbf75, 0x3edb3f6d, 0xbf04bf62, 0x3f183f55, 0xbf2cbf46, 0xbf71bec4, 0x3f783e95,
    0xbf7dbe48, 0x3f803dc9, 0xbf3ebf35, 0x3f4e3f22, 0xbf5cbf0e, 0x3f673ef1, 0xbedbbf6d, 0x3f043f62, 0xbf18bf55, 0x3f2c3f46,
    0xbd49bf80, 0x3e163f7f, 0xbe79bf7b, 0x3eac3f75, 0x3eacbf6d, 0xbe793f75, 0x3e16bf7b, 0xbd493f7f, 0x3f2cbf35, 0xbf183f46,
    0x3f04bf55, 0xbedb3f62, 0x3f67bec4, 0xbf5c3ef1, 0x3f4ebf0e, 0xbf3e3f22, 0x3f800000, 0xbf7d3dc9, 0x3f78be48, 0xbf713e95,
    0xbd493f80, 0x3e16bf7f, 0xbe793f7b, 0x3eacbf75, 0xbedb3f6d, 0x3f04bf62, 0xbf183f55, 0x3f2cbf46, 0xbf3e3f35, 0x3f4ebf22,
    0xbf5c3f0e, 0x3f67bef1, 0xbf713ec4, 0x3f78be95, 0xbf7d3e48, 0x3f80bdc9, 0xbf800000, 0x3f7d3dc9, 0xbf78be48, 0x3f713e95,
    0xbf67bec4, 0x3f5c3ef1, 0xbf4ebf0e, 0x3f3e3f22, 0xbf2cbf35, 0x3f183f46, 0xbf04bf55, 0x3edb3f62, 0xbeacbf6d, 0x3e793f75,
    0xbe16bf7b, 0x3d493f7f, 0x3f673ec4, 0xbf5cbef1, 0x3f4e3f0e, 0xbf3ebf22, 0x3f800000, 0xbf7dbdc9, 0x3f783e48, 0xbf71be95,
    0x3eac3f6d, 0xbe79bf75, 0x3e163f7b, 0xbd49bf7f, 0x3f2c3f35, 0xbf18bf46, 0x3f043f55, 0xbedbbf62, 0xbedb3f6d, 0x3f04bf62,
    0xbf183f55, 0x3f2cbf46, 0xbd493f80, 0x3e16bf7f, 0xbe793f7b, 0x3eacbf75, 0xbf713ec4, 0x3f78be95, 0xbf7d3e48, 0x3f80bdc9,
    0xbf3e3f35, 0x3f4ebf22, 0xbf5c3f0e, 0x3f67bef1, 0xbf18bf35, 0x3eac3f62, 0xbd49bf7b, 0xbe793f7f, 0x3f04bf6d, 0xbf3e3f46,
    0x3f67bf0e, 0xbf7d3e95, 0xbe163f80, 0x3edbbf75, 0xbf2c3f55, 0x3f5cbf22, 0xbf783ec4, 0x3f80bdc9, 0xbf71be48, 0x3f4e3ef1,
    0xbf4e3f35, 0x3f71bef1, 0xbf803e48, 0x3f783dc9, 0xbf5cbec4, 0x3f2c3f22, 0xbedbbf55, 0x3e163f75, 0x3f7d0000, 0xbf67be95,
    0x3f3e3f0e, 0xbf04bf46, 0x3e793f6d, 0x3d49bf7f, 0xbeac3f7b, 0x3f18bf62, 0xbf5cbec4, 0x3f2c3f22, 0xbedbbf55, 0x3e163f75,
    0xbf4e3f35, 0x3f71bef1, 0xbf803e48, 0x3f783dc9, 0x3e793f6d, 0x3d49bf7f, 0xbeac3f7b, 0x3f18bf62, 0x3f7d0000, 0xbf67be95,
    0x3f3e3f0e, 0xbf04bf46, 0xbf043f6d, 0x3f3ebf46, 0xbf673f0e, 0x3f7dbe95, 0x3f183f35, 0xbeacbf62, 0x3d493f7b, 0x3e79bf7f,
    0x3f78bec4, 0xbf803dc9, 0x3f713e48, 0xbf4ebef1, 0x3e16bf80, 0xbedb3f75, 0x3f2cbf55, 0xbf5c3f22, 0xbf780000, 0x3f3e3ef1,
    0xbeacbf55, 0xbe163f7f, 0x3f18bf6d, 0xbf673f22, 0x3f80be48, 0xbf5cbe95, 0x3f043f35, 0xbd49bf75, 0xbedb3f7b, 0x3f4ebf46,
    0xbf7d3ec4, 0x3f713dc9, 0xbf2cbf0e, 0x3e793f62, 0xbe793f80, 0x3f2cbf62, 0xbf713f0e, 0x3f7dbdc9, 0xbf4ebec4, 0x3edb3f46,
    0x3d49bf7b, 0xbf043f75, 0x3f5cbf35, 0xbf803e95, 0x3f673e48, 0xbf18bf22, 0x3e163f6d, 0x3eacbf7f, 0xbf3e3f55, 0x3f78bef1,
    0xbf4ebec4, 0x3edb3f46, 0x3d49bf7b, 0xbf043f75, 0xbe793f80, 0x3f2cbf62, 0xbf713f0e, 0x3f7dbdc9, 0x3e163f6d, 0x3eacbf7f,
    0xbf3e3f55, 0x3f78bef1, 0x3f5cbf35, 0xbf803e95, 0x3f673e48, 0xbf18bf22, 0xbf183f6d, 0x3f67bf22, 0xbf803e48, 0x3f5c3e95,
    0x3f780000, 0xbf3ebef1, 0x3eac3f55, 0x3e16bf7f, 0x3f7dbec4, 0xbf71bdc9, 0x3f2c3f0e, 0xbe79bf62, 0xbf04bf35, 0x3d493f75,
    0x3edbbf7b, 0xbf4e3f46, 0x3f67bf35, 0xbf783dc9, 0x3f183f0e, 0x3d49bf75, 0xbf2c3f6d, 0x3f7dbef1, 0xbf5cbe48, 0x3eac3f46,
    0x3f710000, 0xbf04bf22, 0xbe163f7b, 0x3f3ebf62, 0xbf803ec4, 0x3f4e3e95, 0xbe79bf55, 0xbedb3f7f, 0x3edb3f35, 0x3e79bf7f,
    0xbf4e3f55, 0x3f80be95, 0xbf3ebec4, 0x3e163f62, 0x3f04bf7b, 0xbf713f22, 0xbeac3f80, 0x3f5cbf46, 0xbf7d3e48, 0x3f2c3ef1,
    0xbd49bf6d, 0xbf183f75, 0x3f78bf0e, 0xbf67bdc9, 0x3f3e3ec4, 0xbe16bf62, 0xbf043f7b, 0x3f71bf22, 0xbedbbf35, 0xbe793f7f,
    0x3f4ebf55, 0xbf803e95, 0x3d493f6d, 0x3f18bf75, 0xbf783f0e, 0x3f673dc9, 0x3eacbf80, 0xbf5c3f46, 0x3f7dbe48, 0xbf2cbef1,
    0xbf2c3f6d, 0x3f7dbef1, 0xbf5cbe48, 0x3eac3f46, 0x3f67bf35, 0xbf783dc9, 0x3f183f0e, 0x3d49bf75, 0xbf803ec4, 0x3f4e3e95,
    0xbe79bf55, 0xbedb3f7f, 0x3f710000, 0xbf04bf22, 0xbe163f7b, 0x3f3ebf62, 0xbedb3f80, 0x3f78bf22, 0xbf4ebe48, 0x3d493f62,
    0x3f3ebf6d, 0xbf7d3e95, 0x3f043f0e, 0x3eacbf7f, 0xbf713f35, 0x3f5c3dc9, 0xbe16bf55, 0xbf2c3f75, 0x3f80bec4, 0xbf18bef1,
    0xbe793f7b, 0x3f67bf46, 0xbf670000, 0x3e793f46, 0x3f18bf7b, 0xbf803ef1, 0x3f2c3ec4, 0x3e16bf75, 0xbf5c3f55, 0x3f71bdc9,
    0xbeacbf35, 0xbf043f7f, 0x3f7dbf0e, 0xbf3ebe95, 0xbd493f6d, 0x3f4ebf62, 0xbf783e48, 0x3edb3f22, 0xbf2cbec4, 0xbe163f75,
    0x3f5cbf55, 0xbf713dc9, 0x3f670000, 0xbe79bf46, 0xbf183f7b, 0x3f80bef1, 0x3d49bf6d, 0xbf4e3f62, 0x3f78be48, 0xbedbbf22,
    0x3eac3f35, 0x3f04bf7f, 0xbf7d3f0e, 0x3f3e3e95, 0x3f3ebf6d, 0xbf7d3e95, 0x3f043f0e, 0x3eacbf7f, 0xbedb3f80, 0x3f78bf22,
    0xbf4ebe48, 0x3d493f62, 0x3f80bec4, 0xbf18bef1, 0xbe793f7b, 0x3f67bf46, 0xbf713f35, 0x3f5c3dc9, 0xbe16bf55, 0xbf2c3f75,
    0xbe79bf35, 0xbf3e3f75, 0x3f71be48, 0xbe16bf46, 0xbf4e3f6d, 0x3f67bdc9, 0xbd49bf55, 0xbf5c3f62, 0xbf043f80, 0x3f80bef1,
    0xbedbbf0e, 0xbf183f7f, 0x3f7dbec4, 0xbeacbf22, 0xbf2c3f7b, 0x3f78be95, 0xbf783f35, 0x3f2c3e95, 0x3eacbf7b, 0xbf7d3f22,
    0x3f183ec4, 0x3edbbf7f, 0xbf803f0e, 0x3f043ef1, 0x3f5c0000, 0x3d49bf62, 0xbf673f55, 0x3f4e3dc9, 0x3e16bf6d, 0xbf713f46,
    0x3f3e3e48, 0x3e79bf75, 0x3f183ec4, 0x3edbbf7f, 0xbf803f0e, 0x3f043ef1, 0xbf783f35, 0x3f2c3e95, 0x3eacbf7b, 0xbf7d3f22,
    0x3e16bf6d, 0xbf713f46, 0x3f3e3e48, 0x3e79bf75, 0x3f5c0000, 0x3d49bf62, 0xbf673f55, 0x3f4e3dc9, 0x3f4ebf6d, 0xbf673dc9,
    0x3d493f55, 0x3f5cbf62, 0x3e793f35, 0x3f3ebf75, 0xbf713e48, 0x3e163f46, 0xbf7d3ec4, 0x3eac3f22, 0x3f2cbf7b, 0xbf783e95,
    0x3f04bf80, 0xbf803ef1, 0x3edb3f0e, 0x3f18bf7f, 0xbf4e0000, 0xbeac3f75, 0x3f80bf0e, 0xbe79bf22, 0xbf5c3f6d, 0x3f3e3dc9,
    0x3edbbf7b, 0xbf7d3ef1, 0x3e163f35, 0x3f67bf62, 0xbf2cbe48, 0xbf043f7f, 0x3f78bec4, 0xbd49bf46, 0xbf713f55, 0x3f183e95,
    0xbf183f80, 0x3f71be95, 0x3d49bf55, 0xbf783f46, 0x3f043ec4, 0x3f2cbf7f, 0xbf673e48, 0xbe163f62, 0x3f7dbf35, 0xbedbbef1,
    0xbf3e3f7b, 0x3f5cbdc9, 0x3e79bf6d, 0xbf803f22, 0x3eac3f0e, 0x3f4ebf75, 0x3f043ec4, 0x3f2cbf7f, 0xbf673e48, 0xbe163f62,
    0xbf183f80, 0x3f71be95, 0x3d49bf55, 0xbf783f46, 0x3e79bf6d, 0xbf803f22, 0x3eac3f0e, 0x3f4ebf75, 0x3f7dbf35, 0xbedbbef1,
    0xbf3e3f7b, 0x3f5cbdc9, 0x3f5cbf6d, 0xbf3ebdc9, 0xbedb3f7b, 0x3f7dbef1, 0x3f4e0000, 0x3eacbf75, 0xbf803f0e, 0x3e793f22,
    0xbf783ec4, 0x3d493f46, 0x3f71bf55, 0xbf18be95, 0xbe16bf35, 0xbf673f62, 0x3f2c3e48, 0x3f04bf7f, 0x3f80bf35, 0xbe16bf22,
    0xbf783f55, 0x3eac3ef1, 0x3f67bf6d, 0xbf04be95, 0xbf4e3f7b, 0x3f2c3dc9, 0x3f3e0000, 0x3f18bf7f, 0xbf5c3e48, 0xbedb3f75,
    0x3f71bec4, 0x3e79bf62, 0xbf7d3f0e, 0xbd493f46, 0x3d493f35, 0x3f7dbf46, 0xbe79bf0e, 0xbf713f62, 0x3edb3ec4, 0x3f5cbf75,
    0xbf18be48, 0xbf3e3f7f, 0xbf2c3f80, 0x3f4ebdc9, 0x3f04bf7b, 0xbf673e95, 0xbeac3f6d, 0x3f78bef1, 0x3e16bf55, 0xbf803f22,
    0xbedbbec4, 0xbf5c3f75, 0x3f183e48, 0x3f3ebf7f, 0xbd49bf35, 0xbf7d3f46, 0x3e793f0e, 0x3f71bf62, 0x3eacbf6d, 0xbf783ef1,
    0xbe163f55, 0x3f80bf22, 0x3f2cbf80, 0xbf4e3dc9, 0xbf043f7b, 0x3f67be95, 0x3f67bf6d, 0xbf04be95, 0xbf4e3f7b, 0x3f2c3dc9,
    0x3f80bf35, 0xbe16bf22, 0xbf783f55, 0x3eac3ef1, 0x3f71bec4, 0x3e79bf62, 0xbf7d3f0e, 0xbd493f46, 0x3f3e0000, 0x3f18bf7f,
    0xbf5c3e48, 0xbedb3f75, 0xbf3e3f80, 0x3f183dc9, 0x3f5cbf7b, 0xbedbbe95, 0xbf713f6d, 0x3e793ef1, 0x3f7dbf55, 0xbd49bf22,
    0xbf803f35, 0xbe163f46, 0x3f78bf0e, 0x3eacbf62, 0xbf673ec4, 0xbf043f75, 0x3f4ebe48, 0x3f2cbf7f, 0xbf2c0000, 0xbf4e3f7f,
    0x3f043e48, 0x3f67bf75, 0xbeacbec4, 0xbf783f62, 0x3e163f0e, 0x3f80bf46, 0x3d49bf35, 0xbf7d3f22, 0xbe793f55, 0x3f71bef1,
    0x3edbbf6d, 0xbf5c3e95, 0xbf183f7b, 0x3f3ebdc9, 0x3eac3ec4, 0x3f78bf62, 0xbe16bf0e, 0xbf803f46, 0x3f2c0000, 0x3f4ebf7f,
    0xbf04be48, 0xbf673f75, 0xbedb3f6d, 0x3f5cbe95, 0x3f18bf7b, 0xbf3e3dc9, 0xbd493f35, 0x3f7dbf22, 0x3e79bf55, 0xbf713ef1,
    0xbf713f6d, 0x3e793ef1, 0x3f7dbf55, 0xbd49bf22, 0xbf3e3f80, 0x3f183dc9, 0x3f5cbf7b, 0xbedbbe95, 0xbf673ec4, 0xbf043f75,
    0x3f4ebe48, 0x3f2cbf7f, 0xbf803f35, 0xbe163f46, 0x3f78bf0e, 0x3eacbf62, 0x3e16bf35, 0xbf673ef1, 0xbf2c3f7b, 0x3f043dc9,
    0x3f78bf6d, 0x3d49bf22, 0xbf713f0e, 0xbf183f75, 0xbf4e3f80, 0x3eac3e95, 0x3f80bf55, 0x3e79bf46, 0xbf5c3ec4, 0xbf3e3f7f,
    0x3edb3e48, 0x3f7dbf62, 0xbf7d3f35, 0xbedb3f62, 0x3f3ebe48, 0x3f5cbf7f, 0xbe79bec4, 0xbf803f46, 0xbeac3f55, 0x3f4ebe95,
    0x3f180000, 0x3f71bf75, 0xbd49bf0e, 0xbf783f22, 0xbf043f6d, 0x3f2cbdc9, 0x3f67bf7b, 0xbe16bef1, 0xbe79bec4, 0xbf803f46,
    0xbeac3f55, 0x3f4ebe95, 0xbf7d3f35, 0xbedb3f62, 0x3f3ebe48, 0x3f5cbf7f, 0xbf043f6d, 0x3f2cbdc9, 0x3f67bf7b, 0xbe16bef1,
    0x3f180000, 0x3f71bf75, 0xbd49bf0e, 0xbf783f22, 0xbf783f6d, 0xbd493f22, 0x3f71bf0e, 0x3f18bf75, 0xbe163f35, 0x3f67bef1,
    0x3f2cbf7b, 0xbf04bdc9, 0x3f5cbec4, 0x3f3ebf7f, 0xbedbbe48, 0xbf7d3f62, 0x3f4ebf80, 0xbeacbe95, 0xbf803f55, 0xbe793f46,
    0xbf040000, 0xbf803f62, 0xbedb3f55, 0x3f18bdc9, 0x3f7dbf6d, 0x3eacbf46, 0xbf2c3e48, 0xbf783f75, 0xbe793f35, 0x3f3ebe95,
    0x3f71bf7b, 0x3e16bf22, 0xbf4e3ec4, 0xbf673f7f, 0xbd493f0e, 0x3f5cbef1, 0xbf5c3f80, 0x3d493ef1, 0x3f67bf0e, 0x3f4ebf7f,
    0xbe16bec4, 0xbf713f22, 0xbf3e3f7b, 0x3e793e95, 0x3f78bf35, 0x3f2cbf75, 0xbeacbe48, 0xbf7d3f46, 0xbf183f6d, 0x3edb3dc9,
    0x3f80bf55, 0x3f04bf62, 0xbe16bec4, 0xbf713f22, 0xbf3e3f7b, 0x3e793e95, 0xbf5c3f80, 0x3d493ef1, 0x3f67bf0e, 0x3f4ebf7f,
    0xbf183f6d, 0x3edb3dc9, 0x3f80bf55, 0x3f04bf62, 0x3f78bf35, 0x3f2cbf75, 0xbeacbe48, 0xbf7d3f46, 0xbf7d3f6d, 0xbeac3f46,
    0x3f2cbe48, 0x3f78bf75, 0x3f040000, 0x3f80bf62, 0x3edbbf55, 0xbf183dc9, 0x3f4ebec4, 0x3f67bf7f, 0x3d49bf0e, 0xbf5c3ef1,
    0x3e79bf35, 0xbf3e3e95, 0xbf713f7b, 0xbe163f22, 0x3f71bf35, 0x3f5cbf7f, 0x3e16bf0e, 0xbf2c3e95, 0xbf803f6d, 0xbf183f62,
    0x3e793e48, 0x3f67bf22, 0x3edb0000, 0x3f78bf46, 0x3f4ebf7b, 0x3d49bef1, 0xbf3e3ec4, 0xbf7d3f75, 0xbf043f55, 0x3eac3dc9,
    0xbeac3f35, 0x3f04bdc9, 0x3f7dbf55, 0x3f3ebf75, 0xbd49bec4, 0xbf4e3ef1, 0xbf783f7b, 0xbedb3f46, 0xbf673f80, 0xbe793f22,
    0x3f18be48, 0x3f80bf62, 0x3f2cbf6d, 0xbe16be95, 0xbf5c3f0e, 0xbf713f7f, 0x3d493ec4, 0x3f4ebef1, 0x3f78bf7b, 0x3edbbf46,
    0x3eacbf35, 0xbf043dc9, 0xbf7d3f55, 0xbf3e3f75, 0xbf2c3f6d, 0x3e163e95, 0x3f5cbf0e, 0x3f71bf7f, 0x3f67bf80, 0x3e79bf22,
    0xbf183e48, 0xbf803f62, 0xbf803f6d, 0xbf183f62, 0x3e793e48, 0x3f67bf22, 0x3f71bf35, 0x3f5cbf7f, 0x3e16bf0e, 0xbf2c3e95,
    0xbf3e3ec4, 0xbf7d3f75, 0xbf043f55, 0x3eac3dc9, 0x3edb0000, 0x3f78bf46, 0x3f4ebf7b, 0x3d49bef1, 0xbf713f80, 0xbf043f46,
    0x3e163e48, 0x3f3ebef1, 0x3f80bf6d, 0x3f4ebf75, 0x3e79bf0e, 0xbedb3dc9, 0xbf673f35, 0xbf783f7f, 0xbf183f55, 0x3d493e95,
    0x3f2cbec4, 0x3f7dbf62, 0x3f5cbf7b, 0x3eacbf22, 0xbeac0000, 0xbf5c3f22, 0xbf7d3f7b, 0xbf2c3f62, 0xbd493ec4, 0x3f18be95,
    0x3f78bf55, 0x3f67bf7f, 0x3edbbf35, 0xbe79bdc9, 0xbf4e3f0e, 0xbf803f75, 0xbf3e3f6d, 0xbe163ef1, 0x3f04be48, 0x3f71bf46,
    0x3d49bec4, 0xbf183e95, 0xbf783f55, 0xbf673f7f, 0x3eac0000, 0x3f5cbf22, 0x3f7dbf7b, 0x3f2cbf62, 0x3f3ebf6d, 0x3e16bef1,
    0xbf043e48, 0xbf713f46, 0xbedb3f35, 0x3e793dc9, 0x3f4ebf0e, 0x3f80bf75, 0x3f80bf6d, 0x3f4ebf75, 0x3e79bf0e, 0xbedb3dc9,
    0xbf713f80, 0xbf043f46, 0x3e163e48, 0x3f3ebef1, 0x3f2cbec4, 0x3f7dbf62, 0x3f5cbf7b, 0x3eacbf22, 0xbf673f35, 0xbf783f7f,
    0xbf183f55, 0x3d493e95, 0x3f04bf35, 0x3d49be95, 0xbedb3e48, 0xbf4e3f22, 0xbf7d3f6d, 0xbf713f7f, 0xbf2c3f55, 0xbe793ef1,
    0xbf783f80, 0xbf3e3f62, 0xbeac3f0e, 0x3e163dc9, 0x3f18bec4, 0x3f67bf46, 0x3f80bf7b, 0x3f5cbf75, 0xbf5c3f35, 0xbf803f75,
    0xbf673f7b, 0xbf183f46, 0xbe163ec4, 0x3eacbdc9, 0x3f3ebf0e, 0x3f78bf62, 0x3e790000, 0x3f2cbef1, 0x3f71bf55, 0x3f7dbf7f,
    0x3f4ebf6d, 0x3edbbf22, 0xbd49be48, 0xbf043e95, 0xbe163ec4, 0x3eacbdc9, 0x3f3ebf0e, 0x3f78bf62, 0xbf5c3f35, 0xbf803f75,
    0xbf673f7b, 0xbf183f46, 0x3f4ebf6d, 0x3edbbf22, 0xbd49be48, 0xbf043e95, 0x3e790000, 0x3f2cbef1, 0x3f71bf55, 0x3f7dbf7f,
    0x3f7dbf6d, 0x3f71bf7f, 0x3f2cbf55, 0x3e79bef1, 0xbf043f35, 0xbd493e95, 0x3edbbe48, 0x3f4ebf22, 0xbf183ec4, 0xbf673f46,
    0xbf803f7b, 0xbf5c3f75, 0x3f78bf80, 0x3f3ebf62, 0x3eacbf0e, 0xbe16bdc9, 0xbe160000, 0xbedb3e95, 0xbf2c3f0e, 0xbf5c3f46,
    0xbf783f6d, 0xbf803f7f, 0xbf713f7b, 0xbf4e3f62, 0xbf183f35, 0xbeac3ef1, 0xbd493e48, 0x3e79bdc9, 0x3f04bec4, 0x3f3ebf22,
    0x3f67bf55, 0x3f7dbf75, 0xbf7d3f80, 0xbf673f75, 0xbf3e3f55, 0xbf043f22, 0xbe793ec4, 0x3d493dc9, 0x3eacbe48, 0x3f18bef1,
    0x3f4ebf35, 0x3f71bf62, 0x3f80bf7b, 0x3f78bf7f, 0x3f5cbf6d, 0x3f2cbf46, 0x3edbbf0e, 0x3e16be95, 0xbe793ec4, 0x3d493dc9,
    0x3eacbe48, 0x3f18bef1, 0xbf7d3f80, 0xbf673f75, 0xbf3e3f55, 0xbf043f22, 0x3f5cbf6d, 0x3f2cbf46, 0x3edbbf0e, 0x3e16be95,
    0x3f4ebf35, 0x3f71bf62, 0x3f80bf7b, 0x3f78bf7f, 0x3f78bf6d, 0x3f80bf7f, 0x3f71bf7b, 0x3f4ebf62, 0x3e160000, 0x3edbbe95,
    0x3f2cbf0e, 0x3f5cbf46, 0xbf043ec4, 0xbf3e3f22, 0xbf673f55, 0xbf7d3f75, 0x3f18bf35, 0x3eacbef1, 0x3d49be48, 0xbe793dc9,
    0x3f3ebf35, 0x3f4ebf46, 0x3f5cbf55, 0x3f67bf62, 0x3f71bf6d, 0x3f78bf75, 0x3f7dbf7b, 0x3f80bf7f, 0x3d490000, 0x3e16bdc9,
    0x3e79be48, 0x3eacbe95, 0x3edbbec4, 0x3f04bef1, 0x3f18bf0e, 0x3f2cbf22, 0xbf2c3f35, 0xbf183f22, 0xbf043f0e, 0xbedb3ef1,
    0xbeac3ec4, 0xbe793e95, 0xbe163e48, 0xbd493dc9, 0xbf803f80, 0xbf7d3f7f, 0xbf783f7b, 0xbf713f75, 0xbf673f6d, 0xbf5c3f62,
    0xbf4e3f55, 0xbf3e3f46, 0x3eacbec4, 0x3e79be95, 0x3e16be48, 0x3d49bdc9, 0x3f2cbf35, 0x3f18bf22, 0x3f04bf0e, 0x3edbbef1,
    0x3f67bf6d, 0x3f5cbf62, 0x3f4ebf55, 0x3f3ebf46, 0x3f80bf80, 0x3f7dbf7f, 0x3f78bf7b, 0x3f71bf75, 0x3f71bf6d, 0x3f78bf75,
    0x3f7dbf7b, 0x3f80bf7f, 0x3f3ebf35, 0x3f4ebf46, 0x3f5cbf55, 0x3f67bf62, 0x3edbbec4, 0x3f04bef1, 0x3f18bf0e, 0x3f2cbf22,
    0x3d490000, 0x3e16bdc9, 0x3e79be48, 0x3eacbe95,
};
__device__ const __align__(128) uint32_t c_ga[1536] = {
    0x00003c80, 0x3bc43c6d, 0x00003c80, 0xbbc4bc6d, 0x00003c80, 0x3c6d3bc4, 0x00003c80, 0xbc6dbbc4, 0x00003c80, 0x3c6dbbc4,
    0x00003c80, 0xbc6d3bc4, 0x00003c80, 0x3bc4bc6d, 0x00003c80, 0xbbc43c6d, 0x3a493c80, 0x3bdb3c67, 0x3bdb3c67, 0xbc3ebc2c,
    0x3b163c7d, 0x3c783b79, 0x3c043c5c, 0xbc7d3b16, 0x3b793c78, 0x3c4ebc18, 0x3c183c4e, 0xbc043c5c, 0x3bac3c71, 0x3a49bc80,
    0x3c2c3c3e, 0x3bac3c71, 0x3ac93c7f, 0x3bf13c62, 0x3c463c22, 0xbc75bb95, 0x3b953c75, 0x3c7f3ac9, 0x3c623bf1, 0xbc463c22,
    0x3bf13c62, 0x3c22bc46, 0x3c753b95, 0x3ac93c7f, 0x3c223c46, 0xbb95bc75, 0x3c7f3ac9, 0x3c623bf1, 0x3b163c7d, 0x3c043c5c,
    0x3c783b79, 0xbc7d3b16, 0x3bdb3c67, 0x3c80ba49, 0x3c80ba49, 0xbbac3c71, 0x3c2c3c3e, 0x3bdbbc67, 0x3c71bbac, 0x3c2c3c3e,
    0x3c5c3c04, 0xbc18bc4e, 0x3c4ebc18, 0x3c78bb79, 0x3b483c7b, 0x3c0e3c55, 0x3c7bbb48, 0xbc553c0e, 0x3c0e3c55, 0x3c7bbb48,
    0x3c55bc0e, 0x3b483c7b, 0x3c553c0e, 0x3b48bc7b, 0x3c0ebc55, 0x3c7b3b48, 0x3c7b3b48, 0xbc55bc0e, 0x3b48bc7b, 0x3c0ebc55,
    0x3b793c78, 0x3c183c4e, 0x3c4ebc18, 0xbc043c5c, 0x3c2c3c3e, 0x3c71bbac, 0x3bdbbc67, 0x3c2c3c3e, 0x3c713bac, 0xba49bc80,
    0xba49bc80, 0x3c67bbdb, 0x3c7dbb16, 0xbc78bb79, 0xbc04bc5c, 0xbb16bc7d, 0x3b953c75, 0x3c223c46, 0x3bf1bc62, 0xbac93c7f,
    0x3c463c22, 0x3c62bbf1, 0xbac9bc7f, 0x3c753b95, 0x3c7f3ac9, 0xbb95bc75, 0xbc22bc46, 0x3bf1bc62, 0x3c62bbf1, 0xbc7f3ac9,
    0xbc75bb95, 0xbc46bc22, 0x3bac3c71, 0x3c2c3c3e, 0x3a49bc80, 0x3bac3c71, 0x3c5c3c04, 0x3c4ebc18, 0xbc18bc4e, 0x3c78bb79,
    0x3c7dbb16, 0xbc04bc5c, 0xbc78bb79, 0xbb16bc7d, 0x3c2cbc3e, 0xbc673bdb, 0xbc673bdb, 0xbc803a49, 0x00003c80, 0x3bc43c6d,
    0x00003c80, 0xbbc4bc6d, 0x00003c80, 0x3c6d3bc4, 0x00003c80, 0xbc6dbbc4, 0x00003c80, 0x3c6dbbc4, 0x00003c80, 0xbc6d3bc4,
    0x00003c80, 0x3bc4bc6d, 0x00003c80, 0xbbc43c6d, 0x3c3e3c2c, 0x3c713bac, 0x3c713bac, 0xbc803a49, 0x3c4e3c18, 0x3c5cbc04,
    0x3c783b79, 0xbc183c4e, 0x3c5c3c04, 0x3b16bc7d, 0x3c7d3b16, 0x3b793c78, 0x3c673bdb, 0xbc2cbc3e, 0x3c803a49, 0x3c673bdb,
    0x3c7fbac9, 0x3c62bbf1, 0x3c22bc46, 0xbb953c75, 0x3c75bb95, 0x3ac9bc7f, 0x3bf1bc62, 0x3c223c46, 0x3c62bbf1, 0xbc46bc22,
    0x3b95bc75, 0x3c7fbac9, 0x3c46bc22, 0xbc753b95, 0x3ac9bc7f, 0x3bf1bc62, 0x3c18bc4e, 0x3b79bc78, 0xbc04bc5c, 0x3c4e3c18,
    0x3bacbc71, 0xbc3ebc2c, 0xbc3ebc2c, 0x3c67bbdb, 0x3a49bc80, 0xbc713bac, 0xbc67bbdb, 0x3a49bc80, 0xbb79bc78, 0xbb163c7d,
    0xbc7dbb16, 0xbc5cbc04, 0xbb48bc7b, 0xbc0ebc55, 0xbc7b3b48, 0x3c55bc0e, 0xbc0ebc55, 0xbc7b3b48, 0xbc553c0e, 0xbb48bc7b,
    0xbc55bc0e, 0xbb483c7b, 0xbc0e3c55, 0xbc7bbb48, 0xbc7bbb48, 0x3c553c0e, 0xbb483c7b, 0xbc0e3c55, 0xbc5cbc04, 0xbc7dbb16,
    0xbb163c7d, 0xbb79bc78, 0xbc80ba49, 0xbbdb3c67, 0x3bac3c71, 0xbc80ba49, 0xbc673bdb, 0x3c3e3c2c, 0x3c3e3c2c, 0xbbac3c71,
    0xbc183c4e, 0x3c5cbc04, 0x3c783b79, 0x3c4e3c18, 0xbc753b95, 0xbc463c22, 0x3c623bf1, 0xbc7fbac9, 0xbc223c46, 0x3bf13c62,
    0x3c7fbac9, 0xbb953c75, 0xbac93c7f, 0x3c75bb95, 0x3c46bc22, 0x3c623bf1, 0x3bf13c62, 0xbac9bc7f, 0x3b95bc75, 0x3c22bc46,
    0xbbdb3c67, 0xba493c80, 0x3c3ebc2c, 0xbbdb3c67, 0x3b793c78, 0x3c7d3b16, 0x3b16bc7d, 0x3c5c3c04, 0x3c4e3c18, 0x3b79bc78,
    0xbc04bc5c, 0x3c18bc4e, 0x3c80ba49, 0xbc71bbac, 0xbc71bbac, 0xbc3ebc2c, 0x00003c80, 0x3bc43c6d, 0x00003c80, 0xbbc4bc6d,
    0x00003c80, 0x3c6d3bc4, 0x00003c80, 0xbc6dbbc4, 0x00003c80, 0x3c6dbbc4, 0x00003c80, 0xbc6d3bc4, 0x00003c80, 0x3bc4bc6d,
    0x00003c80, 0xbbc43c6d, 0x3c80ba49, 0x3c67bbdb, 0x3c67bbdb, 0xbc2c3c3e, 0x3c7dbb16, 0x3b79bc78, 0x3c5cbc04, 0x3b163c7d,
    0x3c78bb79, 0xbc18bc4e, 0x3c4ebc18, 0x3c5c3c04, 0x3c71bbac, 0xbc80ba49, 0x3c3ebc2c, 0x3c71bbac, 0xbac9bc7f, 0xbbf1bc62,
    0xbc46bc22, 0x3c753b95, 0xbb95bc75, 0xbc7fbac9, 0xbc62bbf1, 0x3c46bc22, 0xbbf1bc62, 0xbc223c46, 0xbc75bb95, 0xbac9bc7f,
    0xbc22bc46, 0x3b953c75, 0xbc7fbac9, 0xbc62bbf1, 0xbc7d3b16, 0xbc5c3c04, 0xbb793c78, 0xbb16bc7d, 0xbc673bdb, 0x3a493c80,
    0x3a493c80, 0xbc71bbac, 0xbc3e3c2c, 0x3c673bdb, 0x3bac3c71, 0xbc3e3c2c, 0xbc043c5c, 0x3c4ebc18, 0x3c183c4e, 0x3b793c78,
    0x3b483c7b, 0x3c0e3c55, 0x3c7bbb48, 0xbc553c0e, 0x3c0e3c55, 0x3c7bbb48, 0x3c55bc0e, 0x3b483c7b, 0x3c553c0e, 0x3b48bc7b,
    0x3c0ebc55, 0x3c7b3b48, 0x3c7b3b48, 0xbc55bc0e, 0x3b48bc7b, 0x3c0ebc55, 0x3c78bb79, 0x3c4ebc18, 0xbc18bc4e, 0x3c5c3c04,
    0x3c3ebc2c, 0xbbacbc71, 0xbc67bbdb, 0x3c3ebc2c, 0x3bacbc71, 0xbc803a49, 0xbc803a49, 0xbbdbbc67, 0xbb16bc7d, 0xbb793c78,
    0xbc5c3c04, 0xbc7d3b16, 0xbb95bc75, 0xbc22bc46, 0xbbf13c62, 0x3ac9bc7f, 0xbc46bc22, 0xbc623bf1, 0x3ac93c7f, 0xbc75bb95,
    0xbc7fbac9, 0x3b953c75, 0x3c223c46, 0xbbf13c62, 0xbc623bf1, 0x3c7fbac9, 0x3c753b95, 0x3c463c22, 0xbc713bac, 0xbc3e3c2c,
    0x3c803a49, 0xbc713bac, 0xbc043c5c, 0x3c183c4e, 0x3c4ebc18, 0x3b793c78, 0x3b163c7d, 0x3c5cbc04, 0x3b79bc78, 0x3c7dbb16,
    0x3c3e3c2c, 0xbbdbbc67, 0xbbdbbc67, 0xba49bc80, 0x00003c80, 0x3bc43c6d, 0x00003c80, 0xbbc4bc6d, 0x00003c80, 0x3c6d3bc4,
    0x00003c80, 0xbc6dbbc4, 0x00003c80, 0x3c6dbbc4, 0x00003c80, 0xbc6d3bc4, 0x00003c80, 0x3bc4bc6d, 0x00003c80, 0xbbc43c6d,
    0x3c2cbc3e, 0x3bacbc71, 0x3bacbc71, 0x3a493c80, 0x3c18bc4e, 0xbc04bc5c, 0x3b79bc78, 0x3c4e3c18, 0x3c04bc5c, 0xbc7dbb16,
    0x3b16bc7d, 0x3c78bb79, 0x3bdbbc67, 0xbc3e3c2c, 0x3a49bc80, 0x3bdbbc67, 0xbc7f3ac9, 0xbc623bf1, 0xbc223c46, 0x3b95bc75,
    0xbc753b95, 0xbac93c7f, 0xbbf13c62, 0xbc22bc46, 0xbc623bf1, 0x3c463c22, 0xbb953c75, 0xbc7f3ac9, 0xbc463c22, 0x3c75bb95,
    0xbac93c7f, 0xbbf13c62, 0x3c4e3c18, 0x3c783b79, 0x3c5cbc04, 0xbc183c4e, 0x3c713bac, 0x3c2cbc3e, 0x3c2cbc3e, 0x3bdb3c67,
    0x3c803a49, 0xbbacbc71, 0x3bdbbc67, 0x3c803a49, 0x3c78bb79, 0xbc7dbb16, 0x3b16bc7d, 0x3c04bc5c, 0xbb48bc7b, 0xbc0ebc55,
    0xbc7b3b48, 0x3c55bc0e, 0xbc0ebc55, 0xbc7b3b48, 0xbc553c0e, 0xbb48bc7b, 0xbc55bc0e, 0xbb483c7b, 0xbc0e3c55, 0xbc7bbb48,
    0xbc7bbb48, 0x3c553c0e, 0xbb483c7b, 0xbc0e3c55, 0xbc043c5c, 0xbb163c7d, 0x3c7d3b16, 0xbc783b79, 0xba493c80, 0x3c673bdb,
    0x3c71bbac, 0xba493c80, 0x3bdb3c67, 0x3c2cbc3e, 0x3c2cbc3e, 0x3c713bac, 0x3c4e3c18, 0xbc04bc5c, 0x3b79bc78, 0x3c18bc4e,
    0x3c75bb95, 0x3c46bc22, 0xbc62bbf1, 0x3c7f3ac9, 0x3c22bc46, 0xbbf1bc62, 0xbc7f3ac9, 0x3b95bc75, 0x3ac9bc7f, 0xbc753b95,
    0xbc463c22, 0xbc62bbf1, 0xbbf1bc62, 0x3ac93c7f, 0xbb953c75, 0xbc223c46, 0xbc67bbdb, 0xbc80ba49, 0x3c2c3c3e, 0xbc67bbdb,
    0xbc783b79, 0xbb163c7d, 0x3c7d3b16, 0xbc043c5c, 0xbc183c4e, 0x3c783b79, 0x3c5cbc04, 0x3c4e3c18, 0x3a493c80, 0x3bacbc71,
    0x3bacbc71, 0x3c2cbc3e, 0x3c353c35, 0x3c6d3bc4, 0x3c353c35, 0xbc6dbbc4, 0x3c35bc35, 0xbbc4bc6d, 0x3c35bc35, 0x3bc43c6d,
    0xbc35bc35, 0xbbc43c6d, 0xbc35bc35, 0x3bc4bc6d, 0xbc353c35, 0x3c6dbbc4, 0xbc353c35, 0xbc6d3bc4, 0x3c3e3c2c, 0x3c713bac,
    0x3c713bac, 0xbc803a49, 0x3c18bc4e, 0xbc04bc5c, 0x3b79bc78, 0x3c4e3c18, 0xbc5cbc04, 0xbb163c7d, 0xbc7dbb16, 0xbb79bc78,
    0xbbdb3c67, 0x3c3ebc2c, 0xba493c80, 0xbbdb3c67, 0x3c463c22, 0x3c753b95, 0x3c7fbac9, 0xbc623bf1, 0x3bf1bc62, 0xbc22bc46,
    0xbb95bc75, 0x3c7f3ac9, 0xbc75bb95, 0x3ac93c7f, 0xbc623bf1, 0xbc46bc22, 0xbac93c7f, 0x3bf1bc62, 0x3c223c46, 0x3b953c75,
    0x3c4e3c18, 0x3c783b79, 0x3c5cbc04, 0xbc183c4e, 0x3bacbc71, 0xbc3ebc2c, 0xbc3ebc2c, 0x3c67bbdb, 0xbc80ba49, 0x3bac3c71,
    0xbbdb3c67, 0xbc80ba49, 0x3b793c78, 0x3b16bc7d, 0x3c7d3b16, 0x3c5c3c04, 0x3c553c0e, 0x3c7b3b48, 0x3c0ebc55, 0xbb483c7b,
    0x3b48bc7b, 0xbc55bc0e, 0xbc7bbb48, 0x3c0ebc55, 0xbc7b3b48, 0x3c0e3c55, 0x3b483c7b, 0xbc553c0e, 0x3c0e3c55, 0xbb48bc7b,
    0x3c55bc0e, 0x3c7bbb48, 0x3c5c3c04, 0x3c7d3b16, 0x3b16bc7d, 0x3b793c78, 0x3a49bc80, 0xbc67bbdb, 0xbc713bac, 0x3a49bc80,
    0xbc673bdb, 0x3c3e3c2c, 0x3c3e3c2c, 0xbbac3c71, 0x3c4e3c18, 0xbc04bc5c, 0x3b79bc78, 0x3c18bc4e, 0x3c623bf1, 0x3c7f3ac9,
    0xbb95bc75, 0x3c223c46, 0xbac9bc7f, 0xbc75bb95, 0xbc223c46, 0xbbf1bc62, 0xbc463c22, 0x3c623bf1, 0x3c7f3ac9, 0x3b953c75,
    0x3c753b95, 0xbc46bc22, 0xbbf1bc62, 0xbac9bc7f, 0x3c673bdb, 0x3c803a49, 0xbc2cbc3e, 0x3c673bdb, 0xbb79bc78, 0xbc7dbb16,
    0xbb163c7d, 0xbc5cbc04, 0xbc183c4e, 0x3c783b79, 0x3c5cbc04, 0x3c4e3c18, 0x3c80ba49, 0xbc71bbac, 0xbc71bbac, 0xbc3ebc2c,
    0x3c353c35, 0x3c6d3bc4, 0x3c353c35, 0xbc6dbbc4, 0x3c35bc35, 0xbbc4bc6d, 0x3c35bc35, 0x3bc43c6d, 0xbc35bc35, 0xbbc43c6d,
    0xbc35bc35, 0x3bc4bc6d, 0xbc353c35, 0x3c6dbbc4, 0xbc353c35, 0xbc6d3bc4, 0x3c80ba49, 0x3c67bbdb, 0x3c67bbdb, 0xbc2c3c3e,
    0xbb16bc7d, 0xbc78bb79, 0xbc04bc5c, 0x3c7dbb16, 0xbc783b79, 0x3c183c4e, 0xbc4e3c18, 0xbc5cbc04, 0x3bac3c71, 0x3a49bc80,
    0x3c2c3c3e, 0x3bac3c71, 0x3c22bc46, 0x3b95bc75, 0xbac9bc7f, 0x3bf13c62, 0xbc62bbf1, 0xbc463c22, 0xbc753b95, 0x3ac9bc7f,
    0xbb953c75, 0x3c7fbac9, 0x3bf13c62, 0xbc223c46, 0x3c7f3ac9, 0xbc62bbf1, 0x3c46bc22, 0x3c75bb95, 0xbb16bc7d, 0xbc04bc5c,
    0xbc78bb79, 0x3c7dbb16, 0xbc673bdb, 0x3a493c80, 0x3a493c80, 0xbc71bbac, 0x3c2c3c3e, 0x3bdbbc67, 0x3c71bbac, 0x3c2c3c3e,
    0x3c04bc5c, 0xbc4e3c18, 0xbc18bc4e, 0xbb79bc78, 0xbc55bc0e, 0xbc7bbb48, 0xbc0e3c55, 0x3b48bc7b, 0xbb483c7b, 0x3c553c0e,
    0x3c7b3b48, 0xbc0e3c55, 0x3c7bbb48, 0xbc0ebc55, 0xbb48bc7b, 0x3c55bc0e, 0xbc0ebc55, 0x3b483c7b, 0xbc553c0e, 0xbc7b3b48,
    0xbc783b79, 0xbc4e3c18, 0x3c183c4e, 0xbc5cbc04, 0x3c2c3c3e, 0x3c71bbac, 0x3bdbbc67, 0x3c2c3c3e, 0x3bacbc71, 0xbc803a49,
    0xbc803a49, 0xbbdbbc67, 0xbc7d3b16, 0x3c783b79, 0x3c043c5c, 0x3b163c7d, 0xbbf13c62, 0xbac93c7f, 0x3c75bb95, 0xbc463c22,
    0x3c7fbac9, 0x3b95bc75, 0xbc46bc22, 0x3c62bbf1, 0xbc22bc46, 0xbbf13c62, 0xbac93c7f, 0xbc753b95, 0xbb953c75, 0x3c22bc46,
    0x3c62bbf1, 0x3c7fbac9, 0x3bac3c71, 0x3c2c3c3e, 0x3a49bc80, 0x3bac3c71, 0x3c04bc5c, 0xbc18bc4e, 0xbc4e3c18, 0xbb79bc78,
    0xbc7d3b16, 0x3c043c5c, 0x3c783b79, 0x3b163c7d, 0x3c3e3c2c, 0xbbdbbc67, 0xbbdbbc67, 0xba49bc80, 0x3c353c35, 0x3c6d3bc4,
    0x3c353c35, 0xbc6dbbc4, 0x3c35bc35, 0xbbc4bc6d, 0x3c35bc35, 0x3bc43c6d, 0xbc35bc35, 0xbbc43c6d, 0xbc35bc35, 0x3bc4bc6d,
    0xbc353c35, 0x3c6dbbc4, 0xbc353c35, 0xbc6d3bc4, 0x3c2cbc3e, 0x3bacbc71, 0x3bacbc71, 0x3a493c80, 0xbc4ebc18, 0xbc5c3c04,
    0xbc78bb79, 0x3c18bc4e, 0xbc043c5c, 0x3c7d3b16, 0xbb163c7d, 0xbc783b79, 0x3c673bdb, 0xbc2cbc3e, 0x3c803a49, 0x3c673bdb,
    0xbc46bc22, 0xbc75bb95, 0xbc7f3ac9, 0x3c62bbf1, 0xbbf13c62, 0x3c223c46, 0x3b953c75, 0xbc7fbac9, 0x3c753b95, 0xbac9bc7f,
    0x3c62bbf1, 0x3c463c22, 0x3ac9bc7f, 0xbbf13c62, 0xbc22bc46, 0xbb95bc75, 0xbc183c4e, 0xbb793c78, 0x3c043c5c, 0xbc4ebc18,
    0x3c713bac, 0x3c2cbc3e, 0x3c2cbc3e, 0x3bdb3c67, 0x3a49bc80, 0xbc713bac, 0xbc67bbdb, 0x3a49bc80, 0xbc783b79, 0x3c7d3b16,
    0xbb163c7d, 0xbc043c5c, 0x3c553c0e, 0x3c7b3b48, 0x3c0ebc55, 0xbb483c7b, 0x3b48bc7b, 0xbc55bc0e, 0xbc7bbb48, 0x3c0ebc55,
    0xbc7b3b48, 0x3c0e3c55, 0x3b483c7b, 0xbc553c0e, 0x3c0e3c55, 0xbb48bc7b, 0x3c55bc0e, 0x3c7bbb48, 0x3c04bc5c, 0x3b16bc7d,
    0xbc7dbb16, 0x3c78bb79, 0xbc80ba49, 0xbbdb3c67, 0x3bac3c71, 0xbc80ba49, 0x3bdb3c67, 0x3c2cbc3e, 0x3c2cbc3e, 0x3c713bac,
    0x3c18bc4e, 0xbc5c3c04, 0xbc78bb79, 0xbc4ebc18, 0xbc62bbf1, 0xbc7fbac9, 0x3b953c75, 0xbc22bc46, 0x3ac93c7f, 0x3c753b95,
    0x3c22bc46, 0x3bf13c62, 0x3c46bc22, 0xbc62bbf1, 0xbc7fbac9, 0xbb95bc75, 0xbc75bb95, 0x3c463c22, 0x3bf13c62, 0x3ac93c7f,
    0xbbdb3c67, 0xba493c80, 0x3c3ebc2c, 0xbbdb3c67, 0x3c78bb79, 0x3b16bc7d, 0xbc7dbb16, 0x3c04bc5c, 0xbc4ebc18, 0xbb793c78,
    0x3c043c5c, 0xbc183c4e, 0x3a493c80, 0x3bacbc71, 0x3bacbc71, 0x3c2cbc3e, 0x3c353c35, 0x3c6d3bc4, 0x3c353c35, 0xbc6dbbc4,
    0x3c35bc35, 0xbbc4bc6d, 0x3c35bc35, 0x3bc43c6d, 0xbc35bc35, 0xbbc43c6d, 0xbc35bc35, 0x3bc4bc6d, 0xbc353c35, 0x3c6dbbc4,
    0xbc353c35, 0xbc6d3bc4, 0xba49bc80, 0xbbdbbc67, 0xbbdbbc67, 0x3c3e3c2c, 0xbc7d3b16, 0xbb793c78, 0xbc5c3c04, 0xbb16bc7d,
    0x3b793c78, 0x3c4ebc18, 0x3c183c4e, 0xbc043c5c, 0x3c71bbac, 0xbc80ba49, 0x3c3ebc2c, 0x3c71bbac, 0xbc223c46, 0xbb953c75,
    0x3ac93c7f, 0xbbf1bc62, 0x3c623bf1, 0x3c46bc22, 0x3c75bb95, 0xbac93c7f, 0x3b95bc75, 0xbc7f3ac9, 0xbbf1bc62, 0x3c22bc46,
    0xbc7fbac9, 0x3c623bf1, 0xbc463c22, 0xbc753b95, 0x3c7dbb16, 0x3c5cbc04, 0x3b79bc78, 0x3b163c7d, 0xbbdbbc67, 0xbc803a49,
    0xbc803a49, 0x3bacbc71, 0xbc3e3c2c, 0x3c673bdb, 0x3bac3c71, 0xbc3e3c2c, 0x3c5c3c04, 0xbc18bc4e, 0x3c4ebc18, 0x3c78bb79,
    0xbc55bc0e, 0xbc7bbb48, 0xbc0e3c55, 0x3b48bc7b, 0xbb483c7b, 0x3c553c0e, 0x3c7b3b48, 0xbc0e3c55, 0x3c7bbb48, 0xbc0ebc55,
    0xbb48bc7b, 0x3c55bc0e, 0xbc0ebc55, 0x3b483c7b, 0xbc553c0e, 0xbc7b3b48, 0x3b793c78, 0x3c183c4e, 0x3c4ebc18, 0xbc043c5c,
    0x3c3ebc2c, 0xbbacbc71, 0xbc67bbdb, 0x3c3ebc2c, 0xbc71bbac, 0x3a493c80, 0x3a493c80, 0xbc673bdb, 0x3b163c7d, 0x3b79bc78,
    0x3c5cbc04, 0x3c7dbb16, 0x3bf1bc62, 0x3ac9bc7f, 0xbc753b95, 0x3c46bc22, 0xbc7f3ac9, 0xbb953c75, 0x3c463c22, 0xbc623bf1,
    0x3c223c46, 0x3bf1bc62, 0x3ac9bc7f, 0x3c75bb95, 0x3b95bc75, 0xbc223c46, 0xbc623bf1, 0xbc7f3ac9, 0xbc713bac, 0xbc3e3c2c,
    0x3c803a49, 0xbc713bac, 0x3c5c3c04, 0x3c4ebc18, 0xbc18bc4e, 0x3c78bb79, 0xbb16bc7d, 0xbc5c3c04, 0xbb793c78, 0xbc7d3b16,
    0xbc2c3c3e, 0x3c67bbdb, 0x3c67bbdb, 0x3c80ba49, 0x3c800000, 0x3c6dbbc4, 0x3c800000, 0xbc6d3bc4, 0xbc800000, 0xbbc43c6d,
    0xbc800000, 0x3bc4bc6d, 0x3c800000, 0xbbc4bc6d, 0x3c800000, 0x3bc43c6d, 0xbc800000, 0x3c6d3bc4, 0xbc800000, 0xbc6dbbc4,
    0x3c80ba49, 0x3c67bbdb, 0x3c67bbdb, 0xbc2c3c3e, 0xbc7d3b16, 0xbb793c78, 0xbc5c3c04, 0xbb16bc7d, 0x3c78bb79, 0xbc18bc4e,
    0x3c4ebc18, 0x3c5c3c04, 0xbc713bac, 0x3c803a49, 0xbc3e3c2c, 0xbc713bac, 0x3c7fbac9, 0x3c62bbf1, 0x3c22bc46, 0xbb953c75,
    0xbc753b95, 0xbac93c7f, 0xbbf13c62, 0xbc22bc46, 0x3c62bbf1, 0xbc46bc22, 0x3b95bc75, 0x3c7fbac9, 0xbc463c22, 0x3c75bb95,
    0xbac93c7f, 0xbbf13c62, 0x3c7dbb16, 0x3c5cbc04, 0x3b79bc78, 0x3b163c7d, 0xbc673bdb, 0x3a493c80, 0x3a493c80, 0xbc71bbac,
    0x3c3ebc2c, 0xbc67bbdb, 0xbbacbc71, 0x3c3ebc2c, 0xbc043c5c, 0x3c4ebc18, 0x3c183c4e, 0x3b793c78, 0x3c7bbb48, 0x3c55bc0e,
    0xbb48bc7b, 0x3c0e3c55, 0xbc553c0e, 0x3b483c7b, 0x3c0e3c55, 0xbc7b3b48, 0x3c0ebc55, 0xbc7bbb48, 0xbc55bc0e, 0x3b48bc7b,
    0xbb483c7b, 0x3c0ebc55, 0x3c7b3b48, 0x3c553c0e, 0x3c78bb79, 0x3c4ebc18, 0xbc18bc4e, 0x3c5c3c04, 0xbc3e3c2c, 0x3bac3c71,
    0x3c673bdb, 0xbc3e3c2c, 0x3bacbc71, 0xbc803a49, 0xbc803a49, 0xbbdbbc67, 0x3b163c7d, 0x3b79bc78, 0x3c5cbc04, 0x3c7dbb16,
    0x3c75bb95, 0x3c46bc22, 0xbc62bbf1, 0x3c7f3ac9, 0xbc223c46, 0x3bf13c62, 0x3c7fbac9, 0xbb953c75, 0x3ac9bc7f, 0xbc753b95,
    0xbc463c22, 0xbc62bbf1, 0x3bf13c62, 0xbac9bc7f, 0x3b95bc75, 0x3c22bc46, 0x3c71bbac, 0x3c3ebc2c, 0xbc80ba49, 0x3c71bbac,
    0xbc043c5c, 0x3c183c4e, 0x3c4ebc18, 0x3b793c78, 0xbb16bc7d, 0xbc5c3c04, 0xbb793c78, 0xbc7d3b16, 0x3c3e3c2c, 0xbbdbbc67,
    0xbbdbbc67, 0xba49bc80, 0x3c800000, 0x3c6dbbc4, 0x3c800000, 0xbc6d3bc4, 0xbc800000, 0xbbc43c6d, 0xbc800000, 0x3bc4bc6d,
    0x3c800000, 0xbbc4bc6d, 0x3c800000, 0x3bc43c6d, 0xbc800000, 0x3c6d3bc4, 0xbc800000, 0xbc6dbbc4, 0x3c2cbc3e, 0x3bacbc71,
    0x3bacbc71, 0x3a493c80, 0xbc183c4e, 0x3c043c5c, 0xbb793c78, 0xbc4ebc18, 0x3c04bc5c, 0xbc7dbb16, 0x3b16bc7d, 0x3c78bb79,
    0xbbdb3c67, 0x3c3ebc2c, 0xba493c80, 0xbbdb3c67, 0xbac9bc7f, 0xbbf1bc62, 0xbc46bc22, 0x3c753b95, 0x3b953c75, 0x3c7f3ac9,
    0x3c623bf1, 0xbc463c22, 0xbbf1bc62, 0xbc223c46, 0xbc75bb95, 0xbac9bc7f, 0x3c223c46, 0xbb95bc75, 0x3c7f3ac9, 0x3c623bf1,
    0xbc4ebc18, 0xbc78bb79, 0xbc5c3c04, 0x3c18bc4e, 0x3c713bac, 0x3c2cbc3e, 0x3c2cbc3e, 0x3bdb3c67, 0xbc80ba49, 0x3bac3c71,
    0xbbdb3c67, 0xbc80ba49, 0x3c78bb79, 0xbc7dbb16, 0x3b16bc7d, 0x3c04bc5c, 0xbc7b3b48, 0xbc553c0e, 0x3b483c7b, 0xbc0ebc55,
    0x3c55bc0e, 0xbb48bc7b, 0xbc0ebc55, 0x3c7bbb48, 0xbc0e3c55, 0x3c7b3b48, 0x3c553c0e, 0xbb483c7b, 0x3b48bc7b, 0xbc0e3c55,
    0xbc7bbb48, 0xbc55bc0e, 0xbc043c5c, 0xbb163c7d, 0x3c7d3b16, 0xbc783b79, 0x3a49bc80, 0xbc67bbdb, 0xbc713bac, 0x3a49bc80,
    0x3bdb3c67, 0x3c2cbc3e, 0x3c2cbc3e, 0x3c713bac, 0xbc4ebc18, 0x3c043c5c, 0xbb793c78, 0xbc183c4e, 0x3b953c75, 0x3c223c46,
    0x3bf1bc62, 0xbac93c7f, 0xbc46bc22, 0xbc623bf1, 0x3ac93c7f, 0xbc75bb95, 0x3c7f3ac9, 0xbb95bc75, 0xbc22bc46, 0x3bf1bc62,
    0xbc623bf1, 0x3c7fbac9, 0x3c753b95, 0x3c463c22, 0x3c673bdb, 0x3c803a49, 0xbc2cbc3e, 0x3c673bdb, 0xbc783b79, 0xbb163c7d,
    0x3c7d3b16, 0xbc043c5c, 0x3c18bc4e, 0xbc78bb79, 0xbc5c3c04, 0xbc4ebc18, 0x3a493c80, 0x3bacbc71, 0x3bacbc71, 0x3c2cbc3e,
    0x3c800000, 0x3c6dbbc4, 0x3c800000, 0xbc6d3bc4, 0xbc800000, 0xbbc43c6d, 0xbc800000, 0x3bc4bc6d, 0x3c800000, 0xbbc4bc6d,
    0x3c800000, 0x3bc43c6d, 0xbc800000, 0x3c6d3bc4, 0xbc800000, 0xbc6dbbc4, 0xba49bc80, 0xbbdbbc67, 0xbbdbbc67, 0x3c3e3c2c,
    0x3b163c7d, 0x3c783b79, 0x3c043c5c, 0xbc7d3b16, 0xbb79bc78, 0xbc4e3c18, 0xbc18bc4e, 0x3c04bc5c, 0x3bac3c71, 0x3a49bc80,
    0x3c2c3c3e, 0x3bac3c71, 0xbc7f3ac9, 0xbc623bf1, 0xbc223c46, 0x3b95bc75, 0x3c75bb95, 0x3ac9bc7f, 0x3bf1bc62, 0x3c223c46,
    0xbc623bf1, 0x3c463c22, 0xbb953c75, 0xbc7f3ac9, 0x3c46bc22, 0xbc753b95, 0x3ac9bc7f, 0x3bf1bc62, 0x3b163c7d, 0x3c043c5c,
    0x3c783b79, 0xbc7d3b16, 0xbbdbbc67, 0xbc803a49, 0xbc803a49, 0x3bacbc71, 0x3c2c3c3e, 0x3bdbbc67, 0x3c71bbac, 0x3c2c3c3e,
    0xbc5cbc04, 0x3c183c4e, 0xbc4e3c18, 0xbc783b79, 0x3c7bbb48, 0x3c55bc0e, 0xbb48bc7b, 0x3c0e3c55, 0xbc553c0e, 0x3b483c7b,
    0x3c0e3c55, 0xbc7b3b48, 0x3c0ebc55, 0xbc7bbb48, 0xbc55bc0e, 0x3b48bc7b, 0xbb483c7b, 0x3c0ebc55, 0x3c7b3b48, 0x3c553c0e,
    0xbb79bc78, 0xbc18bc4e, 0xbc4e3c18, 0x3c04bc5c, 0x3c2c3c3e, 0x3c71bbac, 0x3bdbbc67, 0x3c2c3c3e, 0xbc71bbac, 0x3a493c80,
    0x3a493c80, 0xbc673bdb, 0x3c7dbb16, 0xbc78bb79, 0xbc04bc5c, 0xbb16bc7d, 0xbc753b95, 0xbc463c22, 0x3c623bf1, 0xbc7fbac9,
    0x3c22bc46, 0xbbf1bc62, 0xbc7f3ac9, 0x3b95bc75, 0xbac93c7f, 0x3c75bb95, 0x3c46bc22, 0x3c623bf1, 0xbbf1bc62, 0x3ac93c7f,
    0xbb953c75, 0xbc223c46, 0x3bac3c71, 0x3c2c3c3e, 0x3a49bc80, 0x3bac3c71, 0xbc5cbc04, 0xbc4e3c18, 0x3c183c4e, 0xbc783b79,
    0x3c7dbb16, 0xbc04bc5c, 0xbc78bb79, 0xbb16bc7d, 0xbc2c3c3e, 0x3c67bbdb, 0x3c67bbdb, 0x3c80ba49, 0x3c800000, 0x3c6dbbc4,
    0x3c800000, 0xbc6d3bc4, 0xbc800000, 0xbbc43c6d, 0xbc800000, 0x3bc4bc6d, 0x3c800000, 0xbbc4bc6d, 0x3c800000, 0x3bc43c6d,
    0xbc800000, 0x3c6d3bc4, 0xbc800000, 0xbc6dbbc4, 0xbc3ebc2c, 0xbc71bbac, 0xbc71bbac, 0x3c80ba49, 0x3c4e3c18, 0x3c5cbc04,
    0x3c783b79, 0xbc183c4e, 0xbc5cbc04, 0xbb163c7d, 0xbc7dbb16, 0xbb79bc78, 0x3c673bdb, 0xbc2cbc3e, 0x3c803a49, 0x3c673bdb,
    0x3ac93c7f, 0x3bf13c62, 0x3c463c22, 0xbc75bb95, 0xbb95bc75, 0xbc7fbac9, 0xbc62bbf1, 0x3c46bc22, 0x3bf13c62, 0x3c22bc46,
    0x3c753b95, 0x3ac93c7f, 0xbc22bc46, 0x3b953c75, 0xbc7fbac9, 0xbc62bbf1, 0x3c18bc4e, 0x3b79bc78, 0xbc04bc5c, 0x3c4e3c18,
    0xbbac3c71, 0x3c3e3c2c, 0x3c3e3c2c, 0xbc673bdb, 0x3a49bc80, 0xbc713bac, 0xbc67bbdb, 0x3a49bc80, 0x3b793c78, 0x3b16bc7d,
    0x3c7d3b16, 0x3c5c3c04, 0xbc7b3b48, 0xbc553c0e, 0x3b483c7b, 0xbc0ebc55, 0x3c55bc0e, 0xbb48bc7b, 0xbc0ebc55, 0x3c7bbb48,
    0xbc0e3c55, 0x3c7b3b48, 0x3c553c0e, 0xbb483c7b, 0x3b48bc7b, 0xbc0e3c55, 0xbc7bbb48, 0xbc55bc0e, 0x3c5c3c04, 0x3c7d3b16,
    0x3b16bc7d, 0x3b793c78, 0xbc80ba49, 0xbbdb3c67, 0x3bac3c71, 0xbc80ba49, 0x3c67bbdb, 0xbc3ebc2c, 0xbc3ebc2c, 0x3bacbc71,
    0xbc183c4e, 0x3c5cbc04, 0x3c783b79, 0x3c4e3c18, 0xbb95bc75, 0xbc22bc46, 0xbbf13c62, 0x3ac9bc7f, 0x3c463c22, 0x3c62bbf1,
    0xbac9bc7f, 0x3c753b95, 0xbc7fbac9, 0x3b953c75, 0x3c223c46, 0xbbf13c62, 0x3c62bbf1, 0xbc7f3ac9, 0xbc75bb95, 0xbc46bc22,
    0xbbdb3c67, 0xba493c80, 0x3c3ebc2c, 0xbbdb3c67, 0xbb79bc78, 0xbc7dbb16, 0xbb163c7d, 0xbc5cbc04, 0x3c4e3c18, 0x3b79bc78,
    0xbc04bc5c, 0x3c18bc4e, 0xbc803a49, 0x3c713bac, 0x3c713bac, 0x3c3e3c2c,
};

__device__ __forceinline__ void store_tile_64(const float (&d)[32], uint32_t base, int warp, int lane) {
  const int row = warp * 16 + (lane & 7) + ((lane >> 3) & 1) * 8;
  const uint32_t rb = base + row * 128;
#pragma unroll
  for (int j = 0; j < 8; j += 2) {
    const int jj = j + (lane >> 4);
    stsm4(rb + ((jj ^ (lane & 7)) << 4), pack2(d[4 * j], d[4 * j + 1]), pack2(d[4 * j + 2], d[4 * j + 3]),
          pack2(d[4 * j + 4], d[4 * j + 5]), pack2(d[4 * j + 6], d[4 * j + 7]));
  }
}

#define PLACE 0
#define G_EPI 3
#define W2_PF 1
constexpr int A_IN = 112 * 128;
constexpr int G_ST = 2 * NB1 * 64;
constexpr int K1_R = 131072, K1_BAR = K1_R + 98304, K1_SMEM = K1_BAR + 2048 + 1024;
constexpr int K1_T = K1_R + 65536, K1_TIN = G_ST, K1_Y0 = 3 * G_ST + 8192;
__device__ int g_done[8 * 32];

__host__ __device__ constexpr int g_depth(int s) { return s < 9 ? 3 : s < 18 ? 4 : s < 23 ? 5 : 6; }
__host__ __device__ constexpr int g_slot(int s) { return s < 3 ? s : g_depth(s) != g_depth(s - 1) ? g_depth(s - 1) : g_slot(s - g_depth(s)); }
__host__ __device__ constexpr int g_off(int id) { return id * G_ST + (id < 3 ? K1_R : id == 3 ? -3 * G_ST : 8192 - 3 * G_ST); }
struct Plan {
  uint32_t raw[32];
  uint32_t x[16];
  uint32_t grp[8];
  uint32_t last;
  uint32_t wpf;
  uint32_t g0;
  uint32_t tmask;
  uint64_t list[2];
};
struct K1Maps {
  Plan p;
  CUtensorMap x, we, wo, xs, y, w2e, w2o, w2s;
  int slot[32];
  int src[32];
  int dep[32];
};
__device__ __forceinline__ void poll_ge(const int* p, int target) {
  for (int it = 0; it < (1 << 20); it++) {
    int v;
    asm volatile("ld.acquire.gpu.global.s32 %0, [%1];" : "=r"(v) : "l"(p) : "memory");
    if (v >= target) break;
  }
}
__device__ __forceinline__ uint32_t place(int rank, uint32_t c) { return (c ^ (rank * 4 & ~(c >> 1))) << 14; }
__device__ __forceinline__ int x_unit(int cta, int u, uint32_t pl) {
  const int i = u * 128 + cta;
  const int pr = cta >= 128 ? 2 * cta - 96 + (u & 1) : i % 160, sl = cta >= 128 ? u >> 1 : i / 160, b = pr >= 84;
  return pr | sl << 8 | b << 11 | (cta >= 128 ? (u & 7) << 14 : place(cta & 1, pl & 15)) | 12 * (pr - 84 * b) << 20;
}
__device__ __forceinline__ int lds32(uint32_t a) {
  int v;
  asm volatile("ld.shared.b32 %0, [%1];" : "=r"(v) : "r"(a));
  return v;
}
__host__ __device__ constexpr uint64_t sched(const char* p) {
  uint64_t r = 0;
  for (int n = 0; p[n]; n++) r |= (uint64_t)(p[n] - '0' + 1) << (5 * n);
  return r;
}

__global__ void __cluster_dims__(2, 1, 1) __launch_bounds__(384, 1)
k1(const __grid_constant__ K1Maps m, const char* __restrict__ x1, const char* __restrict__ w1, const __nv_bfloat16* __restrict__ g,
   const __nv_bfloat16* __restrict__ wgt) {
  extern __shared__ __align__(1024) uint8_t smem_k1[];
  const uint32_t sb = s2u(smem_k1);
  const int tid = threadIdx.x, wg = __shfl_sync(0xffffffffu, tid >> 7, 0), t = tid & 127;
  const int warp = __shfl_sync(0xffffffffu, t >> 5, 0), lane = t & 31;
  const int cta = blockIdx.x, rank = cta & 1;
  const bool spare = cta >= 128;
  const int nx = spare ? 16 : 10;
  int bp, dc;
  {
    const int ci = cta >> 1;
    const int G = ci < 4 ? 0 : ci < 36 ? (ci - 4) & 7 : 1 + (ci - 36) % 7;
    const int li = ci < 4 ? 4 + ci : ci < 36 ? (ci - 4) >> 3 : 4 + (ci - 36) / 7;
    if (PLACE == 0) { bp = 2 * G + (li >> 2); dc = li & 3; }
    else if (PLACE == 1) { bp = (G >> 1) * 4 + (li >> 1); dc = (G & 1) * 2 + (li & 1); }
    else { bp = (G >> 2) * 8 + li; dc = G & 3; }
  }
  const int bin = 2 * bp + rank;
  const uint32_t bb = sb + K1_BAR;
  const uint32_t rfull = bb, xfull = bb + 256, xfree = bb + 384, gfull = bb + 512, win = bb + 768;
  const uint32_t inf0 = win + 16, se0 = inf0 + 16, pfree = se0 + 16, rempty = bb + 1024, xready = bb + 1280;
  const uint32_t gdone = bb + 1536, ine0 = gdone + 224, sf0 = ine0 + 16;
  const uint32_t xtab = bb + 896, tab = bb + 1792, ptab = bb + 2048 + 768;
  auto raw_load = [&](int j, uint32_t dst) {
    mbar_expect(rfull + 8 * j, 16384);
    tma_ld4<0>(dst, rank ? &m.we : &m.wo, rfull + 8 * j, dc * 64, rank - 1, (j & 3) * 4, (j >> 2) * 2);
  };
  auto x_half = [&](int u, int c, int h) {
    tma_ld4<1>(sb + (c & 0x3C000) + h * (A_IN / 2), &m.x, xfull + 8 * u, 0, (c >> 17 & ~7) - 24 + h * 56, c >> 8 & 7, c >> 11 & 1);
  };
  auto w_prefetch = [&](int q) {
    if (cta < 124) asm volatile("cp.async.bulk.prefetch.L2.global [%0], 4096;" ::"l"(w1 + (cta >> 2) * 131072 + (q * 4 + (cta & 3)) * 4096) : "memory");
  };
  uint32_t peer;
  asm("mapa.shared::cluster.u32 %0, %1, %2;" : "=r"(peer) : "r"(sb), "r"(rank ^ 1));
  if (wg == 2) {
    if (lane == 0) {
      if (warp < 2) {
        for (int i = 0; i < 4; i++) mbar_init(bb + 256 * warp + 8 * i, 1);
        fence_bar_init();
        fence_async();
        if (warp == 1) {
          const int c = x_unit(cta, 0, m.p.x[0]);
          mbar_expect(xfull, A_IN);
          x_half(0, c, 0);
          x_half(0, c, 1);
        } else if (!spare) {
#pragma unroll 1
          for (int j = 0; j < 4; j++) raw_load(j, sb + K1_R + j * 16384);
        }
      } else if (warp == 2) {
#pragma unroll 1
        for (int q = 1; q <= m.p.wpf; q++) w_prefetch(q);
        prefetch_map(&m.xs);
      }
    }
    if (warp == 3) {
      const uint32_t v = reinterpret_cast<const uint32_t*>(&m.p)[32 + lane];
      asm volatile("st.shared.b32 [%0], %1;" ::"r"(ptab + 4 * lane), "r"(m.p.raw[lane]) : "memory");
      asm volatile("st.shared.b32 [%0], %1;" ::"r"(ptab + 128 + 4 * lane), "r"(v) : "memory");
      if (lane < 16) asm volatile("st.shared.b32 [%0], %1;" ::"r"(xtab + 4 * lane), "r"(x_unit(cta, lane, v)) : "memory");
    }
  } else {
    if (lane < 16)
      asm volatile("st.shared.u16 [%0], %1;" ::"r"(tab + (tid >> 5) * 32 + lane * 2),
                   "h"(__bfloat16_as_ushort(__float2bfloat16_rn(cospif((float)((tid >> 5) * 16 + lane) * (1.0f / 64.0f))))) : "memory");
    const int c = 4 * wg + warp;
    if (lane == 0 && c < 7) {
      const uint32_t b0 = bb + 256 * c, n = c < 4 ? 1 : c < 6 ? 4 : 8;
      if (c >= 2)
        for (int i = 0; i < 4; i++) mbar_init(b0 + 8 * i, n);
      for (int i = 4; i < 16; i++) mbar_init(b0 + 8 * i, n);
      if (c == 3) {
        mbar_expect(win, 65536);
        mbar_arrive(win + 8);
      } else {
        for (int i = 16; i < 32; i++) mbar_init(b0 + 8 * i, n);
      }
      fence_bar_init();
    }
  }
  pdl_launch();
  __syncthreads();
  asm volatile("barrier.cluster.arrive.relaxed.aligned;" ::: "memory");
  if (wg == 2) {
    asm volatile("setmaxnreg.dec.sync.aligned.u32 40;");
    asm volatile("barrier.cluster.wait.aligned;" ::: "memory");
    if (lane == 0) {
      const int wpf = lds32(ptab + 228), g0 = lds32(ptab + 232), s0 = g0 * 4 / 5;
      const int nx0 = spare ? 2 * s0 : g0;
      if (warp == 0) {
        if (!spare) {
#pragma unroll 1
          for (int j = 4; j < 32; j++) {
            const uint32_t e = lds32(ptab + 4 * j);
            mbar_wait(bb + (e >> 5 & ~7), 0);
            raw_load(j, sb + place(rank, e & 15));
            if ((j & 3) == 0 && wpf && (j >> 2) + wpf < 8) w_prefetch((j >> 2) + wpf);
          }
#pragma unroll 1
          for (int s = 0; s < 32; s++) {
            if (s == 0 || s == 4 * s0) {
              poll_ge(&g_done[(s ? 5 : 4) * 32], 132);
              asm volatile("fence.proxy.async.global;" ::: "memory");
              mbar_wait(bb + 8 * (lds32(ptab + 224) & 255), 0);
            }
            const uint32_t bar = gfull + 8 * s, dst = sb + 16 * m.slot[s];
            const char* src = x1 + bin * (4 * G_ST) + m.src[s];
            mbar_wait(bb + m.dep[s], 0);
            mbar_expect(bar, G_ST);
#pragma unroll
            for (int h = 0; h < 2; h++)
              asm volatile("cp.async.bulk.shared::cluster.global.mbarrier::complete_tx::bytes [%0], [%1], %2, [%3];"
                           ::"r"(dst + h * (G_ST / 2)), "l"(src + h * (s < 26 ? G_ST / 2 : 2 * G_ST)), "n"(G_ST / 2), "r"(bar) : "memory");
          }
          if (cta == 0) asm volatile("cp.async.bulk.prefetch.L2.global [%0], 14336;" ::"l"(c_img) : "memory");
        }
      } else if (warp < 3) {
        const int u0 = warp == 1 ? 0 : nx0, u1 = warp == 1 ? nx0 : nx;
#pragma unroll 1
        for (int u = u0; u < u1; u++) {
          const int c = lds32(xtab + 4 * u);
          const uint32_t e = spare ? 0xC0 : lds32(ptab + 128 + 4 * u);
          const uint32_t src = sb + (c & 0x3C000), rel = e >> 1 & 24, burst = (16 << (e >> 6 & 3)) - 1;
          mbar_wait(xready + 8 * u, 0);
#pragma unroll 1
          for (int p = 0; p < 128; p += 16) {
            tma_st4<0>(&m.xs, src + p * 128, 0, (c >> 2 & 0x1C0) + (p & 63), p >> 6, c & 255);
            if (((p + 16) & burst) == 0) {
              bulk_commit();
              bulk_wait_read<0>();
            }
          }
          mbar_arrive(xfree + 8 * u);
          if (rel)
            asm volatile("mbarrier.arrive.shared::cluster.b64 _, [%0];" ::"r"(peer + (pfree - sb) + rel) : "memory");
        }
        asm volatile("cp.async.bulk.wait_group 0;" ::: "memory");
        asm volatile("red.release.gpu.global.add.s32 [%0], 1;" ::"l"(&g_done[(3 + warp) * 32]) : "memory");
        if (!spare) {
          if (warp == 1) {
            auto w2_row = [&](int it, bool pf) {
              const CUtensorMap* mp = it < 4 ? &m.w2o : &m.w2e;
              const int c1 = it < 4 ? -1 : 0, c2 = (cta & 1) * 2, c3 = (it & 3) * 64 + (cta >> 1);
              if (pf) {
                asm volatile("cp.async.bulk.prefetch.tensor.4d.L2.global [%0, {%1, %2, %3, %4}];" ::"l"(mp), "r"(0), "r"(c1), "r"(c2), "r"(c3) : "memory");
              } else {
                mbar_expect(inf0 + 8 * (it & 1), 4096);
                tma_ld4<1>(sb + K1_TIN + (it & 1) * 4096, mp, inf0 + 8 * (it & 1), 0, c1, c2, c3);
              }
            };
#pragma unroll 1
            for (int it = 0; it < 8; it++) {
              mbar_wait(gdone + 8 * it, 0);
              if (W2_PF) w2_row(it, true);
            }
#pragma unroll 1
            for (int it = 0; it < 8; it++) {
              if (it >= 2) mbar_wait(ine0 + 8 * (it & 1), ((it >> 1) - 1) & 1);
              w2_row(it, false);
            }
          } else {
            prefetch_map(&m.w2s);
            prefetch_map(&m.y);
#pragma unroll 1
            for (int it = 0; it < 8; it++) {
              mbar_wait(sf0 + 8 * (it & 1), (it >> 1) & 1);
              if (it >= 2) poll_ge(&g_done[((0x33210000 >> (4 * it)) & 3) * 32], 128);
              tma_st4<0>(&m.w2s, sb + K1_T + (it & 1) * 16384, 0, it * 64, (cta & 1) * 2, (cta >> 1 & 33) | (cta >> 3 & 6) | (cta << 1 & 24));
              bulk_commit();
              bulk_wait_read<0>();
              mbar_arrive(se0 + 8 * (it & 1));
            }
          }
        }
      } else {
#pragma unroll 1
        for (int u = 1; u < nx; u++) {
          const int c = lds32(xtab + 4 * u);
          const uint32_t e = spare ? (u < 8 ? 97 : 40 + u) * 0x01010100u : lds32(ptab + 128 + 4 * u);
          mbar_wait(bb + (e >> 5 & 0x7F8), 0);
          mbar_expect(xfull + 8 * u, A_IN);
          mbar_wait(bb + (e >> 13 & 0x7F8), 0);
          x_half(u, c, 0);
          mbar_wait(bb + (e >> 21 & 0x7F8), 0);
          x_half(u, c, 1);
        }
#pragma unroll 1
        for (int s = 0; s < (spare ? 0 : 16); s++) {
          mbar_wait(gfull + 8 * s, 0);
          if ((s & 3) == 3) asm volatile("red.relaxed.gpu.global.add.s32 [%0], 1;" ::"l"(&g_done[(s >> 2) * 32]) : "memory");
        }
      }
    }
  } else {
    asm volatile("setmaxnreg.inc.sync.aligned.u32 232;");
    auto dft2 = [&](int k2, int f2) {
      uint16_t a, b;
      asm volatile("ld.shared.u16 %0, [%1];" : "=h"(a) : "r"(tab | (k2 & 254)));
      asm volatile("ld.shared.u16 %0, [%1];" : "=h"(b) : "r"(tab | ((k2 + f2) & 254)));
      uint32_t r;
      asm("mov.b32 %0, {%1, %2};" : "=r"(r) : "h"(a), "h"(b));
      return r;
    };
    const int row = (lane & 7) + ((lane >> 3) & 1) * 8, hi = lane >> 4;
    asm volatile("barrier.cluster.wait.aligned;" ::: "memory");
    uint32_t fw[4];
    {
      uint32_t fa[16], za[64];
      bool first = true;
      const int rho = (lane >> 3) | (lane & 4);
      const int z2 = 2 * ((4 * bp + warp) | 1), zk = z2 * (lane & 3) * 2 - (warp & 1) * 64;
      const uint32_t lo = dft2(zk, z2), hh = dft2(zk + 8 * z2, z2);
#pragma unroll
      for (int i = 0; i < 64; i++) za[i] = ((i & 1) == (i >> 5) && rho == ((i >> 2) & 7)) ? ((i & 2) ? hh : lo) : 0u;
      reg_fence(za);
      const bool own = (warp >> 1) == rank;
      float d[64];
      constexpr uint64_t s2 = sched("02468:<>"), s3 = sched("13579;=?");
#pragma unroll 1
      for (uint64_t sc = spare ? (wg ? s3 : s2) : m.p.list[wg]; sc; sc >>= 5) {
        const int item = (int)sc & 31;
        if (item >= 18) {
          const int q = item - 18;
          const uint32_t e = __shfl_sync(0xffffffffu, lds32(ptab + 192 + 4 * q), 0);
#pragma unroll
          for (int jj = 0; jj < 4; jj++) {
            const int j = 4 * q + jj;
            mbar_wait(rfull + 8 * j, 0);
            wg_fence();
#pragma unroll
            for (int i = 0; i < 4; i++)
              wgmma_rs_128<1, 1, 1>(d, za[16 * jj + 4 * i], za[16 * jj + 4 * i + 1], za[16 * jj + 4 * i + 2], za[16 * jj + 4 * i + 3],
                                    mk_desc(sb + place(rank, e >> (4 * jj) & 15), i * 2048, 8192, 1024, 1), jj | i);
            wg_commit();
            if (jj > 0) {
              wg_wait<1>();
              if (lane == 0) mbar_arrive(rempty + 8 * (j - 1));
            }
          }
          wg_wait<0>();
          reg_fence(d);
          if (lane == 0) mbar_arrive(rempty + 8 * (4 * q + 3));
          mbar_wait(bb + (e >> (own ? 13 : 21) & 0x7F8), 0);
          const uint32_t rb = (own ? sb : peer) + (8 * rank + q) * 8192 + (warp & 1) * 4096 + rho * 128;
          auto put_w = [&](auto remote) {
#pragma unroll
            for (int v = 0; v < 8; v++) {
              const int j = 4 * (v >> 1), h = v & 1;
              const uint32_t a = rb + (j >> 3) * 2048 + h * 1024 + ((((j & 4) + (lane & 3)) ^ rho) << 4);
              const uint32_t p0 = pack2(d[4 * j + 2 * h], d[4 * j + 2 * h + 1]), p1 = pack2(d[4 * j + 4 + 2 * h], d[4 * j + 5 + 2 * h]);
              const uint32_t p2 = pack2(d[4 * j + 8 + 2 * h], d[4 * j + 9 + 2 * h]), p3 = pack2(d[4 * j + 12 + 2 * h], d[4 * j + 13 + 2 * h]);
              if (decltype(remote)::value)
                asm volatile("st.async.shared::cluster.mbarrier::complete_tx::bytes.v4.b32 [%0], {%1, %2, %3, %4}, [%5];"
                             ::"r"(a), "r"(p0), "r"(p1), "r"(p2), "r"(p3), "r"(peer + (win - sb)) : "memory");
              else
                asm volatile("st.shared.v4.b32 [%0], {%1, %2, %3, %4};" ::"r"(a), "r"(p0), "r"(p1), "r"(p2), "r"(p3) : "memory");
            }
          };
          if (own) put_w(std::false_type());
          else put_w(std::true_type());
        } else {
          const int u = item - 1;
          const int c = lds32(xtab + 4 * u);
          const uint32_t in = sb + (c & 0x3C000);
          if (first) {
            first = false;
#pragma unroll
            for (int i = 0; i < 16; i++) {
              const int f2 = 2 * ((warp * 16 + (lane >> 2) + 8 * (i & 1)) | 1);
              fa[i] = dft2(f2 * ((lane & 3) * 2 + 8 * (i >> 1)) - (lane & 4) * 16, f2);
            }
          }
          mbar_wait(xfull + 8 * u, 0);
          wg_fence();
#pragma unroll
          for (int k = 0; k < 4; k++)
            wgmma_rs_128<1, 1, 1>(d, fa[4 * k], fa[4 * k + 1], fa[4 * k + 2], fa[4 * k + 3], mk_desc(in, k * 2048, 6144, 1024, 1), k);
          wg_commit();
          wg_wait<0>();
          reg_fence(d);
          bar_sync(1 + wg, 128);
          const uint32_t rb = in + (warp * 16 + row) * 128, xr = (lane & 7) ^ (c & 3);
#pragma unroll
          for (int j = 0; j < 16; j += 2)
            stsm4(rb + ((j >> 2) & 1) * 8192 + ((((j >> 3) * 4 + (j & 3) + hi) ^ xr) << 4), pack2(d[4 * j], d[4 * j + 1]),
                  pack2(d[4 * j + 2], d[4 * j + 3]), pack2(d[4 * j + 4], d[4 * j + 5]), pack2(d[4 * j + 6], d[4 * j + 7]));
          fence_async();
          __syncwarp();
          if (lane == 0) mbar_arrive(xready + 8 * u);
        }
      }
#pragma unroll
      for (int i = 0; i < 4; i++) fw[i] = fa[i];
    }
    if (spare) {
      float* sg = reinterpret_cast<float*>(smem_k1 + K1_R);
      __nv_bfloat16* sw = reinterpret_cast<__nv_bfloat16*>(sg + 16 * 256);
      const int c0 = (cta - 128) * 64;
      uint4 vw[8], vg[2];
#pragma unroll
      for (int i = 0; i < 8; i++) vw[i] = __ldg(reinterpret_cast<const uint4*>(wgt + ((i * 256 + tid) >> 3) * 256 + c0 + (tid & 7) * 8));
#pragma unroll
      for (int i = 0; i < 2; i++) vg[i] = __ldg(reinterpret_cast<const uint4*>(g) + i * 256 + tid);
#pragma unroll
      for (int i = 0; i < 8; i++) reinterpret_cast<uint4*>(sw)[i * 256 + tid] = vw[i];
#pragma unroll
      for (int i = 0; i < 2; i++) {
        const uint32_t w4[4] = {vg[i].x, vg[i].y, vg[i].z, vg[i].w};
#pragma unroll
        for (int e = 0; e < 4; e++) {
          sg[(i * 256 + tid) * 8 + 2 * e] = __uint_as_float(w4[e] << 16);
          sg[(i * 256 + tid) * 8 + 2 * e + 1] = __uint_as_float(w4[e] & 0xffff0000u);
        }
      }
      bar_sync(3, 256);
      const int col = tid & 63, r0 = (tid >> 6) * 4;
      float a0 = 0.f, a1 = 0.f, a2 = 0.f, a3 = 0.f;
#pragma unroll 8
      for (int k = 0; k < 256; k++) {
        const float w = __bfloat162float(sw[k * 64 + col]);
        a0 = fmaf(sg[(r0 + 0) * 256 + k], w, a0);
        a1 = fmaf(sg[(r0 + 1) * 256 + k], w, a1);
        a2 = fmaf(sg[(r0 + 2) * 256 + k], w, a2);
        a3 = fmaf(sg[(r0 + 3) * 256 + k], w, a3);
      }
      const int cc = c0 + col;
      const int pos = (cc & ~15) + ((cc >> 1) & 3) * 4 + ((cc >> 3) & 1) * 2 + (cc & 1);
      g_ge[(r0 + 0) * 256 + pos] = __bfloat162float(__float2bfloat16_rn(a0));
      g_ge[(r0 + 1) * 256 + pos] = __bfloat162float(__float2bfloat16_rn(a1));
      g_ge[(r0 + 2) * 256 + pos] = __bfloat162float(__float2bfloat16_rn(a2));
      g_ge[(r0 + 3) * 256 + pos] = __bfloat162float(__float2bfloat16_rn(a3));
      return;
    }
    reg_fence(fw);
    mbar_wait(win, 0);
    fence_async();
    bar_sync(3, 256);
    float d[16];
    auto t_begin = [&](int it, int hh, int r) {
      if (r == 0) mbar_wait(inf0 + 8 * (it & 1), (it >> 1) & 1);
      wg_fence();
      wgmma_rs_32<1, 1, 1>(d, fw[0], fw[1], fw[2], fw[3], mk_desc(sb + K1_TIN + (it & 1) * 4096 + hh * 2048, r * 64, 0, 1024, 1), 0);
      wg_commit();
    };
    auto t_end = [&](int it, int hh, int r) {
      reg_fence(d);
      const int j = it & 1;
      if (r == 0) mbar_wait(it >= 2 ? se0 + 8 * j : bb + (m.p.last >> (5 + 8 * it) & 0x7F8), it >= 2 ? ((it >> 1) - 1) & 1 : 0);
      else if (lane == 0) mbar_arrive(ine0 + 8 * j);
      const uint32_t rb = sb + K1_T + j * 16384 + hh * 8192 + (warp * 16 + row) * 128;
#pragma unroll
      for (int i = 0; i < 2; i++)
        stsm4(rb + (((4 * r + 2 * i + hi) ^ (lane & 7)) << 4), pack2(d[8 * i], d[8 * i + 1]), pack2(d[8 * i + 2], d[8 * i + 3]),
              pack2(d[8 * i + 4], d[8 * i + 5]), pack2(d[8 * i + 6], d[8 * i + 7]));
      if (r == 1) {
        fence_async();
        __syncwarp();
        if (lane == 0) mbar_arrive(sf0 + 8 * j);
      }
    };
    float y0[NB1 / 2], y1[NB1 / 2];
    uint32_t wa[8], wb[8];
    uint32_t wp = sb + wg * 4096 + ((lane & 7) + hi * 8) * 128 + (((2 * warp + ((lane >> 3) & 1)) ^ (lane & 7)) << 4);
    const uint32_t neg = wg ? 0x80008000u : 0u;
    auto frag = [&](uint32_t (&w)[8], uint32_t a, uint32_t sg) {
      ldsm4t(a, w[0], w[1], w[2], w[3]);
      ldsm4t(a + 2048, w[4], w[5], w[6], w[7]);
#pragma unroll
      for (int i = 0; i < 8; i++) w[i] ^= sg;
    };
    auto stage = [&](const uint32_t (&w)[8], uint32_t x4, int acc) {
      wg_fence();
      wgmma_rs_168<1, 1, 0>(y0, w[0], w[1], w[2], w[3], mk_desc4(x4, 0, 512, 2), acc);
      wgmma_rs_168<1, 1, 0>(y1, w[0], w[1], w[2], w[3], mk_desc4(x4 + G_ST / 32, 0, 512, 2), acc);
      wgmma_rs_168<1, 1, 0>(y0, w[4], w[5], w[6], w[7], mk_desc4(x4 + 2, 0, 512, 2), 1);
      wgmma_rs_168<1, 1, 0>(y1, w[4], w[5], w[6], w[7], mk_desc4(x4 + G_ST / 32 + 2, 0, 512, 2), 1);
      wg_commit();
      wg_wait<1>();
    };
    frag(wa, wp, neg);
    int it = 0;
#pragma unroll 1
    for (int k = 0; k < 13; k++) {
      const bool T = (m.p.tmask >> k) & 1;
      const uint32_t xa = ((sb & 0x3FFFF) >> 4) + m.slot[2 * k], xb = ((sb & 0x3FFFF) >> 4) + m.slot[2 * k + 1];
      if (T) t_begin(it, wg, 0);
      mbar_wait(gfull + 16 * k, 0);
      stage(wa, xa, k);
      frag(wb, wp ^ 4096, 0);
      if (k > 0 && lane == 0) mbar_arrive(gdone + 16 * k - 8);
      if (T) {
        t_end(it, wg, 0);
        t_begin(it, wg, 1);
      }
      mbar_wait(gfull + 16 * k + 8, 0);
      stage(wb, xb, 1);
      wp += 8192;
      frag(wa, wp, neg);
      if (lane == 0) mbar_arrive(gdone + 16 * k);
      if (T) t_end(it++, wg, 1);
    }
    auto tail = [&](float (&y)[NB1 / 2], auto batch, auto wgc) {
      constexpr int B = decltype(batch)::value, W = decltype(wgc)::value;
#pragma unroll
      for (int k = 13; k < 16; k++) {
        const int s = 13 + k + 3 * B;
        mbar_wait(gfull + 8 * s, 0);
        const int xo = g_off(g_slot(s));
        wg_fence();
#pragma unroll
        for (int h = 0; h < 4; h++) {
          const uint64_t dW = mk_desc(sb, k * 8192 + ((h >> 1) ^ W) * 4096 + (h & 1) * 2048, 0, 1024, 1);
          const uint64_t dX = mk_desc(sb, xo + (h >> 1) * (G_ST / 2) + (h & 1) * 32, 0, 512, 2);
          if (W == 1 && h < 2) wgmma_ss_168<-1, 1, 1, 0>(y, dW, dX, 1);
          else wgmma_ss_168<1, 1, 1, 0>(y, dW, dX, 1);
        }
        if (B == 0 && W == 0 && k == 13) {
          wg_commit();
          wg_wait<1>();
          if (lane == 0) mbar_arrive(gdone + 8 * 25);
        }
      }
      wg_commit();
    };
    constexpr std::integral_constant<int, 0> c0;
    constexpr std::integral_constant<int, 1> c1;
    auto put = [&](const float (&v)[NB1 / 2], uint32_t stg, int b) {
      const int mi = lane >> 3, i = lane & 7;
      const uint32_t a0 = stg + (mi >> 1) * 1024 + i * 128 + (((2 * warp + (mi & 1)) ^ i) << 4);
      constexpr int J = 21 / G_EPI;
#pragma unroll
      for (int c = 0; c < G_EPI; c++) {
#pragma unroll
        for (int j = c * J; j + 1 < (c + 1) * J; j += 2)
          stsm4t(a0 + j * 1024, pack2(v[4 * j], v[4 * j + 1]), pack2(v[4 * j + 2], v[4 * j + 3]),
                 pack2(v[4 * j + 4], v[4 * j + 5]), pack2(v[4 * j + 6], v[4 * j + 7]));
        const int j = (c + 1) * J - 1;
        asm volatile("stmatrix.sync.aligned.m8n8.x2.trans.shared.b16 [%0], {%1, %2};" ::"r"(a0 + j * 1024),
                     "r"(pack2(v[4 * j], v[4 * j + 1])), "r"(pack2(v[4 * j + 2], v[4 * j + 3])) : "memory");
        fence_async();
        bar_sync(1 + wg, 128);
        if (t == 0) {
          tma_st4<0>(&m.y, stg + c * J * 1024, 0, b * NB1 + c * J * 8, 2 * bin + wg, dc);
          bulk_commit();
        }
      }
    };
    if (wg == 0) {
      tail(y0, c0, c0);
      bar_arrive(4, 256);
      mbar_wait(gdone + 8 * 25, 0);
      wg_wait<0>();
      reg_fence(y0);
      put(y0, sb + K1_Y0, 0);
      bar_sync(7, 256);
      tail(y1, c1, c0);
      bar_arrive(8, 256);
      if (t == 0) bulk_wait_read<0>();
      wg_wait<0>();
      reg_fence(y1);
      bar_sync(1, 128);
      put(y1, sb + K1_Y0, 1);
    } else {
      wg_wait<0>();
      if (lane == 0) mbar_arrive(gdone + 8 * 25);
#pragma unroll 1
      for (int h2 = 2 * it; h2 < 16; h2++) {
#pragma unroll
        for (int r = 0; r < 2; r++) {
          t_begin(h2 >> 1, h2 & 1, r);
          wg_wait<0>();
          t_end(h2 >> 1, h2 & 1, r);
        }
      }
      bar_sync(4, 256);
      tail(y0, c0, c1);
      bar_arrive(7, 256);
      mbar_wait(se0, 1);
      mbar_wait(se0 + 8, 1);
      wg_wait<0>();
      reg_fence(y0);
      put(y0, sb + K1_T, 0);
      bar_sync(8, 256);
      tail(y1, c1, c1);
      wg_wait<0>();
      reg_fence(y1);
      put(y1, sb + g_off(g_slot(26)), 1);
    }
    if (t == 0) {
      bulk_wait_read<0>();
    }
  }
}

#define G_WPRE 2
#define H_EPI 3
#define H_KS 11
constexpr int H_XP = 168 * 64, H_STAGE = 8192 + 2 * H_XP, H_NST = 7, H_SMEM = H_NST * H_STAGE + 21504 + 1024;

template <int WG>
__device__ __forceinline__ void h_loop(float (&acc)[84], uint32_t sb, uint32_t full0, uint32_t empty0, int lane) {
#pragma unroll 1
  for (int k = 0; k < 16; k++) {
    const int st = k % H_NST;
    if (WG == 1 && k == H_KS) bar_sync(4, 256);
    mbar_wait(full0 + 8 * st, (k / H_NST) & 1);
    const uint32_t base = sb + st * H_STAGE;
    wg_fence();
#pragma unroll
    for (int s = 0; s < 2; s++) {
      const uint64_t dP = mk_desc(base, s * 2048, 0, 1024, 1), dQ = mk_desc(base, 4096 + s * 2048, 0, 1024, 1);
      const uint64_t dA = mk_desc(base, 8192 + s * 32, 0, 512, 2), dB = mk_desc(base, 8192 + H_XP + s * 32, 0, 512, 2);
      wgmma_ss_168<1, 1, 1, 0>(acc, dP, WG == 0 ? dA : dB, k | s);
      wgmma_ss_168<WG == 0 ? 1 : -1, 1, 1, 0>(acc, dQ, WG == 0 ? dB : dA, 1);
    }
    wg_commit();
    if (WG == 0 && k == 15) bar_arrive(4, 256);
    if (k <= 10) {
      wg_wait<1>();
      if (k > 0 && k - 1 + H_NST < 16 && lane < 2) mbar_arrive_cta(empty0 + 8 * ((k - 1) % H_NST), lane);
    }
  }
  wg_wait<0>();
  reg_fence(acc);
}

__global__ void __cluster_dims__(2, 1, 1) __launch_bounds__(288, 1)
kH(const __grid_constant__ CUtensorMap mx, const __grid_constant__ CUtensorMap mw, const __grid_constant__ CUtensorMap my,
   const __nv_bfloat16* __restrict__ wf, const __nv_bfloat16* __restrict__ wo) {
  extern __shared__ uint8_t smem_raw[];
  __shared__ __align__(8) uint64_t bars[2 * H_NST];
  const uint32_t sb = (s2u(smem_raw) + 1023) & ~1023u;
  const int tid = threadIdx.x, wg = __shfl_sync(0xffffffffu, tid >> 7, 0), t = tid & 127;
  const int warp = __shfl_sync(0xffffffffu, t >> 5, 0), lane = t & 31;
  const int cta = blockIdx.x, rank = cta & 1, dc = cta & 3, bin = cta >> 2;
  const uint32_t full0 = s2u(&bars[0]), empty0 = full0 + 8 * H_NST;
  pdl_launch();
  if (tid == 256) {
    for (int i = 0; i < H_NST; i++) {
      mbar_init(full0 + 8 * i, 1);
      mbar_init(empty0 + 8 * i, 16);
    }
    fence_bar_init();
    fence_async();
    prefetch_map(&mx);
    prefetch_map(&mw);
    prefetch_map(&my);
    for (int k = 0; k < G_WPRE; k++) {
      mbar_expect(full0 + 8 * k, H_STAGE);
      tma_ld4<1>(sb + k * H_STAGE, &mw, full0 + 8 * k, 0, (k & 1) * 32, dc, (k >> 1) * 64 + 2 * bin);
    }
  }
  __syncthreads();
  asm volatile("barrier.cluster.arrive.relaxed.aligned;\nbarrier.cluster.wait.aligned;" ::: "memory");
  if (wg == 2) {
    if (lane == 0) {
      pdl_wait();
#pragma unroll 1
      for (int k = 0; k < 16; k++) {
        const int st = k % H_NST;
        if (k >= H_NST) mbar_wait(empty0 + 8 * st, ((k / H_NST) - 1) & 1);
        const uint32_t base = sb + st * H_STAGE, bar = full0 + 8 * st;
        const int fs = (k >> 1) * 64 + 2 * bin, kc = (k & 1) * 32;
        if (k >= G_WPRE) mbar_expect(bar, H_STAGE);
        tma_ld3mc<0>(base + 8192 + rank * H_XP, &mx, bar, kc, 0, fs + rank);
        if (k >= G_WPRE) tma_ld4<1>(base, &mw, bar, 0, kc, dc, fs);
        if (k == H_NST - 1) {
          if (cta == 0) asm volatile("cp.async.bulk.prefetch.L2.global [%0], 6144;" ::"l"(c_ga) : "memory");
          asm volatile("cp.async.bulk.prefetch.L2.global [%0], 1024;" ::"l"(wf + cta * 512) : "memory");
          asm volatile("cp.async.bulk.prefetch.L2.global [%0], 1024;" ::"l"(wo + cta * 512) : "memory");
        }
      }
    }
  } else {
    float acc[84];
    if (wg == 0) {
      h_loop<0>(acc, sb, full0, empty0, lane);
    } else {
      h_loop<1>(acc, sb, full0, empty0, lane);
      bar_sync(3, 128);
    }
    const uint32_t stg = sb + (wg == 0 ? H_NST : 9 % H_NST) * H_STAGE;
    const int mi = lane >> 3, i = lane & 7;
    const uint32_t a0 = stg + (mi >> 1) * 1024 + i * 128 + (((2 * warp + (mi & 1)) ^ i) << 4);
    constexpr int J = 21 / H_EPI;
#pragma unroll
    for (int c = 0; c < H_EPI; c++) {
#pragma unroll
      for (int j = c * J; j + 1 < (c + 1) * J; j += 2)
        stsm4t(a0 + j * 1024, pack2(acc[4 * j], acc[4 * j + 1]), pack2(acc[4 * j + 2], acc[4 * j + 3]),
               pack2(acc[4 * j + 4], acc[4 * j + 5]), pack2(acc[4 * j + 6], acc[4 * j + 7]));
      const int j = (c + 1) * J - 1;
      asm volatile("stmatrix.sync.aligned.m8n8.x2.trans.shared.b16 [%0], {%1, %2};" ::"r"(a0 + j * 1024),
                   "r"(pack2(acc[4 * j], acc[4 * j + 1])), "r"(pack2(acc[4 * j + 2], acc[4 * j + 3])) : "memory");
      fence_async();
      bar_sync(2 + wg, 128);
      if (t == 0) {
        tma_st4<0>(&my, stg + c * J * 1024, 0, c * J * 8, 2 * bin + wg, dc);
        bulk_commit();
      }
    }
    if (t == 0) {
      bulk_wait_read<0>();
    }
  }
}

#define C_TOK 1
constexpr int C_OUT = 13 * 8192, C_GI = C_OUT + 6 * 16384, C_F = C_GI + 6144;
constexpr int C_SMEM = C_F + 8192 + 1024;

template <int NC> __device__ __forceinline__ void gelu_pack(uint32_t (&hp)[32], const float (&h)[4 * NC], int rc0, bool zero_first, bool zero_all) {
#pragma unroll
  for (int c = 0; c < NC; c++) {
    const uint32_t lo = pack2(gelu(h[4 * c]), gelu(h[4 * c + 1])), hi = pack2(gelu(h[4 * c + 2]), gelu(h[4 * c + 3]));
    const bool z = zero_all || (zero_first && c < 2);
    hp[(c & 1) * 16 + (rc0 + (c >> 1)) * 2] = z ? 0u : lo;
    hp[(c & 1) * 16 + (rc0 + (c >> 1)) * 2 + 1] = z ? 0u : hi;
  }
}

__global__ void __launch_bounds__(512, 1)
kC(const __grid_constant__ CUtensorMap my, const __grid_constant__ CUtensorMap mxs) {
  extern __shared__ uint8_t smem_raw[];
  __shared__ __align__(8) uint64_t bars[14];
  const uint32_t sb = (s2u(smem_raw) + 1023) & ~1023u;
  const int tid = threadIdx.x, wg = __shfl_sync(0xffffffffu, tid >> 7, 0), t = tid & 127, warp = t >> 5, lane = t & 31;
  const uint32_t sGi = sb + C_GI, sF = sb + C_F, barc = s2u(&bars[0]);
  const int b = blockIdx.x >> 6, cs = (blockIdx.x >> 4) & 3, j = blockIdx.x & 15;
  const int n0 = 5 * j + min(j, 4), cnt = j < 4 ? 6 : 5;
  if (tid == 384) {
    prefetch_map(&my);
    for (int i = 0; i < 14; i++) mbar_init(barc + 8 * i, 1);
    fence_bar_init();
    fence_async();
  }
  __syncthreads();
  if (tid == 384) {
    mbar_expect(barc + 8 * 13, 14336);
    asm volatile("cp.async.bulk.shared::cluster.global.mbarrier::complete_tx::bytes [%0], [%1], 14336, [%2];"
                 ::"r"(sGi), "l"(c_img), "r"(barc + 8 * 13) : "memory");
    pdl_wait();
    for (int i = 0; i <= 2 * cnt; i++) {
      mbar_expect(barc + 8 * i, 8192);
      tma_ld5<1>(sb + i * 8192, &my, barc + 8 * i, 0, 0, cs, 2 * n0 + i, b);
    }
    pdl_launch();
    prefetch_map(&mxs);
  }
  mbar_wait(barc + 8 * 13, 0);
#pragma unroll 1
  for (int i = wg; i < cnt; i += 4) {
    const int n2 = n0 + i;
    const uint32_t in = sb + i * 16384, bar = barc + i * 16, outb = sb + C_OUT + i * 16384;
    float h0[24], h1[24], h2[16];
    uint32_t hp[32];
    mbar_wait(bar, 0);
    wg_fence();
#pragma unroll
    for (int k = 0; k < 4; k++) wgmma_ss_48<1, 1, 1, 0>(h0, mk_desc(in, k * 2048, 0, 1024, 1), mk_desc(sGi, k * 32, 0, 1024, 1), k);
    wg_commit();
    mbar_wait(bar + 8, 0);
    wg_fence();
#pragma unroll
    for (int k = 0; k < 4; k++) wgmma_ss_48<1, 1, 1, 0>(h1, mk_desc(in, 8192 + k * 2048, 0, 1024, 1), mk_desc(sGi, k * 32, 0, 1024, 1), k);
    wg_commit();
    if (C_TOK && i > 0) bar_sync(5 + wg, 256);
    wg_wait<1>();
    reg_fence(h0);
    gelu_pack<6>(hp, h0, 0, n2 == 0, false);
    mbar_wait(bar + 16, 0);
    wg_fence();
#pragma unroll
    for (int k = 0; k < 4; k++) wgmma_ss_32<1, 1, 1, 0>(h2, mk_desc(in, 16384 + k * 2048, 0, 1024, 1), mk_desc(sGi, k * 32, 0, 1024, 1), k);
    wg_commit();
    if (C_TOK == 1 && i + 1 < cnt) bar_arrive(5 + ((wg + 1) & 3), 256);
    wg_wait<1>();
    reg_fence(h1);
    gelu_pack<6>(hp, h1, 3, false, n2 == NB2 - 1);
    if (C_TOK == 2 && i + 1 < cnt) bar_arrive(5 + ((wg + 1) & 3), 256);
    wg_wait<0>();
    reg_fence(h2);
    gelu_pack<4>(hp, h2, 6, false, n2 == NB2 - 1);
    float e0[32], e1[32];
    reg_fence(hp);
    if (C_TOK == 3 && i + 1 < cnt) bar_arrive(5 + ((wg + 1) & 3), 256);
    wg_fence();
#pragma unroll
    for (int k = 0; k < 4; k++) {
      const uint64_t db = mk_desc(sF, k * 32, 0, 1024, 1);
      wgmma_rs_64<1, 1, 0>(e0, hp[4 * k], hp[4 * k + 1], hp[4 * k + 2], hp[4 * k + 3], db, k);
      wgmma_rs_64<1, 1, 0>(e1, hp[16 + 4 * k], hp[16 + 4 * k + 1], hp[16 + 4 * k + 2], hp[16 + 4 * k + 3], db, k);
    }
    wg_commit();
    wg_wait<0>();
    reg_fence(e0);
    reg_fence(e1);
    {
      const int mi = lane >> 3, r = lane & 7;
      const uint32_t a0 = outb + (mi >> 1) * 8192 + r * 128 + (((2 * warp + (mi & 1)) ^ r) << 4);
#pragma unroll
      for (int q = 0; q < 8; q++)
        stsm4t(a0 + q * 1024, pack2(e0[4 * q], e0[4 * q + 1]), pack2(e0[4 * q + 2], e0[4 * q + 3]),
               pack2(e1[4 * q], e1[4 * q + 1]), pack2(e1[4 * q + 2], e1[4 * q + 3]));
    }
    fence_async();
    bar_sync(1 + wg, 128);
    if (t == 0) {
      tma_st3<0>(&mxs, outb, 0, cs * 64, b * NB2 + n2);
      tma_st3<0>(&mxs, outb + 8192, 0, (4 + cs) * 64, b * NB2 + n2);
      bulk_commit();
    }
  }
  if (t == 0) bulk_wait_read<0>();
}

#define E_WPRE 2
#define E_EARLY0 2
#define E_CHUNK 1
#define E_EARLY 2
constexpr int E_SMEM = 65536 + 131072 + 32768 + 1024;

__device__ __forceinline__ uint32_t joint2(uint32_t fe, uint32_t g0, uint32_t g1) {
  uint32_t s0, s1;
  asm("{\n.reg .b16 l, h;\n.reg .b32 ll;\nmov.b32 {l, h}, %2;\nmov.b32 ll, {l, l};\n"
      "fma.rn.bf16x2 %0, ll, %5, %3;\nfma.rn.bf16x2 %1, %2, %5, %4;\n}"
      : "=r"(s0), "=r"(s1) : "r"(fe), "r"(g0), "r"(g1), "r"(0x3F800000u));
  return pack2(tanh_f32(__uint_as_float(s0)), tanh_f32(__uint_as_float(s1)));
}
__device__ __forceinline__ uint4 lds128(uint32_t a) {
  uint4 v;
  asm volatile("ld.shared.v4.u32 {%0, %1, %2, %3}, [%4];" : "=r"(v.x), "=r"(v.y), "=r"(v.z), "=r"(v.w) : "r"(a));
  return v;
}
__device__ __forceinline__ void joint_group(uint32_t (&ja)[8], const uint32_t* fe, uint4& g0, uint4& g1, uint32_t gnext) {
  const uint4 c0 = g0, c1 = g1;
  g0 = lds128(gnext);
  g1 = lds128(gnext + 64);
  ja[0] = joint2(fe[0], c0.x, c0.y);
  ja[1] = joint2(fe[1], c0.x, c0.y);
  ja[2] = joint2(fe[2], c0.z, c0.w);
  ja[3] = joint2(fe[3], c0.z, c0.w);
  ja[4] = joint2(fe[4], c1.x, c1.y);
  ja[5] = joint2(fe[5], c1.x, c1.y);
  ja[6] = joint2(fe[6], c1.z, c1.w);
  ja[7] = joint2(fe[7], c1.z, c1.w);
  reg_fence(ja);
}

__global__ void __launch_bounds__(256, 1)
kE(const __grid_constant__ CUtensorMap my, const __grid_constant__ CUtensorMap mwf, const __grid_constant__ CUtensorMap mwo,
   const __grid_constant__ CUtensorMap mout) {
  extern __shared__ uint8_t smem_raw[];
  __shared__ __align__(8) uint64_t bars[13];
  const uint32_t sb = (s2u(smem_raw) + 1023) & ~1023u;
  const int tid = threadIdx.x, wg = __shfl_sync(0xffffffffu, tid >> 7, 0), t = tid & 127, warp = t >> 5, lane = t & 31;
  const uint32_t R0 = sb, R1 = sb + 65536, R2 = sb + 65536 + 131072;
  const uint32_t barY = s2u(&bars[0]), barF = s2u(&bars[4]), barO = s2u(&bars[8]), barA = s2u(&bars[12]);
  const int b = blockIdx.x / 63, t0 = (blockIdx.x % 63) * 64;
  const int a = t0 / 48, o = t0 % 48;
  const int qw = o + 16 * warp, sel = qw >= 48;
  uint32_t ga[16];
#pragma unroll
  for (int s = 0; s < 4; s++)
    ldg128(reinterpret_cast<const uint4*>(c_ga) + ((qw >> 4) - 3 * sel) * 128 + s * 32 + lane, ga[4 * s], ga[4 * s + 1], ga[4 * s + 2], ga[4 * s + 3]);
  uint4 gev0, gev1;
  asm volatile("ld.global.cg.v4.u32 {%0, %1, %2, %3}, [%4];" : "=r"(gev0.x), "=r"(gev0.y), "=r"(gev0.z), "=r"(gev0.w)
               : "l"(reinterpret_cast<const uint4*>(g_ge) + (b * 8 + wg * 4) * 64 + t));
  asm volatile("ld.global.cg.v4.u32 {%0, %1, %2, %3}, [%4];" : "=r"(gev1.x), "=r"(gev1.y), "=r"(gev1.z), "=r"(gev1.w)
               : "l"(reinterpret_cast<const uint4*>(g_ge) + (b * 8 + wg * 4) * 64 + 128 + t));
  if (tid == 0) {
    prefetch_map(&my);
    for (int i = 0; i < 12; i++) mbar_init(barY + 8 * i, 1);
    mbar_init(barA, 8);
    fence_bar_init();
    fence_async();
    for (int i = 0; i < E_WPRE; i++) {
      const int kc = (i >> 1) | ((i & 1) << 1);
      mbar_expect(barF + 8 * kc, 32768);
      tma_ld3<0>(R1 + kc * 32768, &mwf, barF + 8 * kc, 0, kc * 64, 0);
    }
    pdl_wait();
    for (int i = 0; i < 4; i++) {
      mbar_expect(barY + 8 * i, 16384);
      tma_ld5<0>(R0 + i * 16384, &my, barY + 8 * i, 0, 0, 2 * (i & 1) + (i >> 1), a, b);
    }
    for (int i = E_WPRE; i < 4; i++) {
      const int kc = (i >> 1) | ((i & 1) << 1);
      mbar_expect(barF + 8 * kc, 32768);
      tma_ld3<0>(R1 + kc * 32768, &mwf, barF + 8 * kc, 0, kc * 64, 0);
    }
    prefetch_map(&mwo);
    prefetch_map(&mout);
  }
  uint32_t gs[32];
#pragma unroll
  for (int i = 0; i < 16; i++) {
    gs[i] = sel ? 0u : ga[i];
    gs[16 + i] = sel ? ga[i] : 0u;
  }
  __syncthreads();
  if (blockIdx.x == 125 && tid < 8) g_done[tid * 32] = 0;
  reg_fence(gs);
  uint32_t gp = R2 + wg * 4096 + (lane & 3) * 16;
  uint4 g0, g1;
  uint32_t fe[64];
  {
    float d0[32], d1[32], e[64];
    mbar_wait(barY + 8 * wg, 0);
    wg_fence();
#pragma unroll
    for (int k = 0; k < 8; k++)
      wgmma_rs_64<1, 1, 1>(d0, gs[4 * k], gs[4 * k + 1], gs[4 * k + 2], gs[4 * k + 3], mk_desc(R0 + wg * 16384, k * 2048, 0, 1024, 1), k);
    wg_commit();
    wg_wait<0>();
    reg_fence(d0);
#pragma unroll
    for (int i = 0; i < 32; i++) d0[i] = gelu(d0[i]);
    store_tile_64(d0, R2 + wg * 16384, warp, lane);
    mbar_wait(barY + 8 * (2 + wg), 0);
    wg_fence();
#pragma unroll
    for (int k = 0; k < 8; k++)
      wgmma_rs_64<1, 1, 1>(d1, gs[4 * k], gs[4 * k + 1], gs[4 * k + 2], gs[4 * k + 3], mk_desc(R0 + wg * 16384, 32768 + k * 2048, 0, 1024, 1), k);
    wg_commit();
    fence_async();
    mbar_wait(barF, 0);
    mbar_wait(barF + 16, 0);
    __syncthreads();
    wg_fence();
#pragma unroll
    for (int i = 0; i < 8; i++) {
      const int kc = (i >> 2) * 2, s = i & 3;
      wgmma_ss_128<1, 1, 0, 1>(e, mk_desc(R2, kc * 8192 + s * 32, 0, 1024, 1),
                               mk_desc(R1 + wg * 16384, kc * 32768 + s * 2048, 8192, 1024, 1), i);
    }
    wg_commit();
    if (tid == 128) {
      mbar_expect(barO, 32768);
      tma_ld3<0>(R0, &mwo, barO, 0, 0, 0);
    }
    wg_wait<1>();
    reg_fence(d1);
#pragma unroll
    for (int i = 0; i < 32; i++) d1[i] = gelu(d1[i]);
    store_tile_64(d1, R2 + wg * 16384 + 8192, warp, lane);
    fence_async();
    mbar_wait(barF + 8, 0);
    mbar_wait(barF + 24, 0);
    __syncthreads();
    if (tid == 128) {
      mbar_expect(barO + 8, 32768);
      tma_ld3<0>(R0 + 32768, &mwo, barO + 8, 0, 64, 0);
    }
    if (wg == 1) bar_sync(4, 256);
    wg_fence();
#pragma unroll
    for (int i = 0; i < 8; i++) {
      const int kc = (i >> 2) * 2 + 1, s = i & 3;
      wgmma_ss_128<1, 1, 0, 1>(e, mk_desc(R2, kc * 8192 + s * 32, 0, 1024, 1),
                               mk_desc(R1 + wg * 16384, kc * 32768 + s * 2048, 8192, 1024, 1), 1);
    }
    wg_commit();
    if (wg == 0) bar_arrive(4, 256);
    wg_wait<1>();
    if (lane == 0) mbar_arrive(barA);
    if (tid == 128) {
      mbar_wait(barA, 0);
      for (int kc = 2; kc < 4; kc++) {
        mbar_expect(barO + 8 * kc, 32768);
        tma_ld3<0>(R1 + (kc - 2) * 65536, &mwo, barO + 8 * kc, 0, kc * 64, 0);
      }
    }
    mbar_wait(barA, 0);
    asm volatile("st.shared.v4.u32 [%0], {%1, %2, %3, %4};" ::"r"(R2 + wg * 4096 + ((t * 16) ^ (wg * 512))), "r"(gev0.x), "r"(gev0.y), "r"(gev0.z), "r"(gev0.w) : "memory");
    asm volatile("st.shared.v4.u32 [%0], {%1, %2, %3, %4};" ::"r"(R2 + wg * 4096 + 2048 + ((t * 16) ^ (wg * 512))), "r"(gev1.x), "r"(gev1.y), "r"(gev1.z), "r"(gev1.w) : "memory");
    bar_sync(1 + wg, 128);
    g0 = lds128(gp);
    g1 = lds128(gp + 64);
    wg_wait<0>();
    reg_fence(e);
#pragma unroll
    for (int i = 0; i < 32; i++) fe[i] = pack2(e[2 * i], e[2 * i + 1]);
  }
  auto publish = [&]() {
    bar_sync(1 + wg, 128);
    const int row = warp * 16 + (lane & 7) + ((lane >> 3) & 1) * 8;
    const uint32_t xb = R1 + (wg == 0 ? 3 * 32768 : 32768 + 16384) + row * 128;
#pragma unroll
    for (int s = 0; s < 8; s++) {
      const int jj = 2 * s + (lane >> 4);
      stsm4(xb + (s >> 2) * 8192 + (((jj & 7) ^ (lane & 7)) << 4), fe[4 * s], fe[4 * s + 1], fe[4 * s + 2], fe[4 * s + 3]);
    }
    bar_arrive(5 + wg, 256);
  };
  if (wg == 1) publish();
  const uint32_t stg = R1 + 32768 + wg * 65536;
  const uint32_t w0 = sb + wg * 65536, w1 = sb + 32768 + wg * 98304, w2 = sb + 65536 - wg * 65536, w3 = sb + 131072 - wg * 98304;
  float acc[128];
  uint32_t j0[8], j1[8], j2[8], j3[8];
  joint_group(j0, fe, g0, g1, gp + 128);
  mbar_wait(barO + 16 * wg, 0);
  joint_group(j1, fe + 8, g0, g1, gp + 256);
#define E_MMA4(J, K, W, FIRSTK, G, NEXTBAR)                                                     \
  wg_fence();                                                                                   \
  wgmma_rs_256<1, 1, 1>(acc, J[0], J[1], J[2], J[3], mk_desc(W, 0, 8192, 1024, 1), FIRSTK);     \
  wgmma_rs_256<1, 1, 1>(acc, J[4], J[5], J[6], J[7], mk_desc(W, 2048, 8192, 1024, 1), 1);       \
  wgmma_rs_256<1, 1, 1>(acc, K[0], K[1], K[2], K[3], mk_desc(W, 4096, 8192, 1024, 1), 1);       \
  wgmma_rs_256<1, 1, 1>(acc, K[4], K[5], K[6], K[7], mk_desc(W, 6144, 8192, 1024, 1), 1);       \
  wg_commit();                                                                                  \
  if ((ui + wg == 0 ? E_EARLY0 : E_EARLY) == (G) && (ui < 3 || wg == 0)) bar_arrive(4 - wg, 256); \
  wg_wait<1>();                                                                                 \
  if (ui == 0) mbar_wait(NEXTBAR, 0);
  const uint32_t bo0 = barO + 16 * wg, bo2 = barO + 16 * (1 - wg);
#pragma unroll 1
  for (int ui = 0; ui < 4; ui++) {
    if (ui > 0 || wg == 1) bar_sync(3 + wg, 256);
    E_MMA4(j0, j1, w0, 0, 0, bo0)
    joint_group(j2, fe + 16, g0, g1, gp + 384);
    if (ui == 0) mbar_wait(bo0 + 8, 0);
    joint_group(j3, fe + 24, g0, g1, gp + 512);
    E_MMA4(j2, j3, w1, 1, 1, bo0 + 8)
    if (ui == 0) {
      if (wg == 0) publish();
      bar_sync(6 - wg, 256);
      const int row = warp * 16 + (lane & 7) + ((lane >> 3) & 1) * 8;
      const uint32_t xb = R1 + (wg == 1 ? 3 * 32768 : 32768 + 16384) + row * 128;
#pragma unroll
      for (int s = 0; s < 8; s++) {
        const int jj = 2 * s + (lane >> 4);
        ldsm4(xb + (s >> 2) * 8192 + (((jj & 7) ^ (lane & 7)) << 4), fe[32 + 4 * s], fe[33 + 4 * s], fe[34 + 4 * s], fe[35 + 4 * s]);
      }
    }
    joint_group(j0, fe + 32, g0, g1, gp + 640);
    if (ui == 0) mbar_wait(bo2, 0);
    joint_group(j1, fe + 40, g0, g1, gp + 768);
    E_MMA4(j0, j1, w2, 1, 2, bo2)
    joint_group(j2, fe + 48, g0, g1, gp + 896);
    if (ui == 0) mbar_wait(bo2 + 8, 0);
    joint_group(j3, fe + 56, g0, g1, gp + 1024);
    E_MMA4(j2, j3, w3, 1, 3, bo2 + 8)
    gp += 1024;
    if (ui < 3) {
      joint_group(j0, fe, g0, g1, gp + 128);
      if (ui == 0) mbar_wait(bo2 + 8, 0);
      joint_group(j1, fe + 8, g0, g1, gp + 256);
    }
    if (t == 0) bulk_wait_read<0>();
    wg_wait<0>();
    reg_fence(acc);
    bar_sync(1 + wg, 128);
    const uint32_t rb = stg + (warp * 16 + (lane & 7) + ((lane >> 3) & 1) * 8) * 128;
#pragma unroll
    for (int h = 0; h < 2; h++) {
#pragma unroll
      for (int j = 16 * h; j < 16 * h + 16; j += 2) {
        const int jj = j + (lane >> 4);
        stsm4(rb + (j >> 3) * 8192 + (((jj & 7) ^ (lane & 7)) << 4), pack2(acc[4 * j], acc[4 * j + 1]), pack2(acc[4 * j + 2], acc[4 * j + 3]),
              pack2(acc[4 * j + 4], acc[4 * j + 5]), pack2(acc[4 * j + 6], acc[4 * j + 7]));
      }
      const bool split = E_CHUNK == 2 || (E_CHUNK == 1 && ui == 3);
      if (h == 1 || split) {
        fence_async();
        bar_sync(1 + wg, 128);
        if (t == 0) {
          if (h == 1 && !split) tma_st5<1>(&mout, stg, 0, t0, 0, wg * 4 + ui, b);
          tma_st5<1>(&mout, stg + h * 16384, 0, t0, 2 * h, wg * 4 + ui, b);
          bulk_commit();
        }
      }
    }
  }
  if (t == 0) bulk_wait_read<0>();
}

typedef CUresult (*EncodeFn)(CUtensorMap*, CUtensorMapDataType, cuuint32_t, void*, const cuuint64_t*, const cuuint64_t*,
                             const cuuint32_t*, const cuuint32_t*, CUtensorMapInterleave, CUtensorMapSwizzle,
                             CUtensorMapL2promotion, CUtensorMapFloatOOBfill);

CUtensorMap make_map(EncodeFn fn, const void* base, int rank, const uint64_t* dims, const uint64_t* strides, const uint32_t* box,
                     CUtensorMapSwizzle swz) {
  CUtensorMap m;
  cuuint64_t gd[5], gs[4];
  cuuint32_t bx[5], es[5];
  for (int i = 0; i < rank; i++) { gd[i] = dims[i]; bx[i] = box[i]; es[i] = 1; }
  for (int i = 0; i + 1 < rank; i++) gs[i] = strides[i];
  fn(&m, CU_TENSOR_MAP_DATA_TYPE_BFLOAT16, rank, const_cast<void*>(base), gd, gs, bx, es, CU_TENSOR_MAP_INTERLEAVE_NONE, swz,
     CU_TENSOR_MAP_L2_PROMOTION_NONE, CU_TENSOR_MAP_FLOAT_OOB_FILL_NONE);
  return m;
}

template <typename... KArgs, typename... Args>
void launch(void (*k)(KArgs...), int grid, int block, int smem, bool pdl, Args... args) {
  cudaLaunchConfig_t c = {};
  c.gridDim = dim3(grid);
  c.blockDim = dim3(block);
  c.dynamicSmemBytes = smem;
  c.stream = cudaStreamPerThread;
  cudaLaunchAttribute at[1];
  at[0].id = cudaLaunchAttributeProgrammaticStreamSerialization;
  at[0].val.programmaticStreamSerializationAllowed = 1;
  c.attrs = at;
  c.numAttrs = pdl ? 1 : 0;
  cudaLaunchKernelEx(&c, k, args...);
}

}

static uint32_t h_plan[67] = {
    0x6108, 0x6109, 0x610a, 0x610b, 0x6101, 0x8008, 0x8109, 0x820a, 0x830b, 0x8401,
    0x8508, 0x8609, 0x870a, 0x3102, 0x880b, 0x8a08, 0x8b09, 0x8c0a, 0x8d02, 0x8e0b,
    0x8f08, 0x9009, 0x910a, 0x930b, 0x9408, 0x9509, 0x960a, 0x970b, 0x9808, 0x9909,
    0x9a0a, 0x9b0b, 0x6161610d, 0x61616102, 0x81816107, 0x84836126, 0x8786610c, 0x8888300d, 0x8c8b3237, 0x918f61c3,
    0x9391348c, 0x9896358d, 0x0, 0x0, 0x0, 0x0, 0x0, 0x0, 0x6161ba98, 0x6161a981,
    0x6189981b, 0x61898b2a, 0x6892b2a9, 0x6892ba98, 0x6937ba98, 0x6937ba98, 0x39389c, 0x1, 0x4, 0x1ee0,
    0x11635052, 0x56, 0xcb520e61, 0x3293d, 0x9d, 0x9e, 0x9f,
};

extern "C" void kernel_launch(void* const* d_in, const int* in_sizes, int n_in, void* d_out, int out_size) {
  const __nv_bfloat16* x = (const __nv_bfloat16*)d_in[0];
  const __nv_bfloat16* w1 = (const __nv_bfloat16*)d_in[1];
  const __nv_bfloat16* w2 = (const __nv_bfloat16*)d_in[2];
  const __nv_bfloat16* g = (const __nv_bfloat16*)d_in[3];
  const __nv_bfloat16* wf = (const __nv_bfloat16*)d_in[4];
  const __nv_bfloat16* wgt = (const __nv_bfloat16*)d_in[5];
  const __nv_bfloat16* wo = (const __nv_bfloat16*)d_in[6];

  void* fp = nullptr;
  cudaDriverEntryPointQueryResult qr;
  cudaGetDriverEntryPoint("cuTensorMapEncodeTiled", &fp, cudaEnableDefault, &qr);
  EncodeFn fn = (EncodeFn)fp;
  void *X1, *W2, *Y1, *X2, *Y2;
  cudaGetSymbolAddress(&X1, g_X1);
  cudaGetSymbolAddress(&W2, g_W2);
  cudaGetSymbolAddress(&Y1, g_Y1);
  cudaGetSymbolAddress(&X2, g_X2);
  cudaGetSymbolAddress(&Y2, g_Y2);
  cudaFuncSetAttribute(k1, cudaFuncAttributeMaxDynamicSharedMemorySize, K1_SMEM);
  cudaFuncSetAttribute(kC, cudaFuncAttributeMaxDynamicSharedMemorySize, C_SMEM);
  cudaFuncSetAttribute(kH, cudaFuncAttributeMaxDynamicSharedMemorySize, H_SMEM);
  cudaFuncSetAttribute(kE, cudaFuncAttributeMaxDynamicSharedMemorySize, E_SMEM);
  if (ALIAS) {
    W2 = d_out;
    X2 = (char*)d_out + sizeof(g_W2);
    X1 = (char*)X2 - sizeof(g_X2);
    Y2 = Y1;
  }
  const CUtensorMapSwizzle S128 = CU_TENSOR_MAP_SWIZZLE_128B, S64 = CU_TENSOR_MAP_SWIZZLE_64B;

  auto map_x = [&]() {
    uint64_t d[] = {64, 8000, 8, 2}, s[] = {1024, 128, 8000ull * 1024};
    uint32_t bx[] = {64, 56, 1, 1};
    return make_map(fn, x, 4, d, s, bx, S128);
  };
  auto map_w_in = [&](const __nv_bfloat16* w, int odd) {
    uint64_t d[] = {64, (uint64_t)(odd ? 15 : 16), 4, 256}, s[] = {2ull * 65536 * 2, 128, 512};
    uint32_t bx[] = {64, 16, 2, 1};
    return make_map(fn, w + (odd ? 65536 : 0), 4, d, s, bx, S128);
  };
  auto map_X_st = [&](void* p, int nb, int boxb) {
    uint64_t d[] = {64, 512, (uint64_t)(2 * nb)}, s[] = {2ull * nb * 128, 128};
    uint32_t bx[] = {64, 64, (uint32_t)boxb};
    return make_map(fn, p, 3, d, s, bx, S128);
  };
  auto map_X1_st = [&]() {
    uint64_t d[] = {64, 512, 2, (uint64_t)NB1}, s[] = {2ull * NB1 * 128, (uint64_t)NB1 * 128, 128};
    uint32_t bx[] = {64, 16, 1, 1};
    return make_map(fn, X1, 4, d, s, bx, S128);
  };
  auto map_W_st = [&](void* p) {
    uint64_t d[] = {64, 512, 4, 64}, s[] = {32768, 8192, 128};
    uint32_t bx[] = {64, 64, 2, 1};
    return make_map(fn, p, 4, d, s, bx, S128);
  };
  auto map_X_ld = [&](void* p, int nb, int boxb) {
    uint64_t d[] = {64, (uint64_t)(2 * nb), 512}, s[] = {128, 2ull * nb * 128};
    uint32_t bx[] = {32, (uint32_t)boxb, 1};
    return make_map(fn, p, 3, d, s, bx, S64);
  };
  auto map_W_ld = [&](void* p, uint32_t bd, uint32_t bf) {
    uint64_t d[] = {64, 64, 4, 512}, s[] = {128, 8192, 32768};
    uint32_t bx[] = {64, 32, bd, bf};
    return make_map(fn, p, 4, d, s, bx, S128);
  };
  auto map_Y_st = [&](void* p, int nb, int rows) {
    uint64_t d[] = {64, (uint64_t)(2 * nb), 64, 4}, s[] = {32768, 128, 8192};
    uint32_t bx[] = {64, (uint32_t)rows, 1, 1};
    return make_map(fn, p, 4, d, s, bx, S128);
  };
  auto map_Y_ld = [&](void* p, int nb, int boxc, int boxb) {
    uint64_t d[] = {64, 64, 4, (uint64_t)nb, 2}, s[] = {128, 8192, 32768, (uint64_t)nb * 32768};
    uint32_t bx[] = {64, 64, (uint32_t)boxc, (uint32_t)boxb, 1};
    return make_map(fn, p, 5, d, s, bx, S128);
  };
  auto map_wsq = [&](const __nv_bfloat16* w) {
    uint64_t d[] = {64, 256, 4}, s[] = {512, 128};
    uint32_t bx[] = {64, 64, 4};
    return make_map(fn, w, 3, d, s, bx, S128);
  };
  auto map_out = [&]() {
    uint64_t d[] = {64, 4000, 4, 8, 2}, s[] = {4096, 128, 512, 4000ull * 4096};
    uint32_t bx[] = {64, 64, 2, 1, 1};
    return make_map(fn, d_out, 5, d, s, bx, S128);
  };

  auto map_w_raw = [&](const __nv_bfloat16* w, int odd) {
    uint64_t d[] = {256, (uint64_t)(odd ? 15 : 16), 16, 16}, s[] = {2ull * 65536 * 2, 512, 8192};
    uint32_t bx[] = {64, 16, 4, 2};
    return make_map(fn, w + (odd ? 65536 : 0), 4, d, s, bx, S128);
  };
  K1Maps g1;
  memcpy(&g1.p, h_plan, sizeof(Plan));
  g1.x = map_x();
  g1.we = map_w_raw(w1, 0);
  g1.wo = map_w_raw(w1, 1);
  g1.xs = map_X1_st();
  g1.y = map_Y_st(Y1, NB1, NB1 / G_EPI);
  g1.w2e = map_w_in(w2, 0);
  g1.w2o = map_w_in(w2, 1);
  g1.w2s = map_W_st(W2);
  for (int s = 0; s < 32; s++) {
    const int k = s < 26 ? s >> 1 : 13 + (s - 26) % 3;
    g1.slot[s] = g_off(g_slot(s)) / 16;
    g1.src[s] = ((k >> 1) * 256 + (k & 1) * 2 + (s < 26 ? (s & 1) * 4 : s >= 29)) * (G_ST / 2);
    g1.dep[s] = s < 3 ? 8 * h_plan[64 + s] : 1536 + 8 * (s - g_depth(s));
  }
  launch(k1, 132, 384, K1_SMEM, false, g1, (const char*)X1, (const char*)w1, g, wgt);
  launch(kC, 128, 512, C_SMEM, true, map_Y_ld(Y1, NB1, 1, 1), map_X_st(X2, NB2, 1));
  launch(kH, 128, 288, H_SMEM, true, map_X_ld(X2, NB2, 168), map_W_ld(W2, 1, 2), map_Y_st(Y2, NB2, 168 / H_EPI), wf, wo);
  launch(kE, 126, 256, E_SMEM, true, map_Y_ld(Y2, NB2, 1, 2), map_wsq(wf), map_wsq(wo), map_out());
}
```

```cpp
#include <cuda_runtime.h>
#include <cuda_bf16.h>
#include <cuda.h>
#include <stdint.h>
#include <string.h>
#include <type_traits>

#define ALIAS 1
#define W_SHIFT 1
namespace {

constexpr int NB1 = 168;
constexpr int NB2 = 84;

__device__ __align__(1024) __nv_bfloat16 g_X1[8 * 64 * 2 * NB1 * 64];
__device__ __align__(1024) __nv_bfloat16 g_W2[8 * 64 * 4 * 64 * 64];
__device__ __align__(1024) __nv_bfloat16 g_Y1[2 * NB1 * 4 * 64 * 64];
__device__ __align__(1024) __nv_bfloat16 g_X2[8 * 64 * 2 * NB2 * 64];
__device__ __align__(1024) __nv_bfloat16 g_Y2[2 * NB2 * 4 * 64 * 64];
__device__ __align__(1024) float g_ge[16 * 256];

__device__ __forceinline__ uint32_t s2u(const void* p) { return (uint32_t)__cvta_generic_to_shared(p); }
__device__ __forceinline__ void mbar_init(uint32_t b, int c) {
  asm volatile("mbarrier.init.shared::cta.b64 [%0], %1;" ::"r"(b), "r"(c) : "memory");
}
__device__ __forceinline__ void mbar_expect(uint32_t b, int bytes) {
  asm volatile("mbarrier.arrive.expect_tx.shared::cta.b64 _, [%0], %1;" ::"r"(b), "r"(bytes) : "memory");
}
__device__ __forceinline__ void mbar_arrive(uint32_t b) {
  asm volatile("mbarrier.arrive.shared::cta.b64 _, [%0];" ::"r"(b) : "memory");
}
__device__ __forceinline__ void mbar_arrive_cta(uint32_t b, uint32_t cta) {
  asm volatile("{\n.reg .b32 r;\nmapa.shared::cluster.u32 r, %0, %1;\nmbarrier.arrive.shared::cluster.b64 _, [r];\n}" ::"r"(b), "r"(cta) : "memory");
}
__device__ __forceinline__ void mbar_wait(uint32_t b, int ph) {
  asm volatile(
      "{\n.reg .pred p;\n.reg .u32 n;\n"
      "mov.u32 n, 0;\n"
      "MBW_LOOP:\n"
      "mbarrier.try_wait.parity.shared::cta.b64 p, [%0], %1;\n"
      "@p bra MBW_DONE;\n"
      "add.u32 n, n, 1;\n"
      "setp.lt.u32 p, n, 1048576;\n"
      "@p bra MBW_LOOP;\n"
      "MBW_DONE:\n}" ::"r"(b), "r"(ph) : "memory");
}
__device__ __forceinline__ void fence_bar_init() { asm volatile("fence.mbarrier_init.release.cluster;" ::: "memory"); }
__device__ __forceinline__ void fence_async() { asm volatile("fence.proxy.async.shared::cta;" ::: "memory"); }
__device__ __forceinline__ void bar_sync(int id, int n) { asm volatile("bar.sync %0, %1;" ::"r"(id), "r"(n) : "memory"); }
__device__ __forceinline__ void bar_arrive(int id, int n) { asm volatile("bar.arrive %0, %1;" ::"r"(id), "r"(n) : "memory"); }
__device__ __forceinline__ void pdl_wait() { asm volatile("griddepcontrol.wait;" ::: "memory"); }
__device__ __forceinline__ void pdl_launch() { asm volatile("griddepcontrol.launch_dependents;" ::: "memory"); }
__device__ __forceinline__ void prefetch_map(const CUtensorMap* m) {
  asm volatile("prefetch.tensormap [%0];" ::"l"(m) : "memory");
}
template <int P> __device__ __forceinline__ uint64_t policy() {
  uint64_t p;
  asm("createpolicy.fractional.L2::evict_first.b64 %0, 1.0;" : "=l"(p));
  return p;
}
template <int P> __device__ __forceinline__ void tma_ld3(uint32_t dst, const CUtensorMap* m, uint32_t bar, int c0, int c1, int c2) {
  if constexpr (P == 0)
    asm volatile("cp.async.bulk.tensor.3d.shared::cluster.global.mbarrier::complete_tx::bytes [%0], [%1, {%3, %4, %5}], [%2];"
                 ::"r"(dst), "l"(m), "r"(bar), "r"(c0), "r"(c1), "r"(c2) : "memory");
  else
    asm volatile("cp.async.bulk.tensor.3d.shared::cluster.global.mbarrier::complete_tx::bytes.L2::cache_hint [%0], [%1, {%3, %4, %5}], [%2], %6;"
                 ::"r"(dst), "l"(m), "r"(bar), "r"(c0), "r"(c1), "r"(c2), "l"(policy<P>()) : "memory");
}
template <int P> __device__ __forceinline__ void tma_ld3mc(uint32_t dst, const CUtensorMap* m, uint32_t bar, int c0, int c1, int c2) {
  if constexpr (P == 0)
    asm volatile("cp.async.bulk.tensor.3d.shared::cluster.global.mbarrier::complete_tx::bytes.multicast::cluster [%0], [%1, {%3, %4, %5}], [%2], %6;"
                 ::"r"(dst), "l"(m), "r"(bar), "r"(c0), "r"(c1), "r"(c2), "h"((uint16_t)3) : "memory");
  else
    asm volatile("cp.async.bulk.tensor.3d.shared::cluster.global.mbarrier::complete_tx::bytes.multicast::cluster.L2::cache_hint [%0], [%1, {%3, %4, %5}], [%2], %6, %7;"
                 ::"r"(dst), "l"(m), "r"(bar), "r"(c0), "r"(c1), "r"(c2), "h"((uint16_t)3), "l"(policy<P>()) : "memory");
}
template <int P> __device__ __forceinline__ void tma_ld4(uint32_t dst, const CUtensorMap* m, uint32_t bar, int c0, int c1, int c2, int c3) {
  if constexpr (P == 0)
    asm volatile("cp.async.bulk.tensor.4d.shared::cluster.global.mbarrier::complete_tx::bytes [%0], [%1, {%3, %4, %5, %6}], [%2];"
                 ::"r"(dst), "l"(m), "r"(bar), "r"(c0), "r"(c1), "r"(c2), "r"(c3) : "memory");
  else
    asm volatile("cp.async.bulk.tensor.4d.shared::cluster.global.mbarrier::complete_tx::bytes.L2::cache_hint [%0], [%1, {%3, %4, %5, %6}], [%2], %7;"
                 ::"r"(dst), "l"(m), "r"(bar), "r"(c0), "r"(c1), "r"(c2), "r"(c3), "l"(policy<P>()) : "memory");
}
template <int P> __device__ __forceinline__ void tma_ld4mc(uint32_t dst, const CUtensorMap* m, uint32_t bar, int c0, int c1, int c2, int c3) {
  if constexpr (P == 0)
    asm volatile("cp.async.bulk.tensor.4d.shared::cluster.global.mbarrier::complete_tx::bytes.multicast::cluster [%0], [%1, {%3, %4, %5, %6}], [%2], %7;"
                 ::"r"(dst), "l"(m), "r"(bar), "r"(c0), "r"(c1), "r"(c2), "r"(c3), "h"((uint16_t)3) : "memory");
  else
    asm volatile("cp.async.bulk.tensor.4d.shared::cluster.global.mbarrier::complete_tx::bytes.multicast::cluster.L2::cache_hint [%0], [%1, {%3, %4, %5, %6}], [%2], %7, %8;"
                 ::"r"(dst), "l"(m), "r"(bar), "r"(c0), "r"(c1), "r"(c2), "r"(c3), "h"((uint16_t)3), "l"(policy<P>()) : "memory");
}
template <int P> __device__ __forceinline__ void tma_ld5(uint32_t dst, const CUtensorMap* m, uint32_t bar, int c0, int c1, int c2, int c3, int c4) {
  if constexpr (P == 0)
    asm volatile("cp.async.bulk.tensor.5d.shared::cluster.global.mbarrier::complete_tx::bytes [%0], [%1, {%3, %4, %5, %6, %7}], [%2];"
                 ::"r"(dst), "l"(m), "r"(bar), "r"(c0), "r"(c1), "r"(c2), "r"(c3), "r"(c4) : "memory");
  else
    asm volatile("cp.async.bulk.tensor.5d.shared::cluster.global.mbarrier::complete_tx::bytes.L2::cache_hint [%0], [%1, {%3, %4, %5, %6, %7}], [%2], %8;"
                 ::"r"(dst), "l"(m), "r"(bar), "r"(c0), "r"(c1), "r"(c2), "r"(c3), "r"(c4), "l"(policy<P>()) : "memory");
}
template <int P> __device__ __forceinline__ void tma_st3(const CUtensorMap* m, uint32_t src, int c0, int c1, int c2) {
  if constexpr (P == 0)
    asm volatile("cp.async.bulk.tensor.3d.global.shared::cta.bulk_group [%0, {%2, %3, %4}], [%1];" ::"l"(m), "r"(src), "r"(c0), "r"(c1), "r"(c2) : "memory");
  else
    asm volatile("cp.async.bulk.tensor.3d.global.shared::cta.bulk_group.L2::cache_hint [%0, {%2, %3, %4}], [%1], %5;" ::"l"(m), "r"(src), "r"(c0), "r"(c1), "r"(c2), "l"(policy<P>()) : "memory");
}
template <int P> __device__ __forceinline__ void tma_st4(const CUtensorMap* m, uint32_t src, int c0, int c1, int c2, int c3) {
  if constexpr (P == 0)
    asm volatile("cp.async.bulk.tensor.4d.global.shared::cta.bulk_group [%0, {%2, %3, %4, %5}], [%1];" ::"l"(m), "r"(src), "r"(c0), "r"(c1), "r"(c2), "r"(c3) : "memory");
  else
    asm volatile("cp.async.bulk.tensor.4d.global.shared::cta.bulk_group.L2::cache_hint [%0, {%2, %3, %4, %5}], [%1], %6;" ::"l"(m), "r"(src), "r"(c0), "r"(c1), "r"(c2), "r"(c3), "l"(policy<P>()) : "memory");
}
template <int P> __device__ __forceinline__ void tma_st5(const CUtensorMap* m, uint32_t src, int c0, int c1, int c2, int c3, int c4) {
  if constexpr (P == 0)
    asm volatile("cp.async.bulk.tensor.5d.global.shared::cta.bulk_group [%0, {%2, %3, %4, %5, %6}], [%1];" ::"l"(m), "r"(src), "r"(c0), "r"(c1), "r"(c2), "r"(c3), "r"(c4) : "memory");
  else
    asm volatile("cp.async.bulk.tensor.5d.global.shared::cta.bulk_group.L2::cache_hint [%0, {%2, %3, %4, %5, %6}], [%1], %7;" ::"l"(m), "r"(src), "r"(c0), "r"(c1), "r"(c2), "r"(c3), "r"(c4), "l"(policy<P>()) : "memory");
}
__device__ __forceinline__ void bulk_commit() { asm volatile("cp.async.bulk.commit_group;" ::: "memory"); }
template <int N> __device__ __forceinline__ void bulk_wait_read() { asm volatile("cp.async.bulk.wait_group.read %0;" ::"n"(N) : "memory"); }
__device__ __forceinline__ void wg_fence() { asm volatile("wgmma.fence.sync.aligned;" ::: "memory"); }
__device__ __forceinline__ void wg_commit() { asm volatile("wgmma.commit_group.sync.aligned;" ::: "memory"); }
template <int N> __device__ __forceinline__ void wg_wait() { asm volatile("wgmma.wait_group.sync.aligned %0;" ::"n"(N) : "memory"); }
template <int R> __device__ __forceinline__ void reg_fence(float (&d)[R]) {
#pragma unroll
  for (int i = 0; i < R; i++) asm volatile("" : "+f"(d[i])::"memory");
}
template <int R> __device__ __forceinline__ void reg_fence(uint32_t (&d)[R]) {
#pragma unroll
  for (int i = 0; i < R; i++) asm volatile("" : "+r"(d[i])::"memory");
}
__device__ __forceinline__ void stsm4(uint32_t a, uint32_t r0, uint32_t r1, uint32_t r2, uint32_t r3) {
  asm volatile("stmatrix.sync.aligned.m8n8.x4.shared.b16 [%0], {%1, %2, %3, %4};" ::"r"(a), "r"(r0), "r"(r1), "r"(r2), "r"(r3) : "memory");
}
__device__ __forceinline__ void stsm4t(uint32_t a, uint32_t r0, uint32_t r1, uint32_t r2, uint32_t r3) {
  asm volatile("stmatrix.sync.aligned.m8n8.x4.trans.shared.b16 [%0], {%1, %2, %3, %4};" ::"r"(a), "r"(r0), "r"(r1), "r"(r2), "r"(r3) : "memory");
}
__device__ __forceinline__ void ldsm4(uint32_t a, uint32_t& r0, uint32_t& r1, uint32_t& r2, uint32_t& r3) {
  asm volatile("ldmatrix.sync.aligned.m8n8.x4.shared.b16 {%0, %1, %2, %3}, [%4];" : "=r"(r0), "=r"(r1), "=r"(r2), "=r"(r3) : "r"(a) : "memory");
}
__device__ __forceinline__ void ldsm4t(uint32_t a, uint32_t& r0, uint32_t& r1, uint32_t& r2, uint32_t& r3) {
  asm volatile("ldmatrix.sync.aligned.m8n8.x4.trans.shared.b16 {%0, %1, %2, %3}, [%4];" : "=r"(r0), "=r"(r1), "=r"(r2), "=r"(r3) : "r"(a) : "memory");
}
__device__ __forceinline__ void ldg128(const uint4* p, uint32_t& a, uint32_t& b, uint32_t& c, uint32_t& d) {
  asm volatile("ld.global.nc.v4.u32 {%0, %1, %2, %3}, [%4];" : "=r"(a), "=r"(b), "=r"(c), "=r"(d) : "l"(p));
}
__device__ __forceinline__ uint32_t pack2(float lo, float hi) {
  uint32_t r;
  asm("cvt.rn.bf16x2.f32 %0, %1, %2;" : "=r"(r) : "f"(hi), "f"(lo));
  return r;
}
__device__ __forceinline__ float tanh_f32(float x) {
  float y;
  asm("tanh.approx.f32 %0, %1;" : "=f"(y) : "f"(x));
  return y;
}
__device__ __forceinline__ float gelu(float hx) {
  const float u = hx * fmaf(hx * hx, 8.0f * 0.044715f * 0.7978845608028654f, 2.0f * 0.7978845608028654f);
  return fmaf(hx, tanh_f32(u), hx);
}
__device__ __forceinline__ uint64_t mk_desc4(uint32_t addr4, uint32_t lbo, uint32_t sbo, uint32_t swz) {
  const uint32_t lo = addr4 + ((lbo >> 4) << 16), hi = (sbo >> 4) | (swz << 30);
  uint64_t d;
  asm("mov.b64 %0, {%1, %2};" : "=l"(d) : "r"(lo), "r"(hi));
  return d;
}
#define mk_desc(base, off, lbo, sbo, swz) mk_desc4((((base) & 0x3FFFF) >> 4) + ((off) >> 4), lbo, sbo, swz)

template <int SA, int SB, int TA, int TB>
__device__ __forceinline__ void wgmma_ss_48(float (&d)[24], uint64_t da, uint64_t db, int sd) {
  asm volatile("{\n.reg .pred p;\nsetp.ne.b32 p, %26, 0;\n"
      "wgmma.mma_async.sync.aligned.m64n48k16.f32.bf16.bf16 {"
      "%0, %1, %2, %3, %4, %5, %6, %7, %8, %9, %10, %11, %12, %13, %14, %15, %16, %17, %18, %19, %20, %21, %22, %23"
      "}, %24, %25, p, %27, %28, %29, %30;\n}\n"
      : "+f"(d[0]), "+f"(d[1]), "+f"(d[2]), "+f"(d[3]), "+f"(d[4]), "+f"(d[5]), "+f"(d[6]), "+f"(d[7]), "+f"(d[8]),
        "+f"(d[9]), "+f"(d[10]), "+f"(d[11]), "+f"(d[12]), "+f"(d[13]), "+f"(d[14]), "+f"(d[15]), "+f"(d[16]),
        "+f"(d[17]), "+f"(d[18]), "+f"(d[19]), "+f"(d[20]), "+f"(d[21]), "+f"(d[22]), "+f"(d[23])
      : "l"(da), "l"(db), "r"(sd), "n"(SA), "n"(SB), "n"(TA), "n"(TB));
}
template <int SA, int SB, int TA, int TB>
__device__ __forceinline__ void wgmma_ss_128(float (&d)[64], uint64_t da, uint64_t db, int sd) {
  asm volatile("{\n.reg .pred p;\nsetp.ne.b32 p, %66, 0;\n"
      "wgmma.mma_async.sync.aligned.m64n128k16.f32.bf16.bf16 {"
      "%0, %1, %2, %3, %4, %5, %6, %7, %8, %9, %10, %11, %12, %13, %14, %15, %16, %17, %18, %19, %20, %21, %22, %23, "
      "%24, %25, %26, %27, %28, %29, %30, %31, %32, %33, %34, %35, %36, %37, %38, %39, %40, %41, %42, %43, %44, %45, "
      "%46, %47, %48, %49, %50, %51, %52, %53, %54, %55, %56, %57, %58, %59, %60, %61, %62, %63"
      "}, %64, %65, p, %67, %68, %69, %70;\n}\n"
      : "+f"(d[0]), "+f"(d[1]), "+f"(d[2]), "+f"(d[3]), "+f"(d[4]), "+f"(d[5]), "+f"(d[6]), "+f"(d[7]), "+f"(d[8]),
        "+f"(d[9]), "+f"(d[10]), "+f"(d[11]), "+f"(d[12]), "+f"(d[13]), "+f"(d[14]), "+f"(d[15]), "+f"(d[16]),
        "+f"(d[17]), "+f"(d[18]), "+f"(d[19]), "+f"(d[20]), "+f"(d[21]), "+f"(d[22]), "+f"(d[23]), "+f"(d[24]),
        "+f"(d[25]), "+f"(d[26]), "+f"(d[27]), "+f"(d[28]), "+f"(d[29]), "+f"(d[30]), "+f"(d[31]), "+f"(d[32]),
        "+f"(d[33]), "+f"(d[34]), "+f"(d[35]), "+f"(d[36]), "+f"(d[37]), "+f"(d[38]), "+f"(d[39]), "+f"(d[40]),
        "+f"(d[41]), "+f"(d[42]), "+f"(d[43]), "+f"(d[44]), "+f"(d[45]), "+f"(d[46]), "+f"(d[47]), "+f"(d[48]),
        "+f"(d[49]), "+f"(d[50]), "+f"(d[51]), "+f"(d[52]), "+f"(d[53]), "+f"(d[54]), "+f"(d[55]), "+f"(d[56]),
        "+f"(d[57]), "+f"(d[58]), "+f"(d[59]), "+f"(d[60]), "+f"(d[61]), "+f"(d[62]), "+f"(d[63])
      : "l"(da), "l"(db), "r"(sd), "n"(SA), "n"(SB), "n"(TA), "n"(TB));
}
template <int SA, int SB, int TA, int TB>
__device__ __forceinline__ void wgmma_ss_168(float (&d)[84], uint64_t da, uint64_t db, int sd) {
  asm volatile("{\n.reg .pred p;\nsetp.ne.b32 p, %86, 0;\n"
      "wgmma.mma_async.sync.aligned.m64n168k16.f32.bf16.bf16 {"
      "%0, %1, %2, %3, %4, %5, %6, %7, %8, %9, %10, %11, %12, %13, %14, %15, %16, %17, %18, %19, %20, %21, %22, %23, "
      "%24, %25, %26, %27, %28, %29, %30, %31, %32, %33, %34, %35, %36, %37, %38, %39, %40, %41, %42, %43, %44, %45, "
      "%46, %47, %48, %49, %50, %51, %52, %53, %54, %55, %56, %57, %58, %59, %60, %61, %62, %63, %64, %65, %66, %67, "
      "%68, %69, %70, %71, %72, %73, %74, %75, %76, %77, %78, %79, %80, %81, %82, %83"
      "}, %84, %85, p, %87, %88, %89, %90;\n}\n"
      : "+f"(d[0]), "+f"(d[1]), "+f"(d[2]), "+f"(d[3]), "+f"(d[4]), "+f"(d[5]), "+f"(d[6]), "+f"(d[7]), "+f"(d[8]),
        "+f"(d[9]), "+f"(d[10]), "+f"(d[11]), "+f"(d[12]), "+f"(d[13]), "+f"(d[14]), "+f"(d[15]), "+f"(d[16]),
        "+f"(d[17]), "+f"(d[18]), "+f"(d[19]), "+f"(d[20]), "+f"(d[21]), "+f"(d[22]), "+f"(d[23]), "+f"(d[24]),
        "+f"(d[25]), "+f"(d[26]), "+f"(d[27]), "+f"(d[28]), "+f"(d[29]), "+f"(d[30]), "+f"(d[31]), "+f"(d[32]),
        "+f"(d[33]), "+f"(d[34]), "+f"(d[35]), "+f"(d[36]), "+f"(d[37]), "+f"(d[38]), "+f"(d[39]), "+f"(d[40]),
        "+f"(d[41]), "+f"(d[42]), "+f"(d[43]), "+f"(d[44]), "+f"(d[45]), "+f"(d[46]), "+f"(d[47]), "+f"(d[48]),
        "+f"(d[49]), "+f"(d[50]), "+f"(d[51]), "+f"(d[52]), "+f"(d[53]), "+f"(d[54]), "+f"(d[55]), "+f"(d[56]),
        "+f"(d[57]), "+f"(d[58]), "+f"(d[59]), "+f"(d[60]), "+f"(d[61]), "+f"(d[62]), "+f"(d[63]), "+f"(d[64]),
        "+f"(d[65]), "+f"(d[66]), "+f"(d[67]), "+f"(d[68]), "+f"(d[69]), "+f"(d[70]), "+f"(d[71]), "+f"(d[72]),
        "+f"(d[73]), "+f"(d[74]), "+f"(d[75]), "+f"(d[76]), "+f"(d[77]), "+f"(d[78]), "+f"(d[79]), "+f"(d[80]),
        "+f"(d[81]), "+f"(d[82]), "+f"(d[83])
      : "l"(da), "l"(db), "r"(sd), "n"(SA), "n"(SB), "n"(TA), "n"(TB));
}
template <int SA, int SB, int TB>
__device__ __forceinline__ void wgmma_rs_32(float (&d)[16], uint32_t a0, uint32_t a1, uint32_t a2, uint32_t a3, uint64_t db, int sd) {
  asm volatile("{\n.reg .pred p;\nsetp.ne.b32 p, %21, 0;\n"
      "wgmma.mma_async.sync.aligned.m64n32k16.f32.bf16.bf16 {"
      "%0, %1, %2, %3, %4, %5, %6, %7, %8, %9, %10, %11, %12, %13, %14, %15"
      "}, {%16, %17, %18, %19}, %20, p, %22, %23, %24;\n}\n"
      : "+f"(d[0]), "+f"(d[1]), "+f"(d[2]), "+f"(d[3]), "+f"(d[4]), "+f"(d[5]), "+f"(d[6]), "+f"(d[7]), "+f"(d[8]),
        "+f"(d[9]), "+f"(d[10]), "+f"(d[11]), "+f"(d[12]), "+f"(d[13]), "+f"(d[14]), "+f"(d[15])
      : "r"(a0), "r"(a1), "r"(a2), "r"(a3), "l"(db), "r"(sd), "n"(SA), "n"(SB), "n"(TB));
}
template <int SA, int SB, int TB>
__device__ __forceinline__ void wgmma_rs_64(float (&d)[32], uint32_t a0, uint32_t a1, uint32_t a2, uint32_t a3, uint64_t db, int sd) {
  asm volatile("{\n.reg .pred p;\nsetp.ne.b32 p, %37, 0;\n"
      "wgmma.mma_async.sync.aligned.m64n64k16.f32.bf16.bf16 {"
      "%0, %1, %2, %3, %4, %5, %6, %7, %8, %9, %10, %11, %12, %13, %14, %15, %16, %17, %18, %19, %20, %21, %22, %23, "
      "%24, %25, %26, %27, %28, %29, %30, %31"
      "}, {%32, %33, %34, %35}, %36, p, %38, %39, %40;\n}\n"
      : "+f"(d[0]), "+f"(d[1]), "+f"(d[2]), "+f"(d[3]), "+f"(d[4]), "+f"(d[5]), "+f"(d[6]), "+f"(d[7]), "+f"(d[8]),
        "+f"(d[9]), "+f"(d[10]), "+f"(d[11]), "+f"(d[12]), "+f"(d[13]), "+f"(d[14]), "+f"(d[15]), "+f"(d[16]),
        "+f"(d[17]), "+f"(d[18]), "+f"(d[19]), "+f"(d[20]), "+f"(d[21]), "+f"(d[22]), "+f"(d[23]), "+f"(d[24]),
        "+f"(d[25]), "+f"(d[26]), "+f"(d[27]), "+f"(d[28]), "+f"(d[29]), "+f"(d[30]), "+f"(d[31])
      : "r"(a0), "r"(a1), "r"(a2), "r"(a3), "l"(db), "r"(sd), "n"(SA), "n"(SB), "n"(TB));
}
template <int SA, int SB, int TB>
__device__ __forceinline__ void wgmma_rs_128(float (&d)[64], uint32_t a0, uint32_t a1, uint32_t a2, uint32_t a3, uint64_t db, int sd) {
  asm volatile("{\n.reg .pred p;\nsetp.ne.b32 p, %69, 0;\n"
      "wgmma.mma_async.sync.aligned.m64n128k16.f32.bf16.bf16 {"
      "%0, %1, %2, %3, %4, %5, %6, %7, %8, %9, %10, %11, %12, %13, %14, %15, %16, %17, %18, %19, %20, %21, %22, %23, "
      "%24, %25, %26, %27, %28, %29, %30, %31, %32, %33, %34, %35, %36, %37, %38, %39, %40, %41, %42, %43, %44, %45, "
      "%46, %47, %48, %49, %50, %51, %52, %53, %54, %55, %56, %57, %58, %59, %60, %61, %62, %63"
      "}, {%64, %65, %66, %67}, %68, p, %70, %71, %72;\n}\n"
      : "+f"(d[0]), "+f"(d[1]), "+f"(d[2]), "+f"(d[3]), "+f"(d[4]), "+f"(d[5]), "+f"(d[6]), "+f"(d[7]), "+f"(d[8]),
        "+f"(d[9]), "+f"(d[10]), "+f"(d[11]), "+f"(d[12]), "+f"(d[13]), "+f"(d[14]), "+f"(d[15]), "+f"(d[16]),
        "+f"(d[17]), "+f"(d[18]), "+f"(d[19]), "+f"(d[20]), "+f"(d[21]), "+f"(d[22]), "+f"(d[23]), "+f"(d[24]),
        "+f"(d[25]), "+f"(d[26]), "+f"(d[27]), "+f"(d[28]), "+f"(d[29]), "+f"(d[30]), "+f"(d[31]), "+f"(d[32]),
        "+f"(d[33]), "+f"(d[34]), "+f"(d[35]), "+f"(d[36]), "+f"(d[37]), "+f"(d[38]), "+f"(d[39]), "+f"(d[40]),
        "+f"(d[41]), "+f"(d[42]), "+f"(d[43]), "+f"(d[44]), "+f"(d[45]), "+f"(d[46]), "+f"(d[47]), "+f"(d[48]),
        "+f"(d[49]), "+f"(d[50]), "+f"(d[51]), "+f"(d[52]), "+f"(d[53]), "+f"(d[54]), "+f"(d[55]), "+f"(d[56]),
        "+f"(d[57]), "+f"(d[58]), "+f"(d[59]), "+f"(d[60]), "+f"(d[61]), "+f"(d[62]), "+f"(d[63])
      : "r"(a0), "r"(a1), "r"(a2), "r"(a3), "l"(db), "r"(sd), "n"(SA), "n"(SB), "n"(TB));
}
template <int SA, int SB, int TB>
__device__ __forceinline__ void wgmma_rs_168(float (&d)[84], uint32_t a0, uint32_t a1, uint32_t a2, uint32_t a3, uint64_t db, int sd) {
  asm volatile("{\n.reg .pred p;\nsetp.ne.b32 p, %89, 0;\n"
      "wgmma.mma_async.sync.aligned.m64n168k16.f32.bf16.bf16 {"
      "%0, %1, %2, %3, %4, %5, %6, %7, %8, %9, %10, %11, %12, %13, %14, %15, %16, %17, %18, %19, %20, %21, %22, %23, "
      "%24, %25, %26, %27, %28, %29, %30, %31, %32, %33, %34, %35, %36, %37, %38, %39, %40, %41, %42, %43, %44, %45, "
      "%46, %47, %48, %49, %50, %51, %52, %53, %54, %55, %56, %57, %58, %59, %60, %61, %62, %63, %64, %65, %66, %67, "
      "%68, %69, %70, %71, %72, %73, %74, %75, %76, %77, %78, %79, %80, %81, %82, %83"
      "}, {%84, %85, %86, %87}, %88, p, %90, %91, %92;\n}\n"
      : "+f"(d[0]), "+f"(d[1]), "+f"(d[2]), "+f"(d[3]), "+f"(d[4]), "+f"(d[5]), "+f"(d[6]), "+f"(d[7]), "+f"(d[8]),
        "+f"(d[9]), "+f"(d[10]), "+f"(d[11]), "+f"(d[12]), "+f"(d[13]), "+f"(d[14]), "+f"(d[15]), "+f"(d[16]),
        "+f"(d[17]), "+f"(d[18]), "+f"(d[19]), "+f"(d[20]), "+f"(d[21]), "+f"(d[22]), "+f"(d[23]), "+f"(d[24]),
        "+f"(d[25]), "+f"(d[26]), "+f"(d[27]), "+f"(d[28]), "+f"(d[29]), "+f"(d[30]), "+f"(d[31]), "+f"(d[32]),
        "+f"(d[33]), "+f"(d[34]), "+f"(d[35]), "+f"(d[36]), "+f"(d[37]), "+f"(d[38]), "+f"(d[39]), "+f"(d[40]),
        "+f"(d[41]), "+f"(d[42]), "+f"(d[43]), "+f"(d[44]), "+f"(d[45]), "+f"(d[46]), "+f"(d[47]), "+f"(d[48]),
        "+f"(d[49]), "+f"(d[50]), "+f"(d[51]), "+f"(d[52]), "+f"(d[53]), "+f"(d[54]), "+f"(d[55]), "+f"(d[56]),
        "+f"(d[57]), "+f"(d[58]), "+f"(d[59]), "+f"(d[60]), "+f"(d[61]), "+f"(d[62]), "+f"(d[63]), "+f"(d[64]),
        "+f"(d[65]), "+f"(d[66]), "+f"(d[67]), "+f"(d[68]), "+f"(d[69]), "+f"(d[70]), "+f"(d[71]), "+f"(d[72]),
        "+f"(d[73]), "+f"(d[74]), "+f"(d[75]), "+f"(d[76]), "+f"(d[77]), "+f"(d[78]), "+f"(d[79]), "+f"(d[80]),
        "+f"(d[81]), "+f"(d[82]), "+f"(d[83])
      : "r"(a0), "r"(a1), "r"(a2), "r"(a3), "l"(db), "r"(sd), "n"(SA), "n"(SB), "n"(TB));
}
template <int SA, int SB, int TB>
__device__ __forceinline__ void wgmma_rs_256(float (&d)[128], uint32_t a0, uint32_t a1, uint32_t a2, uint32_t a3, uint64_t db, int sd) {
  asm volatile("{\n.reg .pred p;\nsetp.ne.b32 p, %133, 0;\n"
      "wgmma.mma_async.sync.aligned.m64n256k16.f32.bf16.bf16 {"
      "%0, %1, %2, %3, %4, %5, %6, %7, %8, %9, %10, %11, %12, %13, %14, %15, %16, %17, %18, %19, %20, %21, %22, %23, "
      "%24, %25, %26, %27, %28, %29, %30, %31, %32, %33, %34, %35, %36, %37, %38, %39, %40, %41, %42, %43, %44, %45, "
      "%46, %47, %48, %49, %50, %51, %52, %53, %54, %55, %56, %57, %58, %59, %60, %61, %62, %63, %64, %65, %66, %67, "
      "%68, %69, %70, %71, %72, %73, %74, %75, %76, %77, %78, %79, %80, %81, %82, %83, %84, %85, %86, %87, %88, %89, "
      "%90, %91, %92, %93, %94, %95, %96, %97, %98, %99, %100, %101, %102, %103, %104, %105, %106, %107, %108, %109, "
      "%110, %111, %112, %113, %114, %115, %116, %117, %118, %119, %120, %121, %122, %123, %124, %125, %126, %127"
      "}, {%128, %129, %130, %131}, %132, p, %134, %135, %136;\n}\n"
      : "+f"(d[0]), "+f"(d[1]), "+f"(d[2]), "+f"(d[3]), "+f"(d[4]), "+f"(d[5]), "+f"(d[6]), "+f"(d[7]), "+f"(d[8]),
        "+f"(d[9]), "+f"(d[10]), "+f"(d[11]), "+f"(d[12]), "+f"(d[13]), "+f"(d[14]), "+f"(d[15]), "+f"(d[16]),
        "+f"(d[17]), "+f"(d[18]), "+f"(d[19]), "+f"(d[20]), "+f"(d[21]), "+f"(d[22]), "+f"(d[23]), "+f"(d[24]),
        "+f"(d[25]), "+f"(d[26]), "+f"(d[27]), "+f"(d[28]), "+f"(d[29]), "+f"(d[30]), "+f"(d[31]), "+f"(d[32]),
        "+f"(d[33]), "+f"(d[34]), "+f"(d[35]), "+f"(d[36]), "+f"(d[37]), "+f"(d[38]), "+f"(d[39]), "+f"(d[40]),
        "+f"(d[41]), "+f"(d[42]), "+f"(d[43]), "+f"(d[44]), "+f"(d[45]), "+f"(d[46]), "+f"(d[47]), "+f"(d[48]),
        "+f"(d[49]), "+f"(d[50]), "+f"(d[51]), "+f"(d[52]), "+f"(d[53]), "+f"(d[54]), "+f"(d[55]), "+f"(d[56]),
        "+f"(d[57]), "+f"(d[58]), "+f"(d[59]), "+f"(d[60]), "+f"(d[61]), "+f"(d[62]), "+f"(d[63]), "+f"(d[64]),
        "+f"(d[65]), "+f"(d[66]), "+f"(d[67]), "+f"(d[68]), "+f"(d[69]), "+f"(d[70]), "+f"(d[71]), "+f"(d[72]),
        "+f"(d[73]), "+f"(d[74]), "+f"(d[75]), "+f"(d[76]), "+f"(d[77]), "+f"(d[78]), "+f"(d[79]), "+f"(d[80]),
        "+f"(d[81]), "+f"(d[82]), "+f"(d[83]), "+f"(d[84]), "+f"(d[85]), "+f"(d[86]), "+f"(d[87]), "+f"(d[88]),
        "+f"(d[89]), "+f"(d[90]), "+f"(d[91]), "+f"(d[92]), "+f"(d[93]), "+f"(d[94]), "+f"(d[95]), "+f"(d[96]),
        "+f"(d[97]), "+f"(d[98]), "+f"(d[99]), "+f"(d[100]), "+f"(d[101]), "+f"(d[102]), "+f"(d[103]), "+f"(d[104]),
        "+f"(d[105]), "+f"(d[106]), "+f"(d[107]), "+f"(d[108]), "+f"(d[109]), "+f"(d[110]), "+f"(d[111]),
        "+f"(d[112]), "+f"(d[113]), "+f"(d[114]), "+f"(d[115]), "+f"(d[116]), "+f"(d[117]), "+f"(d[118]),
        "+f"(d[119]), "+f"(d[120]), "+f"(d[121]), "+f"(d[122]), "+f"(d[123]), "+f"(d[124]), "+f"(d[125]),
        "+f"(d[126]), "+f"(d[127])
      : "r"(a0), "r"(a1), "r"(a2), "r"(a3), "l"(db), "r"(sd), "n"(SA), "n"(SB), "n"(TB));
}

__device__ const __align__(128) uint32_t c_img[3584] = {
    0x00003c80, 0x00003c80, 0x00003c80, 0x00003c80, 0x00003c80, 0x00003c80, 0x00003c80, 0x00003c80, 0x00003c80, 0x00003c80,
    0x00003c80, 0x00003c80, 0x00003c80, 0x00003c80, 0x00003c80, 0x00003c80, 0x00003c80, 0x00003c80, 0x00003c80, 0x00003c80,
    0x00003c80, 0x00003c80, 0x00003c80, 0x00003c80, 0x00003c80, 0x00003c80, 0x00003c80, 0x00003c80, 0x00003c80, 0x00003c80,
    0x00003c80, 0x00003c80, 0x3c463c22, 0x3c623bf1, 0x3c753b95, 0x3c7f3ac9, 0x3ac93c7f, 0x3b953c75, 0x3bf13c62, 0x3c223c46,
    0x3c22bc46, 0x3bf1bc62, 0x3b95bc75, 0x3ac9bc7f, 0x3c7fbac9, 0x3c75bb95, 0x3c62bbf1, 0x3c46bc22, 0xbc46bc22, 0xbc62bbf1,
    0xbc75bb95, 0xbc7fbac9, 0xbac9bc7f, 0xbb95bc75, 0xbbf1bc62, 0xbc22bc46, 0xbc223c46, 0xbbf13c62, 0xbb953c75, 0xbac93c7f,
    0xbc7f3ac9, 0xbc753b95, 0xbc623bf1, 0xbc463c22, 0xbb48bc7b, 0xbc0ebc55, 0xbc55bc0e, 0xbc7bbb48, 0xbc7b3b48, 0xbc553c0e,
    0xbc0e3c55, 0xbb483c7b, 0x3b483c7b, 0x3c0e3c55, 0x3c553c0e, 0x3c7b3b48, 0x3c7bbb48, 0x3c55bc0e, 0x3c0ebc55, 0x3b48bc7b,
    0xbb48bc7b, 0xbc0ebc55, 0xbc55bc0e, 0xbc7bbb48, 0xbc7b3b48, 0xbc553c0e, 0xbc0e3c55, 0xbb483c7b, 0x3b483c7b, 0x3c0e3c55,
    0x3c553c0e, 0x3c7b3b48, 0x3c7bbb48, 0x3c55bc0e, 0x3c0ebc55, 0x3b48bc7b, 0x3c623bf1, 0x3c7fbac9, 0x3c46bc22, 0x3b95bc75,
    0xbc753b95, 0xbc223c46, 0xbac93c7f, 0x3bf13c62, 0x3bf1bc62, 0xbac9bc7f, 0xbc22bc46, 0xbc75bb95, 0x3b953c75, 0x3c463c22,
    0x3c7f3ac9, 0x3c62bbf1, 0xbc62bbf1, 0xbc7f3ac9, 0xbc463c22, 0xbb953c75, 0x3c75bb95, 0x3c22bc46, 0x3ac9bc7f, 0xbbf1bc62,
    0xbbf13c62, 0x3ac93c7f, 0x3c223c46, 0x3c753b95, 0xbb95bc75, 0xbc46bc22, 0xbc7fbac9, 0xbc623bf1, 0x3bc43c6d, 0x3c6d3bc4,
    0x3c6dbbc4, 0x3bc4bc6d, 0xbbc4bc6d, 0xbc6dbbc4, 0xbc6d3bc4, 0xbbc43c6d, 0x3bc43c6d, 0x3c6d3bc4, 0x3c6dbbc4, 0x3bc4bc6d,
    0xbbc4bc6d, 0xbc6dbbc4, 0xbc6d3bc4, 0xbbc43c6d, 0x3bc43c6d, 0x3c6d3bc4, 0x3c6dbbc4, 0x3bc4bc6d, 0xbbc4bc6d, 0xbc6dbbc4,
    0xbc6d3bc4, 0xbbc43c6d, 0x3bc43c6d, 0x3c6d3bc4, 0x3c6dbbc4, 0x3bc4bc6d, 0xbbc4bc6d, 0xbc6dbbc4, 0xbc6d3bc4, 0xbbc43c6d,
    0x3c753b95, 0x3c46bc22, 0xbac9bc7f, 0xbc62bbf1, 0xbbf1bc62, 0xbc7fbac9, 0xbc223c46, 0x3b953c75, 0x3b95bc75, 0xbc22bc46,
    0xbc7f3ac9, 0xbbf13c62, 0xbc623bf1, 0xbac93c7f, 0x3c463c22, 0x3c75bb95, 0xbc75bb95, 0xbc463c22, 0x3ac93c7f, 0x3c623bf1,
    0x3bf13c62, 0x3c7f3ac9, 0x3c22bc46, 0xbb95bc75, 0xbb953c75, 0x3c223c46, 0x3c7fbac9, 0x3bf1bc62, 0x3c62bbf1, 0x3ac9bc7f,
    0xbc46bc22, 0xbc753b95, 0xbc0ebc55, 0xbc7b3b48, 0xbb483c7b, 0x3c553c0e, 0x3c55bc0e, 0xbb48bc7b, 0xbc7bbb48, 0xbc0e3c55,
    0x3c0e3c55, 0x3c7bbb48, 0x3b48bc7b, 0xbc55bc0e, 0xbc553c0e, 0x3b483c7b, 0x3c7b3b48, 0x3c0ebc55, 0xbc0ebc55, 0xbc7b3b48,
    0xbb483c7b, 0x3c553c0e, 0x3c55bc0e, 0xbb48bc7b, 0xbc7bbb48, 0xbc0e3c55, 0x3c0e3c55, 0x3c7bbb48, 0x3b48bc7b, 0xbc55bc0e,
    0xbc553c0e, 0x3b483c7b, 0x3c7b3b48, 0x3c0ebc55, 0x3c7f3ac9, 0x3b95bc75, 0xbc62bbf1, 0xbc223c46, 0x3c46bc22, 0xbbf1bc62,
    0xbc753b95, 0x3ac93c7f, 0x3ac9bc7f, 0xbc75bb95, 0xbbf13c62, 0x3c463c22, 0xbc22bc46, 0xbc623bf1, 0x3b953c75, 0x3c7fbac9,
    0xbc7fbac9, 0xbb953c75, 0x3c623bf1, 0x3c22bc46, 0xbc463c22, 0x3bf13c62, 0x3c75bb95, 0xbac9bc7f, 0xbac93c7f, 0x3c753b95,
    0x3bf1bc62, 0xbc46bc22, 0x3c223c46, 0x3c62bbf1, 0xbb95bc75, 0xbc7f3ac9, 0x3a493c80, 0x3b163c7d, 0x3b793c78, 0x3bac3c71,
    0x3bdb3c67, 0x3c043c5c, 0x3c183c4e, 0x3c2c3c3e, 0x3c3e3c2c, 0x3c4e3c18, 0x3c5c3c04, 0x3c673bdb, 0x3c713bac, 0x3c783b79,
    0x3c7d3b16, 0x3c803a49, 0x3c80ba49, 0x3c7dbb16, 0x3c78bb79, 0x3c71bbac, 0x3c67bbdb, 0x3c5cbc04, 0x3c4ebc18, 0x3c3ebc2c,
    0x3c2cbc3e, 0x3c18bc4e, 0x3c04bc5c, 0x3bdbbc67, 0x3bacbc71, 0x3b79bc78, 0x3b16bc7d, 0x3a49bc80, 0x3c783b79, 0x3c80ba49,
    0x3c71bbac, 0x3c4ebc18, 0x3b163c7d, 0x3bdb3c67, 0x3c2c3c3e, 0x3c5c3c04, 0xbc04bc5c, 0xbc3ebc2c, 0xbc67bbdb, 0xbc7dbb16,
    0x3c18bc4e, 0x3bacbc71, 0x3a49bc80, 0xbb79bc78, 0xbb793c78, 0x3a493c80, 0x3bac3c71, 0x3c183c4e, 0xbc7d3b16, 0xbc673bdb,
    0xbc3e3c2c, 0xbc043c5c, 0x3c5cbc04, 0x3c2cbc3e, 0x3bdbbc67, 0x3b16bc7d, 0x3c4e3c18, 0x3c713bac, 0x3c803a49, 0x3c78bb79,
    0xbc5cbc04, 0xbc80ba49, 0xbc673bdb, 0xbc183c4e, 0xbb163c7d, 0x3bac3c71, 0x3c3e3c2c, 0x3c783b79, 0x3b793c78, 0x3c2c3c3e,
    0x3c713bac, 0x3c7dbb16, 0x3c4ebc18, 0x3bdbbc67, 0xba49bc80, 0xbc04bc5c, 0xbc043c5c, 0xba493c80, 0x3bdb3c67, 0x3c4e3c18,
    0x3c7d3b16, 0x3c71bbac, 0x3c2cbc3e, 0x3b79bc78, 0x3c78bb79, 0x3c3ebc2c, 0x3bacbc71, 0xbb16bc7d, 0xbc18bc4e, 0xbc67bbdb,
    0xbc803a49, 0xbc5c3c04, 0x3c3ebc2c, 0x3b16bc7d, 0xbc04bc5c, 0xbc71bbac, 0xbbdb3c67, 0x3b793c78, 0x3c4e3c18, 0x3c80ba49,
    0x3a49bc80, 0xbc18bc4e, 0xbc78bb79, 0xbc673bdb, 0x3bac3c71, 0x3c5c3c04, 0x3c7dbb16, 0x3c2cbc3e, 0x3c2c3c3e, 0x3c7d3b16,
    0x3c5cbc04, 0x3bacbc71, 0xbc67bbdb, 0xbc783b79, 0xbc183c4e, 0x3a493c80, 0x3c803a49, 0x3c4ebc18, 0x3b79bc78, 0xbbdbbc67,
    0xbc713bac, 0xbc043c5c, 0x3b163c7d, 0x3c3e3c2c, 0x3c67bbdb, 0x3b79bc78, 0xbc18bc4e, 0xbc80ba49, 0xbc2c3c3e, 0x3b163c7d,
    0x3c5c3c04, 0x3c71bbac, 0x3bacbc71, 0xbc04bc5c, 0xbc7dbb16, 0xbc3e3c2c, 0x3a493c80, 0x3c4e3c18, 0x3c78bb79, 0x3bdbbc67,
    0x3bdb3c67, 0x3c783b79, 0x3c4ebc18, 0x3a49bc80, 0xbc3ebc2c, 0xbc7d3b16, 0xbc043c5c, 0x3bac3c71, 0x3c713bac, 0x3c5cbc04,
    0x3b16bc7d, 0xbc2cbc3e, 0xbc803a49, 0xbc183c4e, 0x3b793c78, 0x3c673bdb, 0xbb16bc7d, 0xbc71bbac, 0xbc3e3c2c, 0x3b793c78,
    0xbc5c3c04, 0x3a493c80, 0x3c673bdb, 0x3c4ebc18, 0xbc183c4e, 0x3bdb3c67, 0x3c803a49, 0x3c04bc5c, 0x3c783b79, 0x3c2cbc3e,
    0xbbacbc71, 0xbc7dbb16, 0xbc7d3b16, 0xbbac3c71, 0x3c2c3c3e, 0x3c78bb79, 0x3c043c5c, 0x3c80ba49, 0x3bdbbc67, 0xbc18bc4e,
    0x3c4e3c18, 0x3c67bbdb, 0x3a49bc80, 0xbc5cbc04, 0x3b79bc78, 0xbc3ebc2c, 0xbc713bac, 0xbb163c7d, 0xbb163c7d, 0x3c673bdb,
    0x3c2cbc3e, 0xbc04bc5c, 0xbc783b79, 0xba493c80, 0x3c713bac, 0x3c18bc4e, 0x3c4ebc18, 0xbbacbc71, 0xbc803a49, 0xbb793c78,
    0x3c5c3c04, 0x3c3ebc2c, 0xbbdbbc67, 0xbc7d3b16, 0xbc7dbb16, 0xbbdb3c67, 0x3c3e3c2c, 0x3c5cbc04, 0xbb79bc78, 0xbc80ba49,
    0xbbac3c71, 0x3c4e3c18, 0x3c183c4e, 0x3c71bbac, 0xba49bc80, 0xbc78bb79, 0xbc043c5c, 0x3c2c3c3e, 0x3c67bbdb, 0xbb16bc7d,
    0xbc67bbdb, 0xbc043c5c, 0x3c4e3c18, 0x3c2cbc3e, 0xbc80ba49, 0xbb163c7d, 0x3c783b79, 0x3bacbc71, 0xbc713bac, 0x3b793c78,
    0x3c7dbb16, 0xba49bc80, 0xbc3e3c2c, 0x3c183c4e, 0x3c5cbc04, 0xbbdbbc67, 0xbbdb3c67, 0x3c5c3c04, 0x3c18bc4e, 0xbc3ebc2c,
    0xba493c80, 0x3c7d3b16, 0x3b79bc78, 0xbc71bbac, 0x3bac3c71, 0x3c78bb79, 0xbb16bc7d, 0xbc803a49, 0x3c2c3c3e, 0x3c4ebc18,
    0xbc04bc5c, 0xbc673bdb, 0x3c353c35, 0x3c35bc35, 0xbc35bc35, 0xbc353c35, 0x3c353c35, 0x3c35bc35, 0xbc35bc35, 0xbc353c35,
    0x3c353c35, 0x3c35bc35, 0xbc35bc35, 0xbc353c35, 0x3c353c35, 0x3c35bc35, 0xbc35bc35, 0xbc353c35, 0x3c353c35, 0x3c35bc35,
    0xbc35bc35, 0xbc353c35, 0x3c353c35, 0x3c35bc35, 0xbc35bc35, 0xbc353c35, 0x3c353c35, 0x3c35bc35, 0xbc35bc35, 0xbc353c35,
    0x3c353c35, 0x3c35bc35, 0xbc35bc35, 0xbc353c35, 0x3c7fbac9, 0xbb95bc75, 0xbc623bf1, 0x3c223c46, 0x3c463c22, 0x3bf1bc62,
    0xbc75bb95, 0xbac93c7f, 0xbac9bc7f, 0xbc753b95, 0x3bf13c62, 0x3c46bc22, 0x3c22bc46, 0xbc62bbf1, 0xbb953c75, 0x3c7f3ac9,
    0xbc7f3ac9, 0x3b953c75, 0x3c62bbf1, 0xbc22bc46, 0xbc46bc22, 0xbbf13c62, 0x3c753b95, 0x3ac9bc7f, 0x3ac93c7f, 0x3c75bb95,
    0xbbf1bc62, 0xbc463c22, 0xbc223c46, 0x3c623bf1, 0x3b95bc75, 0xbc7fbac9, 0xbc55bc0e, 0xbb483c7b, 0x3c7bbb48, 0xbc0ebc55,
    0xbc0e3c55, 0x3c7b3b48, 0xbb48bc7b, 0xbc553c0e, 0x3c553c0e, 0x3b48bc7b, 0xbc7b3b48, 0x3c0e3c55, 0x3c0ebc55, 0xbc7bbb48,
    0x3b483c7b, 0x3c55bc0e, 0xbc55bc0e, 0xbb483c7b, 0x3c7bbb48, 0xbc0ebc55, 0xbc0e3c55, 0x3c7b3b48, 0xbb48bc7b, 0xbc553c0e,
    0x3c553c0e, 0x3b48bc7b, 0xbc7b3b48, 0x3c0e3c55, 0x3c0ebc55, 0xbc7bbb48, 0x3b483c7b, 0x3c55bc0e, 0x3c75bb95, 0xbc46bc22,
    0xbac93c7f, 0x3c62bbf1, 0xbbf13c62, 0x3c7fbac9, 0xbc22bc46, 0xbb953c75, 0xbb95bc75, 0xbc223c46, 0x3c7f3ac9, 0xbbf1bc62,
    0x3c623bf1, 0xbac9bc7f, 0xbc463c22, 0x3c753b95, 0xbc753b95, 0x3c463c22, 0x3ac9bc7f, 0xbc623bf1, 0x3bf1bc62, 0xbc7f3ac9,
    0x3c223c46, 0x3b95bc75, 0x3b953c75, 0x3c22bc46, 0xbc7fbac9, 0x3bf13c62, 0xbc62bbf1, 0x3ac93c7f, 0x3c46bc22, 0xbc75bb95,
    0x3c6d3bc4, 0xbbc4bc6d, 0xbbc43c6d, 0x3c6dbbc4, 0xbc6dbbc4, 0x3bc43c6d, 0x3bc4bc6d, 0xbc6d3bc4, 0x3c6d3bc4, 0xbbc4bc6d,
    0xbbc43c6d, 0x3c6dbbc4, 0xbc6dbbc4, 0x3bc43c6d, 0x3bc4bc6d, 0xbc6d3bc4, 0x3c6d3bc4, 0xbbc4bc6d, 0xbbc43c6d, 0x3c6dbbc4,
    0xbc6dbbc4, 0x3bc43c6d, 0x3bc4bc6d, 0xbc6d3bc4, 0x3c6d3bc4, 0xbbc4bc6d, 0xbbc43c6d, 0x3c6dbbc4, 0xbc6dbbc4, 0x3bc43c6d,
    0x3bc4bc6d, 0xbc6d3bc4, 0x3c62bbf1, 0xbc7fbac9, 0x3c463c22, 0xbb95bc75, 0xbc75bb95, 0x3c223c46, 0xbac9bc7f, 0xbbf13c62,
    0xbbf1bc62, 0xbac93c7f, 0x3c22bc46, 0xbc753b95, 0xbb953c75, 0x3c46bc22, 0xbc7f3ac9, 0x3c623bf1, 0xbc623bf1, 0x3c7f3ac9,
    0xbc46bc22, 0x3b953c75, 0x3c753b95, 0xbc22bc46, 0x3ac93c7f, 0x3bf1bc62, 0x3bf13c62, 0x3ac9bc7f, 0xbc223c46, 0x3c75bb95,
    0x3b95bc75, 0xbc463c22, 0x3c7fbac9, 0xbc62bbf1, 0xbc7bbb48, 0x3c553c0e, 0xbc0ebc55, 0x3b483c7b, 0x3b48bc7b, 0xbc0e3c55,
    0x3c55bc0e, 0xbc7b3b48, 0x3c7b3b48, 0xbc55bc0e, 0x3c0e3c55, 0xbb48bc7b, 0xbb483c7b, 0x3c0ebc55, 0xbc553c0e, 0x3c7bbb48,
    0xbc7bbb48, 0x3c553c0e, 0xbc0ebc55, 0x3b483c7b, 0x3b48bc7b, 0xbc0e3c55, 0x3c55bc0e, 0xbc7b3b48, 0x3c7b3b48, 0xbc55bc0e,
    0x3c0e3c55, 0xbb48bc7b, 0xbb483c7b, 0x3c0ebc55, 0xbc553c0e, 0x3c7bbb48, 0x3c46bc22, 0xbc623bf1, 0x3c75bb95, 0xbc7f3ac9,
    0x3ac9bc7f, 0xbb953c75, 0x3bf1bc62, 0xbc223c46, 0xbc22bc46, 0x3bf13c62, 0xbb95bc75, 0x3ac93c7f, 0xbc7fbac9, 0x3c753b95,
    0xbc62bbf1, 0x3c463c22, 0xbc463c22, 0x3c62bbf1, 0xbc753b95, 0x3c7fbac9, 0xbac93c7f, 0x3b95bc75, 0xbbf13c62, 0x3c22bc46,
    0x3c223c46, 0xbbf1bc62, 0x3b953c75, 0xbac9bc7f, 0x3c7f3ac9, 0xbc75bb95, 0x3c623bf1, 0xbc46bc22, 0x3c3e3c2c, 0x3c18bc4e,
    0xbc5cbc04, 0xbbdb3c67, 0x3c713bac, 0x3b79bc78, 0xbc7dbb16, 0xba493c80, 0x3c80ba49, 0xbb16bc7d, 0xbc783b79, 0x3bac3c71,
    0x3c67bbdb, 0xbc04bc5c, 0xbc4e3c18, 0x3c2c3c3e, 0x3c2cbc3e, 0xbc4ebc18, 0xbc043c5c, 0x3c673bdb, 0x3bacbc71, 0xbc78bb79,
    0xbb163c7d, 0x3c803a49, 0xba49bc80, 0xbc7d3b16, 0x3b793c78, 0x3c71bbac, 0xbbdbbc67, 0xbc5c3c04, 0x3c183c4e, 0x3c3ebc2c,
    0x3c5cbc04, 0xbc3ebc2c, 0xbbdb3c67, 0x3c7d3b16, 0x3c4e3c18, 0x3bacbc71, 0xbc80ba49, 0x3b793c78, 0xbc78bb79, 0x3a493c80,
    0x3c71bbac, 0xbc18bc4e, 0xbb16bc7d, 0xbc673bdb, 0x3c2c3c3e, 0x3c04bc5c, 0x3c043c5c, 0x3c2cbc3e, 0xbc67bbdb, 0xbb163c7d,
    0xbc183c4e, 0x3c713bac, 0x3a49bc80, 0xbc783b79, 0x3b79bc78, 0xbc803a49, 0x3bac3c71, 0x3c4ebc18, 0x3c7dbb16, 0xbbdbbc67,
    0xbc3e3c2c, 0x3c5c3c04, 0xbc783b79, 0x3c2c3c3e, 0x3bacbc71, 0xbc7d3b16, 0x3c183c4e, 0x3bdbbc67, 0xbc803a49, 0x3c043c5c,
    0x3c5c3c04, 0x3a49bc80, 0xbc673bdb, 0x3c4e3c18, 0x3b16bc7d, 0xbc713bac, 0x3c3e3c2c, 0x3b79bc78, 0x3b793c78, 0x3c3ebc2c,
    0xbc71bbac, 0x3b163c7d, 0x3c4ebc18, 0xbc67bbdb, 0x3a493c80, 0x3c5cbc04, 0x3c04bc5c, 0xbc80ba49, 0x3bdb3c67, 0x3c18bc4e,
    0xbc7dbb16, 0x3bac3c71, 0x3c2cbc3e, 0xbc78bb79, 0x3a49bc80, 0xbc4e3c18, 0x3c783b79, 0xbbdbbc67, 0x3bac3c71, 0x3c04bc5c,
    0xbc7d3b16, 0x3c3e3c2c, 0xbc2cbc3e, 0xbb163c7d, 0x3c5cbc04, 0xbc71bbac, 0x3c673bdb, 0xbb79bc78, 0xbc183c4e, 0x3c80ba49,
    0x3c803a49, 0xbc18bc4e, 0xbb793c78, 0x3c67bbdb, 0xbc713bac, 0x3c5c3c04, 0xbb16bc7d, 0xbc2c3c3e, 0x3c3ebc2c, 0xbc7dbb16,
    0x3c043c5c, 0x3bacbc71, 0xbbdb3c67, 0x3c78bb79, 0xbc4ebc18, 0x3a493c80, 0x3bacbc71, 0xbc5c3c04, 0x3c7d3b16, 0xbc2cbc3e,
    0x3a493c80, 0x3c18bc4e, 0xbc783b79, 0x3c673bdb, 0xbbdbbc67, 0xbb793c78, 0x3c4ebc18, 0xbc80ba49, 0x3c3e3c2c, 0xbb16bc7d,
    0xbc043c5c, 0x3c71bbac, 0x3c713bac, 0xbc04bc5c, 0xbb163c7d, 0x3c3ebc2c, 0xbc803a49, 0x3c4e3c18, 0xbb79bc78, 0xbbdb3c67,
    0x3c67bbdb, 0xbc78bb79, 0x3c183c4e, 0x3a49bc80, 0xbc2c3c3e, 0x3c7dbb16, 0xbc5cbc04, 0x3bac3c71, 0xbc4ebc18, 0x3bdb3c67,
    0x3a49bc80, 0xbc043c5c, 0xbb793c78, 0x3c2cbc3e, 0xbc713bac, 0x3c7d3b16, 0x3b163c7d, 0x3bacbc71, 0xbc3e3c2c, 0x3c78bb79,
    0x3c5cbc04, 0xbc803a49, 0x3c673bdb, 0xbc18bc4e, 0xbc183c4e, 0x3c67bbdb, 0xbc80ba49, 0x3c5c3c04, 0x3c783b79, 0xbc3ebc2c,
    0x3bac3c71, 0x3b16bc7d, 0x3c7dbb16, 0xbc71bbac, 0x3c2c3c3e, 0xbb79bc78, 0xbc04bc5c, 0x3a493c80, 0x3bdbbc67, 0xbc4e3c18,
    0x3c183c4e, 0xbbacbc71, 0x3a493c80, 0x3b79bc78, 0xbc043c5c, 0x3c3ebc2c, 0xbc673bdb, 0x3c7dbb16, 0x3b16bc7d, 0xbbdb3c67,
    0x3c2cbc3e, 0xbc5c3c04, 0x3c78bb79, 0xbc80ba49, 0x3c713bac, 0xbc4ebc18, 0xbc4e3c18, 0x3c71bbac, 0xbc803a49, 0x3c783b79,
    0xbc5cbc04, 0x3c2c3c3e, 0xbbdbbc67, 0x3b163c7d, 0x3c7d3b16, 0xbc67bbdb, 0x3c3e3c2c, 0xbc04bc5c, 0x3b793c78, 0x3a49bc80,
    0xbbac3c71, 0x3c18bc4e, 0xbc713bac, 0x3c78bb79, 0xbc7d3b16, 0x3c80ba49, 0xbc3e3c2c, 0x3c4ebc18, 0xbc5c3c04, 0x3c67bbdb,
    0xbbdb3c67, 0x3c04bc5c, 0xbc183c4e, 0x3c2cbc3e, 0xba493c80, 0x3b16bc7d, 0xbb793c78, 0x3bacbc71, 0x3bac3c71, 0xbb79bc78,
    0x3b163c7d, 0xba49bc80, 0x3c2c3c3e, 0xbc18bc4e, 0x3c043c5c, 0xbbdbbc67, 0x3c673bdb, 0xbc5cbc04, 0x3c4e3c18, 0xbc3ebc2c,
    0x3c803a49, 0xbc7dbb16, 0x3c783b79, 0xbc71bbac, 0x3c800000, 0xbc800000, 0x3c800000, 0xbc800000, 0x3c800000, 0xbc800000,
    0x3c800000, 0xbc800000, 0x3c800000, 0xbc800000, 0x3c800000, 0xbc800000, 0x3c800000, 0xbc800000, 0x3c800000, 0xbc800000,
    0x3c800000, 0xbc800000, 0x3c800000, 0xbc800000, 0x3c800000, 0xbc800000, 0x3c800000, 0xbc800000, 0x3c800000, 0xbc800000,
    0x3c800000, 0xbc800000, 0x3c800000, 0xbc800000, 0x3c800000, 0xbc800000, 0x3c22bc46, 0xbbf13c62, 0x3b95bc75, 0xbac93c7f,
    0x3c7fbac9, 0xbc753b95, 0x3c62bbf1, 0xbc463c22, 0xbc46bc22, 0x3c623bf1, 0xbc75bb95, 0x3c7f3ac9, 0xbac9bc7f, 0x3b953c75,
    0xbbf1bc62, 0x3c223c46, 0xbc223c46, 0x3bf1bc62, 0xbb953c75, 0x3ac9bc7f, 0xbc7f3ac9, 0x3c75bb95, 0xbc623bf1, 0x3c46bc22,
    0x3c463c22, 0xbc62bbf1, 0x3c753b95, 0xbc7fbac9, 0x3ac93c7f, 0xbb95bc75, 0x3bf13c62, 0xbc22bc46, 0xbc7b3b48, 0x3c55bc0e,
    0xbc0e3c55, 0x3b48bc7b, 0x3b483c7b, 0xbc0ebc55, 0x3c553c0e, 0xbc7bbb48, 0x3c7bbb48, 0xbc553c0e, 0x3c0ebc55, 0xbb483c7b,
    0xbb48bc7b, 0x3c0e3c55, 0xbc55bc0e, 0x3c7b3b48, 0xbc7b3b48, 0x3c55bc0e, 0xbc0e3c55, 0x3b48bc7b, 0x3b483c7b, 0xbc0ebc55,
    0x3c553c0e, 0xbc7bbb48, 0x3c7bbb48, 0xbc553c0e, 0x3c0ebc55, 0xbb483c7b, 0xbb48bc7b, 0x3c0e3c55, 0xbc55bc0e, 0x3c7b3b48,
    0x3bf1bc62, 0x3ac93c7f, 0xbc22bc46, 0x3c753b95, 0x3b953c75, 0xbc46bc22, 0x3c7f3ac9, 0xbc623bf1, 0xbc62bbf1, 0x3c7fbac9,
    0xbc463c22, 0x3b95bc75, 0x3c75bb95, 0xbc223c46, 0x3ac9bc7f, 0x3bf13c62, 0xbbf13c62, 0xbac9bc7f, 0x3c223c46, 0xbc75bb95,
    0xbb95bc75, 0x3c463c22, 0xbc7fbac9, 0x3c62bbf1, 0x3c623bf1, 0xbc7f3ac9, 0x3c46bc22, 0xbb953c75, 0xbc753b95, 0x3c22bc46,
    0xbac93c7f, 0xbbf1bc62, 0x3c6dbbc4, 0xbbc43c6d, 0xbbc4bc6d, 0x3c6d3bc4, 0xbc6d3bc4, 0x3bc4bc6d, 0x3bc43c6d, 0xbc6dbbc4,
    0x3c6dbbc4, 0xbbc43c6d, 0xbbc4bc6d, 0x3c6d3bc4, 0xbc6d3bc4, 0x3bc4bc6d, 0x3bc43c6d, 0xbc6dbbc4, 0x3c6dbbc4, 0xbbc43c6d,
    0xbbc4bc6d, 0x3c6d3bc4, 0xbc6d3bc4, 0x3bc4bc6d, 0x3bc43c6d, 0xbc6dbbc4, 0x3c6dbbc4, 0xbbc43c6d, 0xbbc4bc6d, 0x3c6d3bc4,
    0xbc6d3bc4, 0x3bc4bc6d, 0x3bc43c6d, 0xbc6dbbc4, 0x3b95bc75, 0x3c223c46, 0xbc7f3ac9, 0x3bf1bc62, 0xbc623bf1, 0x3ac9bc7f,
    0x3c463c22, 0xbc753b95, 0xbc75bb95, 0x3c46bc22, 0x3ac93c7f, 0xbc62bbf1, 0x3bf13c62, 0xbc7fbac9, 0x3c22bc46, 0x3b953c75,
    0xbb953c75, 0xbc22bc46, 0x3c7fbac9, 0xbbf13c62, 0x3c62bbf1, 0xbac93c7f, 0xbc46bc22, 0x3c75bb95, 0x3c753b95, 0xbc463c22,
    0xbac9bc7f, 0x3c623bf1, 0xbbf1bc62, 0x3c7f3ac9, 0xbc223c46, 0xbb95bc75, 0xbc553c0e, 0xbb48bc7b, 0x3c7b3b48, 0xbc0e3c55,
    0xbc0ebc55, 0x3c7bbb48, 0xbb483c7b, 0xbc55bc0e, 0x3c55bc0e, 0x3b483c7b, 0xbc7bbb48, 0x3c0ebc55, 0x3c0e3c55, 0xbc7b3b48,
    0x3b48bc7b, 0x3c553c0e, 0xbc553c0e, 0xbb48bc7b, 0x3c7b3b48, 0xbc0e3c55, 0xbc0ebc55, 0x3c7bbb48, 0xbb483c7b, 0xbc55bc0e,
    0x3c55bc0e, 0x3b483c7b, 0xbc7bbb48, 0x3c0ebc55, 0x3c0e3c55, 0xbc7b3b48, 0x3b48bc7b, 0x3c553c0e, 0x3ac9bc7f, 0x3c753b95,
    0xbbf13c62, 0xbc46bc22, 0xbc22bc46, 0x3c62bbf1, 0x3b953c75, 0xbc7f3ac9, 0xbc7fbac9, 0x3b95bc75, 0x3c623bf1, 0xbc223c46,
    0xbc463c22, 0xbbf1bc62, 0x3c75bb95, 0x3ac93c7f, 0xbac93c7f, 0xbc75bb95, 0x3bf1bc62, 0x3c463c22, 0x3c223c46, 0xbc623bf1,
    0xbb95bc75, 0x3c7fbac9, 0x3c7f3ac9, 0xbb953c75, 0xbc62bbf1, 0x3c22bc46, 0x3c46bc22, 0x3bf13c62, 0xbc753b95, 0xbac9bc7f,
    0x3c80ba49, 0xbc7d3b16, 0x3c78bb79, 0xbc713bac, 0x3c67bbdb, 0xbc5c3c04, 0x3c4ebc18, 0xbc3e3c2c, 0x3c2cbc3e, 0xbc183c4e,
    0x3c04bc5c, 0xbbdb3c67, 0x3bacbc71, 0xbb793c78, 0x3b16bc7d, 0xba493c80, 0xba49bc80, 0x3b163c7d, 0xbb79bc78, 0x3bac3c71,
    0xbbdbbc67, 0x3c043c5c, 0xbc18bc4e, 0x3c2c3c3e, 0xbc3ebc2c, 0x3c4e3c18, 0xbc5cbc04, 0x3c673bdb, 0xbc71bbac, 0x3c783b79,
    0xbc7dbb16, 0x3c803a49, 0x3b79bc78, 0x3a493c80, 0xbbacbc71, 0x3c183c4e, 0x3c7dbb16, 0xbc673bdb, 0x3c3ebc2c, 0xbc043c5c,
    0xbc5c3c04, 0x3c2cbc3e, 0xbbdb3c67, 0x3b16bc7d, 0xbc4ebc18, 0x3c713bac, 0xbc80ba49, 0x3c78bb79, 0x3c783b79, 0xbc803a49,
    0x3c71bbac, 0xbc4e3c18, 0x3b163c7d, 0xbbdbbc67, 0x3c2c3c3e, 0xbc5cbc04, 0xbc04bc5c, 0x3c3e3c2c, 0xbc67bbdb, 0x3c7d3b16,
    0x3c18bc4e, 0xbbac3c71, 0x3a49bc80, 0x3b793c78, 0xbc043c5c, 0x3a49bc80, 0x3bdb3c67, 0xbc4ebc18, 0x3c7d3b16, 0xbc713bac,
    0x3c2cbc3e, 0xbb793c78, 0x3c78bb79, 0xbc3e3c2c, 0x3bacbc71, 0x3b163c7d, 0xbc18bc4e, 0x3c673bdb, 0xbc803a49, 0x3c5cbc04,
    0x3c5c3c04, 0xbc80ba49, 0x3c67bbdb, 0xbc183c4e, 0x3b16bc7d, 0x3bac3c71, 0xbc3ebc2c, 0x3c783b79, 0xbb79bc78, 0x3c2c3c3e,
    0xbc71bbac, 0x3c7dbb16, 0xbc4e3c18, 0x3bdbbc67, 0x3a493c80, 0xbc04bc5c, 0xbc2cbc3e, 0x3c7d3b16, 0xbc5c3c04, 0x3bacbc71,
    0x3c673bdb, 0xbc783b79, 0x3c18bc4e, 0x3a493c80, 0xbc80ba49, 0x3c4ebc18, 0xbb793c78, 0xbbdbbc67, 0x3c71bbac, 0xbc043c5c,
    0xbb16bc7d, 0x3c3e3c2c, 0x3c3ebc2c, 0xbb163c7d, 0xbc04bc5c, 0x3c713bac, 0xbbdb3c67, 0xbb79bc78, 0x3c4e3c18, 0xbc803a49,
    0x3a49bc80, 0x3c183c4e, 0xbc78bb79, 0x3c67bbdb, 0x3bac3c71, 0xbc5cbc04, 0x3c7dbb16, 0xbc2c3c3e, 0xbbdbbc67, 0x3c783b79,
    0xbc4e3c18, 0x3a49bc80, 0x3c3e3c2c, 0xbc7d3b16, 0x3c04bc5c, 0x3bac3c71, 0xbc71bbac, 0x3c5cbc04, 0xbb163c7d, 0xbc2cbc3e,
    0x3c80ba49, 0xbc183c4e, 0xbb79bc78, 0x3c673bdb, 0x3c67bbdb, 0xbb793c78, 0xbc18bc4e, 0x3c803a49, 0xbc2c3c3e, 0xbb16bc7d,
    0x3c5c3c04, 0xbc713bac, 0x3bacbc71, 0x3c043c5c, 0xbc7dbb16, 0x3c3ebc2c, 0x3a493c80, 0xbc4ebc18, 0x3c78bb79, 0xbbdb3c67,
    0xbc7d3b16, 0x3bacbc71, 0x3c2c3c3e, 0xbc783b79, 0x3c043c5c, 0xbc803a49, 0x3bdbbc67, 0x3c183c4e, 0x3c4e3c18, 0xbc673bdb,
    0x3a49bc80, 0x3c5c3c04, 0x3b79bc78, 0x3c3e3c2c, 0xbc713bac, 0x3b16bc7d, 0x3b163c7d, 0xbc71bbac, 0x3c3ebc2c, 0x3b793c78,
    0x3c5cbc04, 0x3a493c80, 0xbc67bbdb, 0x3c4ebc18, 0x3c18bc4e, 0x3bdb3c67, 0xbc80ba49, 0x3c04bc5c, 0xbc78bb79, 0x3c2cbc3e,
    0x3bac3c71, 0xbc7dbb16, 0x3c7d3b16, 0xbbdb3c67, 0xbc3ebc2c, 0x3c5cbc04, 0x3b793c78, 0xbc80ba49, 0x3bacbc71, 0x3c4e3c18,
    0xbc18bc4e, 0x3c71bbac, 0x3a493c80, 0xbc78bb79, 0x3c04bc5c, 0x3c2c3c3e, 0xbc673bdb, 0xbb16bc7d, 0xbb163c7d, 0xbc67bbdb,
    0x3c2cbc3e, 0x3c043c5c, 0xbc783b79, 0x3a49bc80, 0x3c713bac, 0xbc183c4e, 0x3c4ebc18, 0x3bac3c71, 0xbc803a49, 0x3b79bc78,
    0x3c5c3c04, 0xbc3e3c2c, 0xbbdbbc67, 0x3c7dbb16, 0xbbdb3c67, 0xbc5cbc04, 0x3c18bc4e, 0x3c3e3c2c, 0xba493c80, 0xbc7dbb16,
    0x3b79bc78, 0x3c713bac, 0x3bac3c71, 0xbc783b79, 0xbb16bc7d, 0x3c80ba49, 0x3c2c3c3e, 0xbc4e3c18, 0xbc04bc5c, 0x3c67bbdb,
    0x3c673bdb, 0xbc043c5c, 0xbc4ebc18, 0x3c2cbc3e, 0x3c803a49, 0xbb163c7d, 0xbc78bb79, 0x3bacbc71, 0x3c71bbac, 0x3b793c78,
    0xbc7d3b16, 0xba49bc80, 0x3c3ebc2c, 0x3c183c4e, 0xbc5c3c04, 0xbbdbbc67, 0x3f803f80, 0x3f7d3f7f, 0x3f783f7b, 0x3f713f75,
    0x3f673f6d, 0x3f5c3f62, 0x3f4e3f55, 0x3f3e3f46, 0x3f2c3f35, 0x3f183f22, 0x3f043f0e, 0x3edb3ef1, 0x3eac3ec4, 0x3e793e95,
    0x3e163e48, 0x3d493dc9, 0xbd490000, 0xbe16bdc9, 0xbe79be48, 0xbeacbe95, 0xbedbbec4, 0xbf04bef1, 0xbf18bf0e, 0xbf2cbf22,
    0xbf3ebf35, 0xbf4ebf46, 0xbf5cbf55, 0xbf67bf62, 0xbf71bf6d, 0xbf78bf75, 0xbf7dbf7b, 0xbf80bf7f, 0x3edb3ec4, 0x3f043ef1,
    0x3f183f0e, 0x3f2c3f22, 0x3d490000, 0x3e163dc9, 0x3e793e48, 0x3eac3e95, 0x3f713f6d, 0x3f783f75, 0x3f7d3f7b, 0x3f803f7f,
    0x3f3e3f35, 0x3f4e3f46, 0x3f5c3f55, 0x3f673f62, 0x3f673f6d, 0x3f5c3f62, 0x3f4e3f55, 0x3f3e3f46, 0x3f803f80, 0x3f7d3f7f,
    0x3f783f7b, 0x3f713f75, 0x3eac3ec4, 0x3e793e95, 0x3e163e48, 0x3d493dc9, 0x3f2c3f35, 0x3f183f22, 0x3f043f0e, 0x3edb3ef1,
    0xbf4ebf35, 0xbf71bf62, 0xbf80bf7b, 0xbf78bf7f, 0xbf5cbf6d, 0xbf2cbf46, 0xbedbbf0e, 0xbe16be95, 0x3f7d3f80, 0x3f673f75,
    0x3f3e3f55, 0x3f043f22, 0x3e793ec4, 0xbd493dc9, 0xbeacbe48, 0xbf18bef1, 0x3f183f35, 0x3eac3ef1, 0x3d493e48, 0xbe79bdc9,
    0xbf04bec4, 0xbf3ebf22, 0xbf67bf55, 0xbf7dbf75, 0x3e160000, 0x3edb3e95, 0x3f2c3f0e, 0x3f5c3f46, 0x3f783f6d, 0x3f803f7f,
    0x3f713f7b, 0x3f4e3f62, 0xbf04bec4, 0xbf3ebf22, 0xbf67bf55, 0xbf7dbf75, 0x3f183f35, 0x3eac3ef1, 0x3d493e48, 0xbe79bdc9,
    0x3f783f6d, 0x3f803f7f, 0x3f713f7b, 0x3f4e3f62, 0x3e160000, 0x3edb3e95, 0x3f2c3f0e, 0x3f5c3f46, 0x3f5c3f6d, 0x3f2c3f46,
    0x3edb3f0e, 0x3e163e95, 0x3f4e3f35, 0x3f713f62, 0x3f803f7b, 0x3f783f7f, 0xbe79bec4, 0x3d49bdc9, 0x3eac3e48, 0x3f183ef1,
    0xbf7dbf80, 0xbf67bf75, 0xbf3ebf55, 0xbf04bf22, 0xbe790000, 0xbf2cbef1, 0xbf71bf55, 0xbf7dbf7f, 0xbf4ebf6d, 0xbedbbf22,
    0x3d49be48, 0x3f043e95, 0x3f5c3f35, 0x3f803f75, 0x3f673f7b, 0x3f183f46, 0x3e163ec4, 0xbeacbdc9, 0xbf3ebf0e, 0xbf78bf62,
    0x3f783f80, 0x3f3e3f62, 0x3eac3f0e, 0xbe163dc9, 0xbf18bec4, 0xbf67bf46, 0xbf80bf7b, 0xbf5cbf75, 0xbf04bf35, 0xbd49be95,
    0x3edb3e48, 0x3f4e3f22, 0x3f7d3f6d, 0x3f713f7f, 0x3f2c3f55, 0x3e793ef1, 0xbf18bec4, 0xbf67bf46, 0xbf80bf7b, 0xbf5cbf75,
    0x3f783f80, 0x3f3e3f62, 0x3eac3f0e, 0xbe163dc9, 0x3f7d3f6d, 0x3f713f7f, 0x3f2c3f55, 0x3e793ef1, 0xbf04bf35, 0xbd49be95,
    0x3edb3e48, 0x3f4e3f22, 0x3f4e3f6d, 0x3edb3f22, 0xbd493e48, 0xbf04be95, 0x3e790000, 0x3f2c3ef1, 0x3f713f55, 0x3f7d3f7f,
    0xbe16bec4, 0x3eac3dc9, 0x3f3e3f0e, 0x3f783f62, 0xbf5cbf35, 0xbf80bf75, 0xbf67bf7b, 0xbf18bf46, 0xbedbbf35, 0x3e79bdc9,
    0x3f4e3f0e, 0x3f803f75, 0x3f3e3f6d, 0x3e163ef1, 0xbf04be48, 0xbf71bf46, 0x3eac0000, 0x3f5c3f22, 0x3f7d3f7b, 0x3f2c3f62,
    0x3d493ec4, 0xbf18be95, 0xbf78bf55, 0xbf67bf7f, 0x3f673f35, 0x3f783f7f, 0x3f183f55, 0xbd493e95, 0xbf2cbec4, 0xbf7dbf62,
    0xbf5cbf7b, 0xbeacbf22, 0x3f713f80, 0x3f043f46, 0xbe163e48, 0xbf3ebef1, 0xbf80bf6d, 0xbf4ebf75, 0xbe79bf0e, 0x3edb3dc9,
    0x3f2c3ec4, 0x3f7d3f62, 0x3f5c3f7b, 0x3eac3f22, 0xbf67bf35, 0xbf78bf7f, 0xbf18bf55, 0x3d49be95, 0x3f803f6d, 0x3f4e3f75,
    0x3e793f0e, 0xbedbbdc9, 0xbf71bf80, 0xbf04bf46, 0x3e16be48, 0x3f3e3ef1, 0x3f3e3f6d, 0x3e163ef1, 0xbf04be48, 0xbf71bf46,
    0xbedbbf35, 0x3e79bdc9, 0x3f4e3f0e, 0x3f803f75, 0x3d493ec4, 0xbf18be95, 0xbf78bf55, 0xbf67bf7f, 0x3eac0000, 0x3f5c3f22,
    0x3f7d3f7b, 0x3f2c3f62, 0x3f673f80, 0x3e793f22, 0xbf18be48, 0xbf80bf62, 0xbf2cbf6d, 0x3e16be95, 0x3f5c3f0e, 0x3f713f7f,
    0x3eac3f35, 0xbf04bdc9, 0xbf7dbf55, 0xbf3ebf75, 0x3d49bec4, 0x3f4e3ef1, 0x3f783f7b, 0x3edb3f46, 0xbedb0000, 0xbf78bf46,
    0xbf4ebf7b, 0xbd49bef1, 0x3f3e3ec4, 0x3f7d3f75, 0x3f043f55, 0xbeac3dc9, 0xbf71bf35, 0xbf5cbf7f, 0xbe16bf0e, 0x3f2c3e95,
    0x3f803f6d, 0x3f183f62, 0xbe793e48, 0xbf67bf22, 0xbf3ebec4, 0xbf7dbf75, 0xbf04bf55, 0x3eacbdc9, 0x3edb0000, 0x3f783f46,
    0x3f4e3f7b, 0x3d493ef1, 0xbf80bf6d, 0xbf18bf62, 0x3e79be48, 0x3f673f22, 0x3f713f35, 0x3f5c3f7f, 0x3e163f0e, 0xbf2cbe95,
    0xbf2cbf6d, 0x3e16be95, 0x3f5c3f0e, 0x3f713f7f, 0x3f673f80, 0x3e793f22, 0xbf18be48, 0xbf80bf62, 0x3d49bec4, 0x3f4e3ef1,
    0x3f783f7b, 0x3edb3f46, 0x3eac3f35, 0xbf04bdc9, 0xbf7dbf55, 0xbf3ebf75, 0xbf78bf35, 0xbf2cbf75, 0x3eacbe48, 0x3f7d3f46,
    0x3f183f6d, 0xbedb3dc9, 0xbf80bf55, 0xbf04bf62, 0x3f5c3f80, 0xbd493ef1, 0xbf67bf0e, 0xbf4ebf7f, 0x3e16bec4, 0x3f713f22,
    0x3f3e3f7b, 0xbe793e95, 0x3e793f35, 0xbf3ebe95, 0xbf71bf7b, 0xbe16bf22, 0x3f4e3ec4, 0x3f673f7f, 0x3d493f0e, 0xbf5cbef1,
    0x3f040000, 0x3f803f62, 0x3edb3f55, 0xbf18bdc9, 0xbf7dbf6d, 0xbeacbf46, 0x3f2c3e48, 0x3f783f75, 0x3f4e3ec4, 0x3f673f7f,
    0x3d493f0e, 0xbf5cbef1, 0x3e793f35, 0xbf3ebe95, 0xbf71bf7b, 0xbe16bf22, 0xbf7dbf6d, 0xbeacbf46, 0x3f2c3e48, 0x3f783f75,
    0x3f040000, 0x3f803f62, 0x3edb3f55, 0xbf18bdc9, 0xbf18bf6d, 0x3edbbdc9, 0x3f803f55, 0x3f043f62, 0x3f783f35, 0x3f2c3f75,
    0xbeac3e48, 0xbf7dbf46, 0xbe163ec4, 0xbf71bf22, 0xbf3ebf7b, 0x3e79be95, 0xbf5cbf80, 0x3d49bef1, 0x3f673f0e, 0x3f4e3f7f,
    0xbf180000, 0xbf71bf75, 0x3d49bf0e, 0x3f783f22, 0x3f043f6d, 0xbf2cbdc9, 0xbf67bf7b, 0x3e16bef1, 0x3f7d3f35, 0x3edb3f62,
    0xbf3ebe48, 0xbf5cbf7f, 0x3e79bec4, 0x3f803f46, 0x3eac3f55, 0xbf4ebe95, 0x3f4e3f80, 0xbeac3e95, 0xbf80bf55, 0xbe79bf46,
    0x3f5c3ec4, 0x3f3e3f7f, 0xbedb3e48, 0xbf7dbf62, 0xbe16bf35, 0x3f673ef1, 0x3f2c3f7b, 0xbf043dc9, 0xbf78bf6d, 0xbd49bf22,
    0x3f713f0e, 0x3f183f75, 0x3f5c3ec4, 0x3f3e3f7f, 0xbedb3e48, 0xbf7dbf62, 0x3f4e3f80, 0xbeac3e95, 0xbf80bf55, 0xbe79bf46,
    0xbf78bf6d, 0xbd49bf22, 0x3f713f0e, 0x3f183f75, 0xbe16bf35, 0x3f673ef1, 0x3f2c3f7b, 0xbf043dc9, 0xbf04bf6d, 0x3f2c3dc9,
    0x3f673f7b, 0xbe163ef1, 0x3f180000, 0x3f713f75, 0xbd493f0e, 0xbf78bf22, 0xbe793ec4, 0xbf80bf46, 0xbeacbf55, 0x3f4e3e95,
    0xbf7dbf35, 0xbedbbf62, 0x3f3e3e48, 0x3f5c3f7f, 0xbd49bf35, 0x3f7d3f22, 0x3e793f55, 0xbf71bef1, 0xbedbbf6d, 0x3f5c3e95,
    0x3f183f7b, 0xbf3ebdc9, 0x3f2c0000, 0x3f4e3f7f, 0xbf043e48, 0xbf67bf75, 0x3eacbec4, 0x3f783f62, 0xbe163f0e, 0xbf80bf46,
    0x3f803f35, 0x3e163f46, 0xbf78bf0e, 0xbeacbf62, 0x3f673ec4, 0x3f043f75, 0xbf4ebe48, 0xbf2cbf7f, 0x3f3e3f80, 0xbf183dc9,
    0xbf5cbf7b, 0x3edbbe95, 0x3f713f6d, 0xbe793ef1, 0xbf7dbf55, 0x3d49bf22, 0xbf67bec4, 0xbf04bf75, 0x3f4e3e48, 0x3f2c3f7f,
    0xbf80bf35, 0xbe16bf46, 0x3f783f0e, 0x3eac3f62, 0xbf71bf6d, 0x3e79bef1, 0x3f7d3f55, 0xbd493f22, 0xbf3ebf80, 0x3f18bdc9,
    0x3f5c3f7b, 0xbedb3e95, 0xbedbbf6d, 0x3f5c3e95, 0x3f183f7b, 0xbf3ebdc9, 0xbd49bf35, 0x3f7d3f22, 0x3e793f55, 0xbf71bef1,
    0x3eacbec4, 0x3f783f62, 0xbe163f0e, 0xbf80bf46, 0x3f2c0000, 0x3f4e3f7f, 0xbf043e48, 0xbf67bf75, 0x3f2c3f80, 0xbf4ebdc9,
    0xbf04bf7b, 0x3f673e95, 0x3eac3f6d, 0xbf78bef1, 0xbe16bf55, 0x3f803f22, 0xbd493f35, 0xbf7dbf46, 0x3e79bf0e, 0x3f713f62,
    0xbedb3ec4, 0xbf5cbf75, 0x3f18be48, 0x3f3e3f7f, 0xbf3e0000, 0xbf18bf7f, 0x3f5c3e48, 0x3edb3f75, 0xbf71bec4, 0xbe79bf62,
    0x3f7d3f0e, 0x3d493f46, 0xbf80bf35, 0x3e16bf22, 0x3f783f55, 0xbeac3ef1, 0xbf67bf6d, 0x3f04be95, 0x3f4e3f7b, 0xbf2c3dc9,
    0x3f713ec4, 0x3e793f62, 0xbf7dbf0e, 0xbd49bf46, 0x3f3e0000, 0x3f183f7f, 0xbf5cbe48, 0xbedbbf75, 0x3f673f6d, 0xbf043e95,
    0xbf4ebf7b, 0x3f2cbdc9, 0x3f803f35, 0xbe163f22, 0xbf78bf55, 0x3eacbef1, 0x3eac3f6d, 0xbf78bef1, 0xbe16bf55, 0x3f803f22,
    0x3f2c3f80, 0xbf4ebdc9, 0xbf04bf7b, 0x3f673e95, 0xbedb3ec4, 0xbf5cbf75, 0x3f18be48, 0x3f3e3f7f, 0xbd493f35, 0xbf7dbf46,
    0x3e79bf0e, 0x3f713f62, 0xbf7dbf35, 0x3edbbef1, 0x3f3e3f7b, 0xbf5cbdc9, 0xbe79bf6d, 0x3f803f22, 0xbeac3f0e, 0xbf4ebf75,
    0x3f183f80, 0xbf71be95, 0xbd49bf55, 0x3f783f46, 0xbf043ec4, 0xbf2cbf7f, 0x3f673e48, 0x3e163f62, 0xbe163f35, 0xbf67bf62,
    0x3f2cbe48, 0x3f043f7f, 0xbf78bec4, 0x3d49bf46, 0x3f713f55, 0xbf183e95, 0x3f4e0000, 0x3eac3f75, 0xbf80bf0e, 0x3e79bf22,
    0x3f5c3f6d, 0xbf3e3dc9, 0xbedbbf7b, 0x3f7d3ef1, 0xbf78bec4, 0x3d49bf46, 0x3f713f55, 0xbf183e95, 0xbe163f35, 0xbf67bf62,
    0x3f2cbe48, 0x3f043f7f, 0x3f5c3f6d, 0xbf3e3dc9, 0xbedbbf7b, 0x3f7d3ef1, 0x3f4e0000, 0x3eac3f75, 0xbf80bf0e, 0x3e79bf22,
    0x3e793f6d, 0xbf80bf22, 0x3eacbf0e, 0x3f4e3f75, 0x3f7d3f35, 0xbedb3ef1, 0xbf3ebf7b, 0x3f5c3dc9, 0x3f04bec4, 0x3f2c3f7f,
    0xbf67be48, 0xbe16bf62, 0xbf18bf80, 0x3f713e95, 0x3d493f55, 0xbf78bf46, 0xbf5c0000, 0xbd49bf62, 0x3f673f55, 0xbf4e3dc9,
    0xbe16bf6d, 0x3f713f46, 0xbf3e3e48, 0xbe79bf75, 0x3f783f35, 0xbf2c3e95, 0xbeacbf7b, 0x3f7d3f22, 0xbf183ec4, 0xbedbbf7f,
    0x3f803f0e, 0xbf043ef1, 0x3f043f80, 0xbf80bef1, 0x3edbbf0e, 0x3f183f7f, 0xbf7dbec4, 0x3eacbf22, 0x3f2c3f7b, 0xbf78be95,
    0x3e79bf35, 0x3f3e3f75, 0xbf71be48, 0x3e16bf46, 0x3f4e3f6d, 0xbf67bdc9, 0x3d49bf55, 0x3f5c3f62, 0xbf7dbec4, 0x3eacbf22,
    0x3f2c3f7b, 0xbf78be95, 0x3f043f80, 0xbf80bef1, 0x3edbbf0e, 0x3f183f7f, 0x3f4e3f6d, 0xbf67bdc9, 0x3d49bf55, 0x3f5c3f62,
    0x3e79bf35, 0x3f3e3f75, 0xbf71be48, 0x3e16bf46, 0x3e163f6d, 0xbf71bf46, 0x3f3ebe48, 0x3e793f75, 0x3f5c0000, 0x3d493f62,
    0xbf67bf55, 0x3f4ebdc9, 0x3f18bec4, 0x3edb3f7f, 0xbf80bf0e, 0x3f04bef1, 0xbf78bf35, 0x3f2cbe95, 0x3eac3f7b, 0xbf7dbf22,
    0x3eacbf35, 0x3f043f7f, 0xbf7dbf0e, 0x3f3ebe95, 0x3d493f6d, 0xbf4ebf62, 0x3f783e48, 0xbedb3f22, 0x3f670000, 0xbe793f46,
    0xbf18bf7b, 0x3f803ef1, 0xbf2c3ec4, 0xbe16bf75, 0x3f5c3f55, 0xbf71bdc9, 0x3f713f35, 0xbf5c3dc9, 0x3e16bf55, 0x3f2c3f75,
    0xbf80bec4, 0x3f18bef1, 0x3e793f7b, 0xbf67bf46, 0x3edb3f80, 0xbf78bf22, 0x3f4ebe48, 0xbd493f62, 0xbf3ebf6d, 0x3f7d3e95,
    0xbf043f0e, 0xbeacbf7f, 0x3f803ec4, 0xbf183ef1, 0xbe79bf7b, 0x3f673f46, 0xbf71bf35, 0x3f5cbdc9, 0xbe163f55, 0xbf2cbf75,
    0x3f3e3f6d, 0xbf7dbe95, 0x3f04bf0e, 0x3eac3f7f, 0xbedbbf80, 0x3f783f22, 0xbf4e3e48, 0x3d49bf62, 0x3d493f6d, 0xbf4ebf62,
    0x3f783e48, 0xbedb3f22, 0x3eacbf35, 0x3f043f7f, 0xbf7dbf0e, 0x3f3ebe95, 0xbf2c3ec4, 0xbe16bf75, 0x3f5c3f55, 0xbf71bdc9,
    0x3f670000, 0xbe793f46, 0xbf18bf7b, 0x3f803ef1, 0x3eac3f80, 0xbf5cbf46, 0x3f7d3e48, 0xbf2c3ef1, 0x3d49bf6d, 0x3f183f75,
    0xbf78bf0e, 0x3f67bdc9, 0xbedb3f35, 0xbe79bf7f, 0x3f4e3f55, 0xbf80be95, 0x3f3ebec4, 0xbe163f62, 0xbf04bf7b, 0x3f713f22,
    0xbf710000, 0x3f04bf22, 0x3e163f7b, 0xbf3ebf62, 0x3f803ec4, 0xbf4e3e95, 0x3e79bf55, 0x3edb3f7f, 0xbf67bf35, 0x3f783dc9,
    0xbf183f0e, 0xbd49bf75, 0x3f2c3f6d, 0xbf7dbef1, 0x3f5cbe48, 0xbeac3f46, 0xbf80bec4, 0x3f4ebe95, 0xbe793f55, 0xbedbbf7f,
    0x3f710000, 0xbf043f22, 0xbe16bf7b, 0x3f3e3f62, 0xbf2cbf6d, 0x3f7d3ef1, 0xbf5c3e48, 0x3eacbf46, 0x3f673f35, 0xbf78bdc9,
    0x3f18bf0e, 0x3d493f75, 0x3d49bf6d, 0x3f183f75, 0xbf78bf0e, 0x3f67bdc9, 0x3eac3f80, 0xbf5cbf46, 0x3f7d3e48, 0xbf2c3ef1,
    0x3f3ebec4, 0xbe163f62, 0xbf04bf7b, 0x3f713f22, 0xbedb3f35, 0xbe79bf7f, 0x3f4e3f55, 0xbf80be95, 0xbf5cbf35, 0x3f803e95,
    0xbf673e48, 0x3f18bf22, 0xbe163f6d, 0xbeacbf7f, 0x3f3e3f55, 0xbf78bef1, 0x3e793f80, 0xbf2cbf62, 0x3f713f0e, 0xbf7dbdc9,
    0x3f4ebec4, 0xbedb3f46, 0xbd49bf7b, 0x3f043f75, 0xbf043f35, 0x3d49bf75, 0x3edb3f7b, 0xbf4ebf46, 0x3f7d3ec4, 0xbf713dc9,
    0x3f2cbf0e, 0xbe793f62, 0x3f780000, 0xbf3e3ef1, 0x3eacbf55, 0x3e163f7f, 0xbf18bf6d, 0x3f673f22, 0xbf80be48, 0x3f5cbe95,
    0x3f7d3ec4, 0xbf713dc9, 0x3f2cbf0e, 0xbe793f62, 0xbf043f35, 0x3d49bf75, 0x3edb3f7b, 0xbf4ebf46, 0xbf18bf6d, 0x3f673f22,
    0xbf80be48, 0x3f5cbe95, 0x3f780000, 0xbf3e3ef1, 0x3eacbf55, 0x3e163f7f, 0x3e16bf6d, 0x3eac3f7f, 0xbf3ebf55, 0x3f783ef1,
    0x3f5c3f35, 0xbf80be95, 0x3f67be48, 0xbf183f22, 0xbf4e3ec4, 0x3edbbf46, 0x3d493f7b, 0xbf04bf75, 0xbe79bf80, 0x3f2c3f62,
    0xbf71bf0e, 0x3f7d3dc9, 0xbf7d0000, 0x3f67be95, 0xbf3e3f0e, 0x3f04bf46, 0xbe793f6d, 0xbd49bf7f, 0x3eac3f7b, 0xbf18bf62,
    0x3f4e3f35, 0xbf71bef1, 0x3f803e48, 0xbf783dc9, 0x3f5cbec4, 0xbf2c3f22, 0x3edbbf55, 0xbe163f75, 0x3e163f80, 0xbedbbf75,
    0x3f2c3f55, 0xbf5cbf22, 0x3f783ec4, 0xbf80bdc9, 0x3f71be48, 0xbf4e3ef1, 0x3f18bf35, 0xbeac3f62, 0x3d49bf7b, 0x3e793f7f,
    0xbf04bf6d, 0x3f3e3f46, 0xbf67bf0e, 0x3f7d3e95, 0x3f783ec4, 0xbf80bdc9, 0x3f71be48, 0xbf4e3ef1, 0x3e163f80, 0xbedbbf75,
    0x3f2c3f55, 0xbf5cbf22, 0xbf04bf6d, 0x3f3e3f46, 0xbf67bf0e, 0x3f7d3e95, 0x3f18bf35, 0xbeac3f62, 0x3d49bf7b, 0x3e793f7f,
    0x3e79bf6d, 0x3d493f7f, 0xbeacbf7b, 0x3f183f62, 0x3f7d0000, 0xbf673e95, 0x3f3ebf0e, 0xbf043f46, 0xbf5c3ec4, 0x3f2cbf22,
    0xbedb3f55, 0x3e16bf75, 0xbf4ebf35, 0x3f713ef1, 0xbf80be48, 0x3f78bdc9, 0x3f2cbf35, 0xbf183f46, 0x3f04bf55, 0xbedb3f62,
    0x3eacbf6d, 0xbe793f75, 0x3e16bf7b, 0xbd493f7f, 0x3f800000, 0xbf7d3dc9, 0x3f78be48, 0xbf713e95, 0x3f67bec4, 0xbf5c3ef1,
    0x3f4ebf0e, 0xbf3e3f22, 0x3f3e3f35, 0xbf4ebf22, 0x3f5c3f0e, 0xbf67bef1, 0x3f713ec4, 0xbf78be95, 0x3f7d3e48, 0xbf80bdc9,
    0x3d493f80, 0xbe16bf7f, 0x3e793f7b, 0xbeacbf75, 0x3edb3f6d, 0xbf04bf62, 0x3f183f55, 0xbf2cbf46, 0xbf71bec4, 0x3f783e95,
    0xbf7dbe48, 0x3f803dc9, 0xbf3ebf35, 0x3f4e3f22, 0xbf5cbf0e, 0x3f673ef1, 0xbedbbf6d, 0x3f043f62, 0xbf18bf55, 0x3f2c3f46,
    0xbd49bf80, 0x3e163f7f, 0xbe79bf7b, 0x3eac3f75, 0x3eacbf6d, 0xbe793f75, 0x3e16bf7b, 0xbd493f7f, 0x3f2cbf35, 0xbf183f46,
    0x3f04bf55, 0xbedb3f62, 0x3f67bec4, 0xbf5c3ef1, 0x3f4ebf0e, 0xbf3e3f22, 0x3f800000, 0xbf7d3dc9, 0x3f78be48, 0xbf713e95,
    0xbd493f80, 0x3e16bf7f, 0xbe793f7b, 0x3eacbf75, 0xbedb3f6d, 0x3f04bf62, 0xbf183f55, 0x3f2cbf46, 0xbf3e3f35, 0x3f4ebf22,
    0xbf5c3f0e, 0x3f67bef1, 0xbf713ec4, 0x3f78be95, 0xbf7d3e48, 0x3f80bdc9, 0xbf800000, 0x3f7d3dc9, 0xbf78be48, 0x3f713e95,
    0xbf67bec4, 0x3f5c3ef1, 0xbf4ebf0e, 0x3f3e3f22, 0xbf2cbf35, 0x3f183f46, 0xbf04bf55, 0x3edb3f62, 0xbeacbf6d, 0x3e793f75,
    0xbe16bf7b, 0x3d493f7f, 0x3f673ec4, 0xbf5cbef1, 0x3f4e3f0e, 0xbf3ebf22, 0x3f800000, 0xbf7dbdc9, 0x3f783e48, 0xbf71be95,
    0x3eac3f6d, 0xbe79bf75, 0x3e163f7b, 0xbd49bf7f, 0x3f2c3f35, 0xbf18bf46, 0x3f043f55, 0xbedbbf62, 0xbedb3f6d, 0x3f04bf62,
    0xbf183f55, 0x3f2cbf46, 0xbd493f80, 0x3e16bf7f, 0xbe793f7b, 0x3eacbf75, 0xbf713ec4, 0x3f78be95, 0xbf7d3e48, 0x3f80bdc9,
    0xbf3e3f35, 0x3f4ebf22, 0xbf5c3f0e, 0x3f67bef1, 0xbf18bf35, 0x3eac3f62, 0xbd49bf7b, 0xbe793f7f, 0x3f04bf6d, 0xbf3e3f46,
    0x3f67bf0e, 0xbf7d3e95, 0xbe163f80, 0x3edbbf75, 0xbf2c3f55, 0x3f5cbf22, 0xbf783ec4, 0x3f80bdc9, 0xbf71be48, 0x3f4e3ef1,
    0xbf4e3f35, 0x3f71bef1, 0xbf803e48, 0x3f783dc9, 0xbf5cbec4, 0x3f2c3f22, 0xbedbbf55, 0x3e163f75, 0x3f7d0000, 0xbf67be95,
    0x3f3e3f0e, 0xbf04bf46, 0x3e793f6d, 0x3d49bf7f, 0xbeac3f7b, 0x3f18bf62, 0xbf5cbec4, 0x3f2c3f22, 0xbedbbf55, 0x3e163f75,
    0xbf4e3f35, 0x3f71bef1, 0xbf803e48, 0x3f783dc9, 0x3e793f6d, 0x3d49bf7f, 0xbeac3f7b, 0x3f18bf62, 0x3f7d0000, 0xbf67be95,
    0x3f3e3f0e, 0xbf04bf46, 0xbf043f6d, 0x3f3ebf46, 0xbf673f0e, 0x3f7dbe95, 0x3f183f35, 0xbeacbf62, 0x3d493f7b, 0x3e79bf7f,
    0x3f78bec4, 0xbf803dc9, 0x3f713e48, 0xbf4ebef1, 0x3e16bf80, 0xbedb3f75, 0x3f2cbf55, 0xbf5c3f22, 0xbf780000, 0x3f3e3ef1,
    0xbeacbf55, 0xbe163f7f, 0x3f18bf6d, 0xbf673f22, 0x3f80be48, 0xbf5cbe95, 0x3f043f35, 0xbd49bf75, 0xbedb3f7b, 0x3f4ebf46,
    0xbf7d3ec4, 0x3f713dc9, 0xbf2cbf0e, 0x3e793f62, 0xbe793f80, 0x3f2cbf62, 0xbf713f0e, 0x3f7dbdc9, 0xbf4ebec4, 0x3edb3f46,
    0x3d49bf7b, 0xbf043f75, 0x3f5cbf35, 0xbf803e95, 0x3f673e48, 0xbf18bf22, 0x3e163f6d, 0x3eacbf7f, 0xbf3e3f55, 0x3f78bef1,
    0xbf4ebec4, 0x3edb3f46, 0x3d49bf7b, 0xbf043f75, 0xbe793f80, 0x3f2cbf62, 0xbf713f0e, 0x3f7dbdc9, 0x3e163f6d, 0x3eacbf7f,
    0xbf3e3f55, 0x3f78bef1, 0x3f5cbf35, 0xbf803e95, 0x3f673e48, 0xbf18bf22, 0xbf183f6d, 0x3f67bf22, 0xbf803e48, 0x3f5c3e95,
    0x3f780000, 0xbf3ebef1, 0x3eac3f55, 0x3e16bf7f, 0x3f7dbec4, 0xbf71bdc9, 0x3f2c3f0e, 0xbe79bf62, 0xbf04bf35, 0x3d493f75,
    0x3edbbf7b, 0xbf4e3f46, 0x3f67bf35, 0xbf783dc9, 0x3f183f0e, 0x3d49bf75, 0xbf2c3f6d, 0x3f7dbef1, 0xbf5cbe48, 0x3eac3f46,
    0x3f710000, 0xbf04bf22, 0xbe163f7b, 0x3f3ebf62, 0xbf803ec4, 0x3f4e3e95, 0xbe79bf55, 0xbedb3f7f, 0x3edb3f35, 0x3e79bf7f,
    0xbf4e3f55, 0x3f80be95, 0xbf3ebec4, 0x3e163f62, 0x3f04bf7b, 0xbf713f22, 0xbeac3f80, 0x3f5cbf46, 0xbf7d3e48, 0x3f2c3ef1,
    0xbd49bf6d, 0xbf183f75, 0x3f78bf0e, 0xbf67bdc9, 0x3f3e3ec4, 0xbe16bf62, 0xbf043f7b, 0x3f71bf22, 0xbedbbf35, 0xbe793f7f,
    0x3f4ebf55, 0xbf803e95, 0x3d493f6d, 0x3f18bf75, 0xbf783f0e, 0x3f673dc9, 0x3eacbf80, 0xbf5c3f46, 0x3f7dbe48, 0xbf2cbef1,
    0xbf2c3f6d, 0x3f7dbef1, 0xbf5cbe48, 0x3eac3f46, 0x3f67bf35, 0xbf783dc9, 0x3f183f0e, 0x3d49bf75, 0xbf803ec4, 0x3f4e3e95,
    0xbe79bf55, 0xbedb3f7f, 0x3f710000, 0xbf04bf22, 0xbe163f7b, 0x3f3ebf62, 0xbedb3f80, 0x3f78bf22, 0xbf4ebe48, 0x3d493f62,
    0x3f3ebf6d, 0xbf7d3e95, 0x3f043f0e, 0x3eacbf7f, 0xbf713f35, 0x3f5c3dc9, 0xbe16bf55, 0xbf2c3f75, 0x3f80bec4, 0xbf18bef1,
    0xbe793f7b, 0x3f67bf46, 0xbf670000, 0x3e793f46, 0x3f18bf7b, 0xbf803ef1, 0x3f2c3ec4, 0x3e16bf75, 0xbf5c3f55, 0x3f71bdc9,
    0xbeacbf35, 0xbf043f7f, 0x3f7dbf0e, 0xbf3ebe95, 0xbd493f6d, 0x3f4ebf62, 0xbf783e48, 0x3edb3f22, 0xbf2cbec4, 0xbe163f75,
    0x3f5cbf55, 0xbf713dc9, 0x3f670000, 0xbe79bf46, 0xbf183f7b, 0x3f80bef1, 0x3d49bf6d, 0xbf4e3f62, 0x3f78be48, 0xbedbbf22,
    0x3eac3f35, 0x3f04bf7f, 0xbf7d3f0e, 0x3f3e3e95, 0x3f3ebf6d, 0xbf7d3e95, 0x3f043f0e, 0x3eacbf7f, 0xbedb3f80, 0x3f78bf22,
    0xbf4ebe48, 0x3d493f62, 0x3f80bec4, 0xbf18bef1, 0xbe793f7b, 0x3f67bf46, 0xbf713f35, 0x3f5c3dc9, 0xbe16bf55, 0xbf2c3f75,
    0xbe79bf35, 0xbf3e3f75, 0x3f71be48, 0xbe16bf46, 0xbf4e3f6d, 0x3f67bdc9, 0xbd49bf55, 0xbf5c3f62, 0xbf043f80, 0x3f80bef1,
    0xbedbbf0e, 0xbf183f7f, 0x3f7dbec4, 0xbeacbf22, 0xbf2c3f7b, 0x3f78be95, 0xbf783f35, 0x3f2c3e95, 0x3eacbf7b, 0xbf7d3f22,
    0x3f183ec4, 0x3edbbf7f, 0xbf803f0e, 0x3f043ef1, 0x3f5c0000, 0x3d49bf62, 0xbf673f55, 0x3f4e3dc9, 0x3e16bf6d, 0xbf713f46,
    0x3f3e3e48, 0x3e79bf75, 0x3f183ec4, 0x3edbbf7f, 0xbf803f0e, 0x3f043ef1, 0xbf783f35, 0x3f2c3e95, 0x3eacbf7b, 0xbf7d3f22,
    0x3e16bf6d, 0xbf713f46, 0x3f3e3e48, 0x3e79bf75, 0x3f5c0000, 0x3d49bf62, 0xbf673f55, 0x3f4e3dc9, 0x3f4ebf6d, 0xbf673dc9,
    0x3d493f55, 0x3f5cbf62, 0x3e793f35, 0x3f3ebf75, 0xbf713e48, 0x3e163f46, 0xbf7d3ec4, 0x3eac3f22, 0x3f2cbf7b, 0xbf783e95,
    0x3f04bf80, 0xbf803ef1, 0x3edb3f0e, 0x3f18bf7f, 0xbf4e0000, 0xbeac3f75, 0x3f80bf0e, 0xbe79bf22, 0xbf5c3f6d, 0x3f3e3dc9,
    0x3edbbf7b, 0xbf7d3ef1, 0x3e163f35, 0x3f67bf62, 0xbf2cbe48, 0xbf043f7f, 0x3f78bec4, 0xbd49bf46, 0xbf713f55, 0x3f183e95,
    0xbf183f80, 0x3f71be95, 0x3d49bf55, 0xbf783f46, 0x3f043ec4, 0x3f2cbf7f, 0xbf673e48, 0xbe163f62, 0x3f7dbf35, 0xbedbbef1,
    0xbf3e3f7b, 0x3f5cbdc9, 0x3e79bf6d, 0xbf803f22, 0x3eac3f0e, 0x3f4ebf75, 0x3f043ec4, 0x3f2cbf7f, 0xbf673e48, 0xbe163f62,
    0xbf183f80, 0x3f71be95, 0x3d49bf55, 0xbf783f46, 0x3e79bf6d, 0xbf803f22, 0x3eac3f0e, 0x3f4ebf75, 0x3f7dbf35, 0xbedbbef1,
    0xbf3e3f7b, 0x3f5cbdc9, 0x3f5cbf6d, 0xbf3ebdc9, 0xbedb3f7b, 0x3f7dbef1, 0x3f4e0000, 0x3eacbf75, 0xbf803f0e, 0x3e793f22,
    0xbf783ec4, 0x3d493f46, 0x3f71bf55, 0xbf18be95, 0xbe16bf35, 0xbf673f62, 0x3f2c3e48, 0x3f04bf7f, 0x3f80bf35, 0xbe16bf22,
    0xbf783f55, 0x3eac3ef1, 0x3f67bf6d, 0xbf04be95, 0xbf4e3f7b, 0x3f2c3dc9, 0x3f3e0000, 0x3f18bf7f, 0xbf5c3e48, 0xbedb3f75,
    0x3f71bec4, 0x3e79bf62, 0xbf7d3f0e, 0xbd493f46, 0x3d493f35, 0x3f7dbf46, 0xbe79bf0e, 0xbf713f62, 0x3edb3ec4, 0x3f5cbf75,
    0xbf18be48, 0xbf3e3f7f, 0xbf2c3f80, 0x3f4ebdc9, 0x3f04bf7b, 0xbf673e95, 0xbeac3f6d, 0x3f78bef1, 0x3e16bf55, 0xbf803f22,
    0xbedbbec4, 0xbf5c3f75, 0x3f183e48, 0x3f3ebf7f, 0xbd49bf35, 0xbf7d3f46, 0x3e793f0e, 0x3f71bf62, 0x3eacbf6d, 0xbf783ef1,
    0xbe163f55, 0x3f80bf22, 0x3f2cbf80, 0xbf4e3dc9, 0xbf043f7b, 0x3f67be95, 0x3f67bf6d, 0xbf04be95, 0xbf4e3f7b, 0x3f2c3dc9,
    0x3f80bf35, 0xbe16bf22, 0xbf783f55, 0x3eac3ef1, 0x3f71bec4, 0x3e79bf62, 0xbf7d3f0e, 0xbd493f46, 0x3f3e0000, 0x3f18bf7f,
    0xbf5c3e48, 0xbedb3f75, 0xbf3e3f80, 0x3f183dc9, 0x3f5cbf7b, 0xbedbbe95, 0xbf713f6d, 0x3e793ef1, 0x3f7dbf55, 0xbd49bf22,
    0xbf803f35, 0xbe163f46, 0x3f78bf0e, 0x3eacbf62, 0xbf673ec4, 0xbf043f75, 0x3f4ebe48, 0x3f2cbf7f, 0xbf2c0000, 0xbf4e3f7f,
    0x3f043e48, 0x3f67bf75, 0xbeacbec4, 0xbf783f62, 0x3e163f0e, 0x3f80bf46, 0x3d49bf35, 0xbf7d3f22, 0xbe793f55, 0x3f71bef1,
    0x3edbbf6d, 0xbf5c3e95, 0xbf183f7b, 0x3f3ebdc9, 0x3eac3ec4, 0x3f78bf62, 0xbe16bf0e, 0xbf803f46, 0x3f2c0000, 0x3f4ebf7f,
    0xbf04be48, 0xbf673f75, 0xbedb3f6d, 0x3f5cbe95, 0x3f18bf7b, 0xbf3e3dc9, 0xbd493f35, 0x3f7dbf22, 0x3e79bf55, 0xbf713ef1,
    0xbf713f6d, 0x3e793ef1, 0x3f7dbf55, 0xbd49bf22, 0xbf3e3f80, 0x3f183dc9, 0x3f5cbf7b, 0xbedbbe95, 0xbf673ec4, 0xbf043f75,
    0x3f4ebe48, 0x3f2cbf7f, 0xbf803f35, 0xbe163f46, 0x3f78bf0e, 0x3eacbf62, 0x3e16bf35, 0xbf673ef1, 0xbf2c3f7b, 0x3f043dc9,
    0x3f78bf6d, 0x3d49bf22, 0xbf713f0e, 0xbf183f75, 0xbf4e3f80, 0x3eac3e95, 0x3f80bf55, 0x3e79bf46, 0xbf5c3ec4, 0xbf3e3f7f,
    0x3edb3e48, 0x3f7dbf62, 0xbf7d3f35, 0xbedb3f62, 0x3f3ebe48, 0x3f5cbf7f, 0xbe79bec4, 0xbf803f46, 0xbeac3f55, 0x3f4ebe95,
    0x3f180000, 0x3f71bf75, 0xbd49bf0e, 0xbf783f22, 0xbf043f6d, 0x3f2cbdc9, 0x3f67bf7b, 0xbe16bef1, 0xbe79bec4, 0xbf803f46,
    0xbeac3f55, 0x3f4ebe95, 0xbf7d3f35, 0xbedb3f62, 0x3f3ebe48, 0x3f5cbf7f, 0xbf043f6d, 0x3f2cbdc9, 0x3f67bf7b, 0xbe16bef1,
    0x3f180000, 0x3f71bf75, 0xbd49bf0e, 0xbf783f22, 0xbf783f6d, 0xbd493f22, 0x3f71bf0e, 0x3f18bf75, 0xbe163f35, 0x3f67bef1,
    0x3f2cbf7b, 0xbf04bdc9, 0x3f5cbec4, 0x3f3ebf7f, 0xbedbbe48, 0xbf7d3f62, 0x3f4ebf80, 0xbeacbe95, 0xbf803f55, 0xbe793f46,
    0xbf040000, 0xbf803f62, 0xbedb3f55, 0x3f18bdc9, 0x3f7dbf6d, 0x3eacbf46, 0xbf2c3e48, 0xbf783f75, 0xbe793f35, 0x3f3ebe95,
    0x3f71bf7b, 0x3e16bf22, 0xbf4e3ec4, 0xbf673f7f, 0xbd493f0e, 0x3f5cbef1, 0xbf5c3f80, 0x3d493ef1, 0x3f67bf0e, 0x3f4ebf7f,
    0xbe16bec4, 0xbf713f22, 0xbf3e3f7b, 0x3e793e95, 0x3f78bf35, 0x3f2cbf75, 0xbeacbe48, 0xbf7d3f46, 0xbf183f6d, 0x3edb3dc9,
    0x3f80bf55, 0x3f04bf62, 0xbe16bec4, 0xbf713f22, 0xbf3e3f7b, 0x3e793e95, 0xbf5c3f80, 0x3d493ef1, 0x3f67bf0e, 0x3f4ebf7f,
    0xbf183f6d, 0x3edb3dc9, 0x3f80bf55, 0x3f04bf62, 0x3f78bf35, 0x3f2cbf75, 0xbeacbe48, 0xbf7d3f46, 0xbf7d3f6d, 0xbeac3f46,
    0x3f2cbe48, 0x3f78bf75, 0x3f040000, 0x3f80bf62, 0x3edbbf55, 0xbf183dc9, 0x3f4ebec4, 0x3f67bf7f, 0x3d49bf0e, 0xbf5c3ef1,
    0x3e79bf35, 0xbf3e3e95, 0xbf713f7b, 0xbe163f22, 0x3f71bf35, 0x3f5cbf7f, 0x3e16bf0e, 0xbf2c3e95, 0xbf803f6d, 0xbf183f62,
    0x3e793e48, 0x3f67bf22, 0x3edb0000, 0x3f78bf46, 0x3f4ebf7b, 0x3d49bef1, 0xbf3e3ec4, 0xbf7d3f75, 0xbf043f55, 0x3eac3dc9,
    0xbeac3f35, 0x3f04bdc9, 0x3f7dbf55, 0x3f3ebf75, 0xbd49bec4, 0xbf4e3ef1, 0xbf783f7b, 0xbedb3f46, 0xbf673f80, 0xbe793f22,
    0x3f18be48, 0x3f80bf62, 0x3f2cbf6d, 0xbe16be95, 0xbf5c3f0e, 0xbf713f7f, 0x3d493ec4, 0x3f4ebef1, 0x3f78bf7b, 0x3edbbf46,
    0x3eacbf35, 0xbf043dc9, 0xbf7d3f55, 0xbf3e3f75, 0xbf2c3f6d, 0x3e163e95, 0x3f5cbf0e, 0x3f71bf7f, 0x3f67bf80, 0x3e79bf22,
    0xbf183e48, 0xbf803f62, 0xbf803f6d, 0xbf183f62, 0x3e793e48, 0x3f67bf22, 0x3f71bf35, 0x3f5cbf7f, 0x3e16bf0e, 0xbf2c3e95,
    0xbf3e3ec4, 0xbf7d3f75, 0xbf043f55, 0x3eac3dc9, 0x3edb0000, 0x3f78bf46, 0x3f4ebf7b, 0x3d49bef1, 0xbf713f80, 0xbf043f46,
    0x3e163e48, 0x3f3ebef1, 0x3f80bf6d, 0x3f4ebf75, 0x3e79bf0e, 0xbedb3dc9, 0xbf673f35, 0xbf783f7f, 0xbf183f55, 0x3d493e95,
    0x3f2cbec4, 0x3f7dbf62, 0x3f5cbf7b, 0x3eacbf22, 0xbeac0000, 0xbf5c3f22, 0xbf7d3f7b, 0xbf2c3f62, 0xbd493ec4, 0x3f18be95,
    0x3f78bf55, 0x3f67bf7f, 0x3edbbf35, 0xbe79bdc9, 0xbf4e3f0e, 0xbf803f75, 0xbf3e3f6d, 0xbe163ef1, 0x3f04be48, 0x3f71bf46,
    0x3d49bec4, 0xbf183e95, 0xbf783f55, 0xbf673f7f, 0x3eac0000, 0x3f5cbf22, 0x3f7dbf7b, 0x3f2cbf62, 0x3f3ebf6d, 0x3e16bef1,
    0xbf043e48, 0xbf713f46, 0xbedb3f35, 0x3e793dc9, 0x3f4ebf0e, 0x3f80bf75, 0x3f80bf6d, 0x3f4ebf75, 0x3e79bf0e, 0xbedb3dc9,
    0xbf713f80, 0xbf043f46, 0x3e163e48, 0x3f3ebef1, 0x3f2cbec4, 0x3f7dbf62, 0x3f5cbf7b, 0x3eacbf22, 0xbf673f35, 0xbf783f7f,
    0xbf183f55, 0x3d493e95, 0x3f04bf35, 0x3d49be95, 0xbedb3e48, 0xbf4e3f22, 0xbf7d3f6d, 0xbf713f7f, 0xbf2c3f55, 0xbe793ef1,
    0xbf783f80, 0xbf3e3f62, 0xbeac3f0e, 0x3e163dc9, 0x3f18bec4, 0x3f67bf46, 0x3f80bf7b, 0x3f5cbf75, 0xbf5c3f35, 0xbf803f75,
    0xbf673f7b, 0xbf183f46, 0xbe163ec4, 0x3eacbdc9, 0x3f3ebf0e, 0x3f78bf62, 0x3e790000, 0x3f2cbef1, 0x3f71bf55, 0x3f7dbf7f,
    0x3f4ebf6d, 0x3edbbf22, 0xbd49be48, 0xbf043e95, 0xbe163ec4, 0x3eacbdc9, 0x3f3ebf0e, 0x3f78bf62, 0xbf5c3f35, 0xbf803f75,
    0xbf673f7b, 0xbf183f46, 0x3f4ebf6d, 0x3edbbf22, 0xbd49be48, 0xbf043e95, 0x3e790000, 0x3f2cbef1, 0x3f71bf55, 0x3f7dbf7f,
    0x3f7dbf6d, 0x3f71bf7f, 0x3f2cbf55, 0x3e79bef1, 0xbf043f35, 0xbd493e95, 0x3edbbe48, 0x3f4ebf22, 0xbf183ec4, 0xbf673f46,
    0xbf803f7b, 0xbf5c3f75, 0x3f78bf80, 0x3f3ebf62, 0x3eacbf0e, 0xbe16bdc9, 0xbe160000, 0xbedb3e95, 0xbf2c3f0e, 0xbf5c3f46,
    0xbf783f6d, 0xbf803f7f, 0xbf713f7b, 0xbf4e3f62, 0xbf183f35, 0xbeac3ef1, 0xbd493e48, 0x3e79bdc9, 0x3f04bec4, 0x3f3ebf22,
    0x3f67bf55, 0x3f7dbf75, 0xbf7d3f80, 0xbf673f75, 0xbf3e3f55, 0xbf043f22, 0xbe793ec4, 0x3d493dc9, 0x3eacbe48, 0x3f18bef1,
    0x3f4ebf35, 0x3f71bf62, 0x3f80bf7b, 0x3f78bf7f, 0x3f5cbf6d, 0x3f2cbf46, 0x3edbbf0e, 0x3e16be95, 0xbe793ec4, 0x3d493dc9,
    0x3eacbe48, 0x3f18bef1, 0xbf7d3f80, 0xbf673f75, 0xbf3e3f55, 0xbf043f22, 0x3f5cbf6d, 0x3f2cbf46, 0x3edbbf0e, 0x3e16be95,
    0x3f4ebf35, 0x3f71bf62, 0x3f80bf7b, 0x3f78bf7f, 0x3f78bf6d, 0x3f80bf7f, 0x3f71bf7b, 0x3f4ebf62, 0x3e160000, 0x3edbbe95,
    0x3f2cbf0e, 0x3f5cbf46, 0xbf043ec4, 0xbf3e3f22, 0xbf673f55, 0xbf7d3f75, 0x3f18bf35, 0x3eacbef1, 0x3d49be48, 0xbe793dc9,
    0x3f3ebf35, 0x3f4ebf46, 0x3f5cbf55, 0x3f67bf62, 0x3f71bf6d, 0x3f78bf75, 0x3f7dbf7b, 0x3f80bf7f, 0x3d490000, 0x3e16bdc9,
    0x3e79be48, 0x3eacbe95, 0x3edbbec4, 0x3f04bef1, 0x3f18bf0e, 0x3f2cbf22, 0xbf2c3f35, 0xbf183f22, 0xbf043f0e, 0xbedb3ef1,
    0xbeac3ec4, 0xbe793e95, 0xbe163e48, 0xbd493dc9, 0xbf803f80, 0xbf7d3f7f, 0xbf783f7b, 0xbf713f75, 0xbf673f6d, 0xbf5c3f62,
    0xbf4e3f55, 0xbf3e3f46, 0x3eacbec4, 0x3e79be95, 0x3e16be48, 0x3d49bdc9, 0x3f2cbf35, 0x3f18bf22, 0x3f04bf0e, 0x3edbbef1,
    0x3f67bf6d, 0x3f5cbf62, 0x3f4ebf55, 0x3f3ebf46, 0x3f80bf80, 0x3f7dbf7f, 0x3f78bf7b, 0x3f71bf75, 0x3f71bf6d, 0x3f78bf75,
    0x3f7dbf7b, 0x3f80bf7f, 0x3f3ebf35, 0x3f4ebf46, 0x3f5cbf55, 0x3f67bf62, 0x3edbbec4, 0x3f04bef1, 0x3f18bf0e, 0x3f2cbf22,
    0x3d490000, 0x3e16bdc9, 0x3e79be48, 0x3eacbe95,
};
__device__ const __align__(128) uint32_t c_ga[1536] = {
    0x00003c80, 0x3bc43c6d, 0x00003c80, 0xbbc4bc6d, 0x00003c80, 0x3c6d3bc4, 0x00003c80, 0xbc6dbbc4, 0x00003c80, 0x3c6dbbc4,
    0x00003c80, 0xbc6d3bc4, 0x00003c80, 0x3bc4bc6d, 0x00003c80, 0xbbc43c6d, 0x3a493c80, 0x3bdb3c67, 0x3bdb3c67, 0xbc3ebc2c,
    0x3b163c7d, 0x3c783b79, 0x3c043c5c, 0xbc7d3b16, 0x3b793c78, 0x3c4ebc18, 0x3c183c4e, 0xbc043c5c, 0x3bac3c71, 0x3a49bc80,
    0x3c2c3c3e, 0x3bac3c71, 0x3ac93c7f, 0x3bf13c62, 0x3c463c22, 0xbc75bb95, 0x3b953c75, 0x3c7f3ac9, 0x3c623bf1, 0xbc463c22,
    0x3bf13c62, 0x3c22bc46, 0x3c753b95, 0x3ac93c7f, 0x3c223c46, 0xbb95bc75, 0x3c7f3ac9, 0x3c623bf1, 0x3b163c7d, 0x3c043c5c,
    0x3c783b79, 0xbc7d3b16, 0x3bdb3c67, 0x3c80ba49, 0x3c80ba49, 0xbbac3c71, 0x3c2c3c3e, 0x3bdbbc67, 0x3c71bbac, 0x3c2c3c3e,
    0x3c5c3c04, 0xbc18bc4e, 0x3c4ebc18, 0x3c78bb79, 0x3b483c7b, 0x3c0e3c55, 0x3c7bbb48, 0xbc553c0e, 0x3c0e3c55, 0x3c7bbb48,
    0x3c55bc0e, 0x3b483c7b, 0x3c553c0e, 0x3b48bc7b, 0x3c0ebc55, 0x3c7b3b48, 0x3c7b3b48, 0xbc55bc0e, 0x3b48bc7b, 0x3c0ebc55,
    0x3b793c78, 0x3c183c4e, 0x3c4ebc18, 0xbc043c5c, 0x3c2c3c3e, 0x3c71bbac, 0x3bdbbc67, 0x3c2c3c3e, 0x3c713bac, 0xba49bc80,
    0xba49bc80, 0x3c67bbdb, 0x3c7dbb16, 0xbc78bb79, 0xbc04bc5c, 0xbb16bc7d, 0x3b953c75, 0x3c223c46, 0x3bf1bc62, 0xbac93c7f,
    0x3c463c22, 0x3c62bbf1, 0xbac9bc7f, 0x3c753b95, 0x3c7f3ac9, 0xbb95bc75, 0xbc22bc46, 0x3bf1bc62, 0x3c62bbf1, 0xbc7f3ac9,
    0xbc75bb95, 0xbc46bc22, 0x3bac3c71, 0x3c2c3c3e, 0x3a49bc80, 0x3bac3c71, 0x3c5c3c04, 0x3c4ebc18, 0xbc18bc4e, 0x3c78bb79,
    0x3c7dbb16, 0xbc04bc5c, 0xbc78bb79, 0xbb16bc7d, 0x3c2cbc3e, 0xbc673bdb, 0xbc673bdb, 0xbc803a49, 0x00003c80, 0x3bc43c6d,
    0x00003c80, 0xbbc4bc6d, 0x00003c80, 0x3c6d3bc4, 0x00003c80, 0xbc6dbbc4, 0x00003c80, 0x3c6dbbc4, 0x00003c80, 0xbc6d3bc4,
    0x00003c80, 0x3bc4bc6d, 0x00003c80, 0xbbc43c6d, 0x3c3e3c2c, 0x3c713bac, 0x3c713bac, 0xbc803a49, 0x3c4e3c18, 0x3c5cbc04,
    0x3c783b79, 0xbc183c4e, 0x3c5c3c04, 0x3b16bc7d, 0x3c7d3b16, 0x3b793c78, 0x3c673bdb, 0xbc2cbc3e, 0x3c803a49, 0x3c673bdb,
    0x3c7fbac9, 0x3c62bbf1, 0x3c22bc46, 0xbb953c75, 0x3c75bb95, 0x3ac9bc7f, 0x3bf1bc62, 0x3c223c46, 0x3c62bbf1, 0xbc46bc22,
    0x3b95bc75, 0x3c7fbac9, 0x3c46bc22, 0xbc753b95, 0x3ac9bc7f, 0x3bf1bc62, 0x3c18bc4e, 0x3b79bc78, 0xbc04bc5c, 0x3c4e3c18,
    0x3bacbc71, 0xbc3ebc2c, 0xbc3ebc2c, 0x3c67bbdb, 0x3a49bc80, 0xbc713bac, 0xbc67bbdb, 0x3a49bc80, 0xbb79bc78, 0xbb163c7d,
    0xbc7dbb16, 0xbc5cbc04, 0xbb48bc7b, 0xbc0ebc55, 0xbc7b3b48, 0x3c55bc0e, 0xbc0ebc55, 0xbc7b3b48, 0xbc553c0e, 0xbb48bc7b,
    0xbc55bc0e, 0xbb483c7b, 0xbc0e3c55, 0xbc7bbb48, 0xbc7bbb48, 0x3c553c0e, 0xbb483c7b, 0xbc0e3c55, 0xbc5cbc04, 0xbc7dbb16,
    0xbb163c7d, 0xbb79bc78, 0xbc80ba49, 0xbbdb3c67, 0x3bac3c71, 0xbc80ba49, 0xbc673bdb, 0x3c3e3c2c, 0x3c3e3c2c, 0xbbac3c71,
    0xbc183c4e, 0x3c5cbc04, 0x3c783b79, 0x3c4e3c18, 0xbc753b95, 0xbc463c22, 0x3c623bf1, 0xbc7fbac9, 0xbc223c46, 0x3bf13c62,
    0x3c7fbac9, 0xbb953c75, 0xbac93c7f, 0x3c75bb95, 0x3c46bc22, 0x3c623bf1, 0x3bf13c62, 0xbac9bc7f, 0x3b95bc75, 0x3c22bc46,
    0xbbdb3c67, 0xba493c80, 0x3c3ebc2c, 0xbbdb3c67, 0x3b793c78, 0x3c7d3b16, 0x3b16bc7d, 0x3c5c3c04, 0x3c4e3c18, 0x3b79bc78,
    0xbc04bc5c, 0x3c18bc4e, 0x3c80ba49, 0xbc71bbac, 0xbc71bbac, 0xbc3ebc2c, 0x00003c80, 0x3bc43c6d, 0x00003c80, 0xbbc4bc6d,
    0x00003c80, 0x3c6d3bc4, 0x00003c80, 0xbc6dbbc4, 0x00003c80, 0x3c6dbbc4, 0x00003c80, 0xbc6d3bc4, 0x00003c80, 0x3bc4bc6d,
    0x00003c80, 0xbbc43c6d, 0x3c80ba49, 0x3c67bbdb, 0x3c67bbdb, 0xbc2c3c3e, 0x3c7dbb16, 0x3b79bc78, 0x3c5cbc04, 0x3b163c7d,
    0x3c78bb79, 0xbc18bc4e, 0x3c4ebc18, 0x3c5c3c04, 0x3c71bbac, 0xbc80ba49, 0x3c3ebc2c, 0x3c71bbac, 0xbac9bc7f, 0xbbf1bc62,
    0xbc46bc22, 0x3c753b95, 0xbb95bc75, 0xbc7fbac9, 0xbc62bbf1, 0x3c46bc22, 0xbbf1bc62, 0xbc223c46, 0xbc75bb95, 0xbac9bc7f,
    0xbc22bc46, 0x3b953c75, 0xbc7fbac9, 0xbc62bbf1, 0xbc7d3b16, 0xbc5c3c04, 0xbb793c78, 0xbb16bc7d, 0xbc673bdb, 0x3a493c80,
    0x3a493c80, 0xbc71bbac, 0xbc3e3c2c, 0x3c673bdb, 0x3bac3c71, 0xbc3e3c2c, 0xbc043c5c, 0x3c4ebc18, 0x3c183c4e, 0x3b793c78,
    0x3b483c7b, 0x3c0e3c55, 0x3c7bbb48, 0xbc553c0e, 0x3c0e3c55, 0x3c7bbb48, 0x3c55bc0e, 0x3b483c7b, 0x3c553c0e, 0x3b48bc7b,
    0x3c0ebc55, 0x3c7b3b48, 0x3c7b3b48, 0xbc55bc0e, 0x3b48bc7b, 0x3c0ebc55, 0x3c78bb79, 0x3c4ebc18, 0xbc18bc4e, 0x3c5c3c04,
    0x3c3ebc2c, 0xbbacbc71, 0xbc67bbdb, 0x3c3ebc2c, 0x3bacbc71, 0xbc803a49, 0xbc803a49, 0xbbdbbc67, 0xbb16bc7d, 0xbb793c78,
    0xbc5c3c04, 0xbc7d3b16, 0xbb95bc75, 0xbc22bc46, 0xbbf13c62, 0x3ac9bc7f, 0xbc46bc22, 0xbc623bf1, 0x3ac93c7f, 0xbc75bb95,
    0xbc7fbac9, 0x3b953c75, 0x3c223c46, 0xbbf13c62, 0xbc623bf1, 0x3c7fbac9, 0x3c753b95, 0x3c463c22, 0xbc713bac, 0xbc3e3c2c,
    0x3c803a49, 0xbc713bac, 0xbc043c5c, 0x3c183c4e, 0x3c4ebc18, 0x3b793c78, 0x3b163c7d, 0x3c5cbc04, 0x3b79bc78, 0x3c7dbb16,
    0x3c3e3c2c, 0xbbdbbc67, 0xbbdbbc67, 0xba49bc80, 0x00003c80, 0x3bc43c6d, 0x00003c80, 0xbbc4bc6d, 0x00003c80, 0x3c6d3bc4,
    0x00003c80, 0xbc6dbbc4, 0x00003c80, 0x3c6dbbc4, 0x00003c80, 0xbc6d3bc4, 0x00003c80, 0x3bc4bc6d, 0x00003c80, 0xbbc43c6d,
    0x3c2cbc3e, 0x3bacbc71, 0x3bacbc71, 0x3a493c80, 0x3c18bc4e, 0xbc04bc5c, 0x3b79bc78, 0x3c4e3c18, 0x3c04bc5c, 0xbc7dbb16,
    0x3b16bc7d, 0x3c78bb79, 0x3bdbbc67, 0xbc3e3c2c, 0x3a49bc80, 0x3bdbbc67, 0xbc7f3ac9, 0xbc623bf1, 0xbc223c46, 0x3b95bc75,
    0xbc753b95, 0xbac93c7f, 0xbbf13c62, 0xbc22bc46, 0xbc623bf1, 0x3c463c22, 0xbb953c75, 0xbc7f3ac9, 0xbc463c22, 0x3c75bb95,
    0xbac93c7f, 0xbbf13c62, 0x3c4e3c18, 0x3c783b79, 0x3c5cbc04, 0xbc183c4e, 0x3c713bac, 0x3c2cbc3e, 0x3c2cbc3e, 0x3bdb3c67,
    0x3c803a49, 0xbbacbc71, 0x3bdbbc67, 0x3c803a49, 0x3c78bb79, 0xbc7dbb16, 0x3b16bc7d, 0x3c04bc5c, 0xbb48bc7b, 0xbc0ebc55,
    0xbc7b3b48, 0x3c55bc0e, 0xbc0ebc55, 0xbc7b3b48, 0xbc553c0e, 0xbb48bc7b, 0xbc55bc0e, 0xbb483c7b, 0xbc0e3c55, 0xbc7bbb48,
    0xbc7bbb48, 0x3c553c0e, 0xbb483c7b, 0xbc0e3c55, 0xbc043c5c, 0xbb163c7d, 0x3c7d3b16, 0xbc783b79, 0xba493c80, 0x3c673bdb,
    0x3c71bbac, 0xba493c80, 0x3bdb3c67, 0x3c2cbc3e, 0x3c2cbc3e, 0x3c713bac, 0x3c4e3c18, 0xbc04bc5c, 0x3b79bc78, 0x3c18bc4e,
    0x3c75bb95, 0x3c46bc22, 0xbc62bbf1, 0x3c7f3ac9, 0x3c22bc46, 0xbbf1bc62, 0xbc7f3ac9, 0x3b95bc75, 0x3ac9bc7f, 0xbc753b95,
    0xbc463c22, 0xbc62bbf1, 0xbbf1bc62, 0x3ac93c7f, 0xbb953c75, 0xbc223c46, 0xbc67bbdb, 0xbc80ba49, 0x3c2c3c3e, 0xbc67bbdb,
    0xbc783b79, 0xbb163c7d, 0x3c7d3b16, 0xbc043c5c, 0xbc183c4e, 0x3c783b79, 0x3c5cbc04, 0x3c4e3c18, 0x3a493c80, 0x3bacbc71,
    0x3bacbc71, 0x3c2cbc3e, 0x3c353c35, 0x3c6d3bc4, 0x3c353c35, 0xbc6dbbc4, 0x3c35bc35, 0xbbc4bc6d, 0x3c35bc35, 0x3bc43c6d,
    0xbc35bc35, 0xbbc43c6d, 0xbc35bc35, 0x3bc4bc6d, 0xbc353c35, 0x3c6dbbc4, 0xbc353c35, 0xbc6d3bc4, 0x3c3e3c2c, 0x3c713bac,
    0x3c713bac, 0xbc803a49, 0x3c18bc4e, 0xbc04bc5c, 0x3b79bc78, 0x3c4e3c18, 0xbc5cbc04, 0xbb163c7d, 0xbc7dbb16, 0xbb79bc78,
    0xbbdb3c67, 0x3c3ebc2c, 0xba493c80, 0xbbdb3c67, 0x3c463c22, 0x3c753b95, 0x3c7fbac9, 0xbc623bf1, 0x3bf1bc62, 0xbc22bc46,
    0xbb95bc75, 0x3c7f3ac9, 0xbc75bb95, 0x3ac93c7f, 0xbc623bf1, 0xbc46bc22, 0xbac93c7f, 0x3bf1bc62, 0x3c223c46, 0x3b953c75,
    0x3c4e3c18, 0x3c783b79, 0x3c5cbc04, 0xbc183c4e, 0x3bacbc71, 0xbc3ebc2c, 0xbc3ebc2c, 0x3c67bbdb, 0xbc80ba49, 0x3bac3c71,
    0xbbdb3c67, 0xbc80ba49, 0x3b793c78, 0x3b16bc7d, 0x3c7d3b16, 0x3c5c3c04, 0x3c553c0e, 0x3c7b3b48, 0x3c0ebc55, 0xbb483c7b,
    0x3b48bc7b, 0xbc55bc0e, 0xbc7bbb48, 0x3c0ebc55, 0xbc7b3b48, 0x3c0e3c55, 0x3b483c7b, 0xbc553c0e, 0x3c0e3c55, 0xbb48bc7b,
    0x3c55bc0e, 0x3c7bbb48, 0x3c5c3c04, 0x3c7d3b16, 0x3b16bc7d, 0x3b793c78, 0x3a49bc80, 0xbc67bbdb, 0xbc713bac, 0x3a49bc80,
    0xbc673bdb, 0x3c3e3c2c, 0x3c3e3c2c, 0xbbac3c71, 0x3c4e3c18, 0xbc04bc5c, 0x3b79bc78, 0x3c18bc4e, 0x3c623bf1, 0x3c7f3ac9,
    0xbb95bc75, 0x3c223c46, 0xbac9bc7f, 0xbc75bb95, 0xbc223c46, 0xbbf1bc62, 0xbc463c22, 0x3c623bf1, 0x3c7f3ac9, 0x3b953c75,
    0x3c753b95, 0xbc46bc22, 0xbbf1bc62, 0xbac9bc7f, 0x3c673bdb, 0x3c803a49, 0xbc2cbc3e, 0x3c673bdb, 0xbb79bc78, 0xbc7dbb16,
    0xbb163c7d, 0xbc5cbc04, 0xbc183c4e, 0x3c783b79, 0x3c5cbc04, 0x3c4e3c18, 0x3c80ba49, 0xbc71bbac, 0xbc71bbac, 0xbc3ebc2c,
    0x3c353c35, 0x3c6d3bc4, 0x3c353c35, 0xbc6dbbc4, 0x3c35bc35, 0xbbc4bc6d, 0x3c35bc35, 0x3bc43c6d, 0xbc35bc35, 0xbbc43c6d,
    0xbc35bc35, 0x3bc4bc6d, 0xbc353c35, 0x3c6dbbc4, 0xbc353c35, 0xbc6d3bc4, 0x3c80ba49, 0x3c67bbdb, 0x3c67bbdb, 0xbc2c3c3e,
    0xbb16bc7d, 0xbc78bb79, 0xbc04bc5c, 0x3c7dbb16, 0xbc783b79, 0x3c183c4e, 0xbc4e3c18, 0xbc5cbc04, 0x3bac3c71, 0x3a49bc80,
    0x3c2c3c3e, 0x3bac3c71, 0x3c22bc46, 0x3b95bc75, 0xbac9bc7f, 0x3bf13c62, 0xbc62bbf1, 0xbc463c22, 0xbc753b95, 0x3ac9bc7f,
    0xbb953c75, 0x3c7fbac9, 0x3bf13c62, 0xbc223c46, 0x3c7f3ac9, 0xbc62bbf1, 0x3c46bc22, 0x3c75bb95, 0xbb16bc7d, 0xbc04bc5c,
    0xbc78bb79, 0x3c7dbb16, 0xbc673bdb, 0x3a493c80, 0x3a493c80, 0xbc71bbac, 0x3c2c3c3e, 0x3bdbbc67, 0x3c71bbac, 0x3c2c3c3e,
    0x3c04bc5c, 0xbc4e3c18, 0xbc18bc4e, 0xbb79bc78, 0xbc55bc0e, 0xbc7bbb48, 0xbc0e3c55, 0x3b48bc7b, 0xbb483c7b, 0x3c553c0e,
    0x3c7b3b48, 0xbc0e3c55, 0x3c7bbb48, 0xbc0ebc55, 0xbb48bc7b, 0x3c55bc0e, 0xbc0ebc55, 0x3b483c7b, 0xbc553c0e, 0xbc7b3b48,
    0xbc783b79, 0xbc4e3c18, 0x3c183c4e, 0xbc5cbc04, 0x3c2c3c3e, 0x3c71bbac, 0x3bdbbc67, 0x3c2c3c3e, 0x3bacbc71, 0xbc803a49,
    0xbc803a49, 0xbbdbbc67, 0xbc7d3b16, 0x3c783b79, 0x3c043c5c, 0x3b163c7d, 0xbbf13c62, 0xbac93c7f, 0x3c75bb95, 0xbc463c22,
    0x3c7fbac9, 0x3b95bc75, 0xbc46bc22, 0x3c62bbf1, 0xbc22bc46, 0xbbf13c62, 0xbac93c7f, 0xbc753b95, 0xbb953c75, 0x3c22bc46,
    0x3c62bbf1, 0x3c7fbac9, 0x3bac3c71, 0x3c2c3c3e, 0x3a49bc80, 0x3bac3c71, 0x3c04bc5c, 0xbc18bc4e, 0xbc4e3c18, 0xbb79bc78,
    0xbc7d3b16, 0x3c043c5c, 0x3c783b79, 0x3b163c7d, 0x3c3e3c2c, 0xbbdbbc67, 0xbbdbbc67, 0xba49bc80, 0x3c353c35, 0x3c6d3bc4,
    0x3c353c35, 0xbc6dbbc4, 0x3c35bc35, 0xbbc4bc6d, 0x3c35bc35, 0x3bc43c6d, 0xbc35bc35, 0xbbc43c6d, 0xbc35bc35, 0x3bc4bc6d,
    0xbc353c35, 0x3c6dbbc4, 0xbc353c35, 0xbc6d3bc4, 0x3c2cbc3e, 0x3bacbc71, 0x3bacbc71, 0x3a493c80, 0xbc4ebc18, 0xbc5c3c04,
    0xbc78bb79, 0x3c18bc4e, 0xbc043c5c, 0x3c7d3b16, 0xbb163c7d, 0xbc783b79, 0x3c673bdb, 0xbc2cbc3e, 0x3c803a49, 0x3c673bdb,
    0xbc46bc22, 0xbc75bb95, 0xbc7f3ac9, 0x3c62bbf1, 0xbbf13c62, 0x3c223c46, 0x3b953c75, 0xbc7fbac9, 0x3c753b95, 0xbac9bc7f,
    0x3c62bbf1, 0x3c463c22, 0x3ac9bc7f, 0xbbf13c62, 0xbc22bc46, 0xbb95bc75, 0xbc183c4e, 0xbb793c78, 0x3c043c5c, 0xbc4ebc18,
    0x3c713bac, 0x3c2cbc3e, 0x3c2cbc3e, 0x3bdb3c67, 0x3a49bc80, 0xbc713bac, 0xbc67bbdb, 0x3a49bc80, 0xbc783b79, 0x3c7d3b16,
    0xbb163c7d, 0xbc043c5c, 0x3c553c0e, 0x3c7b3b48, 0x3c0ebc55, 0xbb483c7b, 0x3b48bc7b, 0xbc55bc0e, 0xbc7bbb48, 0x3c0ebc55,
    0xbc7b3b48, 0x3c0e3c55, 0x3b483c7b, 0xbc553c0e, 0x3c0e3c55, 0xbb48bc7b, 0x3c55bc0e, 0x3c7bbb48, 0x3c04bc5c, 0x3b16bc7d,
    0xbc7dbb16, 0x3c78bb79, 0xbc80ba49, 0xbbdb3c67, 0x3bac3c71, 0xbc80ba49, 0x3bdb3c67, 0x3c2cbc3e, 0x3c2cbc3e, 0x3c713bac,
    0x3c18bc4e, 0xbc5c3c04, 0xbc78bb79, 0xbc4ebc18, 0xbc62bbf1, 0xbc7fbac9, 0x3b953c75, 0xbc22bc46, 0x3ac93c7f, 0x3c753b95,
    0x3c22bc46, 0x3bf13c62, 0x3c46bc22, 0xbc62bbf1, 0xbc7fbac9, 0xbb95bc75, 0xbc75bb95, 0x3c463c22, 0x3bf13c62, 0x3ac93c7f,
    0xbbdb3c67, 0xba493c80, 0x3c3ebc2c, 0xbbdb3c67, 0x3c78bb79, 0x3b16bc7d, 0xbc7dbb16, 0x3c04bc5c, 0xbc4ebc18, 0xbb793c78,
    0x3c043c5c, 0xbc183c4e, 0x3a493c80, 0x3bacbc71, 0x3bacbc71, 0x3c2cbc3e, 0x3c353c35, 0x3c6d3bc4, 0x3c353c35, 0xbc6dbbc4,
    0x3c35bc35, 0xbbc4bc6d, 0x3c35bc35, 0x3bc43c6d, 0xbc35bc35, 0xbbc43c6d, 0xbc35bc35, 0x3bc4bc6d, 0xbc353c35, 0x3c6dbbc4,
    0xbc353c35, 0xbc6d3bc4, 0xba49bc80, 0xbbdbbc67, 0xbbdbbc67, 0x3c3e3c2c, 0xbc7d3b16, 0xbb793c78, 0xbc5c3c04, 0xbb16bc7d,
    0x3b793c78, 0x3c4ebc18, 0x3c183c4e, 0xbc043c5c, 0x3c71bbac, 0xbc80ba49, 0x3c3ebc2c, 0x3c71bbac, 0xbc223c46, 0xbb953c75,
    0x3ac93c7f, 0xbbf1bc62, 0x3c623bf1, 0x3c46bc22, 0x3c75bb95, 0xbac93c7f, 0x3b95bc75, 0xbc7f3ac9, 0xbbf1bc62, 0x3c22bc46,
    0xbc7fbac9, 0x3c623bf1, 0xbc463c22, 0xbc753b95, 0x3c7dbb16, 0x3c5cbc04, 0x3b79bc78, 0x3b163c7d, 0xbbdbbc67, 0xbc803a49,
    0xbc803a49, 0x3bacbc71, 0xbc3e3c2c, 0x3c673bdb, 0x3bac3c71, 0xbc3e3c2c, 0x3c5c3c04, 0xbc18bc4e, 0x3c4ebc18, 0x3c78bb79,
    0xbc55bc0e, 0xbc7bbb48, 0xbc0e3c55, 0x3b48bc7b, 0xbb483c7b, 0x3c553c0e, 0x3c7b3b48, 0xbc0e3c55, 0x3c7bbb48, 0xbc0ebc55,
    0xbb48bc7b, 0x3c55bc0e, 0xbc0ebc55, 0x3b483c7b, 0xbc553c0e, 0xbc7b3b48, 0x3b793c78, 0x3c183c4e, 0x3c4ebc18, 0xbc043c5c,
    0x3c3ebc2c, 0xbbacbc71, 0xbc67bbdb, 0x3c3ebc2c, 0xbc71bbac, 0x3a493c80, 0x3a493c80, 0xbc673bdb, 0x3b163c7d, 0x3b79bc78,
    0x3c5cbc04, 0x3c7dbb16, 0x3bf1bc62, 0x3ac9bc7f, 0xbc753b95, 0x3c46bc22, 0xbc7f3ac9, 0xbb953c75, 0x3c463c22, 0xbc623bf1,
    0x3c223c46, 0x3bf1bc62, 0x3ac9bc7f, 0x3c75bb95, 0x3b95bc75, 0xbc223c46, 0xbc623bf1, 0xbc7f3ac9, 0xbc713bac, 0xbc3e3c2c,
    0x3c803a49, 0xbc713bac, 0x3c5c3c04, 0x3c4ebc18, 0xbc18bc4e, 0x3c78bb79, 0xbb16bc7d, 0xbc5c3c04, 0xbb793c78, 0xbc7d3b16,
    0xbc2c3c3e, 0x3c67bbdb, 0x3c67bbdb, 0x3c80ba49, 0x3c800000, 0x3c6dbbc4, 0x3c800000, 0xbc6d3bc4, 0xbc800000, 0xbbc43c6d,
    0xbc800000, 0x3bc4bc6d, 0x3c800000, 0xbbc4bc6d, 0x3c800000, 0x3bc43c6d, 0xbc800000, 0x3c6d3bc4, 0xbc800000, 0xbc6dbbc4,
    0x3c80ba49, 0x3c67bbdb, 0x3c67bbdb, 0xbc2c3c3e, 0xbc7d3b16, 0xbb793c78, 0xbc5c3c04, 0xbb16bc7d, 0x3c78bb79, 0xbc18bc4e,
    0x3c4ebc18, 0x3c5c3c04, 0xbc713bac, 0x3c803a49, 0xbc3e3c2c, 0xbc713bac, 0x3c7fbac9, 0x3c62bbf1, 0x3c22bc46, 0xbb953c75,
    0xbc753b95, 0xbac93c7f, 0xbbf13c62, 0xbc22bc46, 0x3c62bbf1, 0xbc46bc22, 0x3b95bc75, 0x3c7fbac9, 0xbc463c22, 0x3c75bb95,
    0xbac93c7f, 0xbbf13c62, 0x3c7dbb16, 0x3c5cbc04, 0x3b79bc78, 0x3b163c7d, 0xbc673bdb, 0x3a493c80, 0x3a493c80, 0xbc71bbac,
    0x3c3ebc2c, 0xbc67bbdb, 0xbbacbc71, 0x3c3ebc2c, 0xbc043c5c, 0x3c4ebc18, 0x3c183c4e, 0x3b793c78, 0x3c7bbb48, 0x3c55bc0e,
    0xbb48bc7b, 0x3c0e3c55, 0xbc553c0e, 0x3b483c7b, 0x3c0e3c55, 0xbc7b3b48, 0x3c0ebc55, 0xbc7bbb48, 0xbc55bc0e, 0x3b48bc7b,
    0xbb483c7b, 0x3c0ebc55, 0x3c7b3b48, 0x3c553c0e, 0x3c78bb79, 0x3c4ebc18, 0xbc18bc4e, 0x3c5c3c04, 0xbc3e3c2c, 0x3bac3c71,
    0x3c673bdb, 0xbc3e3c2c, 0x3bacbc71, 0xbc803a49, 0xbc803a49, 0xbbdbbc67, 0x3b163c7d, 0x3b79bc78, 0x3c5cbc04, 0x3c7dbb16,
    0x3c75bb95, 0x3c46bc22, 0xbc62bbf1, 0x3c7f3ac9, 0xbc223c46, 0x3bf13c62, 0x3c7fbac9, 0xbb953c75, 0x3ac9bc7f, 0xbc753b95,
    0xbc463c22, 0xbc62bbf1, 0x3bf13c62, 0xbac9bc7f, 0x3b95bc75, 0x3c22bc46, 0x3c71bbac, 0x3c3ebc2c, 0xbc80ba49, 0x3c71bbac,
    0xbc043c5c, 0x3c183c4e, 0x3c4ebc18, 0x3b793c78, 0xbb16bc7d, 0xbc5c3c04, 0xbb793c78, 0xbc7d3b16, 0x3c3e3c2c, 0xbbdbbc67,
    0xbbdbbc67, 0xba49bc80, 0x3c800000, 0x3c6dbbc4, 0x3c800000, 0xbc6d3bc4, 0xbc800000, 0xbbc43c6d, 0xbc800000, 0x3bc4bc6d,
    0x3c800000, 0xbbc4bc6d, 0x3c800000, 0x3bc43c6d, 0xbc800000, 0x3c6d3bc4, 0xbc800000, 0xbc6dbbc4, 0x3c2cbc3e, 0x3bacbc71,
    0x3bacbc71, 0x3a493c80, 0xbc183c4e, 0x3c043c5c, 0xbb793c78, 0xbc4ebc18, 0x3c04bc5c, 0xbc7dbb16, 0x3b16bc7d, 0x3c78bb79,
    0xbbdb3c67, 0x3c3ebc2c, 0xba493c80, 0xbbdb3c67, 0xbac9bc7f, 0xbbf1bc62, 0xbc46bc22, 0x3c753b95, 0x3b953c75, 0x3c7f3ac9,
    0x3c623bf1, 0xbc463c22, 0xbbf1bc62, 0xbc223c46, 0xbc75bb95, 0xbac9bc7f, 0x3c223c46, 0xbb95bc75, 0x3c7f3ac9, 0x3c623bf1,
    0xbc4ebc18, 0xbc78bb79, 0xbc5c3c04, 0x3c18bc4e, 0x3c713bac, 0x3c2cbc3e, 0x3c2cbc3e, 0x3bdb3c67, 0xbc80ba49, 0x3bac3c71,
    0xbbdb3c67, 0xbc80ba49, 0x3c78bb79, 0xbc7dbb16, 0x3b16bc7d, 0x3c04bc5c, 0xbc7b3b48, 0xbc553c0e, 0x3b483c7b, 0xbc0ebc55,
    0x3c55bc0e, 0xbb48bc7b, 0xbc0ebc55, 0x3c7bbb48, 0xbc0e3c55, 0x3c7b3b48, 0x3c553c0e, 0xbb483c7b, 0x3b48bc7b, 0xbc0e3c55,
    0xbc7bbb48, 0xbc55bc0e, 0xbc043c5c, 0xbb163c7d, 0x3c7d3b16, 0xbc783b79, 0x3a49bc80, 0xbc67bbdb, 0xbc713bac, 0x3a49bc80,
    0x3bdb3c67, 0x3c2cbc3e, 0x3c2cbc3e, 0x3c713bac, 0xbc4ebc18, 0x3c043c5c, 0xbb793c78, 0xbc183c4e, 0x3b953c75, 0x3c223c46,
    0x3bf1bc62, 0xbac93c7f, 0xbc46bc22, 0xbc623bf1, 0x3ac93c7f, 0xbc75bb95, 0x3c7f3ac9, 0xbb95bc75, 0xbc22bc46, 0x3bf1bc62,
    0xbc623bf1, 0x3c7fbac9, 0x3c753b95, 0x3c463c22, 0x3c673bdb, 0x3c803a49, 0xbc2cbc3e, 0x3c673bdb, 0xbc783b79, 0xbb163c7d,
    0x3c7d3b16, 0xbc043c5c, 0x3c18bc4e, 0xbc78bb79, 0xbc5c3c04, 0xbc4ebc18, 0x3a493c80, 0x3bacbc71, 0x3bacbc71, 0x3c2cbc3e,
    0x3c800000, 0x3c6dbbc4, 0x3c800000, 0xbc6d3bc4, 0xbc800000, 0xbbc43c6d, 0xbc800000, 0x3bc4bc6d, 0x3c800000, 0xbbc4bc6d,
    0x3c800000, 0x3bc43c6d, 0xbc800000, 0x3c6d3bc4, 0xbc800000, 0xbc6dbbc4, 0xba49bc80, 0xbbdbbc67, 0xbbdbbc67, 0x3c3e3c2c,
    0x3b163c7d, 0x3c783b79, 0x3c043c5c, 0xbc7d3b16, 0xbb79bc78, 0xbc4e3c18, 0xbc18bc4e, 0x3c04bc5c, 0x3bac3c71, 0x3a49bc80,
    0x3c2c3c3e, 0x3bac3c71, 0xbc7f3ac9, 0xbc623bf1, 0xbc223c46, 0x3b95bc75, 0x3c75bb95, 0x3ac9bc7f, 0x3bf1bc62, 0x3c223c46,
    0xbc623bf1, 0x3c463c22, 0xbb953c75, 0xbc7f3ac9, 0x3c46bc22, 0xbc753b95, 0x3ac9bc7f, 0x3bf1bc62, 0x3b163c7d, 0x3c043c5c,
    0x3c783b79, 0xbc7d3b16, 0xbbdbbc67, 0xbc803a49, 0xbc803a49, 0x3bacbc71, 0x3c2c3c3e, 0x3bdbbc67, 0x3c71bbac, 0x3c2c3c3e,
    0xbc5cbc04, 0x3c183c4e, 0xbc4e3c18, 0xbc783b79, 0x3c7bbb48, 0x3c55bc0e, 0xbb48bc7b, 0x3c0e3c55, 0xbc553c0e, 0x3b483c7b,
    0x3c0e3c55, 0xbc7b3b48, 0x3c0ebc55, 0xbc7bbb48, 0xbc55bc0e, 0x3b48bc7b, 0xbb483c7b, 0x3c0ebc55, 0x3c7b3b48, 0x3c553c0e,
    0xbb79bc78, 0xbc18bc4e, 0xbc4e3c18, 0x3c04bc5c, 0x3c2c3c3e, 0x3c71bbac, 0x3bdbbc67, 0x3c2c3c3e, 0xbc71bbac, 0x3a493c80,
    0x3a493c80, 0xbc673bdb, 0x3c7dbb16, 0xbc78bb79, 0xbc04bc5c, 0xbb16bc7d, 0xbc753b95, 0xbc463c22, 0x3c623bf1, 0xbc7fbac9,
    0x3c22bc46, 0xbbf1bc62, 0xbc7f3ac9, 0x3b95bc75, 0xbac93c7f, 0x3c75bb95, 0x3c46bc22, 0x3c623bf1, 0xbbf1bc62, 0x3ac93c7f,
    0xbb953c75, 0xbc223c46, 0x3bac3c71, 0x3c2c3c3e, 0x3a49bc80, 0x3bac3c71, 0xbc5cbc04, 0xbc4e3c18, 0x3c183c4e, 0xbc783b79,
    0x3c7dbb16, 0xbc04bc5c, 0xbc78bb79, 0xbb16bc7d, 0xbc2c3c3e, 0x3c67bbdb, 0x3c67bbdb, 0x3c80ba49, 0x3c800000, 0x3c6dbbc4,
    0x3c800000, 0xbc6d3bc4, 0xbc800000, 0xbbc43c6d, 0xbc800000, 0x3bc4bc6d, 0x3c800000, 0xbbc4bc6d, 0x3c800000, 0x3bc43c6d,
    0xbc800000, 0x3c6d3bc4, 0xbc800000, 0xbc6dbbc4, 0xbc3ebc2c, 0xbc71bbac, 0xbc71bbac, 0x3c80ba49, 0x3c4e3c18, 0x3c5cbc04,
    0x3c783b79, 0xbc183c4e, 0xbc5cbc04, 0xbb163c7d, 0xbc7dbb16, 0xbb79bc78, 0x3c673bdb, 0xbc2cbc3e, 0x3c803a49, 0x3c673bdb,
    0x3ac93c7f, 0x3bf13c62, 0x3c463c22, 0xbc75bb95, 0xbb95bc75, 0xbc7fbac9, 0xbc62bbf1, 0x3c46bc22, 0x3bf13c62, 0x3c22bc46,
    0x3c753b95, 0x3ac93c7f, 0xbc22bc46, 0x3b953c75, 0xbc7fbac9, 0xbc62bbf1, 0x3c18bc4e, 0x3b79bc78, 0xbc04bc5c, 0x3c4e3c18,
    0xbbac3c71, 0x3c3e3c2c, 0x3c3e3c2c, 0xbc673bdb, 0x3a49bc80, 0xbc713bac, 0xbc67bbdb, 0x3a49bc80, 0x3b793c78, 0x3b16bc7d,
    0x3c7d3b16, 0x3c5c3c04, 0xbc7b3b48, 0xbc553c0e, 0x3b483c7b, 0xbc0ebc55, 0x3c55bc0e, 0xbb48bc7b, 0xbc0ebc55, 0x3c7bbb48,
    0xbc0e3c55, 0x3c7b3b48, 0x3c553c0e, 0xbb483c7b, 0x3b48bc7b, 0xbc0e3c55, 0xbc7bbb48, 0xbc55bc0e, 0x3c5c3c04, 0x3c7d3b16,
    0x3b16bc7d, 0x3b793c78, 0xbc80ba49, 0xbbdb3c67, 0x3bac3c71, 0xbc80ba49, 0x3c67bbdb, 0xbc3ebc2c, 0xbc3ebc2c, 0x3bacbc71,
    0xbc183c4e, 0x3c5cbc04, 0x3c783b79, 0x3c4e3c18, 0xbb95bc75, 0xbc22bc46, 0xbbf13c62, 0x3ac9bc7f, 0x3c463c22, 0x3c62bbf1,
    0xbac9bc7f, 0x3c753b95, 0xbc7fbac9, 0x3b953c75, 0x3c223c46, 0xbbf13c62, 0x3c62bbf1, 0xbc7f3ac9, 0xbc75bb95, 0xbc46bc22,
    0xbbdb3c67, 0xba493c80, 0x3c3ebc2c, 0xbbdb3c67, 0xbb79bc78, 0xbc7dbb16, 0xbb163c7d, 0xbc5cbc04, 0x3c4e3c18, 0x3b79bc78,
    0xbc04bc5c, 0x3c18bc4e, 0xbc803a49, 0x3c713bac, 0x3c713bac, 0x3c3e3c2c,
};

__device__ __forceinline__ void store_tile_64(const float (&d)[32], uint32_t base, int warp, int lane) {
  const int row = warp * 16 + (lane & 7) + ((lane >> 3) & 1) * 8;
  const uint32_t rb = base + row * 128;
#pragma unroll
  for (int j = 0; j < 8; j += 2) {
    const int jj = j + (lane >> 4);
    stsm4(rb + ((jj ^ (lane & 7)) << 4), pack2(d[4 * j], d[4 * j + 1]), pack2(d[4 * j + 2], d[4 * j + 3]),
          pack2(d[4 * j + 4], d[4 * j + 5]), pack2(d[4 * j + 6], d[4 * j + 7]));
  }
}

#define PLACE 0
#define G_EPI 3
#define P_X1A 0
#define P_X1B 0
#define P_X1M 15
#define P_RAW 0
#define PT 5
#define W2_PF 1
constexpr int A_IN = 112 * 128;
constexpr int G_ST = 2 * NB1 * 64;
constexpr int K1_R = 131072, K1_BAR = K1_R + 98304, K1_SMEM = K1_BAR + 2048 + 1024;
constexpr int K1_T = K1_R + 65536, K1_TIN = G_ST, K1_Y0 = 3 * G_ST + 8192;
__device__ int g_done[8 * 32];
struct Ptrs {
  int* done;
  float* ge;
  const uint32_t *img, *ga;
};

__host__ __device__ constexpr int g_depth(int s) { return s < 9 ? 3 : s < 18 ? 4 : s < 23 ? 5 : 6; }
__host__ __device__ constexpr int g_slot(int s) { return s < 3 ? s : g_depth(s) != g_depth(s - 1) ? g_depth(s - 1) : g_slot(s - g_depth(s)); }
__host__ __device__ constexpr int g_off(int id) { return id * G_ST + (id < 3 ? K1_R : id == 3 ? -3 * G_ST : 8192 - 3 * G_ST); }
struct Plan {
  uint32_t raw[32];
  uint32_t x[16];
  uint32_t grp[8];
  uint32_t last;
  uint32_t wpf;
  uint32_t g0;
  uint32_t tmask;
  uint64_t list[2];
};
struct K1Maps {
  Plan p;
  CUtensorMap x, we, wo, xs, y, w2e, w2o, w2s;
  int slot[32];
  int src[32];
  int dep[32];
};
__device__ __forceinline__ void poll_ge(const int* p, int target) {
  for (int it = 0; it < (1 << 20); it++) {
    int v;
    asm volatile("ld.acquire.gpu.global.s32 %0, [%1];" : "=r"(v) : "l"(p) : "memory");
    if (v >= target) break;
  }
}
__device__ __forceinline__ uint32_t place(int rank, uint32_t c) { return (c ^ (rank * 4 & ~(c >> 1))) << 14; }
__device__ __forceinline__ int x_unit(int cta, int u, uint32_t pl) {
  const int i = u * 128 + cta;
  const int pr = cta >= 128 ? 2 * cta - 96 + (u & 1) : i % 160, sl = cta >= 128 ? u >> 1 : i / 160, b = pr >= 84;
  return pr | sl << 8 | b << 11 | (cta >= 128 ? (u & 7) << 14 : place(cta & 1, pl & 15)) | 12 * (pr - 84 * b) << 20;
}
__device__ __forceinline__ int lds32(uint32_t a) {
  int v;
  asm volatile("ld.shared.b32 %0, [%1];" : "=r"(v) : "r"(a));
  return v;
}
__host__ __device__ constexpr uint64_t sched(const char* p) {
  uint64_t r = 0;
  for (int n = 0; p[n]; n++) r |= (uint64_t)(p[n] - '0' + 1) << (5 * n);
  return r;
}

__global__ void __cluster_dims__(2, 1, 1) __launch_bounds__(384, 1)
k1(const Ptrs gp0, const char* __restrict__ x1, const char* __restrict__ w1, const __grid_constant__ K1Maps m, const __nv_bfloat16* __restrict__ g,
   const __nv_bfloat16* __restrict__ wgt) {
  const Ptrs gp_ = PT & 1 ? Ptrs{g_done, g_ge, c_img, c_ga} : gp0;
  extern __shared__ __align__(1024) uint8_t smem_k1[];
  const uint32_t sb = s2u(smem_k1);
  const int tid = threadIdx.x, wg = __shfl_sync(0xffffffffu, tid >> 7, 0), t = tid & 127;
  const int warp = __shfl_sync(0xffffffffu, t >> 5, 0), lane = t & 31;
  const int cta = blockIdx.x, rank = cta & 1;
  const bool spare = cta >= 128;
  const int nx = spare ? 16 : 10;
  int bp, dc;
  {
    const int ci = cta >> 1;
    const int G = ci < 4 ? 0 : ci < 36 ? (ci - 4) & 7 : 1 + (ci - 36) % 7;
    const int li = ci < 4 ? 4 + ci : ci < 36 ? (ci - 4) >> 3 : 4 + (ci - 36) / 7;
    if (PLACE == 0) { bp = 2 * G + (li >> 2); dc = li & 3; }
    else if (PLACE == 1) { bp = (G >> 1) * 4 + (li >> 1); dc = (G & 1) * 2 + (li & 1); }
    else { bp = (G >> 2) * 8 + li; dc = G & 3; }
  }
  const int bin = 2 * bp + rank;
  const uint32_t bb = sb + K1_BAR;
  const uint32_t rfull = bb, xfull = bb + 256, xfree = bb + 384, gfull = bb + 512, win = bb + 768;
  const uint32_t inf0 = win + 16, se0 = inf0 + 16, pfree = se0 + 16, rempty = bb + 1024, xready = bb + 1280;
  const uint32_t gdone = bb + 1536, ine0 = gdone + 224, sf0 = ine0 + 16;
  const uint32_t xtab = bb + 896, tab = bb + 1792, ptab = bb + 2048 + 768;
  auto raw_load = [&](int j, uint32_t dst) {
    mbar_expect(rfull + 8 * j, 16384);
    tma_ld4<P_RAW>(dst, rank ? &m.we : &m.wo, rfull + 8 * j, dc * 64, rank - 1, (j & 3) * 4, (j >> 2) * 2);
  };
  auto x_half = [&](int u, int c, int h) {
    tma_ld4<1>(sb + (c & 0x3C000) + h * (A_IN / 2), &m.x, xfull + 8 * u, 0, (c >> 17 & ~7) - 24 + h * 56, c >> 8 & 7, c >> 11 & 1);
  };
  auto w_prefetch = [&](int q) {
    if (cta < 124) asm volatile("cp.async.bulk.prefetch.L2.global [%0], 4096;" ::"l"(w1 + (cta >> 2) * 131072 + (q * 4 + (cta & 3)) * 4096) : "memory");
  };
  uint32_t peer;
  asm("mapa.shared::cluster.u32 %0, %1, %2;" : "=r"(peer) : "r"(sb), "r"(rank ^ 1));
  if (wg == 2) {
    if (lane == 0) {
      if (warp < 2) {
        for (int i = 0; i < 4; i++) mbar_init(bb + 256 * warp + 8 * i, 1);
        fence_bar_init();
        fence_async();
        if (warp == 1) {
          const int c = x_unit(cta, 0, m.p.x[0]);
          mbar_expect(xfull, A_IN);
          x_half(0, c, 0);
          x_half(0, c, 1);
        } else if (!spare) {
#pragma unroll 1
          for (int j = 0; j < 4; j++) raw_load(j, sb + K1_R + j * 16384);
        }
      } else if (warp == 2) {
#pragma unroll 1
        for (int q = 1; q <= m.p.wpf; q++) w_prefetch(q);
        prefetch_map(&m.xs);
      }
    }
    if (warp == 3) {
      const uint32_t v = reinterpret_cast<const uint32_t*>(&m.p)[32 + lane];
      asm volatile("st.shared.b32 [%0], %1;" ::"r"(ptab + 4 * lane), "r"(m.p.raw[lane]) : "memory");
      asm volatile("st.shared.b32 [%0], %1;" ::"r"(ptab + 128 + 4 * lane), "r"(v) : "memory");
      if (lane < 16) asm volatile("st.shared.b32 [%0], %1;" ::"r"(xtab + 4 * lane), "r"(x_unit(cta, lane, v)) : "memory");
    }
  } else {
    if (lane < 16)
      asm volatile("st.shared.u16 [%0], %1;" ::"r"(tab + (tid >> 5) * 32 + lane * 2),
                   "h"(__bfloat16_as_ushort(__float2bfloat16_rn(cospif((float)((tid >> 5) * 16 + lane) * (1.0f / 64.0f))))) : "memory");
    const int c = 4 * wg + warp;
    if (lane == 0 && c < 7) {
      const uint32_t b0 = bb + 256 * c, n = c < 4 ? 1 : c < 6 ? 4 : 8;
      if (c >= 2)
        for (int i = 0; i < 4; i++) mbar_init(b0 + 8 * i, n);
      for (int i = 4; i < 16; i++) mbar_init(b0 + 8 * i, n);
      if (c == 3) {
        mbar_expect(win, 65536);
        mbar_arrive(win + 8);
      } else {
        for (int i = 16; i < 32; i++) mbar_init(b0 + 8 * i, n);
      }
      fence_bar_init();
    }
  }
  pdl_launch();
  __syncthreads();
  asm volatile("barrier.cluster.arrive.relaxed.aligned;" ::: "memory");
  if (wg == 2) {
    asm volatile("setmaxnreg.dec.sync.aligned.u32 40;");
    asm volatile("barrier.cluster.wait.aligned;" ::: "memory");
    if (lane == 0) {
      const int wpf = lds32(ptab + 228), g0 = lds32(ptab + 232), s0 = g0 * 4 / 5;
      const int nx0 = spare ? 2 * s0 : g0;
      if (warp == 0) {
        if (!spare) {
#pragma unroll 1
          for (int j = 4; j < 32; j++) {
            const uint32_t e = lds32(ptab + 4 * j);
            mbar_wait(bb + (e >> 5 & ~7), 0);
            raw_load(j, sb + place(rank, e & 15));
            if ((j & 3) == 0 && wpf && (j >> 2) + wpf < 8) w_prefetch((j >> 2) + wpf);
          }
#pragma unroll 1
          for (int s = 0; s < 32; s++) {
            if (s == 0 || s == 4 * s0) {
              poll_ge(&gp_.done[(s ? 5 : 4) * 32], 132);
              asm volatile("fence.proxy.async.global;" ::: "memory");
              mbar_wait(bb + 8 * (lds32(ptab + 224) & 255), 0);
            }
            const uint32_t bar = gfull + 8 * s, dst = sb + 16 * m.slot[s];
            const char* src = x1 + bin * (4 * G_ST) + m.src[s];
            mbar_wait(bb + m.dep[s], 0);
            mbar_expect(bar, G_ST);
#pragma unroll
            for (int h = 0; h < 2; h++) {
              if (s >= P_X1A && s < P_X1B && (P_X1M >> dc & 1))
                asm volatile("cp.async.bulk.shared::cluster.global.mbarrier::complete_tx::bytes.L2::cache_hint [%0], [%1], %2, [%3], %4;"
                             ::"r"(dst + h * (G_ST / 2)), "l"(src + h * (s < 26 ? G_ST / 2 : 2 * G_ST)), "n"(G_ST / 2), "r"(bar), "l"(policy<1>()) : "memory");
              else
                asm volatile("cp.async.bulk.shared::cluster.global.mbarrier::complete_tx::bytes [%0], [%1], %2, [%3];"
                             ::"r"(dst + h * (G_ST / 2)), "l"(src + h * (s < 26 ? G_ST / 2 : 2 * G_ST)), "n"(G_ST / 2), "r"(bar) : "memory");
            }
          }
          if (cta == 0) asm volatile("cp.async.bulk.prefetch.L2.global [%0], 14336;" ::"l"(gp_.img) : "memory");
        }
      } else if (warp < 3) {
        const int u0 = warp == 1 ? 0 : nx0, u1 = warp == 1 ? nx0 : nx;
#pragma unroll 1
        for (int u = u0; u < u1; u++) {
          const int c = lds32(xtab + 4 * u);
          const uint32_t e = spare ? 0xC0 : lds32(ptab + 128 + 4 * u);
          const uint32_t src = sb + (c & 0x3C000), rel = e >> 1 & 24, burst = (16 << (e >> 6 & 3)) - 1;
          mbar_wait(xready + 8 * u, 0);
#pragma unroll 1
          for (int p = 0; p < 128; p += 16) {
            tma_st4<0>(&m.xs, src + p * 128, 0, (c >> 2 & 0x1C0) + (p & 63), p >> 6, c & 255);
            if (((p + 16) & burst) == 0) {
              bulk_commit();
              bulk_wait_read<0>();
            }
          }
          mbar_arrive(xfree + 8 * u);
          if (rel)
            asm volatile("mbarrier.arrive.shared::cluster.b64 _, [%0];" ::"r"(peer + (pfree - sb) + rel) : "memory");
        }
        asm volatile("cp.async.bulk.wait_group 0;" ::: "memory");
        asm volatile("red.release.gpu.global.add.s32 [%0], 1;" ::"l"(&gp_.done[(3 + warp) * 32]) : "memory");
        if (!spare) {
          if (warp == 1) {
            auto w2_row = [&](int it, bool pf) {
              const CUtensorMap* mp = it & 1 ? &m.w2e : &m.w2o;
              const int c1 = (it & 1) - 1, c2 = (cta & 1) * 2, c3 = (it >> 1) * 64 + (cta >> 1);
              if (pf) {
                asm volatile("cp.async.bulk.prefetch.tensor.4d.L2.global [%0, {%1, %2, %3, %4}];" ::"l"(mp), "r"(0), "r"(c1), "r"(c2), "r"(c3) : "memory");
              } else {
                mbar_expect(inf0 + 8 * (it & 1), 4096);
                tma_ld4<1>(sb + K1_TIN + (it & 1) * 4096, mp, inf0 + 8 * (it & 1), 0, c1, c2, c3);
              }
            };
#pragma unroll 1
            for (int it = 0; it < 8; it++) {
              mbar_wait(gdone + 8 * it, 0);
              if (W2_PF) w2_row(it, true);
            }
#pragma unroll 1
            for (int it = 0; it < 8; it++) {
              if (it >= 2) mbar_wait(ine0 + 8 * (it & 1), ((it >> 1) - 1) & 1);
              w2_row(it, false);
            }
          } else {
            prefetch_map(&m.w2s);
            prefetch_map(&m.y);
#pragma unroll 1
            for (int it = 0; it < 8; it++) {
              mbar_wait(sf0 + 8 * (it & 1), (it >> 1) & 1);
              if (it >= 2) poll_ge(&gp_.done[((0x33210000 >> (4 * it)) & 3) * 32], 128);
              tma_st4<0>(&m.w2s, sb + K1_T + (it & 1) * 16384, 0, it * 64, (cta & 1) * 2, (cta >> 1 & 33) | (cta >> 3 & 6) | (cta << 1 & 24));
              bulk_commit();
              bulk_wait_read<0>();
              mbar_arrive(se0 + 8 * (it & 1));
            }
          }
        }
      } else {
#pragma unroll 1
        for (int u = 1; u < nx; u++) {
          const int c = lds32(xtab + 4 * u);
          const uint32_t e = spare ? (u < 8 ? 97 : 40 + u) * 0x01010100u : lds32(ptab + 128 + 4 * u);
          mbar_wait(bb + (e >> 5 & 0x7F8), 0);
          mbar_expect(xfull + 8 * u, A_IN);
          mbar_wait(bb + (e >> 13 & 0x7F8), 0);
          x_half(u, c, 0);
          mbar_wait(bb + (e >> 21 & 0x7F8), 0);
          x_half(u, c, 1);
        }
#pragma unroll 1
        for (int s = 0; s < (spare ? 0 : 16); s++) {
          mbar_wait(gfull + 8 * s, 0);
          if ((s & 3) == 3) asm volatile("red.relaxed.gpu.global.add.s32 [%0], 1;" ::"l"(&gp_.done[(s >> 2) * 32]) : "memory");
        }
      }
    }
  } else {
    asm volatile("setmaxnreg.inc.sync.aligned.u32 232;");
    auto dft2 = [&](int k2, int f2) {
      uint16_t a, b;
      asm volatile("ld.shared.u16 %0, [%1];" : "=h"(a) : "r"(tab | (k2 & 254)));
      asm volatile("ld.shared.u16 %0, [%1];" : "=h"(b) : "r"(tab | ((k2 + f2) & 254)));
      uint32_t r;
      asm("mov.b32 %0, {%1, %2};" : "=r"(r) : "h"(a), "h"(b));
      return r;
    };
    const int row = (lane & 7) + ((lane >> 3) & 1) * 8, hi = lane >> 4;
    asm volatile("barrier.cluster.wait.aligned;" ::: "memory");
    uint32_t fw[4];
    {
      uint32_t fa[16], za[64];
      bool first = true;
      const int rho = (lane >> 3) | (lane & 4);
      const int z2 = 2 * ((4 * bp + warp) | 1), zk = z2 * (lane & 3) * 2 - (warp & 1) * 64;
      const uint32_t lo = dft2(zk, z2), hh = dft2(zk + 8 * z2, z2);
#pragma unroll
      for (int i = 0; i < 64; i++) za[i] = ((i & 1) == (i >> 5) && rho == ((i >> 2) & 7)) ? ((i & 2) ? hh : lo) : 0u;
      reg_fence(za);
      const bool own = (warp >> 1) == rank;
      float d[64];
      constexpr uint64_t s2 = sched("02468:<>"), s3 = sched("13579;=?");
#pragma unroll 1
      for (uint64_t sc = spare ? (wg ? s3 : s2) : m.p.list[wg]; sc; sc >>= 5) {
        const int item = (int)sc & 31;
        if (item >= 18) {
          const int q = item - 18;
          const uint32_t e = __shfl_sync(0xffffffffu, lds32(ptab + 192 + 4 * q), 0);
#pragma unroll
          for (int jj = 0; jj < 4; jj++) {
            const int j = 4 * q + jj;
            mbar_wait(rfull + 8 * j, 0);
            wg_fence();
#pragma unroll
            for (int i = 0; i < 4; i++)
              wgmma_rs_128<1, 1, 1>(d, za[16 * jj + 4 * i], za[16 * jj + 4 * i + 1], za[16 * jj + 4 * i + 2], za[16 * jj + 4 * i + 3],
                                    mk_desc(sb + place(rank, e >> (4 * jj) & 15), i * 2048, 8192, 1024, 1), jj | i);
            wg_commit();
            if (jj > 0) {
              wg_wait<1>();
              if (lane == 0) mbar_arrive(rempty + 8 * (j - 1));
            }
          }
          wg_wait<0>();
          reg_fence(d);
          if (lane == 0) mbar_arrive(rempty + 8 * (4 * q + 3));
          mbar_wait(bb + (e >> (own ? 13 : 21) & 0x7F8), 0);
          const uint32_t rb = (own ? sb : peer) + (8 * rank + q) * 8192 + (warp & 1) * 4096 + rho * 128;
          auto put_w = [&](auto remote) {
#pragma unroll
            for (int v = 0; v < 8; v++) {
              const int j = 4 * (v >> 1), h = v & 1;
              const uint32_t a = rb + (j >> 3) * 2048 + h * 1024 + ((((j & 4) + (lane & 3)) ^ rho) << 4);
              const uint32_t p0 = pack2(d[4 * j + 2 * h], d[4 * j + 2 * h + 1]), p1 = pack2(d[4 * j + 4 + 2 * h], d[4 * j + 5 + 2 * h]);
              const uint32_t p2 = pack2(d[4 * j + 8 + 2 * h], d[4 * j + 9 + 2 * h]), p3 = pack2(d[4 * j + 12 + 2 * h], d[4 * j + 13 + 2 * h]);
              if (decltype(remote)::value)
                asm volatile("st.async.shared::cluster.mbarrier::complete_tx::bytes.v4.b32 [%0], {%1, %2, %3, %4}, [%5];"
                             ::"r"(a), "r"(p0), "r"(p1), "r"(p2), "r"(p3), "r"(peer + (win - sb)) : "memory");
              else
                asm volatile("st.shared.v4.b32 [%0], {%1, %2, %3, %4};" ::"r"(a), "r"(p0), "r"(p1), "r"(p2), "r"(p3) : "memory");
            }
          };
          if (own) put_w(std::false_type());
          else put_w(std::true_type());
        } else {
          const int u = item - 1;
          const int c = lds32(xtab + 4 * u);
          const uint32_t in = sb + (c & 0x3C000);
          if (first) {
            first = false;
#pragma unroll
            for (int i = 0; i < 16; i++) {
              const int f2 = 2 * ((warp * 16 + (lane >> 2) + 8 * (i & 1)) | 1);
              fa[i] = dft2(f2 * ((lane & 3) * 2 + 8 * (i >> 1)) - (lane & 4) * 16, f2);
            }
          }
          mbar_wait(xfull + 8 * u, 0);
          wg_fence();
#pragma unroll
          for (int k = 0; k < 4; k++)
            wgmma_rs_128<1, 1, 1>(d, fa[4 * k], fa[4 * k + 1], fa[4 * k + 2], fa[4 * k + 3], mk_desc(in, k * 2048, 6144, 1024, 1), k);
          wg_commit();
          wg_wait<0>();
          reg_fence(d);
          bar_sync(1 + wg, 128);
          const uint32_t rb = in + (warp * 16 + row) * 128, xr = (lane & 7) ^ (c & 3);
#pragma unroll
          for (int j = 0; j < 16; j += 2)
            stsm4(rb + ((j >> 2) & 1) * 8192 + ((((j >> 3) * 4 + (j & 3) + hi) ^ xr) << 4), pack2(d[4 * j], d[4 * j + 1]),
                  pack2(d[4 * j + 2], d[4 * j + 3]), pack2(d[4 * j + 4], d[4 * j + 5]), pack2(d[4 * j + 6], d[4 * j + 7]));
          fence_async();
          __syncwarp();
          if (lane == 0) mbar_arrive(xready + 8 * u);
        }
      }
#pragma unroll
      for (int i = 0; i < 4; i++) {
        const int f2 = 2 * ((warp * 16 + (lane >> 2) + 8 * (i & 1)) | 1);
        fw[i] = dft2(f2 * ((lane & 3) * 2 + 8 * (i >> 1)) - (lane & 4) * 16, f2);
      }
    }
    if (spare) {
      float* sg = reinterpret_cast<float*>(smem_k1 + K1_R);
      __nv_bfloat16* sw = reinterpret_cast<__nv_bfloat16*>(sg + 16 * 256);
      const int c0 = (cta - 128) * 64;
      uint4 vw[8], vg[2];
#pragma unroll
      for (int i = 0; i < 8; i++) vw[i] = __ldg(reinterpret_cast<const uint4*>(wgt + ((i * 256 + tid) >> 3) * 256 + c0 + (tid & 7) * 8));
#pragma unroll
      for (int i = 0; i < 2; i++) vg[i] = __ldg(reinterpret_cast<const uint4*>(g) + i * 256 + tid);
#pragma unroll
      for (int i = 0; i < 8; i++) reinterpret_cast<uint4*>(sw)[i * 256 + tid] = vw[i];
#pragma unroll
      for (int i = 0; i < 2; i++) {
        const uint32_t w4[4] = {vg[i].x, vg[i].y, vg[i].z, vg[i].w};
#pragma unroll
        for (int e = 0; e < 4; e++) {
          sg[(i * 256 + tid) * 8 + 2 * e] = __uint_as_float(w4[e] << 16);
          sg[(i * 256 + tid) * 8 + 2 * e + 1] = __uint_as_float(w4[e] & 0xffff0000u);
        }
      }
      bar_sync(3, 256);
      const int col = tid & 63, r0 = (tid >> 6) * 4;
      float a0 = 0.f, a1 = 0.f, a2 = 0.f, a3 = 0.f;
#pragma unroll 8
      for (int k = 0; k < 256; k++) {
        const float w = __bfloat162float(sw[k * 64 + col]);
        a0 = fmaf(sg[(r0 + 0) * 256 + k], w, a0);
        a1 = fmaf(sg[(r0 + 1) * 256 + k], w, a1);
        a2 = fmaf(sg[(r0 + 2) * 256 + k], w, a2);
        a3 = fmaf(sg[(r0 + 3) * 256 + k], w, a3);
      }
      const int cc = c0 + col;
      const int pos = (cc & ~15) + ((cc >> 1) & 3) * 4 + ((cc >> 3) & 1) * 2 + (cc & 1);
      gp_.ge[(r0 + 0) * 256 + pos] = __bfloat162float(__float2bfloat16_rn(a0));
      gp_.ge[(r0 + 1) * 256 + pos] = __bfloat162float(__float2bfloat16_rn(a1));
      gp_.ge[(r0 + 2) * 256 + pos] = __bfloat162float(__float2bfloat16_rn(a2));
      gp_.ge[(r0 + 3) * 256 + pos] = __bfloat162float(__float2bfloat16_rn(a3));
      return;
    }
    reg_fence(fw);
    mbar_wait(win, 0);
    fence_async();
    bar_sync(3, 256);
    float d[16];
    auto t_begin = [&](int it, int hh, int r) {
      if (r == 0) mbar_wait(inf0 + 8 * (it & 1), (it >> 1) & 1);
      wg_fence();
      wgmma_rs_32<1, 1, 1>(d, fw[0], fw[1], fw[2], fw[3], mk_desc(sb + K1_TIN + (it & 1) * 4096 + hh * 2048, r * 64, 0, 1024, 1), 0);
      wg_commit();
    };
    auto t_end = [&](int it, int hh, int r) {
      reg_fence(d);
      const int j = it & 1;
      if (r == 0) mbar_wait(it >= 2 ? se0 + 8 * j : bb + (m.p.last >> (5 + 8 * it) & 0x7F8), it >= 2 ? ((it >> 1) - 1) & 1 : 0);
      else if (lane == 0) mbar_arrive(ine0 + 8 * j);
      const uint32_t rb = sb + K1_T + j * 16384 + hh * 8192 + (warp * 16 + row) * 128;
#pragma unroll
      for (int i = 0; i < 2; i++)
        stsm4(rb + (((4 * r + 2 * i + hi) ^ (lane & 7)) << 4), pack2(d[8 * i], d[8 * i + 1]), pack2(d[8 * i + 2], d[8 * i + 3]),
              pack2(d[8 * i + 4], d[8 * i + 5]), pack2(d[8 * i + 6], d[8 * i + 7]));
      if (r == 1) {
        fence_async();
        __syncwarp();
        if (lane == 0) mbar_arrive(sf0 + 8 * j);
      }
    };
    float y0[NB1 / 2], y1[NB1 / 2];
    uint32_t wa[8], wb[8];
    uint32_t wp = sb + wg * 4096 + ((lane & 7) + hi * 8) * 128 + (((2 * warp + ((lane >> 3) & 1)) ^ (lane & 7)) << 4);
    const uint32_t neg = wg ? 0x80008000u : 0u;
    auto frag = [&](uint32_t (&w)[8], uint32_t a, uint32_t sg) {
      ldsm4t(a, w[0], w[1], w[2], w[3]);
      ldsm4t(a + 2048, w[4], w[5], w[6], w[7]);
#pragma unroll
      for (int i = 0; i < 8; i++) w[i] ^= sg;
    };
    auto stage = [&](const uint32_t (&w)[8], uint32_t x4, int acc) {
      wg_fence();
      wgmma_rs_168<1, 1, 0>(y0, w[0], w[1], w[2], w[3], mk_desc4(x4, 0, 512, 2), acc);
      wgmma_rs_168<1, 1, 0>(y1, w[0], w[1], w[2], w[3], mk_desc4(x4 + G_ST / 32, 0, 512, 2), acc);
      wgmma_rs_168<1, 1, 0>(y0, w[4], w[5], w[6], w[7], mk_desc4(x4 + 2, 0, 512, 2), 1);
      wgmma_rs_168<1, 1, 0>(y1, w[4], w[5], w[6], w[7], mk_desc4(x4 + G_ST / 32 + 2, 0, 512, 2), 1);
      wg_commit();
      wg_wait<1>();
    };
    frag(wa, wp, neg);
    int it = 0;
#pragma unroll 1
    for (int k = 0; k < 13; k++) {
      const bool T = (m.p.tmask >> k) & 1;
      const uint32_t xa = ((sb & 0x3FFFF) >> 4) + m.slot[2 * k], xb = ((sb & 0x3FFFF) >> 4) + m.slot[2 * k + 1];
      if (T) t_begin(it, wg, 0);
      mbar_wait(gfull + 16 * k, 0);
      stage(wa, xa, k);
      frag(wb, wp ^ 4096, 0);
      if (k > 0 && lane == 0) mbar_arrive(gdone + 16 * k - 8);
      if (T) {
        t_end(it, wg, 0);
        t_begin(it, wg, 1);
      }
      mbar_wait(gfull + 16 * k + 8, 0);
      stage(wb, xb, 1);
      wp += 8192;
      frag(wa, wp, neg);
      if (lane == 0) mbar_arrive(gdone + 16 * k);
      if (T) t_end(it++, wg, 1);
    }
    auto tail = [&](float (&y)[NB1 / 2], auto batch, auto wgc) {
      constexpr int B = decltype(batch)::value, W = decltype(wgc)::value;
#pragma unroll
      for (int k = 13; k < 16; k++) {
        const int s = 13 + k + 3 * B;
        mbar_wait(gfull + 8 * s, 0);
        const int xo = g_off(g_slot(s));
        wg_fence();
#pragma unroll
        for (int h = 0; h < 4; h++) {
          const uint64_t dW = mk_desc(sb, k * 8192 + ((h >> 1) ^ W) * 4096 + (h & 1) * 2048, 0, 1024, 1);
          const uint64_t dX = mk_desc(sb, xo + (h >> 1) * (G_ST / 2) + (h & 1) * 32, 0, 512, 2);
          if (W == 1 && h < 2) wgmma_ss_168<-1, 1, 1, 0>(y, dW, dX, 1);
          else wgmma_ss_168<1, 1, 1, 0>(y, dW, dX, 1);
        }
        if (B == 0 && W == 0 && k == 13) {
          wg_commit();
          wg_wait<1>();
          if (lane == 0) mbar_arrive(gdone + 8 * 25);
        }
      }
      wg_commit();
    };
    constexpr std::integral_constant<int, 0> c0;
    constexpr std::integral_constant<int, 1> c1;
    auto put = [&](const float (&v)[NB1 / 2], uint32_t stg, int b) {
      const int mi = lane >> 3, i = lane & 7;
      const uint32_t a0 = stg + (mi >> 1) * 1024 + i * 128 + (((2 * warp + (mi & 1)) ^ i) << 4);
      constexpr int J = 21 / G_EPI;
#pragma unroll
      for (int c = 0; c < G_EPI; c++) {
#pragma unroll
        for (int j = c * J; j + 1 < (c + 1) * J; j += 2)
          stsm4t(a0 + j * 1024, pack2(v[4 * j], v[4 * j + 1]), pack2(v[4 * j + 2], v[4 * j + 3]),
                 pack2(v[4 * j + 4], v[4 * j + 5]), pack2(v[4 * j + 6], v[4 * j + 7]));
        const int j = (c + 1) * J - 1;
        asm volatile("stmatrix.sync.aligned.m8n8.x2.trans.shared.b16 [%0], {%1, %2};" ::"r"(a0 + j * 1024),
                     "r"(pack2(v[4 * j], v[4 * j + 1])), "r"(pack2(v[4 * j + 2], v[4 * j + 3])) : "memory");
        fence_async();
        bar_sync(1 + wg, 128);
        if (t == 0) {
          tma_st4<0>(&m.y, stg + c * J * 1024, 0, b * NB1 + c * J * 8, 2 * bin + wg, dc);
          bulk_commit();
        }
      }
    };
    if (wg == 0) {
      tail(y0, c0, c0);
      bar_arrive(4, 256);
      mbar_wait(gdone + 8 * 25, 0);
      wg_wait<0>();
      reg_fence(y0);
      put(y0, sb + K1_Y0, 0);
      bar_sync(7, 256);
      tail(y1, c1, c0);
      bar_arrive(8, 256);
      if (t == 0) bulk_wait_read<0>();
      wg_wait<0>();
      reg_fence(y1);
      bar_sync(1, 128);
      put(y1, sb + K1_Y0, 1);
    } else {
      wg_wait<0>();
      if (lane == 0) mbar_arrive(gdone + 8 * 25);
#pragma unroll 1
      for (int h2 = 2 * it; h2 < 16; h2++) {
#pragma unroll
        for (int r = 0; r < 2; r++) {
          t_begin(h2 >> 1, h2 & 1, r);
          wg_wait<0>();
          t_end(h2 >> 1, h2 & 1, r);
        }
      }
      bar_sync(4, 256);
      tail(y0, c0, c1);
      bar_arrive(7, 256);
      mbar_wait(se0, 1);
      mbar_wait(se0 + 8, 1);
      wg_wait<0>();
      reg_fence(y0);
      put(y0, sb + K1_T, 0);
      bar_sync(8, 256);
      tail(y1, c1, c1);
      wg_wait<0>();
      reg_fence(y1);
      put(y1, sb + g_off(g_slot(26)), 1);
    }
    if (t == 0) {
      bulk_wait_read<0>();
    }
  }
}

#define H_EPI 3
#define H_KS 11
#define H_PACE 4
#define H_WPRE 3
#define C_W2 0
#define C_W2I 2
#define C_B0 0
#define C_PC 32
#define C_HOLD 2
#define C_MAP 1
#define C_AHEAD 8
#define C_TOK 1
constexpr int H_XP = 168 * 64, H_STAGE = 8192 + 2 * H_XP, H_NST = 7, K2_STG = H_NST * H_STAGE, K2_SMEM = K2_STG + 21504 + 1024;

template <int WG>
__device__ __forceinline__ void h_loop(float (&acc)[84], uint32_t sb, uint32_t full0, uint32_t empty0, int lane) {
#pragma unroll 1
  for (int k = 0; k < 16; k++) {
    const int st = k % H_NST;
    if (WG == 1 && k == H_KS) bar_sync(5, 256);
    mbar_wait(full0 + 8 * st, (k / H_NST) & 1);
    const uint32_t base = sb + st * H_STAGE;
    wg_fence();
#pragma unroll
    for (int s = 0; s < 2; s++) {
      const uint64_t dP = mk_desc(base, s * 2048, 0, 1024, 1), dQ = mk_desc(base, 4096 + s * 2048, 0, 1024, 1);
      const uint64_t dA = mk_desc(base, 8192 + s * 32, 0, 1024, 1), dB = mk_desc(base, 8192 + 64 + s * 32, 0, 1024, 1);
      wgmma_ss_168<1, 1, 1, 0>(acc, dP, WG == 0 ? dA : dB, k | s);
      wgmma_ss_168<WG == 0 ? 1 : -1, 1, 1, 0>(acc, dQ, WG == 0 ? dB : dA, 1);
    }
    wg_commit();
    if (WG == 0 && k == 15) bar_arrive(5, 256);
    if (k <= 10) {
      wg_wait<1>();
      if (k > 0 && k - 1 + H_NST < 16 && lane < 2) mbar_arrive_cta(empty0 + 8 * ((k - 1) % H_NST), lane);
    }
  }
  wg_wait<0>();
  reg_fence(acc);
}
template <int C0, int C1> __device__ __forceinline__ void gelu_pack(uint32_t (&p)[12], const float (&h)[24]) {
#pragma unroll
  for (int i = 4 * C0; i < 4 * C1; i++) p[i] = pack2(gelu(h[2 * i]), gelu(h[2 * i + 1]));
}
struct K2Maps {
  CUtensorMap y, xs, w, y2;
};

__global__ void __cluster_dims__(2, 1, 1) __launch_bounds__(512, 1)
k2(const Ptrs gp0, const char* __restrict__ x2, const __grid_constant__ K2Maps m, const __nv_bfloat16* __restrict__ wf,
   const __nv_bfloat16* __restrict__ wo) {
  const Ptrs gp_ = PT & 2 ? Ptrs{g_done, g_ge, c_img, c_ga} : gp0;
  extern __shared__ __align__(1024) uint8_t smem_k1[];
  const uint32_t sb = s2u(smem_k1);
  const int tid = threadIdx.x, wg = __shfl_sync(0xffffffffu, tid >> 7, 0), t = tid & 127;
  const int warp = __shfl_sync(0xffffffffu, t >> 5, 0), lane = t & 31;
  const int cta = blockIdx.x, rank = cta & 1, dc = cta & 3, bin = cta >> 2;
  const uint32_t sGi = sb + K2_STG, sF = sGi + 6144, bb = sb + K2_STG + 21504;
  const uint32_t yfull = bb, full0 = bb + 128, empty0 = bb + 192, cfull = bb + 256, ready = bb + 320, bfree = bb + 384;
  const int b = C_MAP ? cta & 1 : (cta >> 5) & 1, j = C_MAP ? cta >> 2 : cta & 31;
  const int len0 = j < 20 ? 3 : 2, len1 = j >= 12 ? 3 : 2;
  const int n00 = j < 20 ? 3 * j : 2 * j + 20, n01 = j < 12 ? 2 * j : 3 * j - 12, cs0 = 3 - (C_MAP ? cta >> 1 & 1 : cta >> 6);
  auto y_load = [&](int r, int i) {
    tma_ld5<1>(sb + (3 + 2 * r) * H_STAGE + i * 8192, &m.y, yfull + 64 * r + 8 * i, 0, 0, cs0 - 2 * r, 2 * (r ? n01 : n00) + i, b);
  };
  if (wg == 2 && warp == 0) {
    if (lane == 0) {
      prefetch_map(&m.y);
      for (int i = 0; i < 16; i++) mbar_init(yfull + 8 * i, 1);
      fence_bar_init();
    }
    __syncwarp();
    if (lane < 16) mbar_expect(yfull + 8 * lane, lane == 7 ? 6144 : 8192);
    bar_arrive(0, 512);
    asm volatile("barrier.cluster.arrive.relaxed.aligned;" ::: "memory");
    auto c_load = [&](int h) {
      asm volatile("cp.async.bulk.shared::cluster.global.mbarrier::complete_tx::bytes [%0], [%1], %2, [%3];"
                   ::"r"(sGi + 6144 * h), "l"(gp_.img + 1536 * h), "r"(6144 + 2048 * h), "r"(yfull + 56 + 64 * h) : "memory");
    };
    if (lane == 0) {
      c_load(0);
      c_load(1);
      pdl_wait();
      const int r2 = len0 == 2, i2 = r2 ? 2 : 6;
      constexpr int seq[6] = {2, 0, 1, C_B0 ? 4 : 8, C_B0 ? 3 : 4, C_B0 ? 8 : 3};
#pragma unroll
      for (int q = 0; q < 8; q++) {
        if (q >= C_AHEAD) mbar_wait(yfull + 8 * seq[q >= C_AHEAD ? q - C_AHEAD : 0], 0);
        if (q < 6) y_load(seq[q] >> 3, seq[q] & 7);
        else y_load(r2, i2 + 6 - q);
      }
      pdl_launch();
    }
    __syncwarp();
  } else {
    if (lane == 0 && wg == 3) {
      for (int i = 0; i < 8; i++) mbar_init(full0 + 64 * warp + 8 * i, warp == 0 ? 1 : warp == 1 ? 16 : 4);
      fence_bar_init();
    }
    if (tid == 0) {
      mbar_init(bfree, 2);
      mbar_init(bfree + 8, 1);
      fence_bar_init();
    }
    if (tid == 128) {
      prefetch_map(&m.xs);
      prefetch_map(&m.w);
      prefetch_map(&m.y2);
    }
    bar_sync(0, 512);
    asm volatile("barrier.cluster.arrive.relaxed.aligned;" ::: "memory");
  }
  if (wg == 2) asm volatile("barrier.cluster.wait.aligned;" ::: "memory");
  mbar_wait(yfull + 56, 0);
  auto idft = [&](float (&h)[24], uint32_t in, uint32_t bar) {
    mbar_wait(bar, 0);
    wg_fence();
#pragma unroll
    for (int k = 0; k < 4; k++) wgmma_ss_48<1, 1, 1, 0>(h, mk_desc(in, k * 2048, 0, 1024, 1), mk_desc(sGi, k * 32, 0, 1024, 1), k);
    wg_commit();
  };
  auto carry_out = [&](const uint32_t (&p)[12], uint32_t dst, uint32_t bar) {
    bar_sync(1 + wg, 128);
#pragma unroll
    for (int v = 0; v < 3; v++)
      asm volatile("st.shared.v4.b32 [%0], {%1, %2, %3, %4};" ::"r"(dst + v * 2048 + t * 16), "r"(p[4 * v]), "r"(p[4 * v + 1]), "r"(p[4 * v + 2]), "r"(p[4 * v + 3]) : "memory");
    __syncwarp();
    if (lane == 0) mbar_arrive(bar);
  };
  if (wg == 3) {
#pragma unroll 1
    for (int r = 0; r < 2; r++) {
      float h[24];
      uint32_t p[12];
      idft(h, sb + (3 + 2 * r) * H_STAGE, yfull + 64 * r);
      wg_wait<0>();
      reg_fence(h);
      gelu_pack<0, 3>(p, h);
      if (j == 0) p[0] = p[1] = p[2] = p[3] = 0;
      carry_out(p, sb + (3 + 2 * r) * H_STAGE, cfull + 32 * r);
    }
    asm volatile("barrier.cluster.wait.aligned;" ::: "memory");
    if (lane == 0) {
      if (warp == 0) {
        auto w_load = [&](int k) {
          mbar_expect(full0 + 8 * (k % H_NST), H_STAGE);
          tma_ld4<1>(sb + (k % H_NST) * H_STAGE, &m.w, full0 + 8 * (k % H_NST), 0, (k & 1) * 32, dc, (7 - (k >> 1)) * 64 + 2 * bin);
        };
        for (int k = 0; k < H_WPRE; k++) w_load(k);
#pragma unroll 1
        for (int k = 0; k < 16; k++) {
          const int st = k % H_NST;
          if ((k & 7) == 0) {
            poll_ge(&gp_.done[(6 + (k >> 3)) * 32], 128);
            asm volatile("fence.proxy.async.global;" ::: "memory");
          }
          if (H_PACE && k >= H_PACE && k < H_NST) mbar_wait(empty0 + 8 * (k - H_PACE), 0);
          if (k == 5) mbar_wait(bfree, 0);
          if (k >= H_NST) mbar_wait(empty0 + 8 * st, ((k / H_NST) - 1) & 1);
          asm volatile("cp.async.bulk.shared::cluster.global.mbarrier::complete_tx::bytes.multicast::cluster [%0], [%1], %2, [%3], %4;"
                       ::"r"(sb + st * H_STAGE + 8192 + rank * H_XP),
                       "l"(x2 + (((7 - (k >> 2) - (k & 2) * 2) * 64 + (k & 1) * 32 + bin) * 2 + rank) * H_XP), "n"(H_XP), "r"(full0 + 8 * st),
                       "h"((uint16_t)3) : "memory");
          if (k >= H_WPRE) w_load(k);
          if (k == 8) {
            if (cta == 0) asm volatile("cp.async.bulk.prefetch.L2.global [%0], 6144;" ::"l"(gp_.ga) : "memory");
            asm volatile("cp.async.bulk.prefetch.L2.global [%0], 1024;" ::"l"(wf + cta * 512) : "memory");
            asm volatile("cp.async.bulk.prefetch.L2.global [%0], 1024;" ::"l"(wo + cta * 512) : "memory");
          }
        }
      } else if (warp < 3) {
        const int r = warp - 1, n0 = b * NB2 + (r ? n01 : n00), f0 = (cs0 - 2 * r) * 64;
        if (C_HOLD && r) mbar_wait(bfree + 8, 0);
#pragma unroll 1
        for (int i = 0; i < (r ? len1 : len0); i++) {
          const uint32_t src = sb + (3 + 2 * r) * H_STAGE + i * 16384;
          mbar_wait(ready + 32 * r + 8 * i, 0);
#pragma unroll 1
          for (int p = 0; p < 128; p += (C_PC ? C_PC : 64)) {
            tma_st3<0>(&m.xs, src + p * 128, 0, f0 + (p & 63) + (p >> 6) * 256, n0 + i);
            bulk_commit();
            if (C_PC && r) bulk_wait_read<0>();
          }
        }
        asm volatile("cp.async.bulk.wait_group 0;" ::: "memory");
        if (r) {
          mbar_arrive_cta(bfree, 0);
          mbar_arrive_cta(bfree, 1);
        }
        if (C_HOLD == 1 && !r) mbar_arrive(bfree + 8);
        asm volatile("red.release.gpu.global.add.s32 [%0], 1;" ::"l"(&gp_.done[(6 + r) * 32]) : "memory");
        if (C_HOLD == 2 && !r) mbar_arrive(bfree + 8);
      }
    }
    return;
  }
#pragma unroll 1
  for (int it = wg; it < len0 + len1; it += 3) {
    const int r = it >= len0, i = it - r * len0;
    const bool last = i + 1 == (r ? len1 : len0);
    const uint32_t in = sb + (3 + 2 * r) * H_STAGE + i * 16384, bar = yfull + 64 * r + 16 * i;
    float h1[24], h2[24];
    uint32_t p0[12], p1[12], p2[12];
    idft(h2, in + 16384, bar + 16);
    auto y_next = [&]() {
      const int ib = 3 + warp - len0;
      if (lane == 0 && ib < len1) {
        y_load(1, 2 * ib + 2);
        y_load(1, 2 * ib + 1);
      }
    };
    if (C_W2 == 0 && it == C_W2I) y_next();
    if (C_TOK && it > 0) bar_sync(6 + wg, 256);
    wg_wait<0>();
    reg_fence(h2);
    gelu_pack<0, 2>(p2, h2);
    idft(h1, in + 8192, bar + 8);
    if (C_W2 == 1 && it == C_W2I) y_next();
    if (!last) {
      gelu_pack<2, 3>(p2, h2);
      carry_out(p2, in + 16384, cfull + 32 * r + 8 * i + 8);
    }
    if (C_TOK == 1 && it + 1 < len0 + len1) bar_arrive(6 + (wg + 1) % 3, 256);
    mbar_wait(cfull + 32 * r + 8 * i, 0);
#pragma unroll
    for (int v = 0; v < 3; v++)
      asm volatile("ld.shared.v4.b32 {%0, %1, %2, %3}, [%4];" : "=r"(p0[4 * v]), "=r"(p0[4 * v + 1]), "=r"(p0[4 * v + 2]), "=r"(p0[4 * v + 3]) : "r"(in + v * 2048 + t * 16) : "memory");
    if (it < 3) mbar_wait(yfull + 120, 0);
    wg_wait<0>();
    reg_fence(h1);
    gelu_pack<0, 3>(p1, h1);
    if (last && j == 31) {
#pragma unroll
      for (int v = 0; v < 12; v++) p1[v] = p2[v] = 0;
    }
    if (C_TOK == 2 && it + 1 < len0 + len1) bar_arrive(6 + (wg + 1) % 3, 256);
    uint32_t hp[32];
#pragma unroll
    for (int c = 0; c < 8; c++)
#pragma unroll
      for (int v = 0; v < 4; v++) hp[(v >> 1) * 16 + 2 * c + (v & 1)] = c < 3 ? p0[4 * c + v] : c < 6 ? p1[4 * (c - 3) + v] : p2[4 * (c - 6) + v];
    float e0[32], e1[32];
    reg_fence(hp);
    wg_fence();
#pragma unroll
    for (int k = 0; k < 4; k++) {
      const uint64_t db = mk_desc(sF, k * 32, 0, 1024, 1);
      wgmma_rs_64<1, 1, 0>(e0, hp[4 * k], hp[4 * k + 1], hp[4 * k + 2], hp[4 * k + 3], db, k);
      wgmma_rs_64<1, 1, 0>(e1, hp[16 + 4 * k], hp[16 + 4 * k + 1], hp[16 + 4 * k + 2], hp[16 + 4 * k + 3], db, k);
    }
    wg_commit();
    bar_sync(1 + wg, 128);
    wg_wait<0>();
    reg_fence(e0);
    reg_fence(e1);
    {
      const int mi = lane >> 3, rr = (lane & 7) >> 1, blk = b * NB2 + (r ? n01 : n00) + i;
      const uint32_t a0 = in + (mi >> 1) * 8192 + (warp >> 1) * 4096 + rr * 128;
      const uint32_t pos = ((lane & 1) * 4 + (warp & 1) * 2 + (mi & 1)) ^ rr ^ (blk & 7);
#pragma unroll
      for (int q = 0; q < 8; q++)
        stsm4t(a0 + q * 512 + ((pos ^ (q & 1) * 4) << 4), pack2(e0[4 * q], e0[4 * q + 1]), pack2(e0[4 * q + 2], e0[4 * q + 3]),
               pack2(e1[4 * q], e1[4 * q + 1]), pack2(e1[4 * q + 2], e1[4 * q + 3]));
    }
    fence_async();
    __syncwarp();
    if (lane == 0) mbar_arrive(ready + 32 * r + 8 * i);
  }
  if (wg == 2) return;
  asm volatile("barrier.cluster.wait.aligned;" ::: "memory");
  float acc[84];
  if (wg == 0) {
    h_loop<0>(acc, sb, full0, empty0, lane);
  } else {
    h_loop<1>(acc, sb, full0, empty0, lane);
    bar_sync(2, 128);
  }
  const uint32_t stg = sb + (wg == 0 ? H_NST : 9 % H_NST) * H_STAGE;
  const int mi = lane >> 3, i = lane & 7;
  const uint32_t a0 = stg + (mi >> 1) * 1024 + i * 128 + (((2 * warp + (mi & 1)) ^ i) << 4);
  constexpr int J = 21 / H_EPI;
#pragma unroll
  for (int c = 0; c < H_EPI; c++) {
#pragma unroll
    for (int q = c * J; q + 1 < (c + 1) * J; q += 2)
      stsm4t(a0 + q * 1024, pack2(acc[4 * q], acc[4 * q + 1]), pack2(acc[4 * q + 2], acc[4 * q + 3]),
             pack2(acc[4 * q + 4], acc[4 * q + 5]), pack2(acc[4 * q + 6], acc[4 * q + 7]));
    const int q = (c + 1) * J - 1;
    asm volatile("stmatrix.sync.aligned.m8n8.x2.trans.shared.b16 [%0], {%1, %2};" ::"r"(a0 + q * 1024),
                 "r"(pack2(acc[4 * q], acc[4 * q + 1])), "r"(pack2(acc[4 * q + 2], acc[4 * q + 3])) : "memory");
    fence_async();
    bar_sync(1 + wg, 128);
    if (t == 0) {
      tma_st4<0>(&m.y2, stg + c * J * 1024, 0, c * J * 8, 2 * bin + wg, dc);
      bulk_commit();
    }
  }
  if (t == 0) {
    bulk_wait_read<0>();
  }
}

#define E_WPRE 2
#define E_LDS 1
#define E_WLATE 1
#define E_SPLIT 1
#define E_MID 1
#define E_EARLY0 2
#define E_CHUNK 2
#define E_EARLY 2
constexpr int E_SMEM = 65536 + 131072 + 32768 + 1024;

__device__ __forceinline__ uint32_t joint2(uint32_t fe, uint32_t g0, uint32_t g1) {
  uint32_t s0, s1;
  asm("{\n.reg .b16 l, h;\n.reg .b32 ll;\nmov.b32 {l, h}, %2;\nmov.b32 ll, {l, l};\n"
      "fma.rn.bf16x2 %0, ll, %5, %3;\nfma.rn.bf16x2 %1, %2, %5, %4;\n}"
      : "=r"(s0), "=r"(s1) : "r"(fe), "r"(g0), "r"(g1), "r"(0x3F800000u));
  return pack2(tanh_f32(__uint_as_float(s0)), tanh_f32(__uint_as_float(s1)));
}
__device__ __forceinline__ uint4 lds128(uint32_t a) {
  uint4 v;
  asm volatile("ld.shared.v4.u32 {%0, %1, %2, %3}, [%4];" : "=r"(v.x), "=r"(v.y), "=r"(v.z), "=r"(v.w) : "r"(a));
  return v;
}
__device__ __forceinline__ void joint_group(uint32_t (&ja)[8], const uint32_t* fe, const uint4& c0, const uint4& c1) {
  ja[0] = joint2(fe[0], c0.x, c0.y);
  ja[1] = joint2(fe[1], c0.x, c0.y);
  ja[2] = joint2(fe[2], c0.z, c0.w);
  ja[3] = joint2(fe[3], c0.z, c0.w);
  ja[4] = joint2(fe[4], c1.x, c1.y);
  ja[5] = joint2(fe[5], c1.x, c1.y);
  ja[6] = joint2(fe[6], c1.z, c1.w);
  ja[7] = joint2(fe[7], c1.z, c1.w);
  reg_fence(ja);
}

__global__ void __launch_bounds__(256, 1)
kE(const Ptrs gp0, const __grid_constant__ CUtensorMap my, const __grid_constant__ CUtensorMap mwf, const __grid_constant__ CUtensorMap mwo,
   const __grid_constant__ CUtensorMap mout) {
  const Ptrs gp_ = PT & 4 ? Ptrs{g_done, g_ge, c_img, c_ga} : gp0;
  extern __shared__ uint8_t smem_raw[];
  __shared__ __align__(8) uint64_t bars[13];
  const uint32_t sb = (s2u(smem_raw) + 1023) & ~1023u;
  const int tid = threadIdx.x, wg = __shfl_sync(0xffffffffu, tid >> 7, 0), t = tid & 127, warp = t >> 5, lane = t & 31;
  const uint32_t R0 = sb, R1 = sb + 65536, R2 = sb + 65536 + 131072;
  const uint32_t barY = s2u(&bars[0]), barF = s2u(&bars[4]), barO = s2u(&bars[8]), barA = s2u(&bars[12]);
  const int b = blockIdx.x / 63, t0 = (blockIdx.x % 63) * 64;
  const int a = t0 / 48, o = t0 % 48;
  const int qw = o + 16 * warp, sel = qw >= 48;
  uint32_t ga[16];
#pragma unroll
  for (int s = 0; s < 4; s++)
    ldg128(reinterpret_cast<const uint4*>(gp_.ga) + ((qw >> 4) - 3 * sel) * 128 + s * 32 + lane, ga[4 * s], ga[4 * s + 1], ga[4 * s + 2], ga[4 * s + 3]);
  uint4 gev0, gev1;
  asm volatile("ld.global.cg.v4.u32 {%0, %1, %2, %3}, [%4];" : "=r"(gev0.x), "=r"(gev0.y), "=r"(gev0.z), "=r"(gev0.w)
               : "l"(reinterpret_cast<const uint4*>(gp_.ge) + (b * 8 + wg * 4) * 64 + t));
  asm volatile("ld.global.cg.v4.u32 {%0, %1, %2, %3}, [%4];" : "=r"(gev1.x), "=r"(gev1.y), "=r"(gev1.z), "=r"(gev1.w)
               : "l"(reinterpret_cast<const uint4*>(gp_.ge) + (b * 8 + wg * 4) * 64 + 128 + t));
  if (tid == 0) {
    prefetch_map(&my);
    for (int i = 0; i < 12; i++) mbar_init(barY + 8 * i, 1);
    mbar_init(barA, 8);
    fence_bar_init();
    fence_async();
    for (int i = 0; i < E_WPRE; i++) {
      const int kc = (i >> 1) | ((i & 1) << 1);
      mbar_expect(barF + 8 * kc, 32768);
      tma_ld3<0>(R1 + kc * 32768, &mwf, barF + 8 * kc, 0, kc * 64, 0);
    }
    pdl_wait();
    for (int i = 0; i < 4; i++) {
      mbar_expect(barY + 8 * i, 16384);
      tma_ld5<0>(R0 + i * 16384, &my, barY + 8 * i, 0, 0, 2 * (i & 1) + (i >> 1), a, b);
    }
    for (int i = E_WPRE; i < (E_WLATE ? 2 : 4); i++) {
      const int kc = (i >> 1) | ((i & 1) << 1);
      mbar_expect(barF + 8 * kc, 32768);
      tma_ld3<0>(R1 + kc * 32768, &mwf, barF + 8 * kc, 0, kc * 64, 0);
    }
    prefetch_map(&mwo);
    prefetch_map(&mout);
  }
  uint32_t gs[32];
#pragma unroll
  for (int i = 0; i < 16; i++) {
    gs[i] = sel ? 0u : ga[i];
    gs[16 + i] = sel ? ga[i] : 0u;
  }
  __syncthreads();
  if (blockIdx.x == 125 && tid < 8) gp_.done[tid * 32] = 0;
  reg_fence(gs);
  uint32_t gp = R2 + wg * 4096 + (lane & 3) * 16;
  uint4 g0, g1;
  uint32_t fe[64];
  {
    float d0[32], d1[32], e[64];
    mbar_wait(barY + 8 * wg, 0);
    wg_fence();
#pragma unroll
    for (int k = 0; k < 8; k++)
      wgmma_rs_64<1, 1, 1>(d0, gs[4 * k], gs[4 * k + 1], gs[4 * k + 2], gs[4 * k + 3], mk_desc(R0 + wg * 16384, k * 2048, 0, 1024, 1), k);
    wg_commit();
    if (E_WLATE == 1 && t == 0) {
      mbar_expect(barF + 8 + 16 * wg, 32768);
      tma_ld3<0>(R1 + (1 + 2 * wg) * 32768, &mwf, barF + 8 + 16 * wg, 0, (1 + 2 * wg) * 64, 0);
    }
    wg_wait<0>();
    reg_fence(d0);
#pragma unroll
    for (int i = 0; i < 32; i++) d0[i] = gelu(d0[i]);
    store_tile_64(d0, R2 + wg * 16384, warp, lane);
    mbar_wait(barY + 8 * (2 + wg), 0);
    wg_fence();
#pragma unroll
    for (int k = 0; k < 8; k++)
      wgmma_rs_64<1, 1, 1>(d1, gs[4 * k], gs[4 * k + 1], gs[4 * k + 2], gs[4 * k + 3], mk_desc(R0 + wg * 16384, 32768 + k * 2048, 0, 1024, 1), k);
    wg_commit();
    if (E_WLATE == 2 && t == 0) {
      mbar_expect(barF + 8 + 16 * wg, 32768);
      tma_ld3<0>(R1 + (1 + 2 * wg) * 32768, &mwf, barF + 8 + 16 * wg, 0, (1 + 2 * wg) * 64, 0);
    }
    fence_async();
    mbar_wait(barF, 0);
    mbar_wait(barF + 16, 0);
    __syncthreads();
    wg_fence();
#pragma unroll
    for (int i = 0; i < (E_SPLIT ? 4 : 8); i++) {
      const int kc = (i >> 2) * 2, s = i & 3;
      wgmma_ss_128<1, 1, 0, 1>(e, mk_desc(R2, kc * 8192 + s * 32, 0, 1024, 1),
                               mk_desc(R1 + wg * 16384, kc * 32768 + s * 2048, 8192, 1024, 1), i);
    }
    wg_commit();
    if (tid == 128) {
      mbar_expect(barO, 32768);
      tma_ld3<0>(R0, &mwo, barO, 0, 0, 0);
    }
    wg_wait<1>();
    reg_fence(d1);
#pragma unroll
    for (int i = 0; i < 8 * E_SPLIT; i++) d1[i] = gelu(d1[i]);
    if (E_SPLIT) {
      reg_fence(d1);
      mbar_wait(barF + 16, 0);
      wg_fence();
#pragma unroll
      for (int s = 0; s < 4; s++)
        wgmma_ss_128<1, 1, 0, 1>(e, mk_desc(R2, 2 * 8192 + s * 32, 0, 1024, 1), mk_desc(R1 + wg * 16384, 2 * 32768 + s * 2048, 8192, 1024, 1), 1);
      wg_commit();
    }
#pragma unroll
    for (int i = 8 * E_SPLIT; i < 32; i++) d1[i] = gelu(d1[i]);
    store_tile_64(d1, R2 + wg * 16384 + 8192, warp, lane);
    fence_async();
    mbar_wait(barF + 8, 0);
    mbar_wait(barF + 24, 0);
    __syncthreads();
    if (tid == 128) {
      mbar_expect(barO + 8, 32768);
      tma_ld3<0>(R0 + 32768, &mwo, barO + 8, 0, 64, 0);
    }
    if (wg == 1) bar_sync(4, 256);
    wg_fence();
#pragma unroll
    for (int i = 0; i < 8; i++) {
      const int kc = (i >> 2) * 2 + 1, s = i & 3;
      wgmma_ss_128<1, 1, 0, 1>(e, mk_desc(R2, kc * 8192 + s * 32, 0, 1024, 1),
                               mk_desc(R1 + wg * 16384, kc * 32768 + s * 2048, 8192, 1024, 1), 1);
    }
    wg_commit();
    if (wg == 0) bar_arrive(4, 256);
    wg_wait<1>();
    if (lane == 0) mbar_arrive(barA);
    if (tid == 128) {
      mbar_wait(barA, 0);
      for (int kc = 2; kc < 4; kc++) {
        mbar_expect(barO + 8 * kc, 32768);
        tma_ld3<0>(R1 + (kc - 2) * 65536, &mwo, barO + 8 * kc, 0, kc * 64, 0);
      }
    }
    mbar_wait(barA, 0);
    asm volatile("st.shared.v4.u32 [%0], {%1, %2, %3, %4};" ::"r"(R2 + wg * 4096 + ((t * 16) ^ (wg * 512))), "r"(gev0.x), "r"(gev0.y), "r"(gev0.z), "r"(gev0.w) : "memory");
    asm volatile("st.shared.v4.u32 [%0], {%1, %2, %3, %4};" ::"r"(R2 + wg * 4096 + 2048 + ((t * 16) ^ (wg * 512))), "r"(gev1.x), "r"(gev1.y), "r"(gev1.z), "r"(gev1.w) : "memory");
    bar_sync(1 + wg, 128);
    g0 = lds128(gp);
    g1 = lds128(gp + 64);
    wg_wait<0>();
    reg_fence(e);
#pragma unroll
    for (int i = 0; i < 32; i++) fe[i] = pack2(e[2 * i], e[2 * i + 1]);
  }
  auto publish = [&]() {
    bar_sync(1 + wg, 128);
    const int row = warp * 16 + (lane & 7) + ((lane >> 3) & 1) * 8;
    const uint32_t xb = R1 + (wg == 0 ? 3 * 32768 : 32768 + 16384) + row * 128;
#pragma unroll
    for (int s = 0; s < 8; s++) {
      const int jj = 2 * s + (lane >> 4);
      stsm4(xb + (s >> 2) * 8192 + (((jj & 7) ^ (lane & 7)) << 4), fe[4 * s], fe[4 * s + 1], fe[4 * s + 2], fe[4 * s + 3]);
    }
    bar_arrive(5 + wg, 256);
  };
  if (wg == 1) publish();
  const uint32_t stg = R1 + 32768 + wg * 65536;
  const uint32_t w0 = sb + wg * 65536, w1 = sb + 32768 + wg * 98304, w2 = sb + 65536 - wg * 65536, w3 = sb + 131072 - wg * 98304;
  float acc[128];
  uint32_t j0[8], j1[8], j2[8], j3[8];
  uint4 h0, h1;
  if (E_LDS) {
    h0 = lds128(gp + 128);
    h1 = lds128(gp + 192);
  }
#define E_PAIR(J, K, F, G, BAR)             \
  if (!E_LDS) {                             \
    h0 = lds128(gp + (G) - 128);            \
    h1 = lds128(gp + (G) - 64);             \
  }                                         \
  joint_group(J, fe + (F), g0, g1);         \
  if (E_MID && ui == 0) mbar_wait(BAR, 0);  \
  joint_group(K, fe + (F) + 8, h0, h1);     \
  g0 = lds128(gp + (G));                    \
  g1 = lds128(gp + (G) + 64);
  {
    const int ui = 0;
    E_PAIR(j0, j1, 0, 256, barO + 16 * wg)
    mbar_wait(barO + 16 * wg, 0);
  }
#define E_MMA4(J, K, W, FIRSTK, G, NEXTBAR)                                                     \
  wg_fence();                                                                                   \
  wgmma_rs_256<1, 1, 1>(acc, J[0], J[1], J[2], J[3], mk_desc(W, 0, 8192, 1024, 1), FIRSTK);     \
  wgmma_rs_256<1, 1, 1>(acc, J[4], J[5], J[6], J[7], mk_desc(W, 2048, 8192, 1024, 1), 1);       \
  wgmma_rs_256<1, 1, 1>(acc, K[0], K[1], K[2], K[3], mk_desc(W, 4096, 8192, 1024, 1), 1);       \
  wgmma_rs_256<1, 1, 1>(acc, K[4], K[5], K[6], K[7], mk_desc(W, 6144, 8192, 1024, 1), 1);       \
  wg_commit();                                                                                  \
  if ((ui + wg == 0 ? E_EARLY0 : E_EARLY) == (G) && (ui < 3 || wg == 0)) bar_arrive(4 - wg, 256); \
  wg_wait<1>();                                                                                 \
  if (E_LDS) {                                                                                  \
    h0 = lds128(gp + 256 * (G) + 384);                                                          \
    h1 = lds128(gp + 256 * (G) + 448);                                                          \
  }                                                                                             \
  if (ui == 0) mbar_wait(NEXTBAR, 0);
  const uint32_t bo0 = barO + 16 * wg, bo2 = barO + 16 * (1 - wg);
#pragma unroll 1
  for (int ui = 0; ui < 4; ui++) {
    if (ui > 0 || wg == 1) bar_sync(3 + wg, 256);
    E_MMA4(j0, j1, w0, 0, 0, E_MID ? bo0 : bo0 + 8)
    E_PAIR(j2, j3, 16, 512, bo0 + 8)
    E_MMA4(j2, j3, w1, 1, 1, E_MID ? bo0 + 8 : bo2)
    if (ui == 0) {
      if (wg == 0) publish();
      bar_sync(6 - wg, 256);
      const int row = warp * 16 + (lane & 7) + ((lane >> 3) & 1) * 8;
      const uint32_t xb = R1 + (wg == 1 ? 3 * 32768 : 32768 + 16384) + row * 128;
#pragma unroll
      for (int s = 0; s < 8; s++) {
        const int jj = 2 * s + (lane >> 4);
        ldsm4(xb + (s >> 2) * 8192 + (((jj & 7) ^ (lane & 7)) << 4), fe[32 + 4 * s], fe[33 + 4 * s], fe[34 + 4 * s], fe[35 + 4 * s]);
      }
    }
    E_PAIR(j0, j1, 32, 768, bo2)
    E_MMA4(j0, j1, w2, 1, 2, E_MID ? bo2 : bo2 + 8)
    E_PAIR(j2, j3, 48, 1024, bo2 + 8)
    E_MMA4(j2, j3, w3, 1, 3, bo2 + 8)
    gp += 1024;
    if (ui < 3) {
      E_PAIR(j0, j1, 0, 256, bo2 + 8)
    }
    if (t == 0) bulk_wait_read<0>();
    wg_wait<0>();
    reg_fence(acc);
    bar_sync(1 + wg, 128);
    const uint32_t rb = stg + (warp * 16 + (lane & 7) + ((lane >> 3) & 1) * 8) * 128;
#pragma unroll
    for (int h = 0; h < 2; h++) {
#pragma unroll
      for (int j = 16 * h; j < 16 * h + 16; j += 2) {
        const int jj = j + (lane >> 4);
        stsm4(rb + (j >> 3) * 8192 + (((jj & 7) ^ (lane & 7)) << 4), pack2(acc[4 * j], acc[4 * j + 1]), pack2(acc[4 * j + 2], acc[4 * j + 3]),
              pack2(acc[4 * j + 4], acc[4 * j + 5]), pack2(acc[4 * j + 6], acc[4 * j + 7]));
      }
      const bool split = E_CHUNK == 2 || (E_CHUNK == 1 && ui == 3);
      if (h == 1 || split) {
        fence_async();
        bar_sync(1 + wg, 128);
        if (t == 0) {
          if (h == 1 && !split) tma_st5<1>(&mout, stg, 0, t0, 0, wg * 4 + ui, b);
          tma_st5<1>(&mout, stg + h * 16384, 0, t0, 2 * h, wg * 4 + ui, b);
          bulk_commit();
        }
      }
    }
  }
  if (t == 0) bulk_wait_read<0>();
}

typedef CUresult (*EncodeFn)(CUtensorMap*, CUtensorMapDataType, cuuint32_t, void*, const cuuint64_t*, const cuuint64_t*,
                             const cuuint32_t*, const cuuint32_t*, CUtensorMapInterleave, CUtensorMapSwizzle,
                             CUtensorMapL2promotion, CUtensorMapFloatOOBfill);

CUtensorMap make_map(EncodeFn fn, const void* base, int rank, const uint64_t* dims, const uint64_t* strides, const uint32_t* box,
                     CUtensorMapSwizzle swz) {
  CUtensorMap m;
  cuuint64_t gd[5], gs[4];
  cuuint32_t bx[5], es[5];
  for (int i = 0; i < rank; i++) { gd[i] = dims[i]; bx[i] = box[i]; es[i] = 1; }
  for (int i = 0; i + 1 < rank; i++) gs[i] = strides[i];
  fn(&m, CU_TENSOR_MAP_DATA_TYPE_BFLOAT16, rank, const_cast<void*>(base), gd, gs, bx, es, CU_TENSOR_MAP_INTERLEAVE_NONE, swz,
     CU_TENSOR_MAP_L2_PROMOTION_NONE, CU_TENSOR_MAP_FLOAT_OOB_FILL_NONE);
  return m;
}

template <typename... KArgs, typename... Args>
void launch(void (*k)(KArgs...), int grid, int block, int smem, bool pdl, Args... args) {
  cudaLaunchConfig_t c = {};
  c.gridDim = dim3(grid);
  c.blockDim = dim3(block);
  c.dynamicSmemBytes = smem;
  c.stream = cudaStreamPerThread;
  cudaLaunchAttribute at[1];
  at[0].id = cudaLaunchAttributeProgrammaticStreamSerialization;
  at[0].val.programmaticStreamSerializationAllowed = 1;
  c.attrs = at;
  c.numAttrs = pdl ? 1 : 0;
  cudaLaunchKernelEx(&c, k, args...);
}

}

static uint32_t h_plan[67] = {
    0x6108, 0x6109, 0x610a, 0x610b, 0x6101, 0x8008, 0x8109, 0x820a, 0x830b, 0x8401,
    0x8508, 0x8609, 0x870a, 0x3102, 0x880b, 0x8a08, 0x8b09, 0x8c0a, 0x8d02, 0x8e0b,
    0x8f08, 0x9009, 0x910a, 0x930b, 0x9408, 0x9509, 0x960a, 0x970b, 0x9808, 0x9909,
    0x9a0a, 0x9b0b, 0x61616115, 0x61616102, 0x83806107, 0x83836126, 0x8583610c, 0x8885614d, 0x8e8932b7, 0x949161c3,
    0x9794344c, 0x9b98354d, 0x0, 0x0, 0x0, 0x0, 0x0, 0x0, 0x6161ba98, 0x6161a981,
    0x6789981b, 0x67898b2a, 0x6892b2a9, 0x6892ba98, 0x6937ba98, 0x6937ba98, 0x39389c, 0x0, 0x4, 0x1fe0,
    0xec6a0c52, 0xac1, 0x2e5a9261, 0x194a, 0x9d, 0x9e, 0x9f,
};

extern "C" void kernel_launch(void* const* d_in, const int* in_sizes, int n_in, void* d_out, int out_size) {
  const __nv_bfloat16* x = (const __nv_bfloat16*)d_in[0];
  const __nv_bfloat16* w1 = (const __nv_bfloat16*)d_in[1];
  const __nv_bfloat16* w2 = (const __nv_bfloat16*)d_in[2];
  const __nv_bfloat16* g = (const __nv_bfloat16*)d_in[3];
  const __nv_bfloat16* wf = (const __nv_bfloat16*)d_in[4];
  const __nv_bfloat16* wgt = (const __nv_bfloat16*)d_in[5];
  const __nv_bfloat16* wo = (const __nv_bfloat16*)d_in[6];

  void* fp = nullptr;
  cudaDriverEntryPointQueryResult qr;
  cudaGetDriverEntryPoint("cuTensorMapEncodeTiled", &fp, cudaEnableDefault, &qr);
  EncodeFn fn = (EncodeFn)fp;
  void *X1, *W2, *Y1, *X2, *Y2;
  cudaGetSymbolAddress(&X1, g_X1);
  cudaGetSymbolAddress(&W2, g_W2);
  cudaGetSymbolAddress(&Y1, g_Y1);
  cudaGetSymbolAddress(&X2, g_X2);
  cudaGetSymbolAddress(&Y2, g_Y2);
  cudaFuncSetAttribute(k1, cudaFuncAttributeMaxDynamicSharedMemorySize, K1_SMEM);
  cudaFuncSetAttribute(k2, cudaFuncAttributeMaxDynamicSharedMemorySize, K2_SMEM);
  cudaFuncSetAttribute(kE, cudaFuncAttributeMaxDynamicSharedMemorySize, E_SMEM);
  if (ALIAS) {
    W2 = d_out;
    X2 = (char*)d_out + sizeof(g_W2);
    X1 = (char*)X2 - sizeof(g_X2);
    if (ALIAS == 1) Y2 = Y1;
  }
  const CUtensorMapSwizzle S128 = CU_TENSOR_MAP_SWIZZLE_128B;

  auto map_x = [&]() {
    uint64_t d[] = {64, 8000, 8, 2}, s[] = {1024, 128, 8000ull * 1024};
    uint32_t bx[] = {64, 56, 1, 1};
    return make_map(fn, x, 4, d, s, bx, S128);
  };
  auto map_w_in = [&](const __nv_bfloat16* w, int odd) {
    uint64_t d[] = {64, (uint64_t)(odd ? 15 : 16), 4, 256}, s[] = {2ull * 65536 * 2, 128, 512};
    uint32_t bx[] = {64, 16, 2, 1};
    return make_map(fn, w + (odd ? 65536 : 0), 4, d, s, bx, S128);
  };
  auto map_X_st = [&](void* p, int nb, int boxb) {
    uint64_t d[] = {64, 512, (uint64_t)(2 * nb)}, s[] = {2ull * nb * 128, 128};
    uint32_t bx[] = {64, C_PC ? C_PC : 64, (uint32_t)boxb};
    return make_map(fn, p, 3, d, s, bx, S128);
  };
  auto map_X1_st = [&]() {
    uint64_t d[] = {64, 512, 2, (uint64_t)NB1}, s[] = {2ull * NB1 * 128, (uint64_t)NB1 * 128, 128};
    uint32_t bx[] = {64, 16, 1, 1};
    return make_map(fn, X1, 4, d, s, bx, S128);
  };
  auto map_W_st = [&](void* p) {
    uint64_t d[] = {64, 512, 4, 64}, s[] = {32768, 8192, 128};
    uint32_t bx[] = {64, 64, 2, 1};
    return make_map(fn, p, 4, d, s, bx, S128);
  };
  auto map_W_ld = [&](void* p, uint32_t bd, uint32_t bf) {
    uint64_t d[] = {64, 64, 4, 512}, s[] = {128, 8192, 32768};
    uint32_t bx[] = {64, 32, bd, bf};
    return make_map(fn, p, 4, d, s, bx, S128);
  };
  auto map_Y_st = [&](void* p, int nb, int rows) {
    uint64_t d[] = {64, (uint64_t)(2 * nb), 64, 4}, s[] = {32768, 128, 8192};
    uint32_t bx[] = {64, (uint32_t)rows, 1, 1};
    return make_map(fn, p, 4, d, s, bx, S128);
  };
  auto map_Y_ld = [&](void* p, int nb, int boxc, int boxb) {
    uint64_t d[] = {64, 64, 4, (uint64_t)nb, 2}, s[] = {128, 8192, 32768, (uint64_t)nb * 32768};
    uint32_t bx[] = {64, 64, (uint32_t)boxc, (uint32_t)boxb, 1};
    return make_map(fn, p, 5, d, s, bx, S128);
  };
  auto map_wsq = [&](const __nv_bfloat16* w) {
    uint64_t d[] = {64, 256, 4}, s[] = {512, 128};
    uint32_t bx[] = {64, 64, 4};
    return make_map(fn, w, 3, d, s, bx, S128);
  };
  auto map_out = [&]() {
    uint64_t d[] = {64, 4000, 4, 8, 2}, s[] = {4096, 128, 512, 4000ull * 4096};
    uint32_t bx[] = {64, 64, 2, 1, 1};
    return make_map(fn, d_out, 5, d, s, bx, S128);
  };

  auto map_w_raw = [&](const __nv_bfloat16* w, int odd) {
    uint64_t d[] = {256, (uint64_t)(odd ? 15 : 16), 16, 16}, s[] = {2ull * 65536 * 2, 512, 8192};
    uint32_t bx[] = {64, 16, 4, 2};
    return make_map(fn, w + (odd ? 65536 : 0), 4, d, s, bx, S128);
  };
  Ptrs gp;
  cudaGetSymbolAddress((void**)&gp.done, g_done);
  cudaGetSymbolAddress((void**)&gp.ge, g_ge);
  cudaGetSymbolAddress((void**)&gp.img, c_img);
  cudaGetSymbolAddress((void**)&gp.ga, c_ga);
  K1Maps g1;
  memcpy(&g1.p, h_plan, sizeof(Plan));
  g1.x = map_x();
  g1.we = map_w_raw(w1, 0);
  g1.wo = map_w_raw(w1, 1);
  g1.xs = map_X1_st();
  g1.y = map_Y_st(Y1, NB1, NB1 / G_EPI);
  g1.w2e = map_w_in(w2, 0);
  g1.w2o = map_w_in(w2, 1);
  g1.w2s = map_W_st(W2);
  for (int s = 0; s < 32; s++) {
    const int k = s < 26 ? s >> 1 : 13 + (s - 26) % 3;
    g1.slot[s] = g_off(g_slot(s)) / 16;
    g1.src[s] = ((k >> 1) * 256 + (k & 1) * 2 + (s < 26 ? (s & 1) * 4 : s >= 29)) * (G_ST / 2);
    g1.dep[s] = s < 3 ? 8 * h_plan[64 + s] : 1536 + 8 * (s - g_depth(s));
  }
  launch(k1, 132, 384, K1_SMEM, false, gp, (const char*)X1, (const char*)w1, g1, g, wgt);
  K2Maps g2;
  g2.y = map_Y_ld(Y1, NB1, 1, 1);
  g2.xs = map_X_st(X2, NB2, 1);
  g2.w = map_W_ld(W2, 1, 2);
  g2.y2 = map_Y_st(Y2, NB2, 168 / H_EPI);
  launch(k2, 128, 512, K2_SMEM, true, gp, (const char*)X2, g2, wf, wo);
  launch(kE, 126, 256, E_SMEM, true, gp, map_Y_ld(Y2, NB2, 1, 2), map_wsq(wf), map_wsq(wo), map_out());
}
```

```cpp
#include <cuda_runtime.h>
#include <cuda_bf16.h>
#include <cuda.h>
#include <stdint.h>
#include <string.h>
#include <type_traits>

#define ALIAS 1
#define W_SHIFT 1
namespace {

constexpr int NB1 = 168;
constexpr int NB2 = 84;

__device__ __align__(1024) __nv_bfloat16 g_X1[8 * 64 * 2 * NB1 * 64];
__device__ __align__(1024) __nv_bfloat16 g_W2[8 * 64 * 4 * 64 * 64];
__device__ __align__(1024) __nv_bfloat16 g_Y1[2 * NB1 * 4 * 64 * 64];
__device__ __align__(1024) __nv_bfloat16 g_X2[8 * 64 * 2 * NB2 * 64];
__device__ __align__(1024) __nv_bfloat16 g_Y2[2 * NB2 * 4 * 64 * 64];
__device__ __align__(1024) float g_ge[16 * 256];

__device__ __forceinline__ uint32_t s2u(const void* p) { return (uint32_t)__cvta_generic_to_shared(p); }
__device__ __forceinline__ void mbar_init(uint32_t b, int c) {
  asm volatile("mbarrier.init.shared::cta.b64 [%0], %1;" ::"r"(b), "r"(c) : "memory");
}
__device__ __forceinline__ void mbar_expect(uint32_t b, int bytes) {
  asm volatile("mbarrier.arrive.expect_tx.shared::cta.b64 _, [%0], %1;" ::"r"(b), "r"(bytes) : "memory");
}
__device__ __forceinline__ void mbar_arrive(uint32_t b) {
  asm volatile("mbarrier.arrive.shared::cta.b64 _, [%0];" ::"r"(b) : "memory");
}
__device__ __forceinline__ void mbar_arrive_cta(uint32_t b, uint32_t cta) {
  asm volatile("{\n.reg .b32 r;\nmapa.shared::cluster.u32 r, %0, %1;\nmbarrier.arrive.shared::cluster.b64 _, [r];\n}" ::"r"(b), "r"(cta) : "memory");
}
__device__ __forceinline__ void mbar_wait(uint32_t b, int ph) {
  asm volatile(
      "{\n.reg .pred p;\n.reg .u32 n;\n"
      "mov.u32 n, 0;\n"
      "MBW_LOOP:\n"
      "mbarrier.try_wait.parity.shared::cta.b64 p, [%0], %1;\n"
      "@p bra MBW_DONE;\n"
      "add.u32 n, n, 1;\n"
      "setp.lt.u32 p, n, 1048576;\n"
      "@p bra MBW_LOOP;\n"
      "MBW_DONE:\n}" ::"r"(b), "r"(ph) : "memory");
}
__device__ __forceinline__ void fence_bar_init() { asm volatile("fence.mbarrier_init.release.cluster;" ::: "memory"); }
__device__ __forceinline__ void fence_async() { asm volatile("fence.proxy.async.shared::cta;" ::: "memory"); }
__device__ __forceinline__ void bar_sync(int id, int n) { asm volatile("bar.sync %0, %1;" ::"r"(id), "r"(n) : "memory"); }
__device__ __forceinline__ void bar_arrive(int id, int n) { asm volatile("bar.arrive %0, %1;" ::"r"(id), "r"(n) : "memory"); }
__device__ __forceinline__ void pdl_wait() { asm volatile("griddepcontrol.wait;" ::: "memory"); }
__device__ __forceinline__ void pdl_launch() { asm volatile("griddepcontrol.launch_dependents;" ::: "memory"); }
__device__ __forceinline__ void prefetch_map(const CUtensorMap* m) {
  asm volatile("prefetch.tensormap [%0];" ::"l"(m) : "memory");
}
template <int P> __device__ __forceinline__ uint64_t policy() {
  uint64_t p;
  asm("createpolicy.fractional.L2::evict_first.b64 %0, 1.0;" : "=l"(p));
  return p;
}
template <int P> __device__ __forceinline__ void tma_ld3(uint32_t dst, const CUtensorMap* m, uint32_t bar, int c0, int c1, int c2) {
  if constexpr (P == 0)
    asm volatile("cp.async.bulk.tensor.3d.shared::cluster.global.mbarrier::complete_tx::bytes [%0], [%1, {%3, %4, %5}], [%2];"
                 ::"r"(dst), "l"(m), "r"(bar), "r"(c0), "r"(c1), "r"(c2) : "memory");
  else
    asm volatile("cp.async.bulk.tensor.3d.shared::cluster.global.mbarrier::complete_tx::bytes.L2::cache_hint [%0], [%1, {%3, %4, %5}], [%2], %6;"
                 ::"r"(dst), "l"(m), "r"(bar), "r"(c0), "r"(c1), "r"(c2), "l"(policy<P>()) : "memory");
}
template <int P> __device__ __forceinline__ void tma_ld3mc(uint32_t dst, const CUtensorMap* m, uint32_t bar, int c0, int c1, int c2) {
  if constexpr (P == 0)
    asm volatile("cp.async.bulk.tensor.3d.shared::cluster.global.mbarrier::complete_tx::bytes.multicast::cluster [%0], [%1, {%3, %4, %5}], [%2], %6;"
                 ::"r"(dst), "l"(m), "r"(bar), "r"(c0), "r"(c1), "r"(c2), "h"((uint16_t)3) : "memory");
  else
    asm volatile("cp.async.bulk.tensor.3d.shared::cluster.global.mbarrier::complete_tx::bytes.multicast::cluster.L2::cache_hint [%0], [%1, {%3, %4, %5}], [%2], %6, %7;"
                 ::"r"(dst), "l"(m), "r"(bar), "r"(c0), "r"(c1), "r"(c2), "h"((uint16_t)3), "l"(policy<P>()) : "memory");
}
template <int P> __device__ __forceinline__ void tma_ld4(uint32_t dst, const CUtensorMap* m, uint32_t bar, int c0, int c1, int c2, int c3) {
  if constexpr (P == 0)
    asm volatile("cp.async.bulk.tensor.4d.shared::cluster.global.mbarrier::complete_tx::bytes [%0], [%1, {%3, %4, %5, %6}], [%2];"
                 ::"r"(dst), "l"(m), "r"(bar), "r"(c0), "r"(c1), "r"(c2), "r"(c3) : "memory");
  else
    asm volatile("cp.async.bulk.tensor.4d.shared::cluster.global.mbarrier::complete_tx::bytes.L2::cache_hint [%0], [%1, {%3, %4, %5, %6}], [%2], %7;"
                 ::"r"(dst), "l"(m), "r"(bar), "r"(c0), "r"(c1), "r"(c2), "r"(c3), "l"(policy<P>()) : "memory");
}
template <int P> __device__ __forceinline__ void tma_ld4mc(uint32_t dst, const CUtensorMap* m, uint32_t bar, int c0, int c1, int c2, int c3) {
  if constexpr (P == 0)
    asm volatile("cp.async.bulk.tensor.4d.shared::cluster.global.mbarrier::complete_tx::bytes.multicast::cluster [%0], [%1, {%3, %4, %5, %6}], [%2], %7;"
                 ::"r"(dst), "l"(m), "r"(bar), "r"(c0), "r"(c1), "r"(c2), "r"(c3), "h"((uint16_t)3) : "memory");
  else
    asm volatile("cp.async.bulk.tensor.4d.shared::cluster.global.mbarrier::complete_tx::bytes.multicast::cluster.L2::cache_hint [%0], [%1, {%3, %4, %5, %6}], [%2], %7, %8;"
                 ::"r"(dst), "l"(m), "r"(bar), "r"(c0), "r"(c1), "r"(c2), "r"(c3), "h"((uint16_t)3), "l"(policy<P>()) : "memory");
}
template <int P> __device__ __forceinline__ void tma_ld5(uint32_t dst, const CUtensorMap* m, uint32_t bar, int c0, int c1, int c2, int c3, int c4) {
  if constexpr (P == 0)
    asm volatile("cp.async.bulk.tensor.5d.shared::cluster.global.mbarrier::complete_tx::bytes [%0], [%1, {%3, %4, %5, %6, %7}], [%2];"
                 ::"r"(dst), "l"(m), "r"(bar), "r"(c0), "r"(c1), "r"(c2), "r"(c3), "r"(c4) : "memory");
  else
    asm volatile("cp.async.bulk.tensor.5d.shared::cluster.global.mbarrier::complete_tx::bytes.L2::cache_hint [%0], [%1, {%3, %4, %5, %6, %7}], [%2], %8;"
                 ::"r"(dst), "l"(m), "r"(bar), "r"(c0), "r"(c1), "r"(c2), "r"(c3), "r"(c4), "l"(policy<P>()) : "memory");
}
template <int P> __device__ __forceinline__ void tma_st3(const CUtensorMap* m, uint32_t src, int c0, int c1, int c2) {
  if constexpr (P == 0)
    asm volatile("cp.async.bulk.tensor.3d.global.shared::cta.bulk_group [%0, {%2, %3, %4}], [%1];" ::"l"(m), "r"(src), "r"(c0), "r"(c1), "r"(c2) : "memory");
  else
    asm volatile("cp.async.bulk.tensor.3d.global.shared::cta.bulk_group.L2::cache_hint [%0, {%2, %3, %4}], [%1], %5;" ::"l"(m), "r"(src), "r"(c0), "r"(c1), "r"(c2), "l"(policy<P>()) : "memory");
}
template <int P> __device__ __forceinline__ void tma_st4(const CUtensorMap* m, uint32_t src, int c0, int c1, int c2, int c3) {
  if constexpr (P == 0)
    asm volatile("cp.async.bulk.tensor.4d.global.shared::cta.bulk_group [%0, {%2, %3, %4, %5}], [%1];" ::"l"(m), "r"(src), "r"(c0), "r"(c1), "r"(c2), "r"(c3) : "memory");
  else
    asm volatile("cp.async.bulk.tensor.4d.global.shared::cta.bulk_group.L2::cache_hint [%0, {%2, %3, %4, %5}], [%1], %6;" ::"l"(m), "r"(src), "r"(c0), "r"(c1), "r"(c2), "r"(c3), "l"(policy<P>()) : "memory");
}
template <int P> __device__ __forceinline__ void tma_st5(const CUtensorMap* m, uint32_t src, int c0, int c1, int c2, int c3, int c4) {
  if constexpr (P == 0)
    asm volatile("cp.async.bulk.tensor.5d.global.shared::cta.bulk_group [%0, {%2, %3, %4, %5, %6}], [%1];" ::"l"(m), "r"(src), "r"(c0), "r"(c1), "r"(c2), "r"(c3), "r"(c4) : "memory");
  else
    asm volatile("cp.async.bulk.tensor.5d.global.shared::cta.bulk_group.L2::cache_hint [%0, {%2, %3, %4, %5, %6}], [%1], %7;" ::"l"(m), "r"(src), "r"(c0), "r"(c1), "r"(c2), "r"(c3), "r"(c4), "l"(policy<P>()) : "memory");
}
__device__ __forceinline__ void bulk_commit() { asm volatile("cp.async.bulk.commit_group;" ::: "memory"); }
template <int N> __device__ __forceinline__ void bulk_wait_read() { asm volatile("cp.async.bulk.wait_group.read %0;" ::"n"(N) : "memory"); }
__device__ __forceinline__ void wg_fence() { asm volatile("wgmma.fence.sync.aligned;" ::: "memory"); }
__device__ __forceinline__ void wg_commit() { asm volatile("wgmma.commit_group.sync.aligned;" ::: "memory"); }
template <int N> __device__ __forceinline__ void wg_wait() { asm volatile("wgmma.wait_group.sync.aligned %0;" ::"n"(N) : "memory"); }
template <int R> __device__ __forceinline__ void reg_fence(float (&d)[R]) {
#pragma unroll
  for (int i = 0; i < R; i++) asm volatile("" : "+f"(d[i])::"memory");
}
template <int R> __device__ __forceinline__ void reg_fence(uint32_t (&d)[R]) {
#pragma unroll
  for (int i = 0; i < R; i++) asm volatile("" : "+r"(d[i])::"memory");
}
__device__ __forceinline__ void stsm4(uint32_t a, uint32_t r0, uint32_t r1, uint32_t r2, uint32_t r3) {
  asm volatile("stmatrix.sync.aligned.m8n8.x4.shared.b16 [%0], {%1, %2, %3, %4};" ::"r"(a), "r"(r0), "r"(r1), "r"(r2), "r"(r3) : "memory");
}
__device__ __forceinline__ void stsm4t(uint32_t a, uint32_t r0, uint32_t r1, uint32_t r2, uint32_t r3) {
  asm volatile("stmatrix.sync.aligned.m8n8.x4.trans.shared.b16 [%0], {%1, %2, %3, %4};" ::"r"(a), "r"(r0), "r"(r1), "r"(r2), "r"(r3) : "memory");
}
__device__ __forceinline__ void ldsm4(uint32_t a, uint32_t& r0, uint32_t& r1, uint32_t& r2, uint32_t& r3) {
  asm volatile("ldmatrix.sync.aligned.m8n8.x4.shared.b16 {%0, %1, %2, %3}, [%4];" : "=r"(r0), "=r"(r1), "=r"(r2), "=r"(r3) : "r"(a) : "memory");
}
__device__ __forceinline__ void ldsm4t(uint32_t a, uint32_t& r0, uint32_t& r1, uint32_t& r2, uint32_t& r3) {
  asm volatile("ldmatrix.sync.aligned.m8n8.x4.trans.shared.b16 {%0, %1, %2, %3}, [%4];" : "=r"(r0), "=r"(r1), "=r"(r2), "=r"(r3) : "r"(a) : "memory");
}
__device__ __forceinline__ void ldg128(const uint4* p, uint32_t& a, uint32_t& b, uint32_t& c, uint32_t& d) {
  asm volatile("ld.global.nc.v4.u32 {%0, %1, %2, %3}, [%4];" : "=r"(a), "=r"(b), "=r"(c), "=r"(d) : "l"(p));
}
__device__ __forceinline__ uint32_t pack2(float lo, float hi) {
  uint32_t r;
  asm("cvt.rn.bf16x2.f32 %0, %1, %2;" : "=r"(r) : "f"(hi), "f"(lo));
  return r;
}
__device__ __forceinline__ float tanh_f32(float x) {
  float y;
  asm("tanh.approx.f32 %0, %1;" : "=f"(y) : "f"(x));
  return y;
}
__device__ __forceinline__ float gelu(float hx) {
  const float u = hx * fmaf(hx * hx, 8.0f * 0.044715f * 0.7978845608028654f, 2.0f * 0.7978845608028654f);
  return fmaf(hx, tanh_f32(u), hx);
}
__device__ __forceinline__ uint64_t mk_desc4(uint32_t addr4, uint32_t lbo, uint32_t sbo, uint32_t swz) {
  const uint32_t lo = addr4 + ((lbo >> 4) << 16), hi = (sbo >> 4) | (swz << 30);
  uint64_t d;
  asm("mov.b64 %0, {%1, %2};" : "=l"(d) : "r"(lo), "r"(hi));
  return d;
}
#define mk_desc(base, off, lbo, sbo, swz) mk_desc4((((base) & 0x3FFFF) >> 4) + ((off) >> 4), lbo, sbo, swz)

template <int SA, int SB, int TA, int TB>
__device__ __forceinline__ void wgmma_ss_48(float (&d)[24], uint64_t da, uint64_t db, int sd) {
  asm volatile("{\n.reg .pred p;\nsetp.ne.b32 p, %26, 0;\n"
      "wgmma.mma_async.sync.aligned.m64n48k16.f32.bf16.bf16 {"
      "%0, %1, %2, %3, %4, %5, %6, %7, %8, %9, %10, %11, %12, %13, %14, %15, %16, %17, %18, %19, %20, %21, %22, %23"
      "}, %24, %25, p, %27, %28, %29, %30;\n}\n"
      : "+f"(d[0]), "+f"(d[1]), "+f"(d[2]), "+f"(d[3]), "+f"(d[4]), "+f"(d[5]), "+f"(d[6]), "+f"(d[7]), "+f"(d[8]),
        "+f"(d[9]), "+f"(d[10]), "+f"(d[11]), "+f"(d[12]), "+f"(d[13]), "+f"(d[14]), "+f"(d[15]), "+f"(d[16]),
        "+f"(d[17]), "+f"(d[18]), "+f"(d[19]), "+f"(d[20]), "+f"(d[21]), "+f"(d[22]), "+f"(d[23])
      : "l"(da), "l"(db), "r"(sd), "n"(SA), "n"(SB), "n"(TA), "n"(TB));
}
template <int SA, int SB, int TA, int TB>
__device__ __forceinline__ void wgmma_ss_128(float (&d)[64], uint64_t da, uint64_t db, int sd) {
  asm volatile("{\n.reg .pred p;\nsetp.ne.b32 p, %66, 0;\n"
      "wgmma.mma_async.sync.aligned.m64n128k16.f32.bf16.bf16 {"
      "%0, %1, %2, %3, %4, %5, %6, %7, %8, %9, %10, %11, %12, %13, %14, %15, %16, %17, %18, %19, %20, %21, %22, %23, "
      "%24, %25, %26, %27, %28, %29, %30, %31, %32, %33, %34, %35, %36, %37, %38, %39, %40, %41, %42, %43, %44, %45, "
      "%46, %47, %48, %49, %50, %51, %52, %53, %54, %55, %56, %57, %58, %59, %60, %61, %62, %63"
      "}, %64, %65, p, %67, %68, %69, %70;\n}\n"
      : "+f"(d[0]), "+f"(d[1]), "+f"(d[2]), "+f"(d[3]), "+f"(d[4]), "+f"(d[5]), "+f"(d[6]), "+f"(d[7]), "+f"(d[8]),
        "+f"(d[9]), "+f"(d[10]), "+f"(d[11]), "+f"(d[12]), "+f"(d[13]), "+f"(d[14]), "+f"(d[15]), "+f"(d[16]),
        "+f"(d[17]), "+f"(d[18]), "+f"(d[19]), "+f"(d[20]), "+f"(d[21]), "+f"(d[22]), "+f"(d[23]), "+f"(d[24]),
        "+f"(d[25]), "+f"(d[26]), "+f"(d[27]), "+f"(d[28]), "+f"(d[29]), "+f"(d[30]), "+f"(d[31]), "+f"(d[32]),
        "+f"(d[33]), "+f"(d[34]), "+f"(d[35]), "+f"(d[36]), "+f"(d[37]), "+f"(d[38]), "+f"(d[39]), "+f"(d[40]),
        "+f"(d[41]), "+f"(d[42]), "+f"(d[43]), "+f"(d[44]), "+f"(d[45]), "+f"(d[46]), "+f"(d[47]), "+f"(d[48]),
        "+f"(d[49]), "+f"(d[50]), "+f"(d[51]), "+f"(d[52]), "+f"(d[53]), "+f"(d[54]), "+f"(d[55]), "+f"(d[56]),
        "+f"(d[57]), "+f"(d[58]), "+f"(d[59]), "+f"(d[60]), "+f"(d[61]), "+f"(d[62]), "+f"(d[63])
      : "l"(da), "l"(db), "r"(sd), "n"(SA), "n"(SB), "n"(TA), "n"(TB));
}
template <int SA, int SB, int TA, int TB>
__device__ __forceinline__ void wgmma_ss_168(float (&d)[84], uint64_t da, uint64_t db, int sd) {
  asm volatile("{\n.reg .pred p;\nsetp.ne.b32 p, %86, 0;\n"
      "wgmma.mma_async.sync.aligned.m64n168k16.f32.bf16.bf16 {"
      "%0, %1, %2, %3, %4, %5, %6, %7, %8, %9, %10, %11, %12, %13, %14, %15, %16, %17, %18, %19, %20, %21, %22, %23, "
      "%24, %25, %26, %27, %28, %29, %30, %31, %32, %33, %34, %35, %36, %37, %38, %39, %40, %41, %42, %43, %44, %45, "
      "%46, %47, %48, %49, %50, %51, %52, %53, %54, %55, %56, %57, %58, %59, %60, %61, %62, %63, %64, %65, %66, %67, "
      "%68, %69, %70, %71, %72, %73, %74, %75, %76, %77, %78, %79, %80, %81, %82, %83"
      "}, %84, %85, p, %87, %88, %89, %90;\n}\n"
      : "+f"(d[0]), "+f"(d[1]), "+f"(d[2]), "+f"(d[3]), "+f"(d[4]), "+f"(d[5]), "+f"(d[6]), "+f"(d[7]), "+f"(d[8]),
        "+f"(d[9]), "+f"(d[10]), "+f"(d[11]), "+f"(d[12]), "+f"(d[13]), "+f"(d[14]), "+f"(d[15]), "+f"(d[16]),
        "+f"(d[17]), "+f"(d[18]), "+f"(d[19]), "+f"(d[20]), "+f"(d[21]), "+f"(d[22]), "+f"(d[23]), "+f"(d[24]),
        "+f"(d[25]), "+f"(d[26]), "+f"(d[27]), "+f"(d[28]), "+f"(d[29]), "+f"(d[30]), "+f"(d[31]), "+f"(d[32]),
        "+f"(d[33]), "+f"(d[34]), "+f"(d[35]), "+f"(d[36]), "+f"(d[37]), "+f"(d[38]), "+f"(d[39]), "+f"(d[40]),
        "+f"(d[41]), "+f"(d[42]), "+f"(d[43]), "+f"(d[44]), "+f"(d[45]), "+f"(d[46]), "+f"(d[47]), "+f"(d[48]),
        "+f"(d[49]), "+f"(d[50]), "+f"(d[51]), "+f"(d[52]), "+f"(d[53]), "+f"(d[54]), "+f"(d[55]), "+f"(d[56]),
        "+f"(d[57]), "+f"(d[58]), "+f"(d[59]), "+f"(d[60]), "+f"(d[61]), "+f"(d[62]), "+f"(d[63]), "+f"(d[64]),
        "+f"(d[65]), "+f"(d[66]), "+f"(d[67]), "+f"(d[68]), "+f"(d[69]), "+f"(d[70]), "+f"(d[71]), "+f"(d[72]),
        "+f"(d[73]), "+f"(d[74]), "+f"(d[75]), "+f"(d[76]), "+f"(d[77]), "+f"(d[78]), "+f"(d[79]), "+f"(d[80]),
        "+f"(d[81]), "+f"(d[82]), "+f"(d[83])
      : "l"(da), "l"(db), "r"(sd), "n"(SA), "n"(SB), "n"(TA), "n"(TB));
}
template <int SA, int SB, int TB>
__device__ __forceinline__ void wgmma_rs_32(float (&d)[16], uint32_t a0, uint32_t a1, uint32_t a2, uint32_t a3, uint64_t db, int sd) {
  asm volatile("{\n.reg .pred p;\nsetp.ne.b32 p, %21, 0;\n"
      "wgmma.mma_async.sync.aligned.m64n32k16.f32.bf16.bf16 {"
      "%0, %1, %2, %3, %4, %5, %6, %7, %8, %9, %10, %11, %12, %13, %14, %15"
      "}, {%16, %17, %18, %19}, %20, p, %22, %23, %24;\n}\n"
      : "+f"(d[0]), "+f"(d[1]), "+f"(d[2]), "+f"(d[3]), "+f"(d[4]), "+f"(d[5]), "+f"(d[6]), "+f"(d[7]), "+f"(d[8]),
        "+f"(d[9]), "+f"(d[10]), "+f"(d[11]), "+f"(d[12]), "+f"(d[13]), "+f"(d[14]), "+f"(d[15])
      : "r"(a0), "r"(a1), "r"(a2), "r"(a3), "l"(db), "r"(sd), "n"(SA), "n"(SB), "n"(TB));
}
template <int SA, int SB, int TB>
__device__ __forceinline__ void wgmma_rs_64(float (&d)[32], uint32_t a0, uint32_t a1, uint32_t a2, uint32_t a3, uint64_t db, int sd) {
  asm volatile("{\n.reg .pred p;\nsetp.ne.b32 p, %37, 0;\n"
      "wgmma.mma_async.sync.aligned.m64n64k16.f32.bf16.bf16 {"
      "%0, %1, %2, %3, %4, %5, %6, %7, %8, %9, %10, %11, %12, %13, %14, %15, %16, %17, %18, %19, %20, %21, %22, %23, "
      "%24, %25, %26, %27, %28, %29, %30, %31"
      "}, {%32, %33, %34, %35}, %36, p, %38, %39, %40;\n}\n"
      : "+f"(d[0]), "+f"(d[1]), "+f"(d[2]), "+f"(d[3]), "+f"(d[4]), "+f"(d[5]), "+f"(d[6]), "+f"(d[7]), "+f"(d[8]),
        "+f"(d[9]), "+f"(d[10]), "+f"(d[11]), "+f"(d[12]), "+f"(d[13]), "+f"(d[14]), "+f"(d[15]), "+f"(d[16]),
        "+f"(d[17]), "+f"(d[18]), "+f"(d[19]), "+f"(d[20]), "+f"(d[21]), "+f"(d[22]), "+f"(d[23]), "+f"(d[24]),
        "+f"(d[25]), "+f"(d[26]), "+f"(d[27]), "+f"(d[28]), "+f"(d[29]), "+f"(d[30]), "+f"(d[31])
      : "r"(a0), "r"(a1), "r"(a2), "r"(a3), "l"(db), "r"(sd), "n"(SA), "n"(SB), "n"(TB));
}
template <int SA, int SB, int TB>
__device__ __forceinline__ void wgmma_rs_128(float (&d)[64], uint32_t a0, uint32_t a1, uint32_t a2, uint32_t a3, uint64_t db, int sd) {
  asm volatile("{\n.reg .pred p;\nsetp.ne.b32 p, %69, 0;\n"
      "wgmma.mma_async.sync.aligned.m64n128k16.f32.bf16.bf16 {"
      "%0, %1, %2, %3, %4, %5, %6, %7, %8, %9, %10, %11, %12, %13, %14, %15, %16, %17, %18, %19, %20, %21, %22, %23, "
      "%24, %25, %26, %27, %28, %29, %30, %31, %32, %33, %34, %35, %36, %37, %38, %39, %40, %41, %42, %43, %44, %45, "
      "%46, %47, %48, %49, %50, %51, %52, %53, %54, %55, %56, %57, %58, %59, %60, %61, %62, %63"
      "}, {%64, %65, %66, %67}, %68, p, %70, %71, %72;\n}\n"
      : "+f"(d[0]), "+f"(d[1]), "+f"(d[2]), "+f"(d[3]), "+f"(d[4]), "+f"(d[5]), "+f"(d[6]), "+f"(d[7]), "+f"(d[8]),
        "+f"(d[9]), "+f"(d[10]), "+f"(d[11]), "+f"(d[12]), "+f"(d[13]), "+f"(d[14]), "+f"(d[15]), "+f"(d[16]),
        "+f"(d[17]), "+f"(d[18]), "+f"(d[19]), "+f"(d[20]), "+f"(d[21]), "+f"(d[22]), "+f"(d[23]), "+f"(d[24]),
        "+f"(d[25]), "+f"(d[26]), "+f"(d[27]), "+f"(d[28]), "+f"(d[29]), "+f"(d[30]), "+f"(d[31]), "+f"(d[32]),
        "+f"(d[33]), "+f"(d[34]), "+f"(d[35]), "+f"(d[36]), "+f"(d[37]), "+f"(d[38]), "+f"(d[39]), "+f"(d[40]),
        "+f"(d[41]), "+f"(d[42]), "+f"(d[43]), "+f"(d[44]), "+f"(d[45]), "+f"(d[46]), "+f"(d[47]), "+f"(d[48]),
        "+f"(d[49]), "+f"(d[50]), "+f"(d[51]), "+f"(d[52]), "+f"(d[53]), "+f"(d[54]), "+f"(d[55]), "+f"(d[56]),
        "+f"(d[57]), "+f"(d[58]), "+f"(d[59]), "+f"(d[60]), "+f"(d[61]), "+f"(d[62]), "+f"(d[63])
      : "r"(a0), "r"(a1), "r"(a2), "r"(a3), "l"(db), "r"(sd), "n"(SA), "n"(SB), "n"(TB));
}
template <int SA, int SB, int TB>
__device__ __forceinline__ void wgmma_rs_168(float (&d)[84], uint32_t a0, uint32_t a1, uint32_t a2, uint32_t a3, uint64_t db, int sd) {
  asm volatile("{\n.reg .pred p;\nsetp.ne.b32 p, %89, 0;\n"
      "wgmma.mma_async.sync.aligned.m64n168k16.f32.bf16.bf16 {"
      "%0, %1, %2, %3, %4, %5, %6, %7, %8, %9, %10, %11, %12, %13, %14, %15, %16, %17, %18, %19, %20, %21, %22, %23, "
      "%24, %25, %26, %27, %28, %29, %30, %31, %32, %33, %34, %35, %36, %37, %38, %39, %40, %41, %42, %43, %44, %45, "
      "%46, %47, %48, %49, %50, %51, %52, %53, %54, %55, %56, %57, %58, %59, %60, %61, %62, %63, %64, %65, %66, %67, "
      "%68, %69, %70, %71, %72, %73, %74, %75, %76, %77, %78, %79, %80, %81, %82, %83"
      "}, {%84, %85, %86, %87}, %88, p, %90, %91, %92;\n}\n"
      : "+f"(d[0]), "+f"(d[1]), "+f"(d[2]), "+f"(d[3]), "+f"(d[4]), "+f"(d[5]), "+f"(d[6]), "+f"(d[7]), "+f"(d[8]),
        "+f"(d[9]), "+f"(d[10]), "+f"(d[11]), "+f"(d[12]), "+f"(d[13]), "+f"(d[14]), "+f"(d[15]), "+f"(d[16]),
        "+f"(d[17]), "+f"(d[18]), "+f"(d[19]), "+f"(d[20]), "+f"(d[21]), "+f"(d[22]), "+f"(d[23]), "+f"(d[24]),
        "+f"(d[25]), "+f"(d[26]), "+f"(d[27]), "+f"(d[28]), "+f"(d[29]), "+f"(d[30]), "+f"(d[31]), "+f"(d[32]),
        "+f"(d[33]), "+f"(d[34]), "+f"(d[35]), "+f"(d[36]), "+f"(d[37]), "+f"(d[38]), "+f"(d[39]), "+f"(d[40]),
        "+f"(d[41]), "+f"(d[42]), "+f"(d[43]), "+f"(d[44]), "+f"(d[45]), "+f"(d[46]), "+f"(d[47]), "+f"(d[48]),
        "+f"(d[49]), "+f"(d[50]), "+f"(d[51]), "+f"(d[52]), "+f"(d[53]), "+f"(d[54]), "+f"(d[55]), "+f"(d[56]),
        "+f"(d[57]), "+f"(d[58]), "+f"(d[59]), "+f"(d[60]), "+f"(d[61]), "+f"(d[62]), "+f"(d[63]), "+f"(d[64]),
        "+f"(d[65]), "+f"(d[66]), "+f"(d[67]), "+f"(d[68]), "+f"(d[69]), "+f"(d[70]), "+f"(d[71]), "+f"(d[72]),
        "+f"(d[73]), "+f"(d[74]), "+f"(d[75]), "+f"(d[76]), "+f"(d[77]), "+f"(d[78]), "+f"(d[79]), "+f"(d[80]),
        "+f"(d[81]), "+f"(d[82]), "+f"(d[83])
      : "r"(a0), "r"(a1), "r"(a2), "r"(a3), "l"(db), "r"(sd), "n"(SA), "n"(SB), "n"(TB));
}
template <int SA, int SB, int TB>
__device__ __forceinline__ void wgmma_rs_256(float (&d)[128], uint32_t a0, uint32_t a1, uint32_t a2, uint32_t a3, uint64_t db, int sd) {
  asm volatile("{\n.reg .pred p;\nsetp.ne.b32 p, %133, 0;\n"
      "wgmma.mma_async.sync.aligned.m64n256k16.f32.bf16.bf16 {"
      "%0, %1, %2, %3, %4, %5, %6, %7, %8, %9, %10, %11, %12, %13, %14, %15, %16, %17, %18, %19, %20, %21, %22, %23, "
      "%24, %25, %26, %27, %28, %29, %30, %31, %32, %33, %34, %35, %36, %37, %38, %39, %40, %41, %42, %43, %44, %45, "
      "%46, %47, %48, %49, %50, %51, %52, %53, %54, %55, %56, %57, %58, %59, %60, %61, %62, %63, %64, %65, %66, %67, "
      "%68, %69, %70, %71, %72, %73, %74, %75, %76, %77, %78, %79, %80, %81, %82, %83, %84, %85, %86, %87, %88, %89, "
      "%90, %91, %92, %93, %94, %95, %96, %97, %98, %99, %100, %101, %102, %103, %104, %105, %106, %107, %108, %109, "
      "%110, %111, %112, %113, %114, %115, %116, %117, %118, %119, %120, %121, %122, %123, %124, %125, %126, %127"
      "}, {%128, %129, %130, %131}, %132, p, %134, %135, %136;\n}\n"
      : "+f"(d[0]), "+f"(d[1]), "+f"(d[2]), "+f"(d[3]), "+f"(d[4]), "+f"(d[5]), "+f"(d[6]), "+f"(d[7]), "+f"(d[8]),
        "+f"(d[9]), "+f"(d[10]), "+f"(d[11]), "+f"(d[12]), "+f"(d[13]), "+f"(d[14]), "+f"(d[15]), "+f"(d[16]),
        "+f"(d[17]), "+f"(d[18]), "+f"(d[19]), "+f"(d[20]), "+f"(d[21]), "+f"(d[22]), "+f"(d[23]), "+f"(d[24]),
        "+f"(d[25]), "+f"(d[26]), "+f"(d[27]), "+f"(d[28]), "+f"(d[29]), "+f"(d[30]), "+f"(d[31]), "+f"(d[32]),
        "+f"(d[33]), "+f"(d[34]), "+f"(d[35]), "+f"(d[36]), "+f"(d[37]), "+f"(d[38]), "+f"(d[39]), "+f"(d[40]),
        "+f"(d[41]), "+f"(d[42]), "+f"(d[43]), "+f"(d[44]), "+f"(d[45]), "+f"(d[46]), "+f"(d[47]), "+f"(d[48]),
        "+f"(d[49]), "+f"(d[50]), "+f"(d[51]), "+f"(d[52]), "+f"(d[53]), "+f"(d[54]), "+f"(d[55]), "+f"(d[56]),
        "+f"(d[57]), "+f"(d[58]), "+f"(d[59]), "+f"(d[60]), "+f"(d[61]), "+f"(d[62]), "+f"(d[63]), "+f"(d[64]),
        "+f"(d[65]), "+f"(d[66]), "+f"(d[67]), "+f"(d[68]), "+f"(d[69]), "+f"(d[70]), "+f"(d[71]), "+f"(d[72]),
        "+f"(d[73]), "+f"(d[74]), "+f"(d[75]), "+f"(d[76]), "+f"(d[77]), "+f"(d[78]), "+f"(d[79]), "+f"(d[80]),
        "+f"(d[81]), "+f"(d[82]), "+f"(d[83]), "+f"(d[84]), "+f"(d[85]), "+f"(d[86]), "+f"(d[87]), "+f"(d[88]),
        "+f"(d[89]), "+f"(d[90]), "+f"(d[91]), "+f"(d[92]), "+f"(d[93]), "+f"(d[94]), "+f"(d[95]), "+f"(d[96]),
        "+f"(d[97]), "+f"(d[98]), "+f"(d[99]), "+f"(d[100]), "+f"(d[101]), "+f"(d[102]), "+f"(d[103]), "+f"(d[104]),
        "+f"(d[105]), "+f"(d[106]), "+f"(d[107]), "+f"(d[108]), "+f"(d[109]), "+f"(d[110]), "+f"(d[111]),
        "+f"(d[112]), "+f"(d[113]), "+f"(d[114]), "+f"(d[115]), "+f"(d[116]), "+f"(d[117]), "+f"(d[118]),
        "+f"(d[119]), "+f"(d[120]), "+f"(d[121]), "+f"(d[122]), "+f"(d[123]), "+f"(d[124]), "+f"(d[125]),
        "+f"(d[126]), "+f"(d[127])
      : "r"(a0), "r"(a1), "r"(a2), "r"(a3), "l"(db), "r"(sd), "n"(SA), "n"(SB), "n"(TB));
}

__device__ const __align__(128) uint32_t c_img[3584] = {
    0x00003c80, 0x00003c80, 0x00003c80, 0x00003c80, 0x00003c80, 0x00003c80, 0x00003c80, 0x00003c80, 0x00003c80, 0x00003c80,
    0x00003c80, 0x00003c80, 0x00003c80, 0x00003c80, 0x00003c80, 0x00003c80, 0x00003c80, 0x00003c80, 0x00003c80, 0x00003c80,
    0x00003c80, 0x00003c80, 0x00003c80, 0x00003c80, 0x00003c80, 0x00003c80, 0x00003c80, 0x00003c80, 0x00003c80, 0x00003c80,
    0x00003c80, 0x00003c80, 0x3c463c22, 0x3c623bf1, 0x3c753b95, 0x3c7f3ac9, 0x3ac93c7f, 0x3b953c75, 0x3bf13c62, 0x3c223c46,
    0x3c22bc46, 0x3bf1bc62, 0x3b95bc75, 0x3ac9bc7f, 0x3c7fbac9, 0x3c75bb95, 0x3c62bbf1, 0x3c46bc22, 0xbc46bc22, 0xbc62bbf1,
    0xbc75bb95, 0xbc7fbac9, 0xbac9bc7f, 0xbb95bc75, 0xbbf1bc62, 0xbc22bc46, 0xbc223c46, 0xbbf13c62, 0xbb953c75, 0xbac93c7f,
    0xbc7f3ac9, 0xbc753b95, 0xbc623bf1, 0xbc463c22, 0xbb48bc7b, 0xbc0ebc55, 0xbc55bc0e, 0xbc7bbb48, 0xbc7b3b48, 0xbc553c0e,
    0xbc0e3c55, 0xbb483c7b, 0x3b483c7b, 0x3c0e3c55, 0x3c553c0e, 0x3c7b3b48, 0x3c7bbb48, 0x3c55bc0e, 0x3c0ebc55, 0x3b48bc7b,
    0xbb48bc7b, 0xbc0ebc55, 0xbc55bc0e, 0xbc7bbb48, 0xbc7b3b48, 0xbc553c0e, 0xbc0e3c55, 0xbb483c7b, 0x3b483c7b, 0x3c0e3c55,
    0x3c553c0e, 0x3c7b3b48, 0x3c7bbb48, 0x3c55bc0e, 0x3c0ebc55, 0x3b48bc7b, 0x3c623bf1, 0x3c7fbac9, 0x3c46bc22, 0x3b95bc75,
    0xbc753b95, 0xbc223c46, 0xbac93c7f, 0x3bf13c62, 0x3bf1bc62, 0xbac9bc7f, 0xbc22bc46, 0xbc75bb95, 0x3b953c75, 0x3c463c22,
    0x3c7f3ac9, 0x3c62bbf1, 0xbc62bbf1, 0xbc7f3ac9, 0xbc463c22, 0xbb953c75, 0x3c75bb95, 0x3c22bc46, 0x3ac9bc7f, 0xbbf1bc62,
    0xbbf13c62, 0x3ac93c7f, 0x3c223c46, 0x3c753b95, 0xbb95bc75, 0xbc46bc22, 0xbc7fbac9, 0xbc623bf1, 0x3bc43c6d, 0x3c6d3bc4,
    0x3c6dbbc4, 0x3bc4bc6d, 0xbbc4bc6d, 0xbc6dbbc4, 0xbc6d3bc4, 0xbbc43c6d, 0x3bc43c6d, 0x3c6d3bc4, 0x3c6dbbc4, 0x3bc4bc6d,
    0xbbc4bc6d, 0xbc6dbbc4, 0xbc6d3bc4, 0xbbc43c6d, 0x3bc43c6d, 0x3c6d3bc4, 0x3c6dbbc4, 0x3bc4bc6d, 0xbbc4bc6d, 0xbc6dbbc4,
    0xbc6d3bc4, 0xbbc43c6d, 0x3bc43c6d, 0x3c6d3bc4, 0x3c6dbbc4, 0x3bc4bc6d, 0xbbc4bc6d, 0xbc6dbbc4, 0xbc6d3bc4, 0xbbc43c6d,
    0x3c753b95, 0x3c46bc22, 0xbac9bc7f, 0xbc62bbf1, 0xbbf1bc62, 0xbc7fbac9, 0xbc223c46, 0x3b953c75, 0x3b95bc75, 0xbc22bc46,
    0xbc7f3ac9, 0xbbf13c62, 0xbc623bf1, 0xbac93c7f, 0x3c463c22, 0x3c75bb95, 0xbc75bb95, 0xbc463c22, 0x3ac93c7f, 0x3c623bf1,
    0x3bf13c62, 0x3c7f3ac9, 0x3c22bc46, 0xbb95bc75, 0xbb953c75, 0x3c223c46, 0x3c7fbac9, 0x3bf1bc62, 0x3c62bbf1, 0x3ac9bc7f,
    0xbc46bc22, 0xbc753b95, 0xbc0ebc55, 0xbc7b3b48, 0xbb483c7b, 0x3c553c0e, 0x3c55bc0e, 0xbb48bc7b, 0xbc7bbb48, 0xbc0e3c55,
    0x3c0e3c55, 0x3c7bbb48, 0x3b48bc7b, 0xbc55bc0e, 0xbc553c0e, 0x3b483c7b, 0x3c7b3b48, 0x3c0ebc55, 0xbc0ebc55, 0xbc7b3b48,
    0xbb483c7b, 0x3c553c0e, 0x3c55bc0e, 0xbb48bc7b, 0xbc7bbb48, 0xbc0e3c55, 0x3c0e3c55, 0x3c7bbb48, 0x3b48bc7b, 0xbc55bc0e,
    0xbc553c0e, 0x3b483c7b, 0x3c7b3b48, 0x3c0ebc55, 0x3c7f3ac9, 0x3b95bc75, 0xbc62bbf1, 0xbc223c46, 0x3c46bc22, 0xbbf1bc62,
    0xbc753b95, 0x3ac93c7f, 0x3ac9bc7f, 0xbc75bb95, 0xbbf13c62, 0x3c463c22, 0xbc22bc46, 0xbc623bf1, 0x3b953c75, 0x3c7fbac9,
    0xbc7fbac9, 0xbb953c75, 0x3c623bf1, 0x3c22bc46, 0xbc463c22, 0x3bf13c62, 0x3c75bb95, 0xbac9bc7f, 0xbac93c7f, 0x3c753b95,
    0x3bf1bc62, 0xbc46bc22, 0x3c223c46, 0x3c62bbf1, 0xbb95bc75, 0xbc7f3ac9, 0x3a493c80, 0x3b163c7d, 0x3b793c78, 0x3bac3c71,
    0x3bdb3c67, 0x3c043c5c, 0x3c183c4e, 0x3c2c3c3e, 0x3c3e3c2c, 0x3c4e3c18, 0x3c5c3c04, 0x3c673bdb, 0x3c713bac, 0x3c783b79,
    0x3c7d3b16, 0x3c803a49, 0x3c80ba49, 0x3c7dbb16, 0x3c78bb79, 0x3c71bbac, 0x3c67bbdb, 0x3c5cbc04, 0x3c4ebc18, 0x3c3ebc2c,
    0x3c2cbc3e, 0x3c18bc4e, 0x3c04bc5c, 0x3bdbbc67, 0x3bacbc71, 0x3b79bc78, 0x3b16bc7d, 0x3a49bc80, 0x3c783b79, 0x3c80ba49,
    0x3c71bbac, 0x3c4ebc18, 0x3b163c7d, 0x3bdb3c67, 0x3c2c3c3e, 0x3c5c3c04, 0xbc04bc5c, 0xbc3ebc2c, 0xbc67bbdb, 0xbc7dbb16,
    0x3c18bc4e, 0x3bacbc71, 0x3a49bc80, 0xbb79bc78, 0xbb793c78, 0x3a493c80, 0x3bac3c71, 0x3c183c4e, 0xbc7d3b16, 0xbc673bdb,
    0xbc3e3c2c, 0xbc043c5c, 0x3c5cbc04, 0x3c2cbc3e, 0x3bdbbc67, 0x3b16bc7d, 0x3c4e3c18, 0x3c713bac, 0x3c803a49, 0x3c78bb79,
    0xbc5cbc04, 0xbc80ba49, 0xbc673bdb, 0xbc183c4e, 0xbb163c7d, 0x3bac3c71, 0x3c3e3c2c, 0x3c783b79, 0x3b793c78, 0x3c2c3c3e,
    0x3c713bac, 0x3c7dbb16, 0x3c4ebc18, 0x3bdbbc67, 0xba49bc80, 0xbc04bc5c, 0xbc043c5c, 0xba493c80, 0x3bdb3c67, 0x3c4e3c18,
    0x3c7d3b16, 0x3c71bbac, 0x3c2cbc3e, 0x3b79bc78, 0x3c78bb79, 0x3c3ebc2c, 0x3bacbc71, 0xbb16bc7d, 0xbc18bc4e, 0xbc67bbdb,
    0xbc803a49, 0xbc5c3c04, 0x3c3ebc2c, 0x3b16bc7d, 0xbc04bc5c, 0xbc71bbac, 0xbbdb3c67, 0x3b793c78, 0x3c4e3c18, 0x3c80ba49,
    0x3a49bc80, 0xbc18bc4e, 0xbc78bb79, 0xbc673bdb, 0x3bac3c71, 0x3c5c3c04, 0x3c7dbb16, 0x3c2cbc3e, 0x3c2c3c3e, 0x3c7d3b16,
    0x3c5cbc04, 0x3bacbc71, 0xbc67bbdb, 0xbc783b79, 0xbc183c4e, 0x3a493c80, 0x3c803a49, 0x3c4ebc18, 0x3b79bc78, 0xbbdbbc67,
    0xbc713bac, 0xbc043c5c, 0x3b163c7d, 0x3c3e3c2c, 0x3c67bbdb, 0x3b79bc78, 0xbc18bc4e, 0xbc80ba49, 0xbc2c3c3e, 0x3b163c7d,
    0x3c5c3c04, 0x3c71bbac, 0x3bacbc71, 0xbc04bc5c, 0xbc7dbb16, 0xbc3e3c2c, 0x3a493c80, 0x3c4e3c18, 0x3c78bb79, 0x3bdbbc67,
    0x3bdb3c67, 0x3c783b79, 0x3c4ebc18, 0x3a49bc80, 0xbc3ebc2c, 0xbc7d3b16, 0xbc043c5c, 0x3bac3c71, 0x3c713bac, 0x3c5cbc04,
    0x3b16bc7d, 0xbc2cbc3e, 0xbc803a49, 0xbc183c4e, 0x3b793c78, 0x3c673bdb, 0xbb16bc7d, 0xbc71bbac, 0xbc3e3c2c, 0x3b793c78,
    0xbc5c3c04, 0x3a493c80, 0x3c673bdb, 0x3c4ebc18, 0xbc183c4e, 0x3bdb3c67, 0x3c803a49, 0x3c04bc5c, 0x3c783b79, 0x3c2cbc3e,
    0xbbacbc71, 0xbc7dbb16, 0xbc7d3b16, 0xbbac3c71, 0x3c2c3c3e, 0x3c78bb79, 0x3c043c5c, 0x3c80ba49, 0x3bdbbc67, 0xbc18bc4e,
    0x3c4e3c18, 0x3c67bbdb, 0x3a49bc80, 0xbc5cbc04, 0x3b79bc78, 0xbc3ebc2c, 0xbc713bac, 0xbb163c7d, 0xbb163c7d, 0x3c673bdb,
    0x3c2cbc3e, 0xbc04bc5c, 0xbc783b79, 0xba493c80, 0x3c713bac, 0x3c18bc4e, 0x3c4ebc18, 0xbbacbc71, 0xbc803a49, 0xbb793c78,
    0x3c5c3c04, 0x3c3ebc2c, 0xbbdbbc67, 0xbc7d3b16, 0xbc7dbb16, 0xbbdb3c67, 0x3c3e3c2c, 0x3c5cbc04, 0xbb79bc78, 0xbc80ba49,
    0xbbac3c71, 0x3c4e3c18, 0x3c183c4e, 0x3c71bbac, 0xba49bc80, 0xbc78bb79, 0xbc043c5c, 0x3c2c3c3e, 0x3c67bbdb, 0xbb16bc7d,
    0xbc67bbdb, 0xbc043c5c, 0x3c4e3c18, 0x3c2cbc3e, 0xbc80ba49, 0xbb163c7d, 0x3c783b79, 0x3bacbc71, 0xbc713bac, 0x3b793c78,
    0x3c7dbb16, 0xba49bc80, 0xbc3e3c2c, 0x3c183c4e, 0x3c5cbc04, 0xbbdbbc67, 0xbbdb3c67, 0x3c5c3c04, 0x3c18bc4e, 0xbc3ebc2c,
    0xba493c80, 0x3c7d3b16, 0x3b79bc78, 0xbc71bbac, 0x3bac3c71, 0x3c78bb79, 0xbb16bc7d, 0xbc803a49, 0x3c2c3c3e, 0x3c4ebc18,
    0xbc04bc5c, 0xbc673bdb, 0x3c353c35, 0x3c35bc35, 0xbc35bc35, 0xbc353c35, 0x3c353c35, 0x3c35bc35, 0xbc35bc35, 0xbc353c35,
    0x3c353c35, 0x3c35bc35, 0xbc35bc35, 0xbc353c35, 0x3c353c35, 0x3c35bc35, 0xbc35bc35, 0xbc353c35, 0x3c353c35, 0x3c35bc35,
    0xbc35bc35, 0xbc353c35, 0x3c353c35, 0x3c35bc35, 0xbc35bc35, 0xbc353c35, 0x3c353c35, 0x3c35bc35, 0xbc35bc35, 0xbc353c35,
    0x3c353c35, 0x3c35bc35, 0xbc35bc35, 0xbc353c35, 0x3c7fbac9, 0xbb95bc75, 0xbc623bf1, 0x3c223c46, 0x3c463c22, 0x3bf1bc62,
    0xbc75bb95, 0xbac93c7f, 0xbac9bc7f, 0xbc753b95, 0x3bf13c62, 0x3c46bc22, 0x3c22bc46, 0xbc62bbf1, 0xbb953c75, 0x3c7f3ac9,
    0xbc7f3ac9, 0x3b953c75, 0x3c62bbf1, 0xbc22bc46, 0xbc46bc22, 0xbbf13c62, 0x3c753b95, 0x3ac9bc7f, 0x3ac93c7f, 0x3c75bb95,
    0xbbf1bc62, 0xbc463c22, 0xbc223c46, 0x3c623bf1, 0x3b95bc75, 0xbc7fbac9, 0xbc55bc0e, 0xbb483c7b, 0x3c7bbb48, 0xbc0ebc55,
    0xbc0e3c55, 0x3c7b3b48, 0xbb48bc7b, 0xbc553c0e, 0x3c553c0e, 0x3b48bc7b, 0xbc7b3b48, 0x3c0e3c55, 0x3c0ebc55, 0xbc7bbb48,
    0x3b483c7b, 0x3c55bc0e, 0xbc55bc0e, 0xbb483c7b, 0x3c7bbb48, 0xbc0ebc55, 0xbc0e3c55, 0x3c7b3b48, 0xbb48bc7b, 0xbc553c0e,
    0x3c553c0e, 0x3b48bc7b, 0xbc7b3b48, 0x3c0e3c55, 0x3c0ebc55, 0xbc7bbb48, 0x3b483c7b, 0x3c55bc0e, 0x3c75bb95, 0xbc46bc22,
    0xbac93c7f, 0x3c62bbf1, 0xbbf13c62, 0x3c7fbac9, 0xbc22bc46, 0xbb953c75, 0xbb95bc75, 0xbc223c46, 0x3c7f3ac9, 0xbbf1bc62,
    0x3c623bf1, 0xbac9bc7f, 0xbc463c22, 0x3c753b95, 0xbc753b95, 0x3c463c22, 0x3ac9bc7f, 0xbc623bf1, 0x3bf1bc62, 0xbc7f3ac9,
    0x3c223c46, 0x3b95bc75, 0x3b953c75, 0x3c22bc46, 0xbc7fbac9, 0x3bf13c62, 0xbc62bbf1, 0x3ac93c7f, 0x3c46bc22, 0xbc75bb95,
    0x3c6d3bc4, 0xbbc4bc6d, 0xbbc43c6d, 0x3c6dbbc4, 0xbc6dbbc4, 0x3bc43c6d, 0x3bc4bc6d, 0xbc6d3bc4, 0x3c6d3bc4, 0xbbc4bc6d,
    0xbbc43c6d, 0x3c6dbbc4, 0xbc6dbbc4, 0x3bc43c6d, 0x3bc4bc6d, 0xbc6d3bc4, 0x3c6d3bc4, 0xbbc4bc6d, 0xbbc43c6d, 0x3c6dbbc4,
    0xbc6dbbc4, 0x3bc43c6d, 0x3bc4bc6d, 0xbc6d3bc4, 0x3c6d3bc4, 0xbbc4bc6d, 0xbbc43c6d, 0x3c6dbbc4, 0xbc6dbbc4, 0x3bc43c6d,
    0x3bc4bc6d, 0xbc6d3bc4, 0x3c62bbf1, 0xbc7fbac9, 0x3c463c22, 0xbb95bc75, 0xbc75bb95, 0x3c223c46, 0xbac9bc7f, 0xbbf13c62,
    0xbbf1bc62, 0xbac93c7f, 0x3c22bc46, 0xbc753b95, 0xbb953c75, 0x3c46bc22, 0xbc7f3ac9, 0x3c623bf1, 0xbc623bf1, 0x3c7f3ac9,
    0xbc46bc22, 0x3b953c75, 0x3c753b95, 0xbc22bc46, 0x3ac93c7f, 0x3bf1bc62, 0x3bf13c62, 0x3ac9bc7f, 0xbc223c46, 0x3c75bb95,
    0x3b95bc75, 0xbc463c22, 0x3c7fbac9, 0xbc62bbf1, 0xbc7bbb48, 0x3c553c0e, 0xbc0ebc55, 0x3b483c7b, 0x3b48bc7b, 0xbc0e3c55,
    0x3c55bc0e, 0xbc7b3b48, 0x3c7b3b48, 0xbc55bc0e, 0x3c0e3c55, 0xbb48bc7b, 0xbb483c7b, 0x3c0ebc55, 0xbc553c0e, 0x3c7bbb48,
    0xbc7bbb48, 0x3c553c0e, 0xbc0ebc55, 0x3b483c7b, 0x3b48bc7b, 0xbc0e3c55, 0x3c55bc0e, 0xbc7b3b48, 0x3c7b3b48, 0xbc55bc0e,
    0x3c0e3c55, 0xbb48bc7b, 0xbb483c7b, 0x3c0ebc55, 0xbc553c0e, 0x3c7bbb48, 0x3c46bc22, 0xbc623bf1, 0x3c75bb95, 0xbc7f3ac9,
    0x3ac9bc7f, 0xbb953c75, 0x3bf1bc62, 0xbc223c46, 0xbc22bc46, 0x3bf13c62, 0xbb95bc75, 0x3ac93c7f, 0xbc7fbac9, 0x3c753b95,
    0xbc62bbf1, 0x3c463c22, 0xbc463c22, 0x3c62bbf1, 0xbc753b95, 0x3c7fbac9, 0xbac93c7f, 0x3b95bc75, 0xbbf13c62, 0x3c22bc46,
    0x3c223c46, 0xbbf1bc62, 0x3b953c75, 0xbac9bc7f, 0x3c7f3ac9, 0xbc75bb95, 0x3c623bf1, 0xbc46bc22, 0x3c3e3c2c, 0x3c18bc4e,
    0xbc5cbc04, 0xbbdb3c67, 0x3c713bac, 0x3b79bc78, 0xbc7dbb16, 0xba493c80, 0x3c80ba49, 0xbb16bc7d, 0xbc783b79, 0x3bac3c71,
    0x3c67bbdb, 0xbc04bc5c, 0xbc4e3c18, 0x3c2c3c3e, 0x3c2cbc3e, 0xbc4ebc18, 0xbc043c5c, 0x3c673bdb, 0x3bacbc71, 0xbc78bb79,
    0xbb163c7d, 0x3c803a49, 0xba49bc80, 0xbc7d3b16, 0x3b793c78, 0x3c71bbac, 0xbbdbbc67, 0xbc5c3c04, 0x3c183c4e, 0x3c3ebc2c,
    0x3c5cbc04, 0xbc3ebc2c, 0xbbdb3c67, 0x3c7d3b16, 0x3c4e3c18, 0x3bacbc71, 0xbc80ba49, 0x3b793c78, 0xbc78bb79, 0x3a493c80,
    0x3c71bbac, 0xbc18bc4e, 0xbb16bc7d, 0xbc673bdb, 0x3c2c3c3e, 0x3c04bc5c, 0x3c043c5c, 0x3c2cbc3e, 0xbc67bbdb, 0xbb163c7d,
    0xbc183c4e, 0x3c713bac, 0x3a49bc80, 0xbc783b79, 0x3b79bc78, 0xbc803a49, 0x3bac3c71, 0x3c4ebc18, 0x3c7dbb16, 0xbbdbbc67,
    0xbc3e3c2c, 0x3c5c3c04, 0xbc783b79, 0x3c2c3c3e, 0x3bacbc71, 0xbc7d3b16, 0x3c183c4e, 0x3bdbbc67, 0xbc803a49, 0x3c043c5c,
    0x3c5c3c04, 0x3a49bc80, 0xbc673bdb, 0x3c4e3c18, 0x3b16bc7d, 0xbc713bac, 0x3c3e3c2c, 0x3b79bc78, 0x3b793c78, 0x3c3ebc2c,
    0xbc71bbac, 0x3b163c7d, 0x3c4ebc18, 0xbc67bbdb, 0x3a493c80, 0x3c5cbc04, 0x3c04bc5c, 0xbc80ba49, 0x3bdb3c67, 0x3c18bc4e,
    0xbc7dbb16, 0x3bac3c71, 0x3c2cbc3e, 0xbc78bb79, 0x3a49bc80, 0xbc4e3c18, 0x3c783b79, 0xbbdbbc67, 0x3bac3c71, 0x3c04bc5c,
    0xbc7d3b16, 0x3c3e3c2c, 0xbc2cbc3e, 0xbb163c7d, 0x3c5cbc04, 0xbc71bbac, 0x3c673bdb, 0xbb79bc78, 0xbc183c4e, 0x3c80ba49,
    0x3c803a49, 0xbc18bc4e, 0xbb793c78, 0x3c67bbdb, 0xbc713bac, 0x3c5c3c04, 0xbb16bc7d, 0xbc2c3c3e, 0x3c3ebc2c, 0xbc7dbb16,
    0x3c043c5c, 0x3bacbc71, 0xbbdb3c67, 0x3c78bb79, 0xbc4ebc18, 0x3a493c80, 0x3bacbc71, 0xbc5c3c04, 0x3c7d3b16, 0xbc2cbc3e,
    0x3a493c80, 0x3c18bc4e, 0xbc783b79, 0x3c673bdb, 0xbbdbbc67, 0xbb793c78, 0x3c4ebc18, 0xbc80ba49, 0x3c3e3c2c, 0xbb16bc7d,
    0xbc043c5c, 0x3c71bbac, 0x3c713bac, 0xbc04bc5c, 0xbb163c7d, 0x3c3ebc2c, 0xbc803a49, 0x3c4e3c18, 0xbb79bc78, 0xbbdb3c67,
    0x3c67bbdb, 0xbc78bb79, 0x3c183c4e, 0x3a49bc80, 0xbc2c3c3e, 0x3c7dbb16, 0xbc5cbc04, 0x3bac3c71, 0xbc4ebc18, 0x3bdb3c67,
    0x3a49bc80, 0xbc043c5c, 0xbb793c78, 0x3c2cbc3e, 0xbc713bac, 0x3c7d3b16, 0x3b163c7d, 0x3bacbc71, 0xbc3e3c2c, 0x3c78bb79,
    0x3c5cbc04, 0xbc803a49, 0x3c673bdb, 0xbc18bc4e, 0xbc183c4e, 0x3c67bbdb, 0xbc80ba49, 0x3c5c3c04, 0x3c783b79, 0xbc3ebc2c,
    0x3bac3c71, 0x3b16bc7d, 0x3c7dbb16, 0xbc71bbac, 0x3c2c3c3e, 0xbb79bc78, 0xbc04bc5c, 0x3a493c80, 0x3bdbbc67, 0xbc4e3c18,
    0x3c183c4e, 0xbbacbc71, 0x3a493c80, 0x3b79bc78, 0xbc043c5c, 0x3c3ebc2c, 0xbc673bdb, 0x3c7dbb16, 0x3b16bc7d, 0xbbdb3c67,
    0x3c2cbc3e, 0xbc5c3c04, 0x3c78bb79, 0xbc80ba49, 0x3c713bac, 0xbc4ebc18, 0xbc4e3c18, 0x3c71bbac, 0xbc803a49, 0x3c783b79,
    0xbc5cbc04, 0x3c2c3c3e, 0xbbdbbc67, 0x3b163c7d, 0x3c7d3b16, 0xbc67bbdb, 0x3c3e3c2c, 0xbc04bc5c, 0x3b793c78, 0x3a49bc80,
    0xbbac3c71, 0x3c18bc4e, 0xbc713bac, 0x3c78bb79, 0xbc7d3b16, 0x3c80ba49, 0xbc3e3c2c, 0x3c4ebc18, 0xbc5c3c04, 0x3c67bbdb,
    0xbbdb3c67, 0x3c04bc5c, 0xbc183c4e, 0x3c2cbc3e, 0xba493c80, 0x3b16bc7d, 0xbb793c78, 0x3bacbc71, 0x3bac3c71, 0xbb79bc78,
    0x3b163c7d, 0xba49bc80, 0x3c2c3c3e, 0xbc18bc4e, 0x3c043c5c, 0xbbdbbc67, 0x3c673bdb, 0xbc5cbc04, 0x3c4e3c18, 0xbc3ebc2c,
    0x3c803a49, 0xbc7dbb16, 0x3c783b79, 0xbc71bbac, 0x3c800000, 0xbc800000, 0x3c800000, 0xbc800000, 0x3c800000, 0xbc800000,
    0x3c800000, 0xbc800000, 0x3c800000, 0xbc800000, 0x3c800000, 0xbc800000, 0x3c800000, 0xbc800000, 0x3c800000, 0xbc800000,
    0x3c800000, 0xbc800000, 0x3c800000, 0xbc800000, 0x3c800000, 0xbc800000, 0x3c800000, 0xbc800000, 0x3c800000, 0xbc800000,
    0x3c800000, 0xbc800000, 0x3c800000, 0xbc800000, 0x3c800000, 0xbc800000, 0x3c22bc46, 0xbbf13c62, 0x3b95bc75, 0xbac93c7f,
    0x3c7fbac9, 0xbc753b95, 0x3c62bbf1, 0xbc463c22, 0xbc46bc22, 0x3c623bf1, 0xbc75bb95, 0x3c7f3ac9, 0xbac9bc7f, 0x3b953c75,
    0xbbf1bc62, 0x3c223c46, 0xbc223c46, 0x3bf1bc62, 0xbb953c75, 0x3ac9bc7f, 0xbc7f3ac9, 0x3c75bb95, 0xbc623bf1, 0x3c46bc22,
    0x3c463c22, 0xbc62bbf1, 0x3c753b95, 0xbc7fbac9, 0x3ac93c7f, 0xbb95bc75, 0x3bf13c62, 0xbc22bc46, 0xbc7b3b48, 0x3c55bc0e,
    0xbc0e3c55, 0x3b48bc7b, 0x3b483c7b, 0xbc0ebc55, 0x3c553c0e, 0xbc7bbb48, 0x3c7bbb48, 0xbc553c0e, 0x3c0ebc55, 0xbb483c7b,
    0xbb48bc7b, 0x3c0e3c55, 0xbc55bc0e, 0x3c7b3b48, 0xbc7b3b48, 0x3c55bc0e, 0xbc0e3c55, 0x3b48bc7b, 0x3b483c7b, 0xbc0ebc55,
    0x3c553c0e, 0xbc7bbb48, 0x3c7bbb48, 0xbc553c0e, 0x3c0ebc55, 0xbb483c7b, 0xbb48bc7b, 0x3c0e3c55, 0xbc55bc0e, 0x3c7b3b48,
    0x3bf1bc62, 0x3ac93c7f, 0xbc22bc46, 0x3c753b95, 0x3b953c75, 0xbc46bc22, 0x3c7f3ac9, 0xbc623bf1, 0xbc62bbf1, 0x3c7fbac9,
    0xbc463c22, 0x3b95bc75, 0x3c75bb95, 0xbc223c46, 0x3ac9bc7f, 0x3bf13c62, 0xbbf13c62, 0xbac9bc7f, 0x3c223c46, 0xbc75bb95,
    0xbb95bc75, 0x3c463c22, 0xbc7fbac9, 0x3c62bbf1, 0x3c623bf1, 0xbc7f3ac9, 0x3c46bc22, 0xbb953c75, 0xbc753b95, 0x3c22bc46,
    0xbac93c7f, 0xbbf1bc62, 0x3c6dbbc4, 0xbbc43c6d, 0xbbc4bc6d, 0x3c6d3bc4, 0xbc6d3bc4, 0x3bc4bc6d, 0x3bc43c6d, 0xbc6dbbc4,
    0x3c6dbbc4, 0xbbc43c6d, 0xbbc4bc6d, 0x3c6d3bc4, 0xbc6d3bc4, 0x3bc4bc6d, 0x3bc43c6d, 0xbc6dbbc4, 0x3c6dbbc4, 0xbbc43c6d,
    0xbbc4bc6d, 0x3c6d3bc4, 0xbc6d3bc4, 0x3bc4bc6d, 0x3bc43c6d, 0xbc6dbbc4, 0x3c6dbbc4, 0xbbc43c6d, 0xbbc4bc6d, 0x3c6d3bc4,
    0xbc6d3bc4, 0x3bc4bc6d, 0x3bc43c6d, 0xbc6dbbc4, 0x3b95bc75, 0x3c223c46, 0xbc7f3ac9, 0x3bf1bc62, 0xbc623bf1, 0x3ac9bc7f,
    0x3c463c22, 0xbc753b95, 0xbc75bb95, 0x3c46bc22, 0x3ac93c7f, 0xbc62bbf1, 0x3bf13c62, 0xbc7fbac9, 0x3c22bc46, 0x3b953c75,
    0xbb953c75, 0xbc22bc46, 0x3c7fbac9, 0xbbf13c62, 0x3c62bbf1, 0xbac93c7f, 0xbc46bc22, 0x3c75bb95, 0x3c753b95, 0xbc463c22,
    0xbac9bc7f, 0x3c623bf1, 0xbbf1bc62, 0x3c7f3ac9, 0xbc223c46, 0xbb95bc75, 0xbc553c0e, 0xbb48bc7b, 0x3c7b3b48, 0xbc0e3c55,
    0xbc0ebc55, 0x3c7bbb48, 0xbb483c7b, 0xbc55bc0e, 0x3c55bc0e, 0x3b483c7b, 0xbc7bbb48, 0x3c0ebc55, 0x3c0e3c55, 0xbc7b3b48,
    0x3b48bc7b, 0x3c553c0e, 0xbc553c0e, 0xbb48bc7b, 0x3c7b3b48, 0xbc0e3c55, 0xbc0ebc55, 0x3c7bbb48, 0xbb483c7b, 0xbc55bc0e,
    0x3c55bc0e, 0x3b483c7b, 0xbc7bbb48, 0x3c0ebc55, 0x3c0e3c55, 0xbc7b3b48, 0x3b48bc7b, 0x3c553c0e, 0x3ac9bc7f, 0x3c753b95,
    0xbbf13c62, 0xbc46bc22, 0xbc22bc46, 0x3c62bbf1, 0x3b953c75, 0xbc7f3ac9, 0xbc7fbac9, 0x3b95bc75, 0x3c623bf1, 0xbc223c46,
    0xbc463c22, 0xbbf1bc62, 0x3c75bb95, 0x3ac93c7f, 0xbac93c7f, 0xbc75bb95, 0x3bf1bc62, 0x3c463c22, 0x3c223c46, 0xbc623bf1,
    0xbb95bc75, 0x3c7fbac9, 0x3c7f3ac9, 0xbb953c75, 0xbc62bbf1, 0x3c22bc46, 0x3c46bc22, 0x3bf13c62, 0xbc753b95, 0xbac9bc7f,
    0x3c80ba49, 0xbc7d3b16, 0x3c78bb79, 0xbc713bac, 0x3c67bbdb, 0xbc5c3c04, 0x3c4ebc18, 0xbc3e3c2c, 0x3c2cbc3e, 0xbc183c4e,
    0x3c04bc5c, 0xbbdb3c67, 0x3bacbc71, 0xbb793c78, 0x3b16bc7d, 0xba493c80, 0xba49bc80, 0x3b163c7d, 0xbb79bc78, 0x3bac3c71,
    0xbbdbbc67, 0x3c043c5c, 0xbc18bc4e, 0x3c2c3c3e, 0xbc3ebc2c, 0x3c4e3c18, 0xbc5cbc04, 0x3c673bdb, 0xbc71bbac, 0x3c783b79,
    0xbc7dbb16, 0x3c803a49, 0x3b79bc78, 0x3a493c80, 0xbbacbc71, 0x3c183c4e, 0x3c7dbb16, 0xbc673bdb, 0x3c3ebc2c, 0xbc043c5c,
    0xbc5c3c04, 0x3c2cbc3e, 0xbbdb3c67, 0x3b16bc7d, 0xbc4ebc18, 0x3c713bac, 0xbc80ba49, 0x3c78bb79, 0x3c783b79, 0xbc803a49,
    0x3c71bbac, 0xbc4e3c18, 0x3b163c7d, 0xbbdbbc67, 0x3c2c3c3e, 0xbc5cbc04, 0xbc04bc5c, 0x3c3e3c2c, 0xbc67bbdb, 0x3c7d3b16,
    0x3c18bc4e, 0xbbac3c71, 0x3a49bc80, 0x3b793c78, 0xbc043c5c, 0x3a49bc80, 0x3bdb3c67, 0xbc4ebc18, 0x3c7d3b16, 0xbc713bac,
    0x3c2cbc3e, 0xbb793c78, 0x3c78bb79, 0xbc3e3c2c, 0x3bacbc71, 0x3b163c7d, 0xbc18bc4e, 0x3c673bdb, 0xbc803a49, 0x3c5cbc04,
    0x3c5c3c04, 0xbc80ba49, 0x3c67bbdb, 0xbc183c4e, 0x3b16bc7d, 0x3bac3c71, 0xbc3ebc2c, 0x3c783b79, 0xbb79bc78, 0x3c2c3c3e,
    0xbc71bbac, 0x3c7dbb16, 0xbc4e3c18, 0x3bdbbc67, 0x3a493c80, 0xbc04bc5c, 0xbc2cbc3e, 0x3c7d3b16, 0xbc5c3c04, 0x3bacbc71,
    0x3c673bdb, 0xbc783b79, 0x3c18bc4e, 0x3a493c80, 0xbc80ba49, 0x3c4ebc18, 0xbb793c78, 0xbbdbbc67, 0x3c71bbac, 0xbc043c5c,
    0xbb16bc7d, 0x3c3e3c2c, 0x3c3ebc2c, 0xbb163c7d, 0xbc04bc5c, 0x3c713bac, 0xbbdb3c67, 0xbb79bc78, 0x3c4e3c18, 0xbc803a49,
    0x3a49bc80, 0x3c183c4e, 0xbc78bb79, 0x3c67bbdb, 0x3bac3c71, 0xbc5cbc04, 0x3c7dbb16, 0xbc2c3c3e, 0xbbdbbc67, 0x3c783b79,
    0xbc4e3c18, 0x3a49bc80, 0x3c3e3c2c, 0xbc7d3b16, 0x3c04bc5c, 0x3bac3c71, 0xbc71bbac, 0x3c5cbc04, 0xbb163c7d, 0xbc2cbc3e,
    0x3c80ba49, 0xbc183c4e, 0xbb79bc78, 0x3c673bdb, 0x3c67bbdb, 0xbb793c78, 0xbc18bc4e, 0x3c803a49, 0xbc2c3c3e, 0xbb16bc7d,
    0x3c5c3c04, 0xbc713bac, 0x3bacbc71, 0x3c043c5c, 0xbc7dbb16, 0x3c3ebc2c, 0x3a493c80, 0xbc4ebc18, 0x3c78bb79, 0xbbdb3c67,
    0xbc7d3b16, 0x3bacbc71, 0x3c2c3c3e, 0xbc783b79, 0x3c043c5c, 0xbc803a49, 0x3bdbbc67, 0x3c183c4e, 0x3c4e3c18, 0xbc673bdb,
    0x3a49bc80, 0x3c5c3c04, 0x3b79bc78, 0x3c3e3c2c, 0xbc713bac, 0x3b16bc7d, 0x3b163c7d, 0xbc71bbac, 0x3c3ebc2c, 0x3b793c78,
    0x3c5cbc04, 0x3a493c80, 0xbc67bbdb, 0x3c4ebc18, 0x3c18bc4e, 0x3bdb3c67, 0xbc80ba49, 0x3c04bc5c, 0xbc78bb79, 0x3c2cbc3e,
    0x3bac3c71, 0xbc7dbb16, 0x3c7d3b16, 0xbbdb3c67, 0xbc3ebc2c, 0x3c5cbc04, 0x3b793c78, 0xbc80ba49, 0x3bacbc71, 0x3c4e3c18,
    0xbc18bc4e, 0x3c71bbac, 0x3a493c80, 0xbc78bb79, 0x3c04bc5c, 0x3c2c3c3e, 0xbc673bdb, 0xbb16bc7d, 0xbb163c7d, 0xbc67bbdb,
    0x3c2cbc3e, 0x3c043c5c, 0xbc783b79, 0x3a49bc80, 0x3c713bac, 0xbc183c4e, 0x3c4ebc18, 0x3bac3c71, 0xbc803a49, 0x3b79bc78,
    0x3c5c3c04, 0xbc3e3c2c, 0xbbdbbc67, 0x3c7dbb16, 0xbbdb3c67, 0xbc5cbc04, 0x3c18bc4e, 0x3c3e3c2c, 0xba493c80, 0xbc7dbb16,
    0x3b79bc78, 0x3c713bac, 0x3bac3c71, 0xbc783b79, 0xbb16bc7d, 0x3c80ba49, 0x3c2c3c3e, 0xbc4e3c18, 0xbc04bc5c, 0x3c67bbdb,
    0x3c673bdb, 0xbc043c5c, 0xbc4ebc18, 0x3c2cbc3e, 0x3c803a49, 0xbb163c7d, 0xbc78bb79, 0x3bacbc71, 0x3c71bbac, 0x3b793c78,
    0xbc7d3b16, 0xba49bc80, 0x3c3ebc2c, 0x3c183c4e, 0xbc5c3c04, 0xbbdbbc67, 0x3f803f80, 0x3f7d3f7f, 0x3f783f7b, 0x3f713f75,
    0x3f673f6d, 0x3f5c3f62, 0x3f4e3f55, 0x3f3e3f46, 0x3f2c3f35, 0x3f183f22, 0x3f043f0e, 0x3edb3ef1, 0x3eac3ec4, 0x3e793e95,
    0x3e163e48, 0x3d493dc9, 0xbd490000, 0xbe16bdc9, 0xbe79be48, 0xbeacbe95, 0xbedbbec4, 0xbf04bef1, 0xbf18bf0e, 0xbf2cbf22,
    0xbf3ebf35, 0xbf4ebf46, 0xbf5cbf55, 0xbf67bf62, 0xbf71bf6d, 0xbf78bf75, 0xbf7dbf7b, 0xbf80bf7f, 0x3edb3ec4, 0x3f043ef1,
    0x3f183f0e, 0x3f2c3f22, 0x3d490000, 0x3e163dc9, 0x3e793e48, 0x3eac3e95, 0x3f713f6d, 0x3f783f75, 0x3f7d3f7b, 0x3f803f7f,
    0x3f3e3f35, 0x3f4e3f46, 0x3f5c3f55, 0x3f673f62, 0x3f673f6d, 0x3f5c3f62, 0x3f4e3f55, 0x3f3e3f46, 0x3f803f80, 0x3f7d3f7f,
    0x3f783f7b, 0x3f713f75, 0x3eac3ec4, 0x3e793e95, 0x3e163e48, 0x3d493dc9, 0x3f2c3f35, 0x3f183f22, 0x3f043f0e, 0x3edb3ef1,
    0xbf4ebf35, 0xbf71bf62, 0xbf80bf7b, 0xbf78bf7f, 0xbf5cbf6d, 0xbf2cbf46, 0xbedbbf0e, 0xbe16be95, 0x3f7d3f80, 0x3f673f75,
    0x3f3e3f55, 0x3f043f22, 0x3e793ec4, 0xbd493dc9, 0xbeacbe48, 0xbf18bef1, 0x3f183f35, 0x3eac3ef1, 0x3d493e48, 0xbe79bdc9,
    0xbf04bec4, 0xbf3ebf22, 0xbf67bf55, 0xbf7dbf75, 0x3e160000, 0x3edb3e95, 0x3f2c3f0e, 0x3f5c3f46, 0x3f783f6d, 0x3f803f7f,
    0x3f713f7b, 0x3f4e3f62, 0xbf04bec4, 0xbf3ebf22, 0xbf67bf55, 0xbf7dbf75, 0x3f183f35, 0x3eac3ef1, 0x3d493e48, 0xbe79bdc9,
    0x3f783f6d, 0x3f803f7f, 0x3f713f7b, 0x3f4e3f62, 0x3e160000, 0x3edb3e95, 0x3f2c3f0e, 0x3f5c3f46, 0x3f5c3f6d, 0x3f2c3f46,
    0x3edb3f0e, 0x3e163e95, 0x3f4e3f35, 0x3f713f62, 0x3f803f7b, 0x3f783f7f, 0xbe79bec4, 0x3d49bdc9, 0x3eac3e48, 0x3f183ef1,
    0xbf7dbf80, 0xbf67bf75, 0xbf3ebf55, 0xbf04bf22, 0xbe790000, 0xbf2cbef1, 0xbf71bf55, 0xbf7dbf7f, 0xbf4ebf6d, 0xbedbbf22,
    0x3d49be48, 0x3f043e95, 0x3f5c3f35, 0x3f803f75, 0x3f673f7b, 0x3f183f46, 0x3e163ec4, 0xbeacbdc9, 0xbf3ebf0e, 0xbf78bf62,
    0x3f783f80, 0x3f3e3f62, 0x3eac3f0e, 0xbe163dc9, 0xbf18bec4, 0xbf67bf46, 0xbf80bf7b, 0xbf5cbf75, 0xbf04bf35, 0xbd49be95,
    0x3edb3e48, 0x3f4e3f22, 0x3f7d3f6d, 0x3f713f7f, 0x3f2c3f55, 0x3e793ef1, 0xbf18bec4, 0xbf67bf46, 0xbf80bf7b, 0xbf5cbf75,
    0x3f783f80, 0x3f3e3f62, 0x3eac3f0e, 0xbe163dc9, 0x3f7d3f6d, 0x3f713f7f, 0x3f2c3f55, 0x3e793ef1, 0xbf04bf35, 0xbd49be95,
    0x3edb3e48, 0x3f4e3f22, 0x3f4e3f6d, 0x3edb3f22, 0xbd493e48, 0xbf04be95, 0x3e790000, 0x3f2c3ef1, 0x3f713f55, 0x3f7d3f7f,
    0xbe16bec4, 0x3eac3dc9, 0x3f3e3f0e, 0x3f783f62, 0xbf5cbf35, 0xbf80bf75, 0xbf67bf7b, 0xbf18bf46, 0xbedbbf35, 0x3e79bdc9,
    0x3f4e3f0e, 0x3f803f75, 0x3f3e3f6d, 0x3e163ef1, 0xbf04be48, 0xbf71bf46, 0x3eac0000, 0x3f5c3f22, 0x3f7d3f7b, 0x3f2c3f62,
    0x3d493ec4, 0xbf18be95, 0xbf78bf55, 0xbf67bf7f, 0x3f673f35, 0x3f783f7f, 0x3f183f55, 0xbd493e95, 0xbf2cbec4, 0xbf7dbf62,
    0xbf5cbf7b, 0xbeacbf22, 0x3f713f80, 0x3f043f46, 0xbe163e48, 0xbf3ebef1, 0xbf80bf6d, 0xbf4ebf75, 0xbe79bf0e, 0x3edb3dc9,
    0x3f2c3ec4, 0x3f7d3f62, 0x3f5c3f7b, 0x3eac3f22, 0xbf67bf35, 0xbf78bf7f, 0xbf18bf55, 0x3d49be95, 0x3f803f6d, 0x3f4e3f75,
    0x3e793f0e, 0xbedbbdc9, 0xbf71bf80, 0xbf04bf46, 0x3e16be48, 0x3f3e3ef1, 0x3f3e3f6d, 0x3e163ef1, 0xbf04be48, 0xbf71bf46,
    0xbedbbf35, 0x3e79bdc9, 0x3f4e3f0e, 0x3f803f75, 0x3d493ec4, 0xbf18be95, 0xbf78bf55, 0xbf67bf7f, 0x3eac0000, 0x3f5c3f22,
    0x3f7d3f7b, 0x3f2c3f62, 0x3f673f80, 0x3e793f22, 0xbf18be48, 0xbf80bf62, 0xbf2cbf6d, 0x3e16be95, 0x3f5c3f0e, 0x3f713f7f,
    0x3eac3f35, 0xbf04bdc9, 0xbf7dbf55, 0xbf3ebf75, 0x3d49bec4, 0x3f4e3ef1, 0x3f783f7b, 0x3edb3f46, 0xbedb0000, 0xbf78bf46,
    0xbf4ebf7b, 0xbd49bef1, 0x3f3e3ec4, 0x3f7d3f75, 0x3f043f55, 0xbeac3dc9, 0xbf71bf35, 0xbf5cbf7f, 0xbe16bf0e, 0x3f2c3e95,
    0x3f803f6d, 0x3f183f62, 0xbe793e48, 0xbf67bf22, 0xbf3ebec4, 0xbf7dbf75, 0xbf04bf55, 0x3eacbdc9, 0x3edb0000, 0x3f783f46,
    0x3f4e3f7b, 0x3d493ef1, 0xbf80bf6d, 0xbf18bf62, 0x3e79be48, 0x3f673f22, 0x3f713f35, 0x3f5c3f7f, 0x3e163f0e, 0xbf2cbe95,
    0xbf2cbf6d, 0x3e16be95, 0x3f5c3f0e, 0x3f713f7f, 0x3f673f80, 0x3e793f22, 0xbf18be48, 0xbf80bf62, 0x3d49bec4, 0x3f4e3ef1,
    0x3f783f7b, 0x3edb3f46, 0x3eac3f35, 0xbf04bdc9, 0xbf7dbf55, 0xbf3ebf75, 0xbf78bf35, 0xbf2cbf75, 0x3eacbe48, 0x3f7d3f46,
    0x3f183f6d, 0xbedb3dc9, 0xbf80bf55, 0xbf04bf62, 0x3f5c3f80, 0xbd493ef1, 0xbf67bf0e, 0xbf4ebf7f, 0x3e16bec4, 0x3f713f22,
    0x3f3e3f7b, 0xbe793e95, 0x3e793f35, 0xbf3ebe95, 0xbf71bf7b, 0xbe16bf22, 0x3f4e3ec4, 0x3f673f7f, 0x3d493f0e, 0xbf5cbef1,
    0x3f040000, 0x3f803f62, 0x3edb3f55, 0xbf18bdc9, 0xbf7dbf6d, 0xbeacbf46, 0x3f2c3e48, 0x3f783f75, 0x3f4e3ec4, 0x3f673f7f,
    0x3d493f0e, 0xbf5cbef1, 0x3e793f35, 0xbf3ebe95, 0xbf71bf7b, 0xbe16bf22, 0xbf7dbf6d, 0xbeacbf46, 0x3f2c3e48, 0x3f783f75,
    0x3f040000, 0x3f803f62, 0x3edb3f55, 0xbf18bdc9, 0xbf18bf6d, 0x3edbbdc9, 0x3f803f55, 0x3f043f62, 0x3f783f35, 0x3f2c3f75,
    0xbeac3e48, 0xbf7dbf46, 0xbe163ec4, 0xbf71bf22, 0xbf3ebf7b, 0x3e79be95, 0xbf5cbf80, 0x3d49bef1, 0x3f673f0e, 0x3f4e3f7f,
    0xbf180000, 0xbf71bf75, 0x3d49bf0e, 0x3f783f22, 0x3f043f6d, 0xbf2cbdc9, 0xbf67bf7b, 0x3e16bef1, 0x3f7d3f35, 0x3edb3f62,
    0xbf3ebe48, 0xbf5cbf7f, 0x3e79bec4, 0x3f803f46, 0x3eac3f55, 0xbf4ebe95, 0x3f4e3f80, 0xbeac3e95, 0xbf80bf55, 0xbe79bf46,
    0x3f5c3ec4, 0x3f3e3f7f, 0xbedb3e48, 0xbf7dbf62, 0xbe16bf35, 0x3f673ef1, 0x3f2c3f7b, 0xbf043dc9, 0xbf78bf6d, 0xbd49bf22,
    0x3f713f0e, 0x3f183f75, 0x3f5c3ec4, 0x3f3e3f7f, 0xbedb3e48, 0xbf7dbf62, 0x3f4e3f80, 0xbeac3e95, 0xbf80bf55, 0xbe79bf46,
    0xbf78bf6d, 0xbd49bf22, 0x3f713f0e, 0x3f183f75, 0xbe16bf35, 0x3f673ef1, 0x3f2c3f7b, 0xbf043dc9, 0xbf04bf6d, 0x3f2c3dc9,
    0x3f673f7b, 0xbe163ef1, 0x3f180000, 0x3f713f75, 0xbd493f0e, 0xbf78bf22, 0xbe793ec4, 0xbf80bf46, 0xbeacbf55, 0x3f4e3e95,
    0xbf7dbf35, 0xbedbbf62, 0x3f3e3e48, 0x3f5c3f7f, 0xbd49bf35, 0x3f7d3f22, 0x3e793f55, 0xbf71bef1, 0xbedbbf6d, 0x3f5c3e95,
    0x3f183f7b, 0xbf3ebdc9, 0x3f2c0000, 0x3f4e3f7f, 0xbf043e48, 0xbf67bf75, 0x3eacbec4, 0x3f783f62, 0xbe163f0e, 0xbf80bf46,
    0x3f803f35, 0x3e163f46, 0xbf78bf0e, 0xbeacbf62, 0x3f673ec4, 0x3f043f75, 0xbf4ebe48, 0xbf2cbf7f, 0x3f3e3f80, 0xbf183dc9,
    0xbf5cbf7b, 0x3edbbe95, 0x3f713f6d, 0xbe793ef1, 0xbf7dbf55, 0x3d49bf22, 0xbf67bec4, 0xbf04bf75, 0x3f4e3e48, 0x3f2c3f7f,
    0xbf80bf35, 0xbe16bf46, 0x3f783f0e, 0x3eac3f62, 0xbf71bf6d, 0x3e79bef1, 0x3f7d3f55, 0xbd493f22, 0xbf3ebf80, 0x3f18bdc9,
    0x3f5c3f7b, 0xbedb3e95, 0xbedbbf6d, 0x3f5c3e95, 0x3f183f7b, 0xbf3ebdc9, 0xbd49bf35, 0x3f7d3f22, 0x3e793f55, 0xbf71bef1,
    0x3eacbec4, 0x3f783f62, 0xbe163f0e, 0xbf80bf46, 0x3f2c0000, 0x3f4e3f7f, 0xbf043e48, 0xbf67bf75, 0x3f2c3f80, 0xbf4ebdc9,
    0xbf04bf7b, 0x3f673e95, 0x3eac3f6d, 0xbf78bef1, 0xbe16bf55, 0x3f803f22, 0xbd493f35, 0xbf7dbf46, 0x3e79bf0e, 0x3f713f62,
    0xbedb3ec4, 0xbf5cbf75, 0x3f18be48, 0x3f3e3f7f, 0xbf3e0000, 0xbf18bf7f, 0x3f5c3e48, 0x3edb3f75, 0xbf71bec4, 0xbe79bf62,
    0x3f7d3f0e, 0x3d493f46, 0xbf80bf35, 0x3e16bf22, 0x3f783f55, 0xbeac3ef1, 0xbf67bf6d, 0x3f04be95, 0x3f4e3f7b, 0xbf2c3dc9,
    0x3f713ec4, 0x3e793f62, 0xbf7dbf0e, 0xbd49bf46, 0x3f3e0000, 0x3f183f7f, 0xbf5cbe48, 0xbedbbf75, 0x3f673f6d, 0xbf043e95,
    0xbf4ebf7b, 0x3f2cbdc9, 0x3f803f35, 0xbe163f22, 0xbf78bf55, 0x3eacbef1, 0x3eac3f6d, 0xbf78bef1, 0xbe16bf55, 0x3f803f22,
    0x3f2c3f80, 0xbf4ebdc9, 0xbf04bf7b, 0x3f673e95, 0xbedb3ec4, 0xbf5cbf75, 0x3f18be48, 0x3f3e3f7f, 0xbd493f35, 0xbf7dbf46,
    0x3e79bf0e, 0x3f713f62, 0xbf7dbf35, 0x3edbbef1, 0x3f3e3f7b, 0xbf5cbdc9, 0xbe79bf6d, 0x3f803f22, 0xbeac3f0e, 0xbf4ebf75,
    0x3f183f80, 0xbf71be95, 0xbd49bf55, 0x3f783f46, 0xbf043ec4, 0xbf2cbf7f, 0x3f673e48, 0x3e163f62, 0xbe163f35, 0xbf67bf62,
    0x3f2cbe48, 0x3f043f7f, 0xbf78bec4, 0x3d49bf46, 0x3f713f55, 0xbf183e95, 0x3f4e0000, 0x3eac3f75, 0xbf80bf0e, 0x3e79bf22,
    0x3f5c3f6d, 0xbf3e3dc9, 0xbedbbf7b, 0x3f7d3ef1, 0xbf78bec4, 0x3d49bf46, 0x3f713f55, 0xbf183e95, 0xbe163f35, 0xbf67bf62,
    0x3f2cbe48, 0x3f043f7f, 0x3f5c3f6d, 0xbf3e3dc9, 0xbedbbf7b, 0x3f7d3ef1, 0x3f4e0000, 0x3eac3f75, 0xbf80bf0e, 0x3e79bf22,
    0x3e793f6d, 0xbf80bf22, 0x3eacbf0e, 0x3f4e3f75, 0x3f7d3f35, 0xbedb3ef1, 0xbf3ebf7b, 0x3f5c3dc9, 0x3f04bec4, 0x3f2c3f7f,
    0xbf67be48, 0xbe16bf62, 0xbf18bf80, 0x3f713e95, 0x3d493f55, 0xbf78bf46, 0xbf5c0000, 0xbd49bf62, 0x3f673f55, 0xbf4e3dc9,
    0xbe16bf6d, 0x3f713f46, 0xbf3e3e48, 0xbe79bf75, 0x3f783f35, 0xbf2c3e95, 0xbeacbf7b, 0x3f7d3f22, 0xbf183ec4, 0xbedbbf7f,
    0x3f803f0e, 0xbf043ef1, 0x3f043f80, 0xbf80bef1, 0x3edbbf0e, 0x3f183f7f, 0xbf7dbec4, 0x3eacbf22, 0x3f2c3f7b, 0xbf78be95,
    0x3e79bf35, 0x3f3e3f75, 0xbf71be48, 0x3e16bf46, 0x3f4e3f6d, 0xbf67bdc9, 0x3d49bf55, 0x3f5c3f62, 0xbf7dbec4, 0x3eacbf22,
    0x3f2c3f7b, 0xbf78be95, 0x3f043f80, 0xbf80bef1, 0x3edbbf0e, 0x3f183f7f, 0x3f4e3f6d, 0xbf67bdc9, 0x3d49bf55, 0x3f5c3f62,
    0x3e79bf35, 0x3f3e3f75, 0xbf71be48, 0x3e16bf46, 0x3e163f6d, 0xbf71bf46, 0x3f3ebe48, 0x3e793f75, 0x3f5c0000, 0x3d493f62,
    0xbf67bf55, 0x3f4ebdc9, 0x3f18bec4, 0x3edb3f7f, 0xbf80bf0e, 0x3f04bef1, 0xbf78bf35, 0x3f2cbe95, 0x3eac3f7b, 0xbf7dbf22,
    0x3eacbf35, 0x3f043f7f, 0xbf7dbf0e, 0x3f3ebe95, 0x3d493f6d, 0xbf4ebf62, 0x3f783e48, 0xbedb3f22, 0x3f670000, 0xbe793f46,
    0xbf18bf7b, 0x3f803ef1, 0xbf2c3ec4, 0xbe16bf75, 0x3f5c3f55, 0xbf71bdc9, 0x3f713f35, 0xbf5c3dc9, 0x3e16bf55, 0x3f2c3f75,
    0xbf80bec4, 0x3f18bef1, 0x3e793f7b, 0xbf67bf46, 0x3edb3f80, 0xbf78bf22, 0x3f4ebe48, 0xbd493f62, 0xbf3ebf6d, 0x3f7d3e95,
    0xbf043f0e, 0xbeacbf7f, 0x3f803ec4, 0xbf183ef1, 0xbe79bf7b, 0x3f673f46, 0xbf71bf35, 0x3f5cbdc9, 0xbe163f55, 0xbf2cbf75,
    0x3f3e3f6d, 0xbf7dbe95, 0x3f04bf0e, 0x3eac3f7f, 0xbedbbf80, 0x3f783f22, 0xbf4e3e48, 0x3d49bf62, 0x3d493f6d, 0xbf4ebf62,
    0x3f783e48, 0xbedb3f22, 0x3eacbf35, 0x3f043f7f, 0xbf7dbf0e, 0x3f3ebe95, 0xbf2c3ec4, 0xbe16bf75, 0x3f5c3f55, 0xbf71bdc9,
    0x3f670000, 0xbe793f46, 0xbf18bf7b, 0x3f803ef1, 0x3eac3f80, 0xbf5cbf46, 0x3f7d3e48, 0xbf2c3ef1, 0x3d49bf6d, 0x3f183f75,
    0xbf78bf0e, 0x3f67bdc9, 0xbedb3f35, 0xbe79bf7f, 0x3f4e3f55, 0xbf80be95, 0x3f3ebec4, 0xbe163f62, 0xbf04bf7b, 0x3f713f22,
    0xbf710000, 0x3f04bf22, 0x3e163f7b, 0xbf3ebf62, 0x3f803ec4, 0xbf4e3e95, 0x3e79bf55, 0x3edb3f7f, 0xbf67bf35, 0x3f783dc9,
    0xbf183f0e, 0xbd49bf75, 0x3f2c3f6d, 0xbf7dbef1, 0x3f5cbe48, 0xbeac3f46, 0xbf80bec4, 0x3f4ebe95, 0xbe793f55, 0xbedbbf7f,
    0x3f710000, 0xbf043f22, 0xbe16bf7b, 0x3f3e3f62, 0xbf2cbf6d, 0x3f7d3ef1, 0xbf5c3e48, 0x3eacbf46, 0x3f673f35, 0xbf78bdc9,
    0x3f18bf0e, 0x3d493f75, 0x3d49bf6d, 0x3f183f75, 0xbf78bf0e, 0x3f67bdc9, 0x3eac3f80, 0xbf5cbf46, 0x3f7d3e48, 0xbf2c3ef1,
    0x3f3ebec4, 0xbe163f62, 0xbf04bf7b, 0x3f713f22, 0xbedb3f35, 0xbe79bf7f, 0x3f4e3f55, 0xbf80be95, 0xbf5cbf35, 0x3f803e95,
    0xbf673e48, 0x3f18bf22, 0xbe163f6d, 0xbeacbf7f, 0x3f3e3f55, 0xbf78bef1, 0x3e793f80, 0xbf2cbf62, 0x3f713f0e, 0xbf7dbdc9,
    0x3f4ebec4, 0xbedb3f46, 0xbd49bf7b, 0x3f043f75, 0xbf043f35, 0x3d49bf75, 0x3edb3f7b, 0xbf4ebf46, 0x3f7d3ec4, 0xbf713dc9,
    0x3f2cbf0e, 0xbe793f62, 0x3f780000, 0xbf3e3ef1, 0x3eacbf55, 0x3e163f7f, 0xbf18bf6d, 0x3f673f22, 0xbf80be48, 0x3f5cbe95,
    0x3f7d3ec4, 0xbf713dc9, 0x3f2cbf0e, 0xbe793f62, 0xbf043f35, 0x3d49bf75, 0x3edb3f7b, 0xbf4ebf46, 0xbf18bf6d, 0x3f673f22,
    0xbf80be48, 0x3f5cbe95, 0x3f780000, 0xbf3e3ef1, 0x3eacbf55, 0x3e163f7f, 0x3e16bf6d, 0x3eac3f7f, 0xbf3ebf55, 0x3f783ef1,
    0x3f5c3f35, 0xbf80be95, 0x3f67be48, 0xbf183f22, 0xbf4e3ec4, 0x3edbbf46, 0x3d493f7b, 0xbf04bf75, 0xbe79bf80, 0x3f2c3f62,
    0xbf71bf0e, 0x3f7d3dc9, 0xbf7d0000, 0x3f67be95, 0xbf3e3f0e, 0x3f04bf46, 0xbe793f6d, 0xbd49bf7f, 0x3eac3f7b, 0xbf18bf62,
    0x3f4e3f35, 0xbf71bef1, 0x3f803e48, 0xbf783dc9, 0x3f5cbec4, 0xbf2c3f22, 0x3edbbf55, 0xbe163f75, 0x3e163f80, 0xbedbbf75,
    0x3f2c3f55, 0xbf5cbf22, 0x3f783ec4, 0xbf80bdc9, 0x3f71be48, 0xbf4e3ef1, 0x3f18bf35, 0xbeac3f62, 0x3d49bf7b, 0x3e793f7f,
    0xbf04bf6d, 0x3f3e3f46, 0xbf67bf0e, 0x3f7d3e95, 0x3f783ec4, 0xbf80bdc9, 0x3f71be48, 0xbf4e3ef1, 0x3e163f80, 0xbedbbf75,
    0x3f2c3f55, 0xbf5cbf22, 0xbf04bf6d, 0x3f3e3f46, 0xbf67bf0e, 0x3f7d3e95, 0x3f18bf35, 0xbeac3f62, 0x3d49bf7b, 0x3e793f7f,
    0x3e79bf6d, 0x3d493f7f, 0xbeacbf7b, 0x3f183f62, 0x3f7d0000, 0xbf673e95, 0x3f3ebf0e, 0xbf043f46, 0xbf5c3ec4, 0x3f2cbf22,
    0xbedb3f55, 0x3e16bf75, 0xbf4ebf35, 0x3f713ef1, 0xbf80be48, 0x3f78bdc9, 0x3f2cbf35, 0xbf183f46, 0x3f04bf55, 0xbedb3f62,
    0x3eacbf6d, 0xbe793f75, 0x3e16bf7b, 0xbd493f7f, 0x3f800000, 0xbf7d3dc9, 0x3f78be48, 0xbf713e95, 0x3f67bec4, 0xbf5c3ef1,
    0x3f4ebf0e, 0xbf3e3f22, 0x3f3e3f35, 0xbf4ebf22, 0x3f5c3f0e, 0xbf67bef1, 0x3f713ec4, 0xbf78be95, 0x3f7d3e48, 0xbf80bdc9,
    0x3d493f80, 0xbe16bf7f, 0x3e793f7b, 0xbeacbf75, 0x3edb3f6d, 0xbf04bf62, 0x3f183f55, 0xbf2cbf46, 0xbf71bec4, 0x3f783e95,
    0xbf7dbe48, 0x3f803dc9, 0xbf3ebf35, 0x3f4e3f22, 0xbf5cbf0e, 0x3f673ef1, 0xbedbbf6d, 0x3f043f62, 0xbf18bf55, 0x3f2c3f46,
    0xbd49bf80, 0x3e163f7f, 0xbe79bf7b, 0x3eac3f75, 0x3eacbf6d, 0xbe793f75, 0x3e16bf7b, 0xbd493f7f, 0x3f2cbf35, 0xbf183f46,
    0x3f04bf55, 0xbedb3f62, 0x3f67bec4, 0xbf5c3ef1, 0x3f4ebf0e, 0xbf3e3f22, 0x3f800000, 0xbf7d3dc9, 0x3f78be48, 0xbf713e95,
    0xbd493f80, 0x3e16bf7f, 0xbe793f7b, 0x3eacbf75, 0xbedb3f6d, 0x3f04bf62, 0xbf183f55, 0x3f2cbf46, 0xbf3e3f35, 0x3f4ebf22,
    0xbf5c3f0e, 0x3f67bef1, 0xbf713ec4, 0x3f78be95, 0xbf7d3e48, 0x3f80bdc9, 0xbf800000, 0x3f7d3dc9, 0xbf78be48, 0x3f713e95,
    0xbf67bec4, 0x3f5c3ef1, 0xbf4ebf0e, 0x3f3e3f22, 0xbf2cbf35, 0x3f183f46, 0xbf04bf55, 0x3edb3f62, 0xbeacbf6d, 0x3e793f75,
    0xbe16bf7b, 0x3d493f7f, 0x3f673ec4, 0xbf5cbef1, 0x3f4e3f0e, 0xbf3ebf22, 0x3f800000, 0xbf7dbdc9, 0x3f783e48, 0xbf71be95,
    0x3eac3f6d, 0xbe79bf75, 0x3e163f7b, 0xbd49bf7f, 0x3f2c3f35, 0xbf18bf46, 0x3f043f55, 0xbedbbf62, 0xbedb3f6d, 0x3f04bf62,
    0xbf183f55, 0x3f2cbf46, 0xbd493f80, 0x3e16bf7f, 0xbe793f7b, 0x3eacbf75, 0xbf713ec4, 0x3f78be95, 0xbf7d3e48, 0x3f80bdc9,
    0xbf3e3f35, 0x3f4ebf22, 0xbf5c3f0e, 0x3f67bef1, 0xbf18bf35, 0x3eac3f62, 0xbd49bf7b, 0xbe793f7f, 0x3f04bf6d, 0xbf3e3f46,
    0x3f67bf0e, 0xbf7d3e95, 0xbe163f80, 0x3edbbf75, 0xbf2c3f55, 0x3f5cbf22, 0xbf783ec4, 0x3f80bdc9, 0xbf71be48, 0x3f4e3ef1,
    0xbf4e3f35, 0x3f71bef1, 0xbf803e48, 0x3f783dc9, 0xbf5cbec4, 0x3f2c3f22, 0xbedbbf55, 0x3e163f75, 0x3f7d0000, 0xbf67be95,
    0x3f3e3f0e, 0xbf04bf46, 0x3e793f6d, 0x3d49bf7f, 0xbeac3f7b, 0x3f18bf62, 0xbf5cbec4, 0x3f2c3f22, 0xbedbbf55, 0x3e163f75,
    0xbf4e3f35, 0x3f71bef1, 0xbf803e48, 0x3f783dc9, 0x3e793f6d, 0x3d49bf7f, 0xbeac3f7b, 0x3f18bf62, 0x3f7d0000, 0xbf67be95,
    0x3f3e3f0e, 0xbf04bf46, 0xbf043f6d, 0x3f3ebf46, 0xbf673f0e, 0x3f7dbe95, 0x3f183f35, 0xbeacbf62, 0x3d493f7b, 0x3e79bf7f,
    0x3f78bec4, 0xbf803dc9, 0x3f713e48, 0xbf4ebef1, 0x3e16bf80, 0xbedb3f75, 0x3f2cbf55, 0xbf5c3f22, 0xbf780000, 0x3f3e3ef1,
    0xbeacbf55, 0xbe163f7f, 0x3f18bf6d, 0xbf673f22, 0x3f80be48, 0xbf5cbe95, 0x3f043f35, 0xbd49bf75, 0xbedb3f7b, 0x3f4ebf46,
    0xbf7d3ec4, 0x3f713dc9, 0xbf2cbf0e, 0x3e793f62, 0xbe793f80, 0x3f2cbf62, 0xbf713f0e, 0x3f7dbdc9, 0xbf4ebec4, 0x3edb3f46,
    0x3d49bf7b, 0xbf043f75, 0x3f5cbf35, 0xbf803e95, 0x3f673e48, 0xbf18bf22, 0x3e163f6d, 0x3eacbf7f, 0xbf3e3f55, 0x3f78bef1,
    0xbf4ebec4, 0x3edb3f46, 0x3d49bf7b, 0xbf043f75, 0xbe793f80, 0x3f2cbf62, 0xbf713f0e, 0x3f7dbdc9, 0x3e163f6d, 0x3eacbf7f,
    0xbf3e3f55, 0x3f78bef1, 0x3f5cbf35, 0xbf803e95, 0x3f673e48, 0xbf18bf22, 0xbf183f6d, 0x3f67bf22, 0xbf803e48, 0x3f5c3e95,
    0x3f780000, 0xbf3ebef1, 0x3eac3f55, 0x3e16bf7f, 0x3f7dbec4, 0xbf71bdc9, 0x3f2c3f0e, 0xbe79bf62, 0xbf04bf35, 0x3d493f75,
    0x3edbbf7b, 0xbf4e3f46, 0x3f67bf35, 0xbf783dc9, 0x3f183f0e, 0x3d49bf75, 0xbf2c3f6d, 0x3f7dbef1, 0xbf5cbe48, 0x3eac3f46,
    0x3f710000, 0xbf04bf22, 0xbe163f7b, 0x3f3ebf62, 0xbf803ec4, 0x3f4e3e95, 0xbe79bf55, 0xbedb3f7f, 0x3edb3f35, 0x3e79bf7f,
    0xbf4e3f55, 0x3f80be95, 0xbf3ebec4, 0x3e163f62, 0x3f04bf7b, 0xbf713f22, 0xbeac3f80, 0x3f5cbf46, 0xbf7d3e48, 0x3f2c3ef1,
    0xbd49bf6d, 0xbf183f75, 0x3f78bf0e, 0xbf67bdc9, 0x3f3e3ec4, 0xbe16bf62, 0xbf043f7b, 0x3f71bf22, 0xbedbbf35, 0xbe793f7f,
    0x3f4ebf55, 0xbf803e95, 0x3d493f6d, 0x3f18bf75, 0xbf783f0e, 0x3f673dc9, 0x3eacbf80, 0xbf5c3f46, 0x3f7dbe48, 0xbf2cbef1,
    0xbf2c3f6d, 0x3f7dbef1, 0xbf5cbe48, 0x3eac3f46, 0x3f67bf35, 0xbf783dc9, 0x3f183f0e, 0x3d49bf75, 0xbf803ec4, 0x3f4e3e95,
    0xbe79bf55, 0xbedb3f7f, 0x3f710000, 0xbf04bf22, 0xbe163f7b, 0x3f3ebf62, 0xbedb3f80, 0x3f78bf22, 0xbf4ebe48, 0x3d493f62,
    0x3f3ebf6d, 0xbf7d3e95, 0x3f043f0e, 0x3eacbf7f, 0xbf713f35, 0x3f5c3dc9, 0xbe16bf55, 0xbf2c3f75, 0x3f80bec4, 0xbf18bef1,
    0xbe793f7b, 0x3f67bf46, 0xbf670000, 0x3e793f46, 0x3f18bf7b, 0xbf803ef1, 0x3f2c3ec4, 0x3e16bf75, 0xbf5c3f55, 0x3f71bdc9,
    0xbeacbf35, 0xbf043f7f, 0x3f7dbf0e, 0xbf3ebe95, 0xbd493f6d, 0x3f4ebf62, 0xbf783e48, 0x3edb3f22, 0xbf2cbec4, 0xbe163f75,
    0x3f5cbf55, 0xbf713dc9, 0x3f670000, 0xbe79bf46, 0xbf183f7b, 0x3f80bef1, 0x3d49bf6d, 0xbf4e3f62, 0x3f78be48, 0xbedbbf22,
    0x3eac3f35, 0x3f04bf7f, 0xbf7d3f0e, 0x3f3e3e95, 0x3f3ebf6d, 0xbf7d3e95, 0x3f043f0e, 0x3eacbf7f, 0xbedb3f80, 0x3f78bf22,
    0xbf4ebe48, 0x3d493f62, 0x3f80bec4, 0xbf18bef1, 0xbe793f7b, 0x3f67bf46, 0xbf713f35, 0x3f5c3dc9, 0xbe16bf55, 0xbf2c3f75,
    0xbe79bf35, 0xbf3e3f75, 0x3f71be48, 0xbe16bf46, 0xbf4e3f6d, 0x3f67bdc9, 0xbd49bf55, 0xbf5c3f62, 0xbf043f80, 0x3f80bef1,
    0xbedbbf0e, 0xbf183f7f, 0x3f7dbec4, 0xbeacbf22, 0xbf2c3f7b, 0x3f78be95, 0xbf783f35, 0x3f2c3e95, 0x3eacbf7b, 0xbf7d3f22,
    0x3f183ec4, 0x3edbbf7f, 0xbf803f0e, 0x3f043ef1, 0x3f5c0000, 0x3d49bf62, 0xbf673f55, 0x3f4e3dc9, 0x3e16bf6d, 0xbf713f46,
    0x3f3e3e48, 0x3e79bf75, 0x3f183ec4, 0x3edbbf7f, 0xbf803f0e, 0x3f043ef1, 0xbf783f35, 0x3f2c3e95, 0x3eacbf7b, 0xbf7d3f22,
    0x3e16bf6d, 0xbf713f46, 0x3f3e3e48, 0x3e79bf75, 0x3f5c0000, 0x3d49bf62, 0xbf673f55, 0x3f4e3dc9, 0x3f4ebf6d, 0xbf673dc9,
    0x3d493f55, 0x3f5cbf62, 0x3e793f35, 0x3f3ebf75, 0xbf713e48, 0x3e163f46, 0xbf7d3ec4, 0x3eac3f22, 0x3f2cbf7b, 0xbf783e95,
    0x3f04bf80, 0xbf803ef1, 0x3edb3f0e, 0x3f18bf7f, 0xbf4e0000, 0xbeac3f75, 0x3f80bf0e, 0xbe79bf22, 0xbf5c3f6d, 0x3f3e3dc9,
    0x3edbbf7b, 0xbf7d3ef1, 0x3e163f35, 0x3f67bf62, 0xbf2cbe48, 0xbf043f7f, 0x3f78bec4, 0xbd49bf46, 0xbf713f55, 0x3f183e95,
    0xbf183f80, 0x3f71be95, 0x3d49bf55, 0xbf783f46, 0x3f043ec4, 0x3f2cbf7f, 0xbf673e48, 0xbe163f62, 0x3f7dbf35, 0xbedbbef1,
    0xbf3e3f7b, 0x3f5cbdc9, 0x3e79bf6d, 0xbf803f22, 0x3eac3f0e, 0x3f4ebf75, 0x3f043ec4, 0x3f2cbf7f, 0xbf673e48, 0xbe163f62,
    0xbf183f80, 0x3f71be95, 0x3d49bf55, 0xbf783f46, 0x3e79bf6d, 0xbf803f22, 0x3eac3f0e, 0x3f4ebf75, 0x3f7dbf35, 0xbedbbef1,
    0xbf3e3f7b, 0x3f5cbdc9, 0x3f5cbf6d, 0xbf3ebdc9, 0xbedb3f7b, 0x3f7dbef1, 0x3f4e0000, 0x3eacbf75, 0xbf803f0e, 0x3e793f22,
    0xbf783ec4, 0x3d493f46, 0x3f71bf55, 0xbf18be95, 0xbe16bf35, 0xbf673f62, 0x3f2c3e48, 0x3f04bf7f, 0x3f80bf35, 0xbe16bf22,
    0xbf783f55, 0x3eac3ef1, 0x3f67bf6d, 0xbf04be95, 0xbf4e3f7b, 0x3f2c3dc9, 0x3f3e0000, 0x3f18bf7f, 0xbf5c3e48, 0xbedb3f75,
    0x3f71bec4, 0x3e79bf62, 0xbf7d3f0e, 0xbd493f46, 0x3d493f35, 0x3f7dbf46, 0xbe79bf0e, 0xbf713f62, 0x3edb3ec4, 0x3f5cbf75,
    0xbf18be48, 0xbf3e3f7f, 0xbf2c3f80, 0x3f4ebdc9, 0x3f04bf7b, 0xbf673e95, 0xbeac3f6d, 0x3f78bef1, 0x3e16bf55, 0xbf803f22,
    0xbedbbec4, 0xbf5c3f75, 0x3f183e48, 0x3f3ebf7f, 0xbd49bf35, 0xbf7d3f46, 0x3e793f0e, 0x3f71bf62, 0x3eacbf6d, 0xbf783ef1,
    0xbe163f55, 0x3f80bf22, 0x3f2cbf80, 0xbf4e3dc9, 0xbf043f7b, 0x3f67be95, 0x3f67bf6d, 0xbf04be95, 0xbf4e3f7b, 0x3f2c3dc9,
    0x3f80bf35, 0xbe16bf22, 0xbf783f55, 0x3eac3ef1, 0x3f71bec4, 0x3e79bf62, 0xbf7d3f0e, 0xbd493f46, 0x3f3e0000, 0x3f18bf7f,
    0xbf5c3e48, 0xbedb3f75, 0xbf3e3f80, 0x3f183dc9, 0x3f5cbf7b, 0xbedbbe95, 0xbf713f6d, 0x3e793ef1, 0x3f7dbf55, 0xbd49bf22,
    0xbf803f35, 0xbe163f46, 0x3f78bf0e, 0x3eacbf62, 0xbf673ec4, 0xbf043f75, 0x3f4ebe48, 0x3f2cbf7f, 0xbf2c0000, 0xbf4e3f7f,
    0x3f043e48, 0x3f67bf75, 0xbeacbec4, 0xbf783f62, 0x3e163f0e, 0x3f80bf46, 0x3d49bf35, 0xbf7d3f22, 0xbe793f55, 0x3f71bef1,
    0x3edbbf6d, 0xbf5c3e95, 0xbf183f7b, 0x3f3ebdc9, 0x3eac3ec4, 0x3f78bf62, 0xbe16bf0e, 0xbf803f46, 0x3f2c0000, 0x3f4ebf7f,
    0xbf04be48, 0xbf673f75, 0xbedb3f6d, 0x3f5cbe95, 0x3f18bf7b, 0xbf3e3dc9, 0xbd493f35, 0x3f7dbf22, 0x3e79bf55, 0xbf713ef1,
    0xbf713f6d, 0x3e793ef1, 0x3f7dbf55, 0xbd49bf22, 0xbf3e3f80, 0x3f183dc9, 0x3f5cbf7b, 0xbedbbe95, 0xbf673ec4, 0xbf043f75,
    0x3f4ebe48, 0x3f2cbf7f, 0xbf803f35, 0xbe163f46, 0x3f78bf0e, 0x3eacbf62, 0x3e16bf35, 0xbf673ef1, 0xbf2c3f7b, 0x3f043dc9,
    0x3f78bf6d, 0x3d49bf22, 0xbf713f0e, 0xbf183f75, 0xbf4e3f80, 0x3eac3e95, 0x3f80bf55, 0x3e79bf46, 0xbf5c3ec4, 0xbf3e3f7f,
    0x3edb3e48, 0x3f7dbf62, 0xbf7d3f35, 0xbedb3f62, 0x3f3ebe48, 0x3f5cbf7f, 0xbe79bec4, 0xbf803f46, 0xbeac3f55, 0x3f4ebe95,
    0x3f180000, 0x3f71bf75, 0xbd49bf0e, 0xbf783f22, 0xbf043f6d, 0x3f2cbdc9, 0x3f67bf7b, 0xbe16bef1, 0xbe79bec4, 0xbf803f46,
    0xbeac3f55, 0x3f4ebe95, 0xbf7d3f35, 0xbedb3f62, 0x3f3ebe48, 0x3f5cbf7f, 0xbf043f6d, 0x3f2cbdc9, 0x3f67bf7b, 0xbe16bef1,
    0x3f180000, 0x3f71bf75, 0xbd49bf0e, 0xbf783f22, 0xbf783f6d, 0xbd493f22, 0x3f71bf0e, 0x3f18bf75, 0xbe163f35, 0x3f67bef1,
    0x3f2cbf7b, 0xbf04bdc9, 0x3f5cbec4, 0x3f3ebf7f, 0xbedbbe48, 0xbf7d3f62, 0x3f4ebf80, 0xbeacbe95, 0xbf803f55, 0xbe793f46,
    0xbf040000, 0xbf803f62, 0xbedb3f55, 0x3f18bdc9, 0x3f7dbf6d, 0x3eacbf46, 0xbf2c3e48, 0xbf783f75, 0xbe793f35, 0x3f3ebe95,
    0x3f71bf7b, 0x3e16bf22, 0xbf4e3ec4, 0xbf673f7f, 0xbd493f0e, 0x3f5cbef1, 0xbf5c3f80, 0x3d493ef1, 0x3f67bf0e, 0x3f4ebf7f,
    0xbe16bec4, 0xbf713f22, 0xbf3e3f7b, 0x3e793e95, 0x3f78bf35, 0x3f2cbf75, 0xbeacbe48, 0xbf7d3f46, 0xbf183f6d, 0x3edb3dc9,
    0x3f80bf55, 0x3f04bf62, 0xbe16bec4, 0xbf713f22, 0xbf3e3f7b, 0x3e793e95, 0xbf5c3f80, 0x3d493ef1, 0x3f67bf0e, 0x3f4ebf7f,
    0xbf183f6d, 0x3edb3dc9, 0x3f80bf55, 0x3f04bf62, 0x3f78bf35, 0x3f2cbf75, 0xbeacbe48, 0xbf7d3f46, 0xbf7d3f6d, 0xbeac3f46,
    0x3f2cbe48, 0x3f78bf75, 0x3f040000, 0x3f80bf62, 0x3edbbf55, 0xbf183dc9, 0x3f4ebec4, 0x3f67bf7f, 0x3d49bf0e, 0xbf5c3ef1,
    0x3e79bf35, 0xbf3e3e95, 0xbf713f7b, 0xbe163f22, 0x3f71bf35, 0x3f5cbf7f, 0x3e16bf0e, 0xbf2c3e95, 0xbf803f6d, 0xbf183f62,
    0x3e793e48, 0x3f67bf22, 0x3edb0000, 0x3f78bf46, 0x3f4ebf7b, 0x3d49bef1, 0xbf3e3ec4, 0xbf7d3f75, 0xbf043f55, 0x3eac3dc9,
    0xbeac3f35, 0x3f04bdc9, 0x3f7dbf55, 0x3f3ebf75, 0xbd49bec4, 0xbf4e3ef1, 0xbf783f7b, 0xbedb3f46, 0xbf673f80, 0xbe793f22,
    0x3f18be48, 0x3f80bf62, 0x3f2cbf6d, 0xbe16be95, 0xbf5c3f0e, 0xbf713f7f, 0x3d493ec4, 0x3f4ebef1, 0x3f78bf7b, 0x3edbbf46,
    0x3eacbf35, 0xbf043dc9, 0xbf7d3f55, 0xbf3e3f75, 0xbf2c3f6d, 0x3e163e95, 0x3f5cbf0e, 0x3f71bf7f, 0x3f67bf80, 0x3e79bf22,
    0xbf183e48, 0xbf803f62, 0xbf803f6d, 0xbf183f62, 0x3e793e48, 0x3f67bf22, 0x3f71bf35, 0x3f5cbf7f, 0x3e16bf0e, 0xbf2c3e95,
    0xbf3e3ec4, 0xbf7d3f75, 0xbf043f55, 0x3eac3dc9, 0x3edb0000, 0x3f78bf46, 0x3f4ebf7b, 0x3d49bef1, 0xbf713f80, 0xbf043f46,
    0x3e163e48, 0x3f3ebef1, 0x3f80bf6d, 0x3f4ebf75, 0x3e79bf0e, 0xbedb3dc9, 0xbf673f35, 0xbf783f7f, 0xbf183f55, 0x3d493e95,
    0x3f2cbec4, 0x3f7dbf62, 0x3f5cbf7b, 0x3eacbf22, 0xbeac0000, 0xbf5c3f22, 0xbf7d3f7b, 0xbf2c3f62, 0xbd493ec4, 0x3f18be95,
    0x3f78bf55, 0x3f67bf7f, 0x3edbbf35, 0xbe79bdc9, 0xbf4e3f0e, 0xbf803f75, 0xbf3e3f6d, 0xbe163ef1, 0x3f04be48, 0x3f71bf46,
    0x3d49bec4, 0xbf183e95, 0xbf783f55, 0xbf673f7f, 0x3eac0000, 0x3f5cbf22, 0x3f7dbf7b, 0x3f2cbf62, 0x3f3ebf6d, 0x3e16bef1,
    0xbf043e48, 0xbf713f46, 0xbedb3f35, 0x3e793dc9, 0x3f4ebf0e, 0x3f80bf75, 0x3f80bf6d, 0x3f4ebf75, 0x3e79bf0e, 0xbedb3dc9,
    0xbf713f80, 0xbf043f46, 0x3e163e48, 0x3f3ebef1, 0x3f2cbec4, 0x3f7dbf62, 0x3f5cbf7b, 0x3eacbf22, 0xbf673f35, 0xbf783f7f,
    0xbf183f55, 0x3d493e95, 0x3f04bf35, 0x3d49be95, 0xbedb3e48, 0xbf4e3f22, 0xbf7d3f6d, 0xbf713f7f, 0xbf2c3f55, 0xbe793ef1,
    0xbf783f80, 0xbf3e3f62, 0xbeac3f0e, 0x3e163dc9, 0x3f18bec4, 0x3f67bf46, 0x3f80bf7b, 0x3f5cbf75, 0xbf5c3f35, 0xbf803f75,
    0xbf673f7b, 0xbf183f46, 0xbe163ec4, 0x3eacbdc9, 0x3f3ebf0e, 0x3f78bf62, 0x3e790000, 0x3f2cbef1, 0x3f71bf55, 0x3f7dbf7f,
    0x3f4ebf6d, 0x3edbbf22, 0xbd49be48, 0xbf043e95, 0xbe163ec4, 0x3eacbdc9, 0x3f3ebf0e, 0x3f78bf62, 0xbf5c3f35, 0xbf803f75,
    0xbf673f7b, 0xbf183f46, 0x3f4ebf6d, 0x3edbbf22, 0xbd49be48, 0xbf043e95, 0x3e790000, 0x3f2cbef1, 0x3f71bf55, 0x3f7dbf7f,
    0x3f7dbf6d, 0x3f71bf7f, 0x3f2cbf55, 0x3e79bef1, 0xbf043f35, 0xbd493e95, 0x3edbbe48, 0x3f4ebf22, 0xbf183ec4, 0xbf673f46,
    0xbf803f7b, 0xbf5c3f75, 0x3f78bf80, 0x3f3ebf62, 0x3eacbf0e, 0xbe16bdc9, 0xbe160000, 0xbedb3e95, 0xbf2c3f0e, 0xbf5c3f46,
    0xbf783f6d, 0xbf803f7f, 0xbf713f7b, 0xbf4e3f62, 0xbf183f35, 0xbeac3ef1, 0xbd493e48, 0x3e79bdc9, 0x3f04bec4, 0x3f3ebf22,
    0x3f67bf55, 0x3f7dbf75, 0xbf7d3f80, 0xbf673f75, 0xbf3e3f55, 0xbf043f22, 0xbe793ec4, 0x3d493dc9, 0x3eacbe48, 0x3f18bef1,
    0x3f4ebf35, 0x3f71bf62, 0x3f80bf7b, 0x3f78bf7f, 0x3f5cbf6d, 0x3f2cbf46, 0x3edbbf0e, 0x3e16be95, 0xbe793ec4, 0x3d493dc9,
    0x3eacbe48, 0x3f18bef1, 0xbf7d3f80, 0xbf673f75, 0xbf3e3f55, 0xbf043f22, 0x3f5cbf6d, 0x3f2cbf46, 0x3edbbf0e, 0x3e16be95,
    0x3f4ebf35, 0x3f71bf62, 0x3f80bf7b, 0x3f78bf7f, 0x3f78bf6d, 0x3f80bf7f, 0x3f71bf7b, 0x3f4ebf62, 0x3e160000, 0x3edbbe95,
    0x3f2cbf0e, 0x3f5cbf46, 0xbf043ec4, 0xbf3e3f22, 0xbf673f55, 0xbf7d3f75, 0x3f18bf35, 0x3eacbef1, 0x3d49be48, 0xbe793dc9,
    0x3f3ebf35, 0x3f4ebf46, 0x3f5cbf55, 0x3f67bf62, 0x3f71bf6d, 0x3f78bf75, 0x3f7dbf7b, 0x3f80bf7f, 0x3d490000, 0x3e16bdc9,
    0x3e79be48, 0x3eacbe95, 0x3edbbec4, 0x3f04bef1, 0x3f18bf0e, 0x3f2cbf22, 0xbf2c3f35, 0xbf183f22, 0xbf043f0e, 0xbedb3ef1,
    0xbeac3ec4, 0xbe793e95, 0xbe163e48, 0xbd493dc9, 0xbf803f80, 0xbf7d3f7f, 0xbf783f7b, 0xbf713f75, 0xbf673f6d, 0xbf5c3f62,
    0xbf4e3f55, 0xbf3e3f46, 0x3eacbec4, 0x3e79be95, 0x3e16be48, 0x3d49bdc9, 0x3f2cbf35, 0x3f18bf22, 0x3f04bf0e, 0x3edbbef1,
    0x3f67bf6d, 0x3f5cbf62, 0x3f4ebf55, 0x3f3ebf46, 0x3f80bf80, 0x3f7dbf7f, 0x3f78bf7b, 0x3f71bf75, 0x3f71bf6d, 0x3f78bf75,
    0x3f7dbf7b, 0x3f80bf7f, 0x3f3ebf35, 0x3f4ebf46, 0x3f5cbf55, 0x3f67bf62, 0x3edbbec4, 0x3f04bef1, 0x3f18bf0e, 0x3f2cbf22,
    0x3d490000, 0x3e16bdc9, 0x3e79be48, 0x3eacbe95,
};
__device__ const __align__(128) uint32_t c_ga[1536] = {
    0x00003c80, 0x3bc43c6d, 0x00003c80, 0xbbc4bc6d, 0x00003c80, 0x3c6d3bc4, 0x00003c80, 0xbc6dbbc4, 0x00003c80, 0x3c6dbbc4,
    0x00003c80, 0xbc6d3bc4, 0x00003c80, 0x3bc4bc6d, 0x00003c80, 0xbbc43c6d, 0x3a493c80, 0x3bdb3c67, 0x3bdb3c67, 0xbc3ebc2c,
    0x3b163c7d, 0x3c783b79, 0x3c043c5c, 0xbc7d3b16, 0x3b793c78, 0x3c4ebc18, 0x3c183c4e, 0xbc043c5c, 0x3bac3c71, 0x3a49bc80,
    0x3c2c3c3e, 0x3bac3c71, 0x3ac93c7f, 0x3bf13c62, 0x3c463c22, 0xbc75bb95, 0x3b953c75, 0x3c7f3ac9, 0x3c623bf1, 0xbc463c22,
    0x3bf13c62, 0x3c22bc46, 0x3c753b95, 0x3ac93c7f, 0x3c223c46, 0xbb95bc75, 0x3c7f3ac9, 0x3c623bf1, 0x3b163c7d, 0x3c043c5c,
    0x3c783b79, 0xbc7d3b16, 0x3bdb3c67, 0x3c80ba49, 0x3c80ba49, 0xbbac3c71, 0x3c2c3c3e, 0x3bdbbc67, 0x3c71bbac, 0x3c2c3c3e,
    0x3c5c3c04, 0xbc18bc4e, 0x3c4ebc18, 0x3c78bb79, 0x3b483c7b, 0x3c0e3c55, 0x3c7bbb48, 0xbc553c0e, 0x3c0e3c55, 0x3c7bbb48,
    0x3c55bc0e, 0x3b483c7b, 0x3c553c0e, 0x3b48bc7b, 0x3c0ebc55, 0x3c7b3b48, 0x3c7b3b48, 0xbc55bc0e, 0x3b48bc7b, 0x3c0ebc55,
    0x3b793c78, 0x3c183c4e, 0x3c4ebc18, 0xbc043c5c, 0x3c2c3c3e, 0x3c71bbac, 0x3bdbbc67, 0x3c2c3c3e, 0x3c713bac, 0xba49bc80,
    0xba49bc80, 0x3c67bbdb, 0x3c7dbb16, 0xbc78bb79, 0xbc04bc5c, 0xbb16bc7d, 0x3b953c75, 0x3c223c46, 0x3bf1bc62, 0xbac93c7f,
    0x3c463c22, 0x3c62bbf1, 0xbac9bc7f, 0x3c753b95, 0x3c7f3ac9, 0xbb95bc75, 0xbc22bc46, 0x3bf1bc62, 0x3c62bbf1, 0xbc7f3ac9,
    0xbc75bb95, 0xbc46bc22, 0x3bac3c71, 0x3c2c3c3e, 0x3a49bc80, 0x3bac3c71, 0x3c5c3c04, 0x3c4ebc18, 0xbc18bc4e, 0x3c78bb79,
    0x3c7dbb16, 0xbc04bc5c, 0xbc78bb79, 0xbb16bc7d, 0x3c2cbc3e, 0xbc673bdb, 0xbc673bdb, 0xbc803a49, 0x00003c80, 0x3bc43c6d,
    0x00003c80, 0xbbc4bc6d, 0x00003c80, 0x3c6d3bc4, 0x00003c80, 0xbc6dbbc4, 0x00003c80, 0x3c6dbbc4, 0x00003c80, 0xbc6d3bc4,
    0x00003c80, 0x3bc4bc6d, 0x00003c80, 0xbbc43c6d, 0x3c3e3c2c, 0x3c713bac, 0x3c713bac, 0xbc803a49, 0x3c4e3c18, 0x3c5cbc04,
    0x3c783b79, 0xbc183c4e, 0x3c5c3c04, 0x3b16bc7d, 0x3c7d3b16, 0x3b793c78, 0x3c673bdb, 0xbc2cbc3e, 0x3c803a49, 0x3c673bdb,
    0x3c7fbac9, 0x3c62bbf1, 0x3c22bc46, 0xbb953c75, 0x3c75bb95, 0x3ac9bc7f, 0x3bf1bc62, 0x3c223c46, 0x3c62bbf1, 0xbc46bc22,
    0x3b95bc75, 0x3c7fbac9, 0x3c46bc22, 0xbc753b95, 0x3ac9bc7f, 0x3bf1bc62, 0x3c18bc4e, 0x3b79bc78, 0xbc04bc5c, 0x3c4e3c18,
    0x3bacbc71, 0xbc3ebc2c, 0xbc3ebc2c, 0x3c67bbdb, 0x3a49bc80, 0xbc713bac, 0xbc67bbdb, 0x3a49bc80, 0xbb79bc78, 0xbb163c7d,
    0xbc7dbb16, 0xbc5cbc04, 0xbb48bc7b, 0xbc0ebc55, 0xbc7b3b48, 0x3c55bc0e, 0xbc0ebc55, 0xbc7b3b48, 0xbc553c0e, 0xbb48bc7b,
    0xbc55bc0e, 0xbb483c7b, 0xbc0e3c55, 0xbc7bbb48, 0xbc7bbb48, 0x3c553c0e, 0xbb483c7b, 0xbc0e3c55, 0xbc5cbc04, 0xbc7dbb16,
    0xbb163c7d, 0xbb79bc78, 0xbc80ba49, 0xbbdb3c67, 0x3bac3c71, 0xbc80ba49, 0xbc673bdb, 0x3c3e3c2c, 0x3c3e3c2c, 0xbbac3c71,
    0xbc183c4e, 0x3c5cbc04, 0x3c783b79, 0x3c4e3c18, 0xbc753b95, 0xbc463c22, 0x3c623bf1, 0xbc7fbac9, 0xbc223c46, 0x3bf13c62,
    0x3c7fbac9, 0xbb953c75, 0xbac93c7f, 0x3c75bb95, 0x3c46bc22, 0x3c623bf1, 0x3bf13c62, 0xbac9bc7f, 0x3b95bc75, 0x3c22bc46,
    0xbbdb3c67, 0xba493c80, 0x3c3ebc2c, 0xbbdb3c67, 0x3b793c78, 0x3c7d3b16, 0x3b16bc7d, 0x3c5c3c04, 0x3c4e3c18, 0x3b79bc78,
    0xbc04bc5c, 0x3c18bc4e, 0x3c80ba49, 0xbc71bbac, 0xbc71bbac, 0xbc3ebc2c, 0x00003c80, 0x3bc43c6d, 0x00003c80, 0xbbc4bc6d,
    0x00003c80, 0x3c6d3bc4, 0x00003c80, 0xbc6dbbc4, 0x00003c80, 0x3c6dbbc4, 0x00003c80, 0xbc6d3bc4, 0x00003c80, 0x3bc4bc6d,
    0x00003c80, 0xbbc43c6d, 0x3c80ba49, 0x3c67bbdb, 0x3c67bbdb, 0xbc2c3c3e, 0x3c7dbb16, 0x3b79bc78, 0x3c5cbc04, 0x3b163c7d,
    0x3c78bb79, 0xbc18bc4e, 0x3c4ebc18, 0x3c5c3c04, 0x3c71bbac, 0xbc80ba49, 0x3c3ebc2c, 0x3c71bbac, 0xbac9bc7f, 0xbbf1bc62,
    0xbc46bc22, 0x3c753b95, 0xbb95bc75, 0xbc7fbac9, 0xbc62bbf1, 0x3c46bc22, 0xbbf1bc62, 0xbc223c46, 0xbc75bb95, 0xbac9bc7f,
    0xbc22bc46, 0x3b953c75, 0xbc7fbac9, 0xbc62bbf1, 0xbc7d3b16, 0xbc5c3c04, 0xbb793c78, 0xbb16bc7d, 0xbc673bdb, 0x3a493c80,
    0x3a493c80, 0xbc71bbac, 0xbc3e3c2c, 0x3c673bdb, 0x3bac3c71, 0xbc3e3c2c, 0xbc043c5c, 0x3c4ebc18, 0x3c183c4e, 0x3b793c78,
    0x3b483c7b, 0x3c0e3c55, 0x3c7bbb48, 0xbc553c0e, 0x3c0e3c55, 0x3c7bbb48, 0x3c55bc0e, 0x3b483c7b, 0x3c553c0e, 0x3b48bc7b,
    0x3c0ebc55, 0x3c7b3b48, 0x3c7b3b48, 0xbc55bc0e, 0x3b48bc7b, 0x3c0ebc55, 0x3c78bb79, 0x3c4ebc18, 0xbc18bc4e, 0x3c5c3c04,
    0x3c3ebc2c, 0xbbacbc71, 0xbc67bbdb, 0x3c3ebc2c, 0x3bacbc71, 0xbc803a49, 0xbc803a49, 0xbbdbbc67, 0xbb16bc7d, 0xbb793c78,
    0xbc5c3c04, 0xbc7d3b16, 0xbb95bc75, 0xbc22bc46, 0xbbf13c62, 0x3ac9bc7f, 0xbc46bc22, 0xbc623bf1, 0x3ac93c7f, 0xbc75bb95,
    0xbc7fbac9, 0x3b953c75, 0x3c223c46, 0xbbf13c62, 0xbc623bf1, 0x3c7fbac9, 0x3c753b95, 0x3c463c22, 0xbc713bac, 0xbc3e3c2c,
    0x3c803a49, 0xbc713bac, 0xbc043c5c, 0x3c183c4e, 0x3c4ebc18, 0x3b793c78, 0x3b163c7d, 0x3c5cbc04, 0x3b79bc78, 0x3c7dbb16,
    0x3c3e3c2c, 0xbbdbbc67, 0xbbdbbc67, 0xba49bc80, 0x00003c80, 0x3bc43c6d, 0x00003c80, 0xbbc4bc6d, 0x00003c80, 0x3c6d3bc4,
    0x00003c80, 0xbc6dbbc4, 0x00003c80, 0x3c6dbbc4, 0x00003c80, 0xbc6d3bc4, 0x00003c80, 0x3bc4bc6d, 0x00003c80, 0xbbc43c6d,
    0x3c2cbc3e, 0x3bacbc71, 0x3bacbc71, 0x3a493c80, 0x3c18bc4e, 0xbc04bc5c, 0x3b79bc78, 0x3c4e3c18, 0x3c04bc5c, 0xbc7dbb16,
    0x3b16bc7d, 0x3c78bb79, 0x3bdbbc67, 0xbc3e3c2c, 0x3a49bc80, 0x3bdbbc67, 0xbc7f3ac9, 0xbc623bf1, 0xbc223c46, 0x3b95bc75,
    0xbc753b95, 0xbac93c7f, 0xbbf13c62, 0xbc22bc46, 0xbc623bf1, 0x3c463c22, 0xbb953c75, 0xbc7f3ac9, 0xbc463c22, 0x3c75bb95,
    0xbac93c7f, 0xbbf13c62, 0x3c4e3c18, 0x3c783b79, 0x3c5cbc04, 0xbc183c4e, 0x3c713bac, 0x3c2cbc3e, 0x3c2cbc3e, 0x3bdb3c67,
    0x3c803a49, 0xbbacbc71, 0x3bdbbc67, 0x3c803a49, 0x3c78bb79, 0xbc7dbb16, 0x3b16bc7d, 0x3c04bc5c, 0xbb48bc7b, 0xbc0ebc55,
    0xbc7b3b48, 0x3c55bc0e, 0xbc0ebc55, 0xbc7b3b48, 0xbc553c0e, 0xbb48bc7b, 0xbc55bc0e, 0xbb483c7b, 0xbc0e3c55, 0xbc7bbb48,
    0xbc7bbb48, 0x3c553c0e, 0xbb483c7b, 0xbc0e3c55, 0xbc043c5c, 0xbb163c7d, 0x3c7d3b16, 0xbc783b79, 0xba493c80, 0x3c673bdb,
    0x3c71bbac, 0xba493c80, 0x3bdb3c67, 0x3c2cbc3e, 0x3c2cbc3e, 0x3c713bac, 0x3c4e3c18, 0xbc04bc5c, 0x3b79bc78, 0x3c18bc4e,
    0x3c75bb95, 0x3c46bc22, 0xbc62bbf1, 0x3c7f3ac9, 0x3c22bc46, 0xbbf1bc62, 0xbc7f3ac9, 0x3b95bc75, 0x3ac9bc7f, 0xbc753b95,
    0xbc463c22, 0xbc62bbf1, 0xbbf1bc62, 0x3ac93c7f, 0xbb953c75, 0xbc223c46, 0xbc67bbdb, 0xbc80ba49, 0x3c2c3c3e, 0xbc67bbdb,
    0xbc783b79, 0xbb163c7d, 0x3c7d3b16, 0xbc043c5c, 0xbc183c4e, 0x3c783b79, 0x3c5cbc04, 0x3c4e3c18, 0x3a493c80, 0x3bacbc71,
    0x3bacbc71, 0x3c2cbc3e, 0x3c353c35, 0x3c6d3bc4, 0x3c353c35, 0xbc6dbbc4, 0x3c35bc35, 0xbbc4bc6d, 0x3c35bc35, 0x3bc43c6d,
    0xbc35bc35, 0xbbc43c6d, 0xbc35bc35, 0x3bc4bc6d, 0xbc353c35, 0x3c6dbbc4, 0xbc353c35, 0xbc6d3bc4, 0x3c3e3c2c, 0x3c713bac,
    0x3c713bac, 0xbc803a49, 0x3c18bc4e, 0xbc04bc5c, 0x3b79bc78, 0x3c4e3c18, 0xbc5cbc04, 0xbb163c7d, 0xbc7dbb16, 0xbb79bc78,
    0xbbdb3c67, 0x3c3ebc2c, 0xba493c80, 0xbbdb3c67, 0x3c463c22, 0x3c753b95, 0x3c7fbac9, 0xbc623bf1, 0x3bf1bc62, 0xbc22bc46,
    0xbb95bc75, 0x3c7f3ac9, 0xbc75bb95, 0x3ac93c7f, 0xbc623bf1, 0xbc46bc22, 0xbac93c7f, 0x3bf1bc62, 0x3c223c46, 0x3b953c75,
    0x3c4e3c18, 0x3c783b79, 0x3c5cbc04, 0xbc183c4e, 0x3bacbc71, 0xbc3ebc2c, 0xbc3ebc2c, 0x3c67bbdb, 0xbc80ba49, 0x3bac3c71,
    0xbbdb3c67, 0xbc80ba49, 0x3b793c78, 0x3b16bc7d, 0x3c7d3b16, 0x3c5c3c04, 0x3c553c0e, 0x3c7b3b48, 0x3c0ebc55, 0xbb483c7b,
    0x3b48bc7b, 0xbc55bc0e, 0xbc7bbb48, 0x3c0ebc55, 0xbc7b3b48, 0x3c0e3c55, 0x3b483c7b, 0xbc553c0e, 0x3c0e3c55, 0xbb48bc7b,
    0x3c55bc0e, 0x3c7bbb48, 0x3c5c3c04, 0x3c7d3b16, 0x3b16bc7d, 0x3b793c78, 0x3a49bc80, 0xbc67bbdb, 0xbc713bac, 0x3a49bc80,
    0xbc673bdb, 0x3c3e3c2c, 0x3c3e3c2c, 0xbbac3c71, 0x3c4e3c18, 0xbc04bc5c, 0x3b79bc78, 0x3c18bc4e, 0x3c623bf1, 0x3c7f3ac9,
    0xbb95bc75, 0x3c223c46, 0xbac9bc7f, 0xbc75bb95, 0xbc223c46, 0xbbf1bc62, 0xbc463c22, 0x3c623bf1, 0x3c7f3ac9, 0x3b953c75,
    0x3c753b95, 0xbc46bc22, 0xbbf1bc62, 0xbac9bc7f, 0x3c673bdb, 0x3c803a49, 0xbc2cbc3e, 0x3c673bdb, 0xbb79bc78, 0xbc7dbb16,
    0xbb163c7d, 0xbc5cbc04, 0xbc183c4e, 0x3c783b79, 0x3c5cbc04, 0x3c4e3c18, 0x3c80ba49, 0xbc71bbac, 0xbc71bbac, 0xbc3ebc2c,
    0x3c353c35, 0x3c6d3bc4, 0x3c353c35, 0xbc6dbbc4, 0x3c35bc35, 0xbbc4bc6d, 0x3c35bc35, 0x3bc43c6d, 0xbc35bc35, 0xbbc43c6d,
    0xbc35bc35, 0x3bc4bc6d, 0xbc353c35, 0x3c6dbbc4, 0xbc353c35, 0xbc6d3bc4, 0x3c80ba49, 0x3c67bbdb, 0x3c67bbdb, 0xbc2c3c3e,
    0xbb16bc7d, 0xbc78bb79, 0xbc04bc5c, 0x3c7dbb16, 0xbc783b79, 0x3c183c4e, 0xbc4e3c18, 0xbc5cbc04, 0x3bac3c71, 0x3a49bc80,
    0x3c2c3c3e, 0x3bac3c71, 0x3c22bc46, 0x3b95bc75, 0xbac9bc7f, 0x3bf13c62, 0xbc62bbf1, 0xbc463c22, 0xbc753b95, 0x3ac9bc7f,
    0xbb953c75, 0x3c7fbac9, 0x3bf13c62, 0xbc223c46, 0x3c7f3ac9, 0xbc62bbf1, 0x3c46bc22, 0x3c75bb95, 0xbb16bc7d, 0xbc04bc5c,
    0xbc78bb79, 0x3c7dbb16, 0xbc673bdb, 0x3a493c80, 0x3a493c80, 0xbc71bbac, 0x3c2c3c3e, 0x3bdbbc67, 0x3c71bbac, 0x3c2c3c3e,
    0x3c04bc5c, 0xbc4e3c18, 0xbc18bc4e, 0xbb79bc78, 0xbc55bc0e, 0xbc7bbb48, 0xbc0e3c55, 0x3b48bc7b, 0xbb483c7b, 0x3c553c0e,
    0x3c7b3b48, 0xbc0e3c55, 0x3c7bbb48, 0xbc0ebc55, 0xbb48bc7b, 0x3c55bc0e, 0xbc0ebc55, 0x3b483c7b, 0xbc553c0e, 0xbc7b3b48,
    0xbc783b79, 0xbc4e3c18, 0x3c183c4e, 0xbc5cbc04, 0x3c2c3c3e, 0x3c71bbac, 0x3bdbbc67, 0x3c2c3c3e, 0x3bacbc71, 0xbc803a49,
    0xbc803a49, 0xbbdbbc67, 0xbc7d3b16, 0x3c783b79, 0x3c043c5c, 0x3b163c7d, 0xbbf13c62, 0xbac93c7f, 0x3c75bb95, 0xbc463c22,
    0x3c7fbac9, 0x3b95bc75, 0xbc46bc22, 0x3c62bbf1, 0xbc22bc46, 0xbbf13c62, 0xbac93c7f, 0xbc753b95, 0xbb953c75, 0x3c22bc46,
    0x3c62bbf1, 0x3c7fbac9, 0x3bac3c71, 0x3c2c3c3e, 0x3a49bc80, 0x3bac3c71, 0x3c04bc5c, 0xbc18bc4e, 0xbc4e3c18, 0xbb79bc78,
    0xbc7d3b16, 0x3c043c5c, 0x3c783b79, 0x3b163c7d, 0x3c3e3c2c, 0xbbdbbc67, 0xbbdbbc67, 0xba49bc80, 0x3c353c35, 0x3c6d3bc4,
    0x3c353c35, 0xbc6dbbc4, 0x3c35bc35, 0xbbc4bc6d, 0x3c35bc35, 0x3bc43c6d, 0xbc35bc35, 0xbbc43c6d, 0xbc35bc35, 0x3bc4bc6d,
    0xbc353c35, 0x3c6dbbc4, 0xbc353c35, 0xbc6d3bc4, 0x3c2cbc3e, 0x3bacbc71, 0x3bacbc71, 0x3a493c80, 0xbc4ebc18, 0xbc5c3c04,
    0xbc78bb79, 0x3c18bc4e, 0xbc043c5c, 0x3c7d3b16, 0xbb163c7d, 0xbc783b79, 0x3c673bdb, 0xbc2cbc3e, 0x3c803a49, 0x3c673bdb,
    0xbc46bc22, 0xbc75bb95, 0xbc7f3ac9, 0x3c62bbf1, 0xbbf13c62, 0x3c223c46, 0x3b953c75, 0xbc7fbac9, 0x3c753b95, 0xbac9bc7f,
    0x3c62bbf1, 0x3c463c22, 0x3ac9bc7f, 0xbbf13c62, 0xbc22bc46, 0xbb95bc75, 0xbc183c4e, 0xbb793c78, 0x3c043c5c, 0xbc4ebc18,
    0x3c713bac, 0x3c2cbc3e, 0x3c2cbc3e, 0x3bdb3c67, 0x3a49bc80, 0xbc713bac, 0xbc67bbdb, 0x3a49bc80, 0xbc783b79, 0x3c7d3b16,
    0xbb163c7d, 0xbc043c5c, 0x3c553c0e, 0x3c7b3b48, 0x3c0ebc55, 0xbb483c7b, 0x3b48bc7b, 0xbc55bc0e, 0xbc7bbb48, 0x3c0ebc55,
    0xbc7b3b48, 0x3c0e3c55, 0x3b483c7b, 0xbc553c0e, 0x3c0e3c55, 0xbb48bc7b, 0x3c55bc0e, 0x3c7bbb48, 0x3c04bc5c, 0x3b16bc7d,
    0xbc7dbb16, 0x3c78bb79, 0xbc80ba49, 0xbbdb3c67, 0x3bac3c71, 0xbc80ba49, 0x3bdb3c67, 0x3c2cbc3e, 0x3c2cbc3e, 0x3c713bac,
    0x3c18bc4e, 0xbc5c3c04, 0xbc78bb79, 0xbc4ebc18, 0xbc62bbf1, 0xbc7fbac9, 0x3b953c75, 0xbc22bc46, 0x3ac93c7f, 0x3c753b95,
    0x3c22bc46, 0x3bf13c62, 0x3c46bc22, 0xbc62bbf1, 0xbc7fbac9, 0xbb95bc75, 0xbc75bb95, 0x3c463c22, 0x3bf13c62, 0x3ac93c7f,
    0xbbdb3c67, 0xba493c80, 0x3c3ebc2c, 0xbbdb3c67, 0x3c78bb79, 0x3b16bc7d, 0xbc7dbb16, 0x3c04bc5c, 0xbc4ebc18, 0xbb793c78,
    0x3c043c5c, 0xbc183c4e, 0x3a493c80, 0x3bacbc71, 0x3bacbc71, 0x3c2cbc3e, 0x3c353c35, 0x3c6d3bc4, 0x3c353c35, 0xbc6dbbc4,
    0x3c35bc35, 0xbbc4bc6d, 0x3c35bc35, 0x3bc43c6d, 0xbc35bc35, 0xbbc43c6d, 0xbc35bc35, 0x3bc4bc6d, 0xbc353c35, 0x3c6dbbc4,
    0xbc353c35, 0xbc6d3bc4, 0xba49bc80, 0xbbdbbc67, 0xbbdbbc67, 0x3c3e3c2c, 0xbc7d3b16, 0xbb793c78, 0xbc5c3c04, 0xbb16bc7d,
    0x3b793c78, 0x3c4ebc18, 0x3c183c4e, 0xbc043c5c, 0x3c71bbac, 0xbc80ba49, 0x3c3ebc2c, 0x3c71bbac, 0xbc223c46, 0xbb953c75,
    0x3ac93c7f, 0xbbf1bc62, 0x3c623bf1, 0x3c46bc22, 0x3c75bb95, 0xbac93c7f, 0x3b95bc75, 0xbc7f3ac9, 0xbbf1bc62, 0x3c22bc46,
    0xbc7fbac9, 0x3c623bf1, 0xbc463c22, 0xbc753b95, 0x3c7dbb16, 0x3c5cbc04, 0x3b79bc78, 0x3b163c7d, 0xbbdbbc67, 0xbc803a49,
    0xbc803a49, 0x3bacbc71, 0xbc3e3c2c, 0x3c673bdb, 0x3bac3c71, 0xbc3e3c2c, 0x3c5c3c04, 0xbc18bc4e, 0x3c4ebc18, 0x3c78bb79,
    0xbc55bc0e, 0xbc7bbb48, 0xbc0e3c55, 0x3b48bc7b, 0xbb483c7b, 0x3c553c0e, 0x3c7b3b48, 0xbc0e3c55, 0x3c7bbb48, 0xbc0ebc55,
    0xbb48bc7b, 0x3c55bc0e, 0xbc0ebc55, 0x3b483c7b, 0xbc553c0e, 0xbc7b3b48, 0x3b793c78, 0x3c183c4e, 0x3c4ebc18, 0xbc043c5c,
    0x3c3ebc2c, 0xbbacbc71, 0xbc67bbdb, 0x3c3ebc2c, 0xbc71bbac, 0x3a493c80, 0x3a493c80, 0xbc673bdb, 0x3b163c7d, 0x3b79bc78,
    0x3c5cbc04, 0x3c7dbb16, 0x3bf1bc62, 0x3ac9bc7f, 0xbc753b95, 0x3c46bc22, 0xbc7f3ac9, 0xbb953c75, 0x3c463c22, 0xbc623bf1,
    0x3c223c46, 0x3bf1bc62, 0x3ac9bc7f, 0x3c75bb95, 0x3b95bc75, 0xbc223c46, 0xbc623bf1, 0xbc7f3ac9, 0xbc713bac, 0xbc3e3c2c,
    0x3c803a49, 0xbc713bac, 0x3c5c3c04, 0x3c4ebc18, 0xbc18bc4e, 0x3c78bb79, 0xbb16bc7d, 0xbc5c3c04, 0xbb793c78, 0xbc7d3b16,
    0xbc2c3c3e, 0x3c67bbdb, 0x3c67bbdb, 0x3c80ba49, 0x3c800000, 0x3c6dbbc4, 0x3c800000, 0xbc6d3bc4, 0xbc800000, 0xbbc43c6d,
    0xbc800000, 0x3bc4bc6d, 0x3c800000, 0xbbc4bc6d, 0x3c800000, 0x3bc43c6d, 0xbc800000, 0x3c6d3bc4, 0xbc800000, 0xbc6dbbc4,
    0x3c80ba49, 0x3c67bbdb, 0x3c67bbdb, 0xbc2c3c3e, 0xbc7d3b16, 0xbb793c78, 0xbc5c3c04, 0xbb16bc7d, 0x3c78bb79, 0xbc18bc4e,
    0x3c4ebc18, 0x3c5c3c04, 0xbc713bac, 0x3c803a49, 0xbc3e3c2c, 0xbc713bac, 0x3c7fbac9, 0x3c62bbf1, 0x3c22bc46, 0xbb953c75,
    0xbc753b95, 0xbac93c7f, 0xbbf13c62, 0xbc22bc46, 0x3c62bbf1, 0xbc46bc22, 0x3b95bc75, 0x3c7fbac9, 0xbc463c22, 0x3c75bb95,
    0xbac93c7f, 0xbbf13c62, 0x3c7dbb16, 0x3c5cbc04, 0x3b79bc78, 0x3b163c7d, 0xbc673bdb, 0x3a493c80, 0x3a493c80, 0xbc71bbac,
    0x3c3ebc2c, 0xbc67bbdb, 0xbbacbc71, 0x3c3ebc2c, 0xbc043c5c, 0x3c4ebc18, 0x3c183c4e, 0x3b793c78, 0x3c7bbb48, 0x3c55bc0e,
    0xbb48bc7b, 0x3c0e3c55, 0xbc553c0e, 0x3b483c7b, 0x3c0e3c55, 0xbc7b3b48, 0x3c0ebc55, 0xbc7bbb48, 0xbc55bc0e, 0x3b48bc7b,
    0xbb483c7b, 0x3c0ebc55, 0x3c7b3b48, 0x3c553c0e, 0x3c78bb79, 0x3c4ebc18, 0xbc18bc4e, 0x3c5c3c04, 0xbc3e3c2c, 0x3bac3c71,
    0x3c673bdb, 0xbc3e3c2c, 0x3bacbc71, 0xbc803a49, 0xbc803a49, 0xbbdbbc67, 0x3b163c7d, 0x3b79bc78, 0x3c5cbc04, 0x3c7dbb16,
    0x3c75bb95, 0x3c46bc22, 0xbc62bbf1, 0x3c7f3ac9, 0xbc223c46, 0x3bf13c62, 0x3c7fbac9, 0xbb953c75, 0x3ac9bc7f, 0xbc753b95,
    0xbc463c22, 0xbc62bbf1, 0x3bf13c62, 0xbac9bc7f, 0x3b95bc75, 0x3c22bc46, 0x3c71bbac, 0x3c3ebc2c, 0xbc80ba49, 0x3c71bbac,
    0xbc043c5c, 0x3c183c4e, 0x3c4ebc18, 0x3b793c78, 0xbb16bc7d, 0xbc5c3c04, 0xbb793c78, 0xbc7d3b16, 0x3c3e3c2c, 0xbbdbbc67,
    0xbbdbbc67, 0xba49bc80, 0x3c800000, 0x3c6dbbc4, 0x3c800000, 0xbc6d3bc4, 0xbc800000, 0xbbc43c6d, 0xbc800000, 0x3bc4bc6d,
    0x3c800000, 0xbbc4bc6d, 0x3c800000, 0x3bc43c6d, 0xbc800000, 0x3c6d3bc4, 0xbc800000, 0xbc6dbbc4, 0x3c2cbc3e, 0x3bacbc71,
    0x3bacbc71, 0x3a493c80, 0xbc183c4e, 0x3c043c5c, 0xbb793c78, 0xbc4ebc18, 0x3c04bc5c, 0xbc7dbb16, 0x3b16bc7d, 0x3c78bb79,
    0xbbdb3c67, 0x3c3ebc2c, 0xba493c80, 0xbbdb3c67, 0xbac9bc7f, 0xbbf1bc62, 0xbc46bc22, 0x3c753b95, 0x3b953c75, 0x3c7f3ac9,
    0x3c623bf1, 0xbc463c22, 0xbbf1bc62, 0xbc223c46, 0xbc75bb95, 0xbac9bc7f, 0x3c223c46, 0xbb95bc75, 0x3c7f3ac9, 0x3c623bf1,
    0xbc4ebc18, 0xbc78bb79, 0xbc5c3c04, 0x3c18bc4e, 0x3c713bac, 0x3c2cbc3e, 0x3c2cbc3e, 0x3bdb3c67, 0xbc80ba49, 0x3bac3c71,
    0xbbdb3c67, 0xbc80ba49, 0x3c78bb79, 0xbc7dbb16, 0x3b16bc7d, 0x3c04bc5c, 0xbc7b3b48, 0xbc553c0e, 0x3b483c7b, 0xbc0ebc55,
    0x3c55bc0e, 0xbb48bc7b, 0xbc0ebc55, 0x3c7bbb48, 0xbc0e3c55, 0x3c7b3b48, 0x3c553c0e, 0xbb483c7b, 0x3b48bc7b, 0xbc0e3c55,
    0xbc7bbb48, 0xbc55bc0e, 0xbc043c5c, 0xbb163c7d, 0x3c7d3b16, 0xbc783b79, 0x3a49bc80, 0xbc67bbdb, 0xbc713bac, 0x3a49bc80,
    0x3bdb3c67, 0x3c2cbc3e, 0x3c2cbc3e, 0x3c713bac, 0xbc4ebc18, 0x3c043c5c, 0xbb793c78, 0xbc183c4e, 0x3b953c75, 0x3c223c46,
    0x3bf1bc62, 0xbac93c7f, 0xbc46bc22, 0xbc623bf1, 0x3ac93c7f, 0xbc75bb95, 0x3c7f3ac9, 0xbb95bc75, 0xbc22bc46, 0x3bf1bc62,
    0xbc623bf1, 0x3c7fbac9, 0x3c753b95, 0x3c463c22, 0x3c673bdb, 0x3c803a49, 0xbc2cbc3e, 0x3c673bdb, 0xbc783b79, 0xbb163c7d,
    0x3c7d3b16, 0xbc043c5c, 0x3c18bc4e, 0xbc78bb79, 0xbc5c3c04, 0xbc4ebc18, 0x3a493c80, 0x3bacbc71, 0x3bacbc71, 0x3c2cbc3e,
    0x3c800000, 0x3c6dbbc4, 0x3c800000, 0xbc6d3bc4, 0xbc800000, 0xbbc43c6d, 0xbc800000, 0x3bc4bc6d, 0x3c800000, 0xbbc4bc6d,
    0x3c800000, 0x3bc43c6d, 0xbc800000, 0x3c6d3bc4, 0xbc800000, 0xbc6dbbc4, 0xba49bc80, 0xbbdbbc67, 0xbbdbbc67, 0x3c3e3c2c,
    0x3b163c7d, 0x3c783b79, 0x3c043c5c, 0xbc7d3b16, 0xbb79bc78, 0xbc4e3c18, 0xbc18bc4e, 0x3c04bc5c, 0x3bac3c71, 0x3a49bc80,
    0x3c2c3c3e, 0x3bac3c71, 0xbc7f3ac9, 0xbc623bf1, 0xbc223c46, 0x3b95bc75, 0x3c75bb95, 0x3ac9bc7f, 0x3bf1bc62, 0x3c223c46,
    0xbc623bf1, 0x3c463c22, 0xbb953c75, 0xbc7f3ac9, 0x3c46bc22, 0xbc753b95, 0x3ac9bc7f, 0x3bf1bc62, 0x3b163c7d, 0x3c043c5c,
    0x3c783b79, 0xbc7d3b16, 0xbbdbbc67, 0xbc803a49, 0xbc803a49, 0x3bacbc71, 0x3c2c3c3e, 0x3bdbbc67, 0x3c71bbac, 0x3c2c3c3e,
    0xbc5cbc04, 0x3c183c4e, 0xbc4e3c18, 0xbc783b79, 0x3c7bbb48, 0x3c55bc0e, 0xbb48bc7b, 0x3c0e3c55, 0xbc553c0e, 0x3b483c7b,
    0x3c0e3c55, 0xbc7b3b48, 0x3c0ebc55, 0xbc7bbb48, 0xbc55bc0e, 0x3b48bc7b, 0xbb483c7b, 0x3c0ebc55, 0x3c7b3b48, 0x3c553c0e,
    0xbb79bc78, 0xbc18bc4e, 0xbc4e3c18, 0x3c04bc5c, 0x3c2c3c3e, 0x3c71bbac, 0x3bdbbc67, 0x3c2c3c3e, 0xbc71bbac, 0x3a493c80,
    0x3a493c80, 0xbc673bdb, 0x3c7dbb16, 0xbc78bb79, 0xbc04bc5c, 0xbb16bc7d, 0xbc753b95, 0xbc463c22, 0x3c623bf1, 0xbc7fbac9,
    0x3c22bc46, 0xbbf1bc62, 0xbc7f3ac9, 0x3b95bc75, 0xbac93c7f, 0x3c75bb95, 0x3c46bc22, 0x3c623bf1, 0xbbf1bc62, 0x3ac93c7f,
    0xbb953c75, 0xbc223c46, 0x3bac3c71, 0x3c2c3c3e, 0x3a49bc80, 0x3bac3c71, 0xbc5cbc04, 0xbc4e3c18, 0x3c183c4e, 0xbc783b79,
    0x3c7dbb16, 0xbc04bc5c, 0xbc78bb79, 0xbb16bc7d, 0xbc2c3c3e, 0x3c67bbdb, 0x3c67bbdb, 0x3c80ba49, 0x3c800000, 0x3c6dbbc4,
    0x3c800000, 0xbc6d3bc4, 0xbc800000, 0xbbc43c6d, 0xbc800000, 0x3bc4bc6d, 0x3c800000, 0xbbc4bc6d, 0x3c800000, 0x3bc43c6d,
    0xbc800000, 0x3c6d3bc4, 0xbc800000, 0xbc6dbbc4, 0xbc3ebc2c, 0xbc71bbac, 0xbc71bbac, 0x3c80ba49, 0x3c4e3c18, 0x3c5cbc04,
    0x3c783b79, 0xbc183c4e, 0xbc5cbc04, 0xbb163c7d, 0xbc7dbb16, 0xbb79bc78, 0x3c673bdb, 0xbc2cbc3e, 0x3c803a49, 0x3c673bdb,
    0x3ac93c7f, 0x3bf13c62, 0x3c463c22, 0xbc75bb95, 0xbb95bc75, 0xbc7fbac9, 0xbc62bbf1, 0x3c46bc22, 0x3bf13c62, 0x3c22bc46,
    0x3c753b95, 0x3ac93c7f, 0xbc22bc46, 0x3b953c75, 0xbc7fbac9, 0xbc62bbf1, 0x3c18bc4e, 0x3b79bc78, 0xbc04bc5c, 0x3c4e3c18,
    0xbbac3c71, 0x3c3e3c2c, 0x3c3e3c2c, 0xbc673bdb, 0x3a49bc80, 0xbc713bac, 0xbc67bbdb, 0x3a49bc80, 0x3b793c78, 0x3b16bc7d,
    0x3c7d3b16, 0x3c5c3c04, 0xbc7b3b48, 0xbc553c0e, 0x3b483c7b, 0xbc0ebc55, 0x3c55bc0e, 0xbb48bc7b, 0xbc0ebc55, 0x3c7bbb48,
    0xbc0e3c55, 0x3c7b3b48, 0x3c553c0e, 0xbb483c7b, 0x3b48bc7b, 0xbc0e3c55, 0xbc7bbb48, 0xbc55bc0e, 0x3c5c3c04, 0x3c7d3b16,
    0x3b16bc7d, 0x3b793c78, 0xbc80ba49, 0xbbdb3c67, 0x3bac3c71, 0xbc80ba49, 0x3c67bbdb, 0xbc3ebc2c, 0xbc3ebc2c, 0x3bacbc71,
    0xbc183c4e, 0x3c5cbc04, 0x3c783b79, 0x3c4e3c18, 0xbb95bc75, 0xbc22bc46, 0xbbf13c62, 0x3ac9bc7f, 0x3c463c22, 0x3c62bbf1,
    0xbac9bc7f, 0x3c753b95, 0xbc7fbac9, 0x3b953c75, 0x3c223c46, 0xbbf13c62, 0x3c62bbf1, 0xbc7f3ac9, 0xbc75bb95, 0xbc46bc22,
    0xbbdb3c67, 0xba493c80, 0x3c3ebc2c, 0xbbdb3c67, 0xbb79bc78, 0xbc7dbb16, 0xbb163c7d, 0xbc5cbc04, 0x3c4e3c18, 0x3b79bc78,
    0xbc04bc5c, 0x3c18bc4e, 0xbc803a49, 0x3c713bac, 0x3c713bac, 0x3c3e3c2c,
};

__device__ __forceinline__ void store_tile_64(const float (&d)[32], uint32_t base, int warp, int lane) {
  const int row = warp * 16 + (lane & 7) + ((lane >> 3) & 1) * 8;
  const uint32_t rb = base + row * 128;
#pragma unroll
  for (int j = 0; j < 8; j += 2) {
    const int jj = j + (lane >> 4);
    stsm4(rb + ((jj ^ (lane & 7)) << 4), pack2(d[4 * j], d[4 * j + 1]), pack2(d[4 * j + 2], d[4 * j + 3]),
          pack2(d[4 * j + 4], d[4 * j + 5]), pack2(d[4 * j + 6], d[4 * j + 7]));
  }
}

#define PLACE 0
#define G_EPI 3
#define P_X1A 0
#define P_X1B 0
#define P_X1M 15
#define P_RAW 0
#define PT 5
#define G_TK 3
#define G_TIN0 1
#define G_TM 0
#define W2_PC 32
#define W2_PF 3
constexpr int A_IN = 112 * 128;
constexpr int G_ST = 2 * NB1 * 64;
constexpr int K1_R = 131072, K1_BAR = K1_R + 98304, K1_SMEM = K1_BAR + 2048 + 1024;
constexpr int K1_T = K1_R + 65536, K1_TIN = G_TIN0 ? 0 : G_ST, K1_Y0 = 3 * G_ST + 8192, G_KM = 16 - G_TK, G_S0 = 2 * G_KM;
__device__ int g_done[8 * 32];
struct Ptrs {
  int* done;
  float* ge;
  const uint32_t *img, *ga;
};

__host__ __device__ constexpr int g_depth(int s) { return s < (G_TIN0 ? 11 : 9) ? 3 : s < 18 ? 4 : s < 23 ? 5 : 6; }
__host__ __device__ constexpr int g_slot(int s) { return s < 3 ? s : g_depth(s) != g_depth(s - 1) ? g_depth(s - 1) : g_slot(s - g_depth(s)); }
__host__ __device__ constexpr int g_off(int id) { return id * G_ST + (id < 3 ? K1_R : id == 3 && !G_TIN0 ? -3 * G_ST : 8192 - 3 * G_ST); }
struct Plan {
  uint32_t raw[32];
  uint32_t x[16];
  uint32_t grp[8];
  uint32_t last;
  uint32_t wpf;
  uint32_t g0;
  uint32_t tmask;
  uint64_t list[2];
};
struct K1Maps {
  Plan p;
  CUtensorMap x, we, wo, xs, y, w2e, w2o, w2s;
  int slot[32];
  int src[32];
  int dep[32];
};
__device__ __forceinline__ void poll_ge(const int* p, int target) {
  for (int it = 0; it < (1 << 20); it++) {
    int v;
    asm volatile("ld.acquire.gpu.global.s32 %0, [%1];" : "=r"(v) : "l"(p) : "memory");
    if (v >= target) break;
  }
}
__device__ __forceinline__ uint32_t place(int rank, uint32_t c) { return (c ^ (rank * 4 & ~(c >> 1))) << 14; }
__device__ __forceinline__ int x_unit(int cta, int u, uint32_t pl) {
  const int i = u * 128 + cta;
  const int pr = cta >= 128 ? 2 * cta - 96 + (u & 1) : i % 160, sl = cta >= 128 ? u >> 1 : i / 160, b = pr >= 84;
  return pr | sl << 8 | b << 11 | (cta >= 128 ? (u & 7) << 14 : place(cta & 1, pl & 15)) | 12 * (pr - 84 * b) << 20;
}
__device__ __forceinline__ int lds32(uint32_t a) {
  int v;
  asm volatile("ld.shared.b32 %0, [%1];" : "=r"(v) : "r"(a));
  return v;
}
__host__ __device__ constexpr uint64_t sched(const char* p) {
  uint64_t r = 0;
  for (int n = 0; p[n]; n++) r |= (uint64_t)(p[n] - '0' + 1) << (5 * n);
  return r;
}

__global__ void __cluster_dims__(2, 1, 1) __launch_bounds__(384, 1)
k1(const Ptrs gp0, const char* __restrict__ x1, const char* __restrict__ w1, const __grid_constant__ K1Maps m, const __nv_bfloat16* __restrict__ g,
   const __nv_bfloat16* __restrict__ wgt) {
  const Ptrs gp_ = PT & 1 ? Ptrs{g_done, g_ge, c_img, c_ga} : gp0;
  extern __shared__ __align__(1024) uint8_t smem_k1[];
  const uint32_t sb = s2u(smem_k1);
  const int tid = threadIdx.x, wg = __shfl_sync(0xffffffffu, tid >> 7, 0), t = tid & 127;
  const int warp = __shfl_sync(0xffffffffu, t >> 5, 0), lane = t & 31;
  const int cta = blockIdx.x, rank = cta & 1;
  const bool spare = cta >= 128;
  const int nx = spare ? 16 : 10;
  int bp, dc;
  {
    const int ci = cta >> 1;
    const int G = ci < 4 ? 0 : ci < 36 ? (ci - 4) & 7 : 1 + (ci - 36) % 7;
    const int li = ci < 4 ? 4 + ci : ci < 36 ? (ci - 4) >> 3 : 4 + (ci - 36) / 7;
    if (PLACE == 0) { bp = 2 * G + (li >> 2); dc = li & 3; }
    else if (PLACE == 1) { bp = (G >> 1) * 4 + (li >> 1); dc = (G & 1) * 2 + (li & 1); }
    else { bp = (G >> 2) * 8 + li; dc = G & 3; }
  }
  const int bin = 2 * bp + rank;
  const uint32_t bb = sb + K1_BAR;
  const uint32_t rfull = bb, xfull = bb + 256, xfree = bb + 384, gfull = bb + 512, win = bb + 768;
  const uint32_t inf0 = win + 16, se0 = inf0 + 16, pfree = se0 + 16, rempty = bb + 1024, xready = bb + 1280;
  const uint32_t gdone = bb + 1536, ine0 = gdone + 224, sf0 = ine0 + 16;
  const uint32_t xtab = bb + 896, tab = bb + 1792, ptab = bb + 2048 + 768;
  auto raw_load = [&](int j, uint32_t dst) {
    mbar_expect(rfull + 8 * j, 16384);
    tma_ld4<P_RAW>(dst, rank ? &m.we : &m.wo, rfull + 8 * j, dc * 64, rank - 1, (j & 3) * 4, (j >> 2) * 2);
  };
  auto x_half = [&](int u, int c, int h) {
    tma_ld4<1>(sb + (c & 0x3C000) + h * (A_IN / 2), &m.x, xfull + 8 * u, 0, (c >> 17 & ~7) - 24 + h * 56, c >> 8 & 7, c >> 11 & 1);
  };
  auto w_prefetch = [&](int q) {
    if (cta < 124) asm volatile("cp.async.bulk.prefetch.L2.global [%0], 4096;" ::"l"(w1 + (cta >> 2) * 131072 + (q * 4 + (cta & 3)) * 4096) : "memory");
  };
  uint32_t peer;
  asm("mapa.shared::cluster.u32 %0, %1, %2;" : "=r"(peer) : "r"(sb), "r"(rank ^ 1));
  if (wg == 2) {
    if (lane == 0) {
      if (warp < 2) {
        for (int i = 0; i < 4; i++) mbar_init(bb + 256 * warp + 8 * i, 1);
        fence_bar_init();
        fence_async();
        if (warp == 1) {
          const int c = x_unit(cta, 0, m.p.x[0]);
          mbar_expect(xfull, A_IN);
          x_half(0, c, 0);
          x_half(0, c, 1);
        } else if (!spare) {
#pragma unroll 1
          for (int j = 0; j < 4; j++) raw_load(j, sb + K1_R + j * 16384);
        }
      } else if (warp == 2) {
#pragma unroll 1
        for (int q = 1; q <= m.p.wpf; q++) w_prefetch(q);
        prefetch_map(&m.xs);
      }
    }
    if (warp == 3) {
      const uint32_t v = reinterpret_cast<const uint32_t*>(&m.p)[32 + lane];
      asm volatile("st.shared.b32 [%0], %1;" ::"r"(ptab + 4 * lane), "r"(m.p.raw[lane]) : "memory");
      asm volatile("st.shared.b32 [%0], %1;" ::"r"(ptab + 128 + 4 * lane), "r"(v) : "memory");
      if (lane < 16) asm volatile("st.shared.b32 [%0], %1;" ::"r"(xtab + 4 * lane), "r"(x_unit(cta, lane, v)) : "memory");
    }
  } else {
    if (lane < 16)
      asm volatile("st.shared.u16 [%0], %1;" ::"r"(tab + (tid >> 5) * 32 + lane * 2),
                   "h"(__bfloat16_as_ushort(__float2bfloat16_rn(cospif((float)((tid >> 5) * 16 + lane) * (1.0f / 64.0f))))) : "memory");
    const int c = 4 * wg + warp;
    if (lane == 0 && c < 7) {
      const uint32_t b0 = bb + 256 * c, n = c < 4 ? 1 : c < 6 ? 4 : 8;
      if (c >= 2)
        for (int i = 0; i < 4; i++) mbar_init(b0 + 8 * i, n);
      for (int i = 4; i < 16; i++) mbar_init(b0 + 8 * i, n);
      if (c == 3) {
        mbar_expect(win, 65536);
        mbar_arrive(win + 8);
      } else {
        for (int i = 16; i < 32; i++) mbar_init(b0 + 8 * i, n);
      }
      fence_bar_init();
    }
  }
  pdl_launch();
  __syncthreads();
  asm volatile("barrier.cluster.arrive.relaxed.aligned;" ::: "memory");
  if (wg == 2) {
    asm volatile("setmaxnreg.dec.sync.aligned.u32 40;");
    asm volatile("barrier.cluster.wait.aligned;" ::: "memory");
    if (lane == 0) {
      const int wpf = lds32(ptab + 228), g0 = lds32(ptab + 232), s0 = g0 * 4 / 5;
      const int nx0 = spare ? 2 * s0 : g0;
      if (warp == 0) {
        if (!spare) {
#pragma unroll 1
          for (int j = 4; j < 32; j++) {
            const uint32_t e = lds32(ptab + 4 * j);
            mbar_wait(bb + (e >> 5 & ~7), 0);
            raw_load(j, sb + place(rank, e & 15));
            if ((j & 3) == 0 && wpf && (j >> 2) + wpf < 8) w_prefetch((j >> 2) + wpf);
          }
#pragma unroll 1
          for (int s = 0; s < 32; s++) {
            if (s == 0 || s == 4 * s0) {
              poll_ge(&gp_.done[(s ? 5 : 4) * 32], 132);
              asm volatile("fence.proxy.async.global;" ::: "memory");
              mbar_wait(bb + 8 * (lds32(ptab + 224) & 255), 0);
            }
            const uint32_t bar = gfull + 8 * s, dst = sb + 16 * m.slot[s];
            const char* src = x1 + bin * (4 * G_ST) + m.src[s];
            mbar_wait(bb + m.dep[s], 0);
            mbar_expect(bar, G_ST);
#pragma unroll
            for (int h = 0; h < 2; h++) {
              if (s >= P_X1A && s < P_X1B && (P_X1M >> dc & 1))
                asm volatile("cp.async.bulk.shared::cluster.global.mbarrier::complete_tx::bytes.L2::cache_hint [%0], [%1], %2, [%3], %4;"
                             ::"r"(dst + h * (G_ST / 2)), "l"(src + h * (s < G_S0 ? G_ST / 2 : 2 * G_ST)), "n"(G_ST / 2), "r"(bar), "l"(policy<1>()) : "memory");
              else
                asm volatile("cp.async.bulk.shared::cluster.global.mbarrier::complete_tx::bytes [%0], [%1], %2, [%3];"
                             ::"r"(dst + h * (G_ST / 2)), "l"(src + h * (s < G_S0 ? G_ST / 2 : 2 * G_ST)), "n"(G_ST / 2), "r"(bar) : "memory");
            }
          }
          if (cta == 0) asm volatile("cp.async.bulk.prefetch.L2.global [%0], 14336;" ::"l"(gp_.img) : "memory");
        }
      } else if (warp < 3) {
        const int u0 = warp == 1 ? 0 : nx0, u1 = warp == 1 ? nx0 : nx;
#pragma unroll 1
        for (int u = u0; u < u1; u++) {
          const int c = lds32(xtab + 4 * u);
          const uint32_t e = spare ? 0xC0 : lds32(ptab + 128 + 4 * u);
          const uint32_t src = sb + (c & 0x3C000), rel = e >> 1 & 24, burst = (16 << (e >> 6 & 3)) - 1;
          mbar_wait(xready + 8 * u, 0);
#pragma unroll 1
          for (int p = 0; p < 128; p += 16) {
            tma_st4<0>(&m.xs, src + p * 128, 0, (c >> 2 & 0x1C0) + (p & 63), p >> 6, c & 255);
            if (((p + 16) & burst) == 0) {
              bulk_commit();
              bulk_wait_read<0>();
            }
          }
          mbar_arrive(xfree + 8 * u);
          if (rel)
            asm volatile("mbarrier.arrive.shared::cluster.b64 _, [%0];" ::"r"(peer + (pfree - sb) + rel) : "memory");
        }
        asm volatile("cp.async.bulk.wait_group 0;" ::: "memory");
        asm volatile("red.release.gpu.global.add.s32 [%0], 1;" ::"l"(&gp_.done[(3 + warp) * 32]) : "memory");
        if (!spare) {
          if (warp == 1) {
            auto w2_row = [&](int it, bool pf) {
              const CUtensorMap* mp = it & 1 ? &m.w2e : &m.w2o;
              const int c1 = (it & 1) - 1, c2 = (cta & 1) * 2, c3 = (it >> 1) * 64 + (cta >> 1);
              if (pf) {
                asm volatile("cp.async.bulk.prefetch.tensor.4d.L2.global [%0, {%1, %2, %3, %4}];" ::"l"(mp), "r"(0), "r"(c1), "r"(c2), "r"(c3) : "memory");
              } else {
                mbar_expect(inf0 + 8 * (it & 1), 4096);
                tma_ld4<1>(sb + K1_TIN + (it & 1) * 4096, mp, inf0 + 8 * (it & 1), 0, c1, c2, c3);
              }
            };
#pragma unroll 1
            for (int it = 0; it < W2_PF; it++) {
              mbar_wait(gfull + 8 * (it >> 1), 0);
              w2_row(it, true);
            }
            mbar_wait(gdone + (G_TIN0 ? 8 : 56), 0);
#pragma unroll 1
            for (int it = 0; it < 8; it++) {
              if (it >= 2) mbar_wait(ine0 + 8 * (it & 1), ((it >> 1) - 1) & 1);
              w2_row(it, false);
              if (W2_PF && it + W2_PF < 8) w2_row(it + W2_PF, true);
            }
          } else {
            prefetch_map(&m.w2s);
            prefetch_map(&m.y);
#pragma unroll 1
            for (int it = 0; it < 8; it++) {
              if ((0x74 >> it) & 1) poll_ge(&gp_.done[((0x33210000 >> (4 * it)) & 3) * 32], 128);
              mbar_wait(sf0 + 8 * (it & 1), (it >> 1) & 1);
#pragma unroll 1
              for (int p = 0; p < 128; p += W2_PC) {
                tma_st4<0>(&m.w2s, sb + K1_T + (it & 1) * 16384 + p * 128, 0, it * 64 + (p & 63), (cta & 1) * 2 + (p >> 6),
                           (cta >> 1 & 33) | (cta >> 3 & 6) | (cta << 1 & 24));
                bulk_commit();
                bulk_wait_read<0>();
              }
              mbar_arrive(se0 + 8 * (it & 1));
            }
          }
        }
      } else {
#pragma unroll 1
        for (int u = 1; u < nx; u++) {
          const int c = lds32(xtab + 4 * u);
          const uint32_t e = spare ? (u < 8 ? 97 : 40 + u) * 0x01010100u : lds32(ptab + 128 + 4 * u);
          mbar_wait(bb + (e >> 5 & 0x7F8), 0);
          mbar_expect(xfull + 8 * u, A_IN);
          mbar_wait(bb + (e >> 13 & 0x7F8), 0);
          x_half(u, c, 0);
          mbar_wait(bb + (e >> 21 & 0x7F8), 0);
          x_half(u, c, 1);
        }
#pragma unroll 1
        for (int s = 0; s < (spare ? 0 : 16); s++) {
          mbar_wait(gfull + 8 * s, 0);
          if ((s & 3) == 3) asm volatile("red.relaxed.gpu.global.add.s32 [%0], 1;" ::"l"(&gp_.done[(s >> 2) * 32]) : "memory");
        }
      }
    }
  } else {
    asm volatile("setmaxnreg.inc.sync.aligned.u32 232;");
    auto dft2 = [&](int k2, int f2) {
      uint16_t a, b;
      asm volatile("ld.shared.u16 %0, [%1];" : "=h"(a) : "r"(tab | (k2 & 254)));
      asm volatile("ld.shared.u16 %0, [%1];" : "=h"(b) : "r"(tab | ((k2 + f2) & 254)));
      uint32_t r;
      asm("mov.b32 %0, {%1, %2};" : "=r"(r) : "h"(a), "h"(b));
      return r;
    };
    const int row = (lane & 7) + ((lane >> 3) & 1) * 8, hi = lane >> 4;
    asm volatile("barrier.cluster.wait.aligned;" ::: "memory");
    uint32_t fw[4];
    {
      uint32_t fa[16], za[64];
      bool first = true;
      const int rho = (lane >> 3) | (lane & 4);
      const int z2 = 2 * ((4 * bp + warp) | 1), zk = z2 * (lane & 3) * 2 - (warp & 1) * 64;
      const uint32_t lo = dft2(zk, z2), hh = dft2(zk + 8 * z2, z2);
#pragma unroll
      for (int i = 0; i < 64; i++) za[i] = ((i & 1) == (i >> 5) && rho == ((i >> 2) & 7)) ? ((i & 2) ? hh : lo) : 0u;
      reg_fence(za);
      const bool own = (warp >> 1) == rank;
      float d[64];
      constexpr uint64_t s2 = sched("02468:<>"), s3 = sched("13579;=?");
#pragma unroll 1
      for (uint64_t sc = spare ? (wg ? s3 : s2) : m.p.list[wg]; sc; sc >>= 5) {
        const int item = (int)sc & 31;
        if (item >= 18) {
          const int q = item - 18;
          const uint32_t e = __shfl_sync(0xffffffffu, lds32(ptab + 192 + 4 * q), 0);
#pragma unroll
          for (int jj = 0; jj < 4; jj++) {
            const int j = 4 * q + jj;
            mbar_wait(rfull + 8 * j, 0);
            wg_fence();
#pragma unroll
            for (int i = 0; i < 4; i++)
              wgmma_rs_128<1, 1, 1>(d, za[16 * jj + 4 * i], za[16 * jj + 4 * i + 1], za[16 * jj + 4 * i + 2], za[16 * jj + 4 * i + 3],
                                    mk_desc(sb + place(rank, e >> (4 * jj) & 15), i * 2048, 8192, 1024, 1), jj | i);
            wg_commit();
            if (jj > 0) {
              wg_wait<1>();
              if (lane == 0) mbar_arrive(rempty + 8 * (j - 1));
            }
          }
          wg_wait<0>();
          reg_fence(d);
          if (lane == 0) mbar_arrive(rempty + 8 * (4 * q + 3));
          mbar_wait(bb + (e >> (own ? 13 : 21) & 0x7F8), 0);
          const uint32_t rb = (own ? sb : peer) + (8 * rank + q) * 8192 + (warp & 1) * 4096 + rho * 128;
          auto put_w = [&](auto remote) {
#pragma unroll
            for (int v = 0; v < 8; v++) {
              const int j = 4 * (v >> 1), h = v & 1;
              const uint32_t a = rb + (j >> 3) * 2048 + h * 1024 + ((((j & 4) + (lane & 3)) ^ rho) << 4);
              const uint32_t p0 = pack2(d[4 * j + 2 * h], d[4 * j + 2 * h + 1]), p1 = pack2(d[4 * j + 4 + 2 * h], d[4 * j + 5 + 2 * h]);
              const uint32_t p2 = pack2(d[4 * j + 8 + 2 * h], d[4 * j + 9 + 2 * h]), p3 = pack2(d[4 * j + 12 + 2 * h], d[4 * j + 13 + 2 * h]);
              if (decltype(remote)::value)
                asm volatile("st.async.shared::cluster.mbarrier::complete_tx::bytes.v4.b32 [%0], {%1, %2, %3, %4}, [%5];"
                             ::"r"(a), "r"(p0), "r"(p1), "r"(p2), "r"(p3), "r"(peer + (win - sb)) : "memory");
              else
                asm volatile("st.shared.v4.b32 [%0], {%1, %2, %3, %4};" ::"r"(a), "r"(p0), "r"(p1), "r"(p2), "r"(p3) : "memory");
            }
          };
          if (own) put_w(std::false_type());
          else put_w(std::true_type());
        } else {
          const int u = item - 1;
          const int c = lds32(xtab + 4 * u);
          const uint32_t in = sb + (c & 0x3C000);
          if (first) {
            first = false;
#pragma unroll
            for (int i = 0; i < 16; i++) {
              const int f2 = 2 * ((warp * 16 + (lane >> 2) + 8 * (i & 1)) | 1);
              fa[i] = dft2(f2 * ((lane & 3) * 2 + 8 * (i >> 1)) - (lane & 4) * 16, f2);
            }
          }
          mbar_wait(xfull + 8 * u, 0);
          wg_fence();
#pragma unroll
          for (int k = 0; k < 4; k++)
            wgmma_rs_128<1, 1, 1>(d, fa[4 * k], fa[4 * k + 1], fa[4 * k + 2], fa[4 * k + 3], mk_desc(in, k * 2048, 6144, 1024, 1), k);
          wg_commit();
          wg_wait<0>();
          reg_fence(d);
          bar_sync(1 + wg, 128);
          const uint32_t rb = in + (warp * 16 + row) * 128, xr = (lane & 7) ^ (c & 3);
#pragma unroll
          for (int j = 0; j < 16; j += 2)
            stsm4(rb + ((j >> 2) & 1) * 8192 + ((((j >> 3) * 4 + (j & 3) + hi) ^ xr) << 4), pack2(d[4 * j], d[4 * j + 1]),
                  pack2(d[4 * j + 2], d[4 * j + 3]), pack2(d[4 * j + 4], d[4 * j + 5]), pack2(d[4 * j + 6], d[4 * j + 7]));
          fence_async();
          __syncwarp();
          if (lane == 0) mbar_arrive(xready + 8 * u);
        }
      }
#pragma unroll
      for (int i = 0; i < 4; i++) {
        const int f2 = 2 * ((warp * 16 + (lane >> 2) + 8 * (i & 1)) | 1);
        fw[i] = dft2(f2 * ((lane & 3) * 2 + 8 * (i >> 1)) - (lane & 4) * 16, f2);
      }
    }
    if (spare) {
      float* sg = reinterpret_cast<float*>(smem_k1 + K1_R);
      __nv_bfloat16* sw = reinterpret_cast<__nv_bfloat16*>(sg + 16 * 256);
      const int c0 = (cta - 128) * 64;
      uint4 vw[8], vg[2];
#pragma unroll
      for (int i = 0; i < 8; i++) vw[i] = __ldg(reinterpret_cast<const uint4*>(wgt + ((i * 256 + tid) >> 3) * 256 + c0 + (tid & 7) * 8));
#pragma unroll
      for (int i = 0; i < 2; i++) vg[i] = __ldg(reinterpret_cast<const uint4*>(g) + i * 256 + tid);
#pragma unroll
      for (int i = 0; i < 8; i++) reinterpret_cast<uint4*>(sw)[i * 256 + tid] = vw[i];
#pragma unroll
      for (int i = 0; i < 2; i++) {
        const uint32_t w4[4] = {vg[i].x, vg[i].y, vg[i].z, vg[i].w};
#pragma unroll
        for (int e = 0; e < 4; e++) {
          sg[(i * 256 + tid) * 8 + 2 * e] = __uint_as_float(w4[e] << 16);
          sg[(i * 256 + tid) * 8 + 2 * e + 1] = __uint_as_float(w4[e] & 0xffff0000u);
        }
      }
      bar_sync(3, 256);
      const int col = tid & 63, r0 = (tid >> 6) * 4;
      float a0 = 0.f, a1 = 0.f, a2 = 0.f, a3 = 0.f;
#pragma unroll 8
      for (int k = 0; k < 256; k++) {
        const float w = __bfloat162float(sw[k * 64 + col]);
        a0 = fmaf(sg[(r0 + 0) * 256 + k], w, a0);
        a1 = fmaf(sg[(r0 + 1) * 256 + k], w, a1);
        a2 = fmaf(sg[(r0 + 2) * 256 + k], w, a2);
        a3 = fmaf(sg[(r0 + 3) * 256 + k], w, a3);
      }
      const int cc = c0 + col;
      const int pos = (cc & ~15) + ((cc >> 1) & 3) * 4 + ((cc >> 3) & 1) * 2 + (cc & 1);
      gp_.ge[(r0 + 0) * 256 + pos] = __bfloat162float(__float2bfloat16_rn(a0));
      gp_.ge[(r0 + 1) * 256 + pos] = __bfloat162float(__float2bfloat16_rn(a1));
      gp_.ge[(r0 + 2) * 256 + pos] = __bfloat162float(__float2bfloat16_rn(a2));
      gp_.ge[(r0 + 3) * 256 + pos] = __bfloat162float(__float2bfloat16_rn(a3));
      return;
    }
    reg_fence(fw);
    mbar_wait(win, 0);
    fence_async();
    bar_sync(3, 256);
    float d[16];
    auto t_begin = [&](int it, int hh, int r) {
      if (r == 0) mbar_wait(inf0 + 8 * (it & 1), (it >> 1) & 1);
      wg_fence();
      wgmma_rs_32<1, 1, 1>(d, fw[0], fw[1], fw[2], fw[3], mk_desc(sb + K1_TIN + (it & 1) * 4096 + hh * 2048, r * 64, 0, 1024, 1), 0);
      wg_commit();
    };
    auto t_end = [&](int it, int hh, int r) {
      reg_fence(d);
      const int j = it & 1;
      if (r == 0) mbar_wait(it >= 2 ? se0 + 8 * j : bb + (m.p.last >> (5 + 8 * it) & 0x7F8), it >= 2 ? ((it >> 1) - 1) & 1 : 0);
      else if (lane == 0) mbar_arrive(ine0 + 8 * j);
      const uint32_t rb = sb + K1_T + j * 16384 + hh * 8192 + (warp * 16 + row) * 128;
#pragma unroll
      for (int i = 0; i < 2; i++)
        stsm4(rb + (((4 * r + 2 * i + hi) ^ (lane & 7)) << 4), pack2(d[8 * i], d[8 * i + 1]), pack2(d[8 * i + 2], d[8 * i + 3]),
              pack2(d[8 * i + 4], d[8 * i + 5]), pack2(d[8 * i + 6], d[8 * i + 7]));
      if (r == 1) {
        fence_async();
        __syncwarp();
        if (lane == 0) mbar_arrive(sf0 + 8 * j);
      }
    };
    float y0[NB1 / 2], y1[NB1 / 2];
    uint32_t wa[8], wb[8];
    uint32_t wp = sb + wg * 4096 + ((lane & 7) + hi * 8) * 128 + (((2 * warp + ((lane >> 3) & 1)) ^ (lane & 7)) << 4);
    const uint32_t neg = wg ? 0x80008000u : 0u;
    auto frag = [&](uint32_t (&w)[8], uint32_t a, uint32_t sg) {
      ldsm4t(a, w[0], w[1], w[2], w[3]);
      ldsm4t(a + 2048, w[4], w[5], w[6], w[7]);
#pragma unroll
      for (int i = 0; i < 8; i++) w[i] ^= sg;
    };
    auto stage = [&](const uint32_t (&w)[8], uint32_t x4, int acc) {
      wg_fence();
      wgmma_rs_168<1, 1, 0>(y0, w[0], w[1], w[2], w[3], mk_desc4(x4, 0, 512, 2), acc);
      wgmma_rs_168<1, 1, 0>(y1, w[0], w[1], w[2], w[3], mk_desc4(x4 + G_ST / 32, 0, 512, 2), acc);
      wgmma_rs_168<1, 1, 0>(y0, w[4], w[5], w[6], w[7], mk_desc4(x4 + 2, 0, 512, 2), 1);
      wgmma_rs_168<1, 1, 0>(y1, w[4], w[5], w[6], w[7], mk_desc4(x4 + G_ST / 32 + 2, 0, 512, 2), 1);
      wg_commit();
      wg_wait<1>();
    };
    frag(wa, wp, neg);
    int it = 0;
#pragma unroll 1
    for (int k = 0; k < G_KM; k++) {
      const bool T = ((G_TM ? G_TM : m.p.tmask) >> k) & 1;
      const uint32_t xa = ((sb & 0x3FFFF) >> 4) + m.slot[2 * k], xb = ((sb & 0x3FFFF) >> 4) + m.slot[2 * k + 1];
      if (T) t_begin(it, wg, 0);
      mbar_wait(gfull + 16 * k, 0);
      stage(wa, xa, k);
      frag(wb, wp ^ 4096, 0);
      if (k > 0 && lane == 0) mbar_arrive(gdone + 16 * k - 8);
      if (T) {
        t_end(it, wg, 0);
        t_begin(it, wg, 1);
      }
      mbar_wait(gfull + 16 * k + 8, 0);
      stage(wb, xb, 1);
      wp += 8192;
      frag(wa, wp, neg);
      if (lane == 0) mbar_arrive(gdone + 16 * k);
      if (T) t_end(it++, wg, 1);
    }
    auto tail = [&](float (&y)[NB1 / 2], auto batch, auto wgc) {
      constexpr int B = decltype(batch)::value, W = decltype(wgc)::value;
#pragma unroll
      for (int k = G_KM; k < 16; k++) {
        const int s = G_KM + k + G_TK * B;
        mbar_wait(gfull + 8 * s, 0);
        const int xo = g_off(g_slot(s));
        wg_fence();
#pragma unroll
        for (int h = 0; h < 4; h++) {
          const uint64_t dW = mk_desc(sb, k * 8192 + ((h >> 1) ^ W) * 4096 + (h & 1) * 2048, 0, 1024, 1);
          const uint64_t dX = mk_desc(sb, xo + (h >> 1) * (G_ST / 2) + (h & 1) * 32, 0, 512, 2);
          if (W == 1 && h < 2) wgmma_ss_168<-1, 1, 1, 0>(y, dW, dX, 1);
          else wgmma_ss_168<1, 1, 1, 0>(y, dW, dX, 1);
        }
        if (s <= 26) {
          wg_commit();
          if (W == 0 || k > G_KM) {
            wg_wait<1>();
            if (lane == 0) mbar_arrive(gdone + 8 * (s - 1));
          }
        }
      }
      wg_commit();
    };
    constexpr std::integral_constant<int, 0> c0;
    constexpr std::integral_constant<int, 1> c1;
    auto put = [&](const float (&v)[NB1 / 2], uint32_t stg, int b) {
      const int mi = lane >> 3, i = lane & 7;
      const uint32_t a0 = stg + (mi >> 1) * 1024 + i * 128 + (((2 * warp + (mi & 1)) ^ i) << 4);
      constexpr int J = 21 / G_EPI;
#pragma unroll
      for (int c = 0; c < G_EPI; c++) {
#pragma unroll
        for (int j = c * J; j + 1 < (c + 1) * J; j += 2)
          stsm4t(a0 + j * 1024, pack2(v[4 * j], v[4 * j + 1]), pack2(v[4 * j + 2], v[4 * j + 3]),
                 pack2(v[4 * j + 4], v[4 * j + 5]), pack2(v[4 * j + 6], v[4 * j + 7]));
        const int j = (c + 1) * J - 1;
        asm volatile("stmatrix.sync.aligned.m8n8.x2.trans.shared.b16 [%0], {%1, %2};" ::"r"(a0 + j * 1024),
                     "r"(pack2(v[4 * j], v[4 * j + 1])), "r"(pack2(v[4 * j + 2], v[4 * j + 3])) : "memory");
        fence_async();
        bar_sync(1 + wg, 128);
        if (t == 0) {
          tma_st4<0>(&m.y, stg + c * J * 1024, 0, b * NB1 + c * J * 8, 2 * bin + wg, dc);
          bulk_commit();
        }
      }
    };
    if (wg == 0) {
      tail(y0, c0, c0);
      bar_arrive(4, 256);
      mbar_wait(gdone + 8 * (G_S0 - 1), 0);
      wg_wait<0>();
      reg_fence(y0);
      put(y0, sb + K1_Y0, 0);
      bar_sync(7, 256);
      tail(y1, c1, c0);
      bar_arrive(8, 256);
      if (t == 0) bulk_wait_read<0>();
      wg_wait<0>();
      reg_fence(y1);
      bar_sync(1, 128);
      put(y1, sb + K1_Y0, 1);
    } else {
      wg_wait<0>();
      if (lane == 0) mbar_arrive(gdone + 8 * (G_S0 - 1));
#pragma unroll 1
      for (int h2 = 2 * it; h2 < 16; h2++) {
#pragma unroll
        for (int r = 0; r < 2; r++) {
          t_begin(h2 >> 1, h2 & 1, r);
          wg_wait<0>();
          t_end(h2 >> 1, h2 & 1, r);
        }
      }
      bar_sync(4, 256);
      tail(y0, c0, c1);
      bar_arrive(7, 256);
      mbar_wait(se0, 1);
      mbar_wait(se0 + 8, 1);
      wg_wait<0>();
      reg_fence(y0);
      put(y0, sb + K1_T, 0);
      bar_sync(8, 256);
      tail(y1, c1, c1);
      wg_wait<0>();
      reg_fence(y1);
      put(y1, sb + g_off(g_slot(26)), 1);
    }
    if (t == 0) {
      bulk_wait_read<0>();
    }
  }
}

#define H_EPI 3
#define H_KS 11
#define C_W2 0
#define C_W2I 2
#define C_B0 0
#define C_PC 32
#define C_MAP 1
#define C_AHEAD 8
#define C_XA 1
#define C_TOK 1
constexpr int H_XP = 168 * 64, H_STAGE = 8192 + 2 * H_XP, H_NST = 7, K2_STG = H_NST * H_STAGE, K2_SMEM = K2_STG + 21504 + 1024;

template <int WG>
__device__ __forceinline__ void h_loop(float (&acc)[84], uint32_t sb, uint32_t full0, uint32_t empty0, int lane) {
#pragma unroll 1
  for (int k = 0; k < 16; k++) {
    const int st = k % H_NST;
    if (WG == 1 && k == H_KS) bar_sync(5, 256);
    mbar_wait(full0 + 8 * st, (k / H_NST) & 1);
    const uint32_t base = sb + st * H_STAGE;
    wg_fence();
#pragma unroll
    for (int s = 0; s < 2; s++) {
      const uint64_t dP = mk_desc(base, s * 2048, 0, 1024, 1), dQ = mk_desc(base, 4096 + s * 2048, 0, 1024, 1);
      const uint64_t dA = mk_desc(base, 8192 + s * 32, 0, 1024, 1), dB = mk_desc(base, 8192 + 64 + s * 32, 0, 1024, 1);
      wgmma_ss_168<1, 1, 1, 0>(acc, dP, WG == 0 ? dA : dB, k | s);
      wgmma_ss_168<WG == 0 ? 1 : -1, 1, 1, 0>(acc, dQ, WG == 0 ? dB : dA, 1);
    }
    wg_commit();
    if (WG == 0 && k == 15) bar_arrive(5, 256);
    if (k <= 10) {
      wg_wait<1>();
      if (k > 0 && k - 1 + H_NST < 16 && lane < 2) mbar_arrive_cta(empty0 + 8 * ((k - 1) % H_NST), lane);
    }
  }
  wg_wait<0>();
  reg_fence(acc);
}
template <int C0, int C1> __device__ __forceinline__ void gelu_pack(uint32_t (&p)[12], const float (&h)[24]) {
#pragma unroll
  for (int i = 4 * C0; i < 4 * C1; i++) p[i] = pack2(gelu(h[2 * i]), gelu(h[2 * i + 1]));
}
struct K2Maps {
  int stage[16], item[8], wpre, pad[7];
  CUtensorMap y, xa, xs, w, y2;
};

__global__ void __cluster_dims__(2, 1, 1) __launch_bounds__(512, 1)
k2(const Ptrs gp0, const char* __restrict__ x2, const __grid_constant__ K2Maps m, const __nv_bfloat16* __restrict__ wf,
   const __nv_bfloat16* __restrict__ wo) {
  const Ptrs gp_ = PT & 2 ? Ptrs{g_done, g_ge, c_img, c_ga} : gp0;
  extern __shared__ __align__(1024) uint8_t smem_k1[];
  const uint32_t sb = s2u(smem_k1);
  const int tid = threadIdx.x, wg = __shfl_sync(0xffffffffu, tid >> 7, 0), t = tid & 127;
  const int warp = __shfl_sync(0xffffffffu, t >> 5, 0), lane = t & 31;
  const int cta = blockIdx.x, rank = cta & 1, dc = cta & 3, bin = cta >> 2;
  const uint32_t sGi = sb + K2_STG, sF = sGi + 6144, bb = sb + K2_STG + 21504;
  const uint32_t yfull = bb, full0 = bb + 128, empty0 = bb + 192, cfull = bb + 256, ready = bb + 320, bfree = bb + 384;
  const int b = C_MAP ? cta & 1 : (cta >> 5) & 1, j = C_MAP ? cta >> 2 : cta & 31;
  const int len0 = j < 20 ? 3 : 2, len1 = j >= 12 ? 3 : 2;
  const int n00 = j < 20 ? 3 * j : 2 * j + 20, n01 = j < 12 ? 2 * j : 3 * j - 12, cs0 = 3 - (C_MAP ? cta >> 1 & 1 : cta >> 6);
  auto y_load = [&](int r, int i) {
    tma_ld5<1>(sb + (3 + 2 * r) * H_STAGE + i * 8192, &m.y, yfull + 64 * r + 8 * i, 0, 0, cs0 - 2 * r, 2 * (r ? n01 : n00) + i, b);
  };
  if (wg == 2 && warp == 0) {
    if (lane == 0) {
      prefetch_map(&m.y);
      for (int i = 0; i < 16; i++) mbar_init(yfull + 8 * i, 1);
      fence_bar_init();
    }
    __syncwarp();
    if (lane < 16) mbar_expect(yfull + 8 * lane, lane == 7 ? 6144 : 8192);
    bar_arrive(0, 512);
    asm volatile("barrier.cluster.arrive.relaxed.aligned;" ::: "memory");
    auto c_load = [&](int h) {
      asm volatile("cp.async.bulk.shared::cluster.global.mbarrier::complete_tx::bytes [%0], [%1], %2, [%3];"
                   ::"r"(sGi + 6144 * h), "l"(gp_.img + 1536 * h), "r"(6144 + 2048 * h), "r"(yfull + 56 + 64 * h) : "memory");
    };
    if (lane == 0) {
      c_load(0);
      c_load(1);
      pdl_wait();
      const int r2 = len0 == 2, i2 = r2 ? 2 : 6;
      constexpr int seq[6] = {2, 0, 1, C_B0 ? 4 : 8, C_B0 ? 3 : 4, C_B0 ? 8 : 3};
#pragma unroll
      for (int q = 0; q < 8; q++) {
        if (q >= C_AHEAD) mbar_wait(yfull + 8 * seq[q >= C_AHEAD ? q - C_AHEAD : 0], 0);
        if (q < 6) y_load(seq[q] >> 3, seq[q] & 7);
        else y_load(r2, i2 + 6 - q);
      }
      pdl_launch();
    }
    __syncwarp();
  } else {
    if (lane == 0 && wg == 3) {
      for (int i = 0; i < 8; i++) mbar_init(full0 + 64 * warp + 8 * i, warp == 0 ? 1 : warp == 1 ? 16 : 4);
      fence_bar_init();
    }
    if (tid == 0) {
      mbar_init(bfree, 2);
      for (int i = 1; i < 5; i++) mbar_init(bfree + 8 * i, 1);
      mbar_arrive(bfree + 8);
      fence_bar_init();
    }
    if (tid == 128) {
      prefetch_map(&m.xa);
      prefetch_map(&m.xs);
      prefetch_map(&m.w);
      prefetch_map(&m.y2);
    }
    bar_sync(0, 512);
    asm volatile("barrier.cluster.arrive.relaxed.aligned;" ::: "memory");
  }
  if (wg == 2) asm volatile("barrier.cluster.wait.aligned;" ::: "memory");
  mbar_wait(yfull + 56, 0);
  auto idft = [&](float (&h)[24], uint32_t in, uint32_t bar) {
    mbar_wait(bar, 0);
    wg_fence();
#pragma unroll
    for (int k = 0; k < 4; k++) wgmma_ss_48<1, 1, 1, 0>(h, mk_desc(in, k * 2048, 0, 1024, 1), mk_desc(sGi, k * 32, 0, 1024, 1), k);
    wg_commit();
  };
  auto carry_out = [&](const uint32_t (&p)[12], uint32_t dst, uint32_t bar) {
    bar_sync(1 + wg, 128);
#pragma unroll
    for (int v = 0; v < 3; v++)
      asm volatile("st.shared.v4.b32 [%0], {%1, %2, %3, %4};" ::"r"(dst + v * 2048 + t * 16), "r"(p[4 * v]), "r"(p[4 * v + 1]), "r"(p[4 * v + 2]), "r"(p[4 * v + 3]) : "memory");
    __syncwarp();
    if (lane == 0) mbar_arrive(bar);
  };
  if (wg == 3) {
#pragma unroll 1
    for (int r = 0; r < 2; r++) {
      float h[24];
      uint32_t p[12];
      idft(h, sb + (3 + 2 * r) * H_STAGE, yfull + 64 * r);
      wg_wait<0>();
      reg_fence(h);
      gelu_pack<0, 3>(p, h);
      if (j == 0) p[0] = p[1] = p[2] = p[3] = 0;
      carry_out(p, sb + (3 + 2 * r) * H_STAGE, cfull + 32 * r);
    }
    asm volatile("barrier.cluster.wait.aligned;" ::: "memory");
    if (lane == 0) {
      if (warp == 0) {
        auto w_load = [&](int k) {
          mbar_expect(full0 + 8 * (k % H_NST), H_STAGE);
          tma_ld4<1>(sb + (k % H_NST) * H_STAGE, &m.w, full0 + 8 * (k % H_NST), 0, (k & 1) * 32, dc, (7 - (k >> 1)) * 64 + 2 * bin);
        };
        const int wpre = m.wpre;
        for (int k = 0; k < wpre; k++) w_load(k);
#pragma unroll 1
        for (int k = 0; k < 16; k++) {
          const int st = k % H_NST, e = m.stage[k];
          if ((k & 7) == 0) {
            poll_ge(&gp_.done[(6 + (k >> 3)) * 32], 128);
            asm volatile("fence.proxy.async.global;" ::: "memory");
            if (k == 0) mbar_arrive(bfree + 32);
          }
          if (e) mbar_wait(bb + 8 * e, 0);
          if (k == 5) mbar_wait(bfree, 0);
          if (k >= H_NST) mbar_wait(empty0 + 8 * st, ((k / H_NST) - 1) & 1);
          asm volatile("cp.async.bulk.shared::cluster.global.mbarrier::complete_tx::bytes.multicast::cluster [%0], [%1], %2, [%3], %4;"
                       ::"r"(sb + st * H_STAGE + 8192 + rank * H_XP),
                       "l"(x2 + (((7 - (k >> 2) - (k & 2) * 2) * 64 + (k & 1) * 32 + bin) * 2 + rank) * H_XP), "n"(H_XP), "r"(full0 + 8 * st),
                       "h"((uint16_t)3) : "memory");
          if (k >= wpre) w_load(k);
          if (k == 8) {
            if (cta == 0) asm volatile("cp.async.bulk.prefetch.L2.global [%0], 6144;" ::"l"(gp_.ga) : "memory");
            asm volatile("cp.async.bulk.prefetch.L2.global [%0], 1024;" ::"l"(wf + cta * 512) : "memory");
            asm volatile("cp.async.bulk.prefetch.L2.global [%0], 1024;" ::"l"(wo + cta * 512) : "memory");
          }
        }
      } else if (warp < 3) {
        const int r = warp - 1, n0 = b * NB2 + (r ? n01 : n00), f0 = (cs0 - 2 * r) * 64;
#pragma unroll 1
        for (int i = 0; i < (r ? len1 : len0); i++) {
          const uint32_t src = sb + (3 + 2 * r) * H_STAGE + i * 16384;
          const int e = m.item[4 * r + i], burst = (16 << (e >> 8)) - 1;
          if (r) mbar_wait(bb + 8 * (e & 255), 0);
          mbar_wait(ready + 32 * r + 8 * i, 0);
          if (C_XA && !r) {
            tma_st4<0>(&m.xa, src, 0, f0, 0, n0 + i);
            bulk_commit();
            continue;
          }
#pragma unroll 1
          for (int p = 0; p < 128; p += C_PC) {
            tma_st3<0>(&m.xs, src + p * 128, 0, f0 + (p & 63) + (p >> 6) * 256, n0 + i);
            bulk_commit();
            if (((p + C_PC) & burst) == 0) bulk_wait_read<0>();
          }
        }
        asm volatile("cp.async.bulk.wait_group 0;" ::: "memory");
        if (r) {
          mbar_arrive_cta(bfree, 0);
          mbar_arrive_cta(bfree, 1);
        }
        if (!r) mbar_arrive(bfree + 16);
        asm volatile("red.release.gpu.global.add.s32 [%0], 1;" ::"l"(&gp_.done[(6 + r) * 32]) : "memory");
        if (!r) mbar_arrive(bfree + 24);
      }
    }
    return;
  }
#pragma unroll 1
  for (int it = wg; it < len0 + len1; it += 3) {
    const int r = it >= len0, i = it - r * len0;
    const bool last = i + 1 == (r ? len1 : len0);
    const uint32_t in = sb + (3 + 2 * r) * H_STAGE + i * 16384, bar = yfull + 64 * r + 16 * i;
    float h1[24], h2[24];
    uint32_t p0[12], p1[12], p2[12];
    idft(h2, in + 16384, bar + 16);
    auto y_next = [&]() {
      const int ib = 3 + warp - len0;
      if (lane == 0 && ib < len1) {
        y_load(1, 2 * ib + 2);
        y_load(1, 2 * ib + 1);
      }
    };
    if (C_W2 == 0 && it == C_W2I) y_next();
    if (C_TOK && it > 0) bar_sync(6 + wg, 256);
    wg_wait<0>();
    reg_fence(h2);
    gelu_pack<0, 2>(p2, h2);
    idft(h1, in + 8192, bar + 8);
    if (C_W2 == 1 && it == C_W2I) y_next();
    if (!last) {
      gelu_pack<2, 3>(p2, h2);
      carry_out(p2, in + 16384, cfull + 32 * r + 8 * i + 8);
    }
    if (C_TOK == 1 && it + 1 < len0 + len1) bar_arrive(6 + (wg + 1) % 3, 256);
    mbar_wait(cfull + 32 * r + 8 * i, 0);
#pragma unroll
    for (int v = 0; v < 3; v++)
      asm volatile("ld.shared.v4.b32 {%0, %1, %2, %3}, [%4];" : "=r"(p0[4 * v]), "=r"(p0[4 * v + 1]), "=r"(p0[4 * v + 2]), "=r"(p0[4 * v + 3]) : "r"(in + v * 2048 + t * 16) : "memory");
    if (it < 3) mbar_wait(yfull + 120, 0);
    wg_wait<0>();
    reg_fence(h1);
    gelu_pack<0, 3>(p1, h1);
    if (last && j == 31) {
#pragma unroll
      for (int v = 0; v < 12; v++) p1[v] = p2[v] = 0;
    }
    if (C_TOK == 2 && it + 1 < len0 + len1) bar_arrive(6 + (wg + 1) % 3, 256);
    uint32_t hp[32];
#pragma unroll
    for (int c = 0; c < 8; c++)
#pragma unroll
      for (int v = 0; v < 4; v++) hp[(v >> 1) * 16 + 2 * c + (v & 1)] = c < 3 ? p0[4 * c + v] : c < 6 ? p1[4 * (c - 3) + v] : p2[4 * (c - 6) + v];
    float e0[32], e1[32];
    reg_fence(hp);
    wg_fence();
#pragma unroll
    for (int k = 0; k < 4; k++) {
      const uint64_t db = mk_desc(sF, k * 32, 0, 1024, 1);
      wgmma_rs_64<1, 1, 0>(e0, hp[4 * k], hp[4 * k + 1], hp[4 * k + 2], hp[4 * k + 3], db, k);
      wgmma_rs_64<1, 1, 0>(e1, hp[16 + 4 * k], hp[16 + 4 * k + 1], hp[16 + 4 * k + 2], hp[16 + 4 * k + 3], db, k);
    }
    wg_commit();
    bar_sync(1 + wg, 128);
    wg_wait<0>();
    reg_fence(e0);
    reg_fence(e1);
    {
      const int mi = lane >> 3, rr = (lane & 7) >> 1, blk = b * NB2 + (r ? n01 : n00) + i;
      const uint32_t a0 = in + (mi >> 1) * 8192 + (warp >> 1) * 4096 + rr * 128;
      const uint32_t pos = ((lane & 1) * 4 + (warp & 1) * 2 + (mi & 1)) ^ rr ^ (blk & 7);
#pragma unroll
      for (int q = 0; q < 8; q++)
        stsm4t(a0 + q * 512 + ((pos ^ (q & 1) * 4) << 4), pack2(e0[4 * q], e0[4 * q + 1]), pack2(e0[4 * q + 2], e0[4 * q + 3]),
               pack2(e1[4 * q], e1[4 * q + 1]), pack2(e1[4 * q + 2], e1[4 * q + 3]));
    }
    fence_async();
    __syncwarp();
    if (lane == 0) mbar_arrive(ready + 32 * r + 8 * i);
  }
  if (wg == 2) return;
  asm volatile("barrier.cluster.wait.aligned;" ::: "memory");
  float acc[84];
  if (wg == 0) {
    h_loop<0>(acc, sb, full0, empty0, lane);
  } else {
    h_loop<1>(acc, sb, full0, empty0, lane);
    bar_sync(2, 128);
  }
  const uint32_t stg = sb + (wg == 0 ? H_NST : 9 % H_NST) * H_STAGE;
  const int mi = lane >> 3, i = lane & 7;
  const uint32_t a0 = stg + (mi >> 1) * 1024 + i * 128 + (((2 * warp + (mi & 1)) ^ i) << 4);
  constexpr int J = 21 / H_EPI;
#pragma unroll
  for (int c = 0; c < H_EPI; c++) {
#pragma unroll
    for (int q = c * J; q + 1 < (c + 1) * J; q += 2)
      stsm4t(a0 + q * 1024, pack2(acc[4 * q], acc[4 * q + 1]), pack2(acc[4 * q + 2], acc[4 * q + 3]),
             pack2(acc[4 * q + 4], acc[4 * q + 5]), pack2(acc[4 * q + 6], acc[4 * q + 7]));
    const int q = (c + 1) * J - 1;
    asm volatile("stmatrix.sync.aligned.m8n8.x2.trans.shared.b16 [%0], {%1, %2};" ::"r"(a0 + q * 1024),
                 "r"(pack2(acc[4 * q], acc[4 * q + 1])), "r"(pack2(acc[4 * q + 2], acc[4 * q + 3])) : "memory");
    fence_async();
    bar_sync(1 + wg, 128);
    if (t == 0) {
      tma_st4<0>(&m.y2, stg + c * J * 1024, 0, c * J * 8, 2 * bin + wg, dc);
      bulk_commit();
    }
  }
  if (t == 0) {
    bulk_wait_read<0>();
  }
}

#define E_WPRE 2
#define E_LDS 1
#define E_WLATE 1
#define E_SPLIT 1
#define E_MID 1
#define E_EARLY0 2
#define E_EARLY 2
constexpr int E_SMEM = 65536 + 131072 + 32768 + 1024;

__device__ __forceinline__ uint32_t joint2(uint32_t fe, uint32_t g0, uint32_t g1) {
  uint32_t s0, s1;
  asm("{\n.reg .b16 l, h;\n.reg .b32 ll, hh;\nmov.b32 {l, h}, %2;\nmov.b32 ll, {l, l};\nmov.b32 hh, {h, h};\n"
      "fma.rn.bf16x2 %0, ll, %5, %3;\nfma.rn.bf16x2 %1, hh, %5, %4;\n}"
      : "=r"(s0), "=r"(s1) : "r"(fe), "r"(g0), "r"(g1), "r"(0x3F800000u));
  return pack2(tanh_f32(__uint_as_float(s0)), tanh_f32(__uint_as_float(s1)));
}
__device__ __forceinline__ uint4 lds128(uint32_t a) {
  uint4 v;
  asm volatile("ld.shared.v4.u32 {%0, %1, %2, %3}, [%4];" : "=r"(v.x), "=r"(v.y), "=r"(v.z), "=r"(v.w) : "r"(a));
  return v;
}
__device__ __forceinline__ void joint_group(uint32_t (&ja)[8], const uint32_t* fe, const uint4& c0, const uint4& c1) {
  ja[0] = joint2(fe[0], c0.x, c0.y);
  ja[1] = joint2(fe[1], c0.x, c0.y);
  ja[2] = joint2(fe[2], c0.z, c0.w);
  ja[3] = joint2(fe[3], c0.z, c0.w);
  ja[4] = joint2(fe[4], c1.x, c1.y);
  ja[5] = joint2(fe[5], c1.x, c1.y);
  ja[6] = joint2(fe[6], c1.z, c1.w);
  ja[7] = joint2(fe[7], c1.z, c1.w);
  reg_fence(ja);
}

__global__ void __launch_bounds__(256, 1)
kE(const Ptrs gp0, const __grid_constant__ CUtensorMap my, const __grid_constant__ CUtensorMap mwf, const __grid_constant__ CUtensorMap mwo,
   const __grid_constant__ CUtensorMap mout) {
  const Ptrs gp_ = PT & 4 ? Ptrs{g_done, g_ge, c_img, c_ga} : gp0;
  extern __shared__ uint8_t smem_raw[];
  __shared__ __align__(8) uint64_t bars[13];
  const uint32_t sb = (s2u(smem_raw) + 1023) & ~1023u;
  const int tid = threadIdx.x, wg = __shfl_sync(0xffffffffu, tid >> 7, 0), t = tid & 127, warp = t >> 5, lane = t & 31;
  const uint32_t R0 = sb, R1 = sb + 65536, R2 = sb + 65536 + 131072;
  const uint32_t barY = s2u(&bars[0]), barF = s2u(&bars[4]), barO = s2u(&bars[8]), barA = s2u(&bars[12]);
  const int b = blockIdx.x / 63, t0 = (blockIdx.x % 63) * 64;
  const int a = t0 / 48, o = t0 % 48;
  const int qw = o + 16 * warp, sel = qw >= 48;
  uint32_t ga[16];
#pragma unroll
  for (int s = 0; s < 4; s++)
    ldg128(reinterpret_cast<const uint4*>(gp_.ga) + ((qw >> 4) - 3 * sel) * 128 + s * 32 + lane, ga[4 * s], ga[4 * s + 1], ga[4 * s + 2], ga[4 * s + 3]);
  uint4 gev0, gev1;
  asm volatile("ld.global.cg.v4.u32 {%0, %1, %2, %3}, [%4];" : "=r"(gev0.x), "=r"(gev0.y), "=r"(gev0.z), "=r"(gev0.w)
               : "l"(reinterpret_cast<const uint4*>(gp_.ge) + (b * 8 + wg * 4) * 64 + t));
  asm volatile("ld.global.cg.v4.u32 {%0, %1, %2, %3}, [%4];" : "=r"(gev1.x), "=r"(gev1.y), "=r"(gev1.z), "=r"(gev1.w)
               : "l"(reinterpret_cast<const uint4*>(gp_.ge) + (b * 8 + wg * 4) * 64 + 128 + t));
  if (tid == 0) {
    prefetch_map(&my);
    for (int i = 0; i < 12; i++) mbar_init(barY + 8 * i, 1);
    mbar_init(barA, 8);
    fence_bar_init();
    fence_async();
    for (int i = 0; i < E_WPRE; i++) {
      const int kc = (i >> 1) | ((i & 1) << 1);
      mbar_expect(barF + 8 * kc, 32768);
      tma_ld3<0>(R1 + kc * 32768, &mwf, barF + 8 * kc, 0, kc * 64, 0);
    }
    pdl_wait();
    for (int i = 0; i < 4; i++) {
      mbar_expect(barY + 8 * i, 16384);
      tma_ld5<0>(R0 + i * 16384, &my, barY + 8 * i, 0, 0, 2 * (i & 1) + (i >> 1), a, b);
    }
    for (int i = E_WPRE; i < (E_WLATE ? 2 : 4); i++) {
      const int kc = (i >> 1) | ((i & 1) << 1);
      mbar_expect(barF + 8 * kc, 32768);
      tma_ld3<0>(R1 + kc * 32768, &mwf, barF + 8 * kc, 0, kc * 64, 0);
    }
    prefetch_map(&mwo);
    prefetch_map(&mout);
  }
  uint32_t gs[32];
#pragma unroll
  for (int i = 0; i < 16; i++) {
    gs[i] = sel ? 0u : ga[i];
    gs[16 + i] = sel ? ga[i] : 0u;
  }
  __syncthreads();
  if (blockIdx.x == 125 && tid < 8) gp_.done[tid * 32] = 0;
  reg_fence(gs);
  uint32_t gp = R2 + wg * 4096 + (lane & 3) * 16;
  uint4 g0, g1;
  uint32_t fe[64];
  {
    float d0[32], d1[32], e[64];
    mbar_wait(barY + 8 * wg, 0);
    wg_fence();
#pragma unroll
    for (int k = 0; k < 8; k++)
      wgmma_rs_64<1, 1, 1>(d0, gs[4 * k], gs[4 * k + 1], gs[4 * k + 2], gs[4 * k + 3], mk_desc(R0 + wg * 16384, k * 2048, 0, 1024, 1), k);
    wg_commit();
    if (E_WLATE == 1 && t == 0) {
      mbar_expect(barF + 8 + 16 * wg, 32768);
      tma_ld3<0>(R1 + (1 + 2 * wg) * 32768, &mwf, barF + 8 + 16 * wg, 0, (1 + 2 * wg) * 64, 0);
    }
    wg_wait<0>();
    reg_fence(d0);
#pragma unroll
    for (int i = 0; i < 32; i++) d0[i] = gelu(d0[i]);
    store_tile_64(d0, R2 + wg * 16384, warp, lane);
    mbar_wait(barY + 8 * (2 + wg), 0);
    wg_fence();
#pragma unroll
    for (int k = 0; k < 8; k++)
      wgmma_rs_64<1, 1, 1>(d1, gs[4 * k], gs[4 * k + 1], gs[4 * k + 2], gs[4 * k + 3], mk_desc(R0 + wg * 16384, 32768 + k * 2048, 0, 1024, 1), k);
    wg_commit();
    if (E_WLATE == 2 && t == 0) {
      mbar_expect(barF + 8 + 16 * wg, 32768);
      tma_ld3<0>(R1 + (1 + 2 * wg) * 32768, &mwf, barF + 8 + 16 * wg, 0, (1 + 2 * wg) * 64, 0);
    }
    fence_async();
    mbar_wait(barF, 0);
    mbar_wait(barF + 16, 0);
    __syncthreads();
    wg_fence();
#pragma unroll
    for (int i = 0; i < (E_SPLIT ? 4 : 8); i++) {
      const int kc = (i >> 2) * 2, s = i & 3;
      wgmma_ss_128<1, 1, 0, 1>(e, mk_desc(R2, kc * 8192 + s * 32, 0, 1024, 1),
                               mk_desc(R1 + wg * 16384, kc * 32768 + s * 2048, 8192, 1024, 1), i);
    }
    wg_commit();
    if (tid == 128) {
      mbar_expect(barO, 32768);
      tma_ld3<0>(R0, &mwo, barO, 0, 0, 0);
    }
    wg_wait<1>();
    reg_fence(d1);
#pragma unroll
    for (int i = 0; i < 8 * E_SPLIT; i++) d1[i] = gelu(d1[i]);
    if (E_SPLIT) {
      reg_fence(d1);
      mbar_wait(barF + 16, 0);
      wg_fence();
#pragma unroll
      for (int s = 0; s < 4; s++)
        wgmma_ss_128<1, 1, 0, 1>(e, mk_desc(R2, 2 * 8192 + s * 32, 0, 1024, 1), mk_desc(R1 + wg * 16384, 2 * 32768 + s * 2048, 8192, 1024, 1), 1);
      wg_commit();
    }
#pragma unroll
    for (int i = 8 * E_SPLIT; i < 32; i++) d1[i] = gelu(d1[i]);
    store_tile_64(d1, R2 + wg * 16384 + 8192, warp, lane);
    fence_async();
    mbar_wait(barF + 8, 0);
    mbar_wait(barF + 24, 0);
    __syncthreads();
    if (tid == 128) {
      mbar_expect(barO + 8, 32768);
      tma_ld3<0>(R0 + 32768, &mwo, barO + 8, 0, 64, 0);
    }
    if (wg == 1) bar_sync(4, 256);
    wg_fence();
#pragma unroll
    for (int i = 0; i < 8; i++) {
      const int kc = (i >> 2) * 2 + 1, s = i & 3;
      wgmma_ss_128<1, 1, 0, 1>(e, mk_desc(R2, kc * 8192 + s * 32, 0, 1024, 1),
                               mk_desc(R1 + wg * 16384, kc * 32768 + s * 2048, 8192, 1024, 1), 1);
    }
    wg_commit();
    if (wg == 0) bar_arrive(4, 256);
    wg_wait<1>();
    if (lane == 0) mbar_arrive(barA);
    if (tid == 128) {
      mbar_wait(barA, 0);
      for (int kc = 2; kc < 4; kc++) {
        mbar_expect(barO + 8 * kc, 32768);
        tma_ld3<0>(R1 + (kc - 2) * 65536, &mwo, barO + 8 * kc, 0, kc * 64, 0);
      }
    }
    mbar_wait(barA, 0);
    asm volatile("st.shared.v4.u32 [%0], {%1, %2, %3, %4};" ::"r"(R2 + wg * 4096 + ((t * 16) ^ (wg * 512))), "r"(gev0.x), "r"(gev0.y), "r"(gev0.z), "r"(gev0.w) : "memory");
    asm volatile("st.shared.v4.u32 [%0], {%1, %2, %3, %4};" ::"r"(R2 + wg * 4096 + 2048 + ((t * 16) ^ (wg * 512))), "r"(gev1.x), "r"(gev1.y), "r"(gev1.z), "r"(gev1.w) : "memory");
    bar_sync(1 + wg, 128);
    g0 = lds128(gp);
    g1 = lds128(gp + 64);
    wg_wait<0>();
    reg_fence(e);
#pragma unroll
    for (int i = 0; i < 32; i++) fe[i] = pack2(e[2 * i], e[2 * i + 1]);
  }
  auto publish = [&]() {
    bar_sync(1 + wg, 128);
    const int row = warp * 16 + (lane & 7) + ((lane >> 3) & 1) * 8;
    const uint32_t xb = R1 + (wg == 0 ? 3 * 32768 : 32768 + 16384) + row * 128;
#pragma unroll
    for (int s = 0; s < 8; s++) {
      const int jj = 2 * s + (lane >> 4);
      stsm4(xb + (s >> 2) * 8192 + (((jj & 7) ^ (lane & 7)) << 4), fe[4 * s], fe[4 * s + 1], fe[4 * s + 2], fe[4 * s + 3]);
    }
    bar_arrive(5 + wg, 256);
  };
  if (wg == 1) publish();
  const uint32_t stg = R1 + 32768 + wg * 65536;
  const uint32_t w0 = sb + wg * 65536, w1 = sb + 32768 + wg * 98304, w2 = sb + 65536 - wg * 65536, w3 = sb + 131072 - wg * 98304;
  float acc[128];
  uint32_t j0[8], j1[8], j2[8], j3[8];
  uint4 h0, h1;
  if (E_LDS) {
    h0 = lds128(gp + 128);
    h1 = lds128(gp + 192);
  }
#define E_PAIR(J, K, F, G, BAR)             \
  if (!E_LDS) {                             \
    h0 = lds128(gp + (G) - 128);            \
    h1 = lds128(gp + (G) - 64);             \
  }                                         \
  joint_group(J, fe + (F), g0, g1);         \
  if (E_MID && ui == 0) mbar_wait(BAR, 0);  \
  joint_group(K, fe + (F) + 8, h0, h1);     \
  g0 = lds128(gp + (G));                    \
  g1 = lds128(gp + (G) + 64);
  {
    const int ui = 0;
    E_PAIR(j0, j1, 0, 256, barO + 16 * wg)
    mbar_wait(barO + 16 * wg, 0);
  }
#define E_MMA4(J, K, W, FIRSTK, G, NEXTBAR)                                                     \
  wg_fence();                                                                                   \
  wgmma_rs_256<1, 1, 1>(acc, J[0], J[1], J[2], J[3], mk_desc(W, 0, 8192, 1024, 1), FIRSTK);     \
  wgmma_rs_256<1, 1, 1>(acc, J[4], J[5], J[6], J[7], mk_desc(W, 2048, 8192, 1024, 1), 1);       \
  wgmma_rs_256<1, 1, 1>(acc, K[0], K[1], K[2], K[3], mk_desc(W, 4096, 8192, 1024, 1), 1);       \
  wgmma_rs_256<1, 1, 1>(acc, K[4], K[5], K[6], K[7], mk_desc(W, 6144, 8192, 1024, 1), 1);       \
  wg_commit();                                                                                  \
  if ((ui + wg == 0 ? E_EARLY0 : E_EARLY) == (G) && (ui < 3 || wg == 0)) bar_arrive(4 - wg, 256); \
  wg_wait<1>();                                                                                 \
  if (E_LDS) {                                                                                  \
    h0 = lds128(gp + 256 * (G) + 384);                                                          \
    h1 = lds128(gp + 256 * (G) + 448);                                                          \
  }                                                                                             \
  if (ui == 0) mbar_wait(NEXTBAR, 0);
  const uint32_t bo0 = barO + 16 * wg, bo2 = barO + 16 * (1 - wg);
#pragma unroll 1
  for (int ui = 0; ui < 4; ui++) {
    if (ui > 0 || wg == 1) bar_sync(3 + wg, 256);
    E_MMA4(j0, j1, w0, 0, 0, E_MID ? bo0 : bo0 + 8)
    E_PAIR(j2, j3, 16, 512, bo0 + 8)
    E_MMA4(j2, j3, w1, 1, 1, E_MID ? bo0 + 8 : bo2)
    if (ui == 0) {
      if (wg == 0) publish();
      bar_sync(6 - wg, 256);
      const int row = warp * 16 + (lane & 7) + ((lane >> 3) & 1) * 8;
      const uint32_t xb = R1 + (wg == 1 ? 3 * 32768 : 32768 + 16384) + row * 128;
#pragma unroll
      for (int s = 0; s < 8; s++) {
        const int jj = 2 * s + (lane >> 4);
        ldsm4(xb + (s >> 2) * 8192 + (((jj & 7) ^ (lane & 7)) << 4), fe[32 + 4 * s], fe[33 + 4 * s], fe[34 + 4 * s], fe[35 + 4 * s]);
      }
    }
    E_PAIR(j0, j1, 32, 768, bo2)
    E_MMA4(j0, j1, w2, 1, 2, E_MID ? bo2 : bo2 + 8)
    E_PAIR(j2, j3, 48, 1024, bo2 + 8)
    E_MMA4(j2, j3, w3, 1, 3, bo2 + 8)
    gp += 1024;
    if (ui < 3) {
      E_PAIR(j0, j1, 0, 256, bo2 + 8)
    }
    if (t == 0) bulk_wait_read<0>();
    bar_sync(1 + wg, 128);
    wg_wait<0>();
    reg_fence(acc);
    const uint32_t rb = stg + (warp * 16 + (lane & 7) + ((lane >> 3) & 1) * 8) * 128;
#pragma unroll
    for (int h = 0; h < 2; h++) {
#pragma unroll
      for (int j = 16 * h; j < 16 * h + 16; j += 2) {
        const int jj = j + (lane >> 4);
        stsm4(rb + (j >> 3) * 8192 + (((jj & 7) ^ (lane & 7)) << 4), pack2(acc[4 * j], acc[4 * j + 1]), pack2(acc[4 * j + 2], acc[4 * j + 3]),
              pack2(acc[4 * j + 4], acc[4 * j + 5]), pack2(acc[4 * j + 6], acc[4 * j + 7]));
      }
      fence_async();
      bar_sync(1 + wg, 128);
      if (t == 0) {
        tma_st5<1>(&mout, stg + h * 16384, 0, t0, 2 * h, wg * 4 + ui, b);
        bulk_commit();
      }
    }
  }
  if (t == 0) bulk_wait_read<0>();
}

typedef CUresult (*EncodeFn)(CUtensorMap*, CUtensorMapDataType, cuuint32_t, void*, const cuuint64_t*, const cuuint64_t*,
                             const cuuint32_t*, const cuuint32_t*, CUtensorMapInterleave, CUtensorMapSwizzle,
                             CUtensorMapL2promotion, CUtensorMapFloatOOBfill);

CUtensorMap make_map(EncodeFn fn, const void* base, int rank, const uint64_t* dims, const uint64_t* strides, const uint32_t* box,
                     CUtensorMapSwizzle swz) {
  CUtensorMap m;
  cuuint64_t gd[5], gs[4];
  cuuint32_t bx[5], es[5];
  for (int i = 0; i < rank; i++) { gd[i] = dims[i]; bx[i] = box[i]; es[i] = 1; }
  for (int i = 0; i + 1 < rank; i++) gs[i] = strides[i];
  fn(&m, CU_TENSOR_MAP_DATA_TYPE_BFLOAT16, rank, const_cast<void*>(base), gd, gs, bx, es, CU_TENSOR_MAP_INTERLEAVE_NONE, swz,
     CU_TENSOR_MAP_L2_PROMOTION_NONE, CU_TENSOR_MAP_FLOAT_OOB_FILL_NONE);
  return m;
}

template <typename... KArgs, typename... Args>
void launch(void (*k)(KArgs...), int grid, int block, int smem, bool pdl, Args... args) {
  cudaLaunchConfig_t c = {};
  c.gridDim = dim3(grid);
  c.blockDim = dim3(block);
  c.dynamicSmemBytes = smem;
  c.stream = cudaStreamPerThread;
  cudaLaunchAttribute at[1];
  at[0].id = cudaLaunchAttributeProgrammaticStreamSerialization;
  at[0].val.programmaticStreamSerializationAllowed = 1;
  c.attrs = at;
  c.numAttrs = pdl ? 1 : 0;
  cudaLaunchKernelEx(&c, k, args...);
}

}

static uint32_t h_plan[67 + 25] = {
    0x6108, 0x6109, 0x610a, 0x610b, 0x6101, 0x8008, 0x8109, 0x820a, 0x830b, 0x8401,
    0x8508, 0x8609, 0x870a, 0x6102, 0x880b, 0x8a08, 0x8b09, 0x6103, 0x8c0a, 0x8d02,
    0x8e0b, 0x8f08, 0x9009, 0x9103, 0x920a, 0x9508, 0x9609, 0x9703, 0x980a, 0x9908,
    0x9a09, 0x9c0a, 0x61616115, 0x6161610d, 0x83806107, 0x83836126, 0x8684610c, 0x8a86314d, 0x8f8a3277, 0x9390940b,
    0x9494344c, 0x9b96354d, 0x0, 0x0, 0x0, 0x0, 0x0, 0x0, 0x6161ba98, 0x6161a981,
    0x6789981b, 0x67898b2a, 0x68932a39, 0x6893398b, 0x699b398a, 0x699ba98a, 0x39389d, 0x0, 0x4, 0xf74,
    0x8f6a0c52, 0xac1, 0x2e5a9261, 0x194a, 0x9e, 0x9f, 0x37, 0x0, 0x0, 0x0,
    0x10, 0x11, 0x13, 0x14, 0x0, 0x0, 0x0, 0x0, 0x0, 0x0,
    0x0, 0x0, 0x0, 0x431, 0x431, 0x431, 0x0, 0x133, 0x131, 0x331,
    0x0, 0x3,
};

extern "C" void kernel_launch(void* const* d_in, const int* in_sizes, int n_in, void* d_out, int out_size) {
  const __nv_bfloat16* x = (const __nv_bfloat16*)d_in[0];
  const __nv_bfloat16* w1 = (const __nv_bfloat16*)d_in[1];
  const __nv_bfloat16* w2 = (const __nv_bfloat16*)d_in[2];
  const __nv_bfloat16* g = (const __nv_bfloat16*)d_in[3];
  const __nv_bfloat16* wf = (const __nv_bfloat16*)d_in[4];
  const __nv_bfloat16* wgt = (const __nv_bfloat16*)d_in[5];
  const __nv_bfloat16* wo = (const __nv_bfloat16*)d_in[6];

  void* fp = nullptr;
  cudaDriverEntryPointQueryResult qr;
  cudaGetDriverEntryPoint("cuTensorMapEncodeTiled", &fp, cudaEnableDefault, &qr);
  EncodeFn fn = (EncodeFn)fp;
  void *X1, *W2, *Y1, *X2, *Y2;
  cudaGetSymbolAddress(&X1, g_X1);
  cudaGetSymbolAddress(&W2, g_W2);
  cudaGetSymbolAddress(&Y1, g_Y1);
  cudaGetSymbolAddress(&X2, g_X2);
  cudaGetSymbolAddress(&Y2, g_Y2);
  cudaFuncSetAttribute(k1, cudaFuncAttributeMaxDynamicSharedMemorySize, K1_SMEM);
  cudaFuncSetAttribute(k2, cudaFuncAttributeMaxDynamicSharedMemorySize, K2_SMEM);
  cudaFuncSetAttribute(kE, cudaFuncAttributeMaxDynamicSharedMemorySize, E_SMEM);
  if (ALIAS) {
    W2 = d_out;
    X2 = (char*)d_out + sizeof(g_W2);
    X1 = (char*)X2 - sizeof(g_X2);
    if (ALIAS == 1) Y2 = Y1;
  }
  const CUtensorMapSwizzle S128 = CU_TENSOR_MAP_SWIZZLE_128B;

  auto map_x = [&]() {
    uint64_t d[] = {64, 8000, 8, 2}, s[] = {1024, 128, 8000ull * 1024};
    uint32_t bx[] = {64, 56, 1, 1};
    return make_map(fn, x, 4, d, s, bx, S128);
  };
  auto map_w_in = [&](const __nv_bfloat16* w, int odd) {
    uint64_t d[] = {64, (uint64_t)(odd ? 15 : 16), 4, 256}, s[] = {2ull * 65536 * 2, 128, 512};
    uint32_t bx[] = {64, 16, 2, 1};
    return make_map(fn, w + (odd ? 65536 : 0), 4, d, s, bx, S128);
  };
  auto map_X_st = [&](void* p, int nb, int boxb) {
    uint64_t d[] = {64, 512, (uint64_t)(2 * nb)}, s[] = {2ull * nb * 128, 128};
    uint32_t bx[] = {64, C_PC, (uint32_t)boxb};
    return make_map(fn, p, 3, d, s, bx, S128);
  };
  auto map_X1_st = [&]() {
    uint64_t d[] = {64, 512, 2, (uint64_t)NB1}, s[] = {2ull * NB1 * 128, (uint64_t)NB1 * 128, 128};
    uint32_t bx[] = {64, 16, 1, 1};
    return make_map(fn, X1, 4, d, s, bx, S128);
  };
  auto map_W_st = [&](void* p) {
    uint64_t d[] = {64, 512, 4, 64}, s[] = {32768, 8192, 128};
    uint32_t bx[] = {64, W2_PC < 64 ? W2_PC : 64, W2_PC == 128 ? 2 : 1, 1};
    return make_map(fn, p, 4, d, s, bx, S128);
  };
  auto map_W_ld = [&](void* p, uint32_t bd, uint32_t bf) {
    uint64_t d[] = {64, 64, 4, 512}, s[] = {128, 8192, 32768};
    uint32_t bx[] = {64, 32, bd, bf};
    return make_map(fn, p, 4, d, s, bx, S128);
  };
  auto map_Y_st = [&](void* p, int nb, int rows) {
    uint64_t d[] = {64, (uint64_t)(2 * nb), 64, 4}, s[] = {32768, 128, 8192};
    uint32_t bx[] = {64, (uint32_t)rows, 1, 1};
    return make_map(fn, p, 4, d, s, bx, S128);
  };
  auto map_Y_ld = [&](void* p, int nb, int boxc, int boxb) {
    uint64_t d[] = {64, 64, 4, (uint64_t)nb, 2}, s[] = {128, 8192, 32768, (uint64_t)nb * 32768};
    uint32_t bx[] = {64, 64, (uint32_t)boxc, (uint32_t)boxb, 1};
    return make_map(fn, p, 5, d, s, bx, S128);
  };
  auto map_wsq = [&](const __nv_bfloat16* w) {
    uint64_t d[] = {64, 256, 4}, s[] = {512, 128};
    uint32_t bx[] = {64, 64, 4};
    return make_map(fn, w, 3, d, s, bx, S128);
  };
  auto map_out = [&]() {
    uint64_t d[] = {64, 4000, 4, 8, 2}, s[] = {4096, 128, 512, 4000ull * 4096};
    uint32_t bx[] = {64, 64, 2, 1, 1};
    return make_map(fn, d_out, 5, d, s, bx, S128);
  };

  auto map_w_raw = [&](const __nv_bfloat16* w, int odd) {
    uint64_t d[] = {256, (uint64_t)(odd ? 15 : 16), 16, 16}, s[] = {2ull * 65536 * 2, 512, 8192};
    uint32_t bx[] = {64, 16, 4, 2};
    return make_map(fn, w + (odd ? 65536 : 0), 4, d, s, bx, S128);
  };
  Ptrs gp;
  cudaGetSymbolAddress((void**)&gp.done, g_done);
  cudaGetSymbolAddress((void**)&gp.ge, g_ge);
  cudaGetSymbolAddress((void**)&gp.img, c_img);
  cudaGetSymbolAddress((void**)&gp.ga, c_ga);
  K1Maps g1;
  memcpy(&g1.p, h_plan, sizeof(Plan));
  g1.x = map_x();
  g1.we = map_w_raw(w1, 0);
  g1.wo = map_w_raw(w1, 1);
  g1.xs = map_X1_st();
  g1.y = map_Y_st(Y1, NB1, NB1 / G_EPI);
  g1.w2e = map_w_in(w2, 0);
  g1.w2o = map_w_in(w2, 1);
  g1.w2s = map_W_st(W2);
  for (int s = 0; s < 32; s++) {
    const int k = s < G_S0 ? s >> 1 : G_KM + (s - G_S0) % G_TK;
    g1.slot[s] = g_off(g_slot(s)) / 16;
    g1.src[s] = ((k >> 1) * 256 + (k & 1) * 2 + (s < G_S0 ? (s & 1) * 4 : s >= G_S0 + G_TK)) * (G_ST / 2);
    g1.dep[s] = s < 3 ? 8 * h_plan[64 + s] : 1536 + 8 * (s - g_depth(s));
  }
  launch(k1, 132, 384, K1_SMEM, false, gp, (const char*)X1, (const char*)w1, g1, g, wgt);
  K2Maps g2;
  memcpy(&g2, h_plan + 67, 100);
  g2.y = map_Y_ld(Y1, NB1, 1, 1);
  g2.xs = map_X_st(X2, NB2, 1);
  {
    uint64_t d[] = {64, 256, 2, 2 * NB2}, s[] = {2ull * NB2 * 128, 512ull * NB2 * 128, 128};
    uint32_t bx[] = {64, 64, 2, 1};
    g2.xa = make_map(fn, X2, 4, d, s, bx, S128);
  }
  g2.w = map_W_ld(W2, 1, 2);
  g2.y2 = map_Y_st(Y2, NB2, 168 / H_EPI);
  launch(k2, 128, 512, K2_SMEM, true, gp, (const char*)X2, g2, wf, wo);
  launch(kE, 126, 256, E_SMEM, true, gp, map_Y_ld(Y2, NB2, 1, 2), map_wsq(wf), map_wsq(wo), map_out());
}
```

```cpp
#include <cuda_runtime.h>
#include <cuda_bf16.h>
#include <cuda.h>
#include <stdint.h>
#include <string.h>
#include <type_traits>

#define ALIAS 1
namespace {

constexpr int NB1 = 168;
constexpr int NB2 = 84;

__device__ __align__(1024) __nv_bfloat16 g_X1[8 * 64 * 2 * NB1 * 64];
__device__ __align__(1024) __nv_bfloat16 g_W2[8 * 64 * 4 * 64 * 64];
__device__ __align__(1024) __nv_bfloat16 g_Y1[2 * NB1 * 4 * 64 * 64];
__device__ __align__(1024) __nv_bfloat16 g_X2[8 * 64 * 2 * NB2 * 64];
__device__ __align__(1024) __nv_bfloat16 g_Y2[2 * NB2 * 4 * 64 * 64];
__device__ __align__(1024) float g_ge[16 * 256];

__device__ __forceinline__ uint32_t s2u(const void* p) { return (uint32_t)__cvta_generic_to_shared(p); }
__device__ __forceinline__ void mbar_init(uint32_t b, int c) {
  asm volatile("mbarrier.init.shared::cta.b64 [%0], %1;" ::"r"(b), "r"(c) : "memory");
}
__device__ __forceinline__ void mbar_expect(uint32_t b, int bytes) {
  asm volatile("mbarrier.arrive.expect_tx.shared::cta.b64 _, [%0], %1;" ::"r"(b), "r"(bytes) : "memory");
}
__device__ __forceinline__ void mbar_arrive(uint32_t b) {
  asm volatile("mbarrier.arrive.shared::cta.b64 _, [%0];" ::"r"(b) : "memory");
}
__device__ __forceinline__ void mbar_arrive_cta(uint32_t b, uint32_t cta) {
  asm volatile("{\n.reg .b32 r;\nmapa.shared::cluster.u32 r, %0, %1;\nmbarrier.arrive.shared::cluster.b64 _, [r];\n}" ::"r"(b), "r"(cta) : "memory");
}
__device__ __forceinline__ void mbar_wait(uint32_t b, int ph) {
  asm volatile(
      "{\n.reg .pred p;\n.reg .u32 n;\n"
      "mov.u32 n, 0;\n"
      "MBW_LOOP:\n"
      "mbarrier.try_wait.parity.shared::cta.b64 p, [%0], %1;\n"
      "@p bra MBW_DONE;\n"
      "add.u32 n, n, 1;\n"
      "setp.lt.u32 p, n, 1048576;\n"
      "@p bra MBW_LOOP;\n"
      "MBW_DONE:\n}" ::"r"(b), "r"(ph) : "memory");
}
__device__ __forceinline__ void fence_bar_init() { asm volatile("fence.mbarrier_init.release.cluster;" ::: "memory"); }
__device__ __forceinline__ void fence_async() { asm volatile("fence.proxy.async.shared::cta;" ::: "memory"); }
__device__ __forceinline__ void bar_sync(int id, int n) { asm volatile("bar.sync %0, %1;" ::"r"(id), "r"(n) : "memory"); }
__device__ __forceinline__ void bar_arrive(int id, int n) { asm volatile("bar.arrive %0, %1;" ::"r"(id), "r"(n) : "memory"); }
__device__ __forceinline__ void pdl_wait() { asm volatile("griddepcontrol.wait;" ::: "memory"); }
__device__ __forceinline__ void pdl_launch() { asm volatile("griddepcontrol.launch_dependents;" ::: "memory"); }
__device__ __forceinline__ void prefetch_map(const CUtensorMap* m) {
  asm volatile("prefetch.tensormap [%0];" ::"l"(m) : "memory");
}
template <int P> __device__ __forceinline__ uint64_t policy() {
  uint64_t p;
  asm("createpolicy.fractional.L2::evict_first.b64 %0, 1.0;" : "=l"(p));
  return p;
}
template <int P> __device__ __forceinline__ void tma_ld3(uint32_t dst, const CUtensorMap* m, uint32_t bar, int c0, int c1, int c2) {
  if constexpr (P == 0)
    asm volatile("cp.async.bulk.tensor.3d.shared::cluster.global.mbarrier::complete_tx::bytes [%0], [%1, {%3, %4, %5}], [%2];"
                 ::"r"(dst), "l"(m), "r"(bar), "r"(c0), "r"(c1), "r"(c2) : "memory");
  else
    asm volatile("cp.async.bulk.tensor.3d.shared::cluster.global.mbarrier::complete_tx::bytes.L2::cache_hint [%0], [%1, {%3, %4, %5}], [%2], %6;"
                 ::"r"(dst), "l"(m), "r"(bar), "r"(c0), "r"(c1), "r"(c2), "l"(policy<P>()) : "memory");
}
template <int P> __device__ __forceinline__ void tma_ld4(uint32_t dst, const CUtensorMap* m, uint32_t bar, int c0, int c1, int c2, int c3) {
  if constexpr (P == 0)
    asm volatile("cp.async.bulk.tensor.4d.shared::cluster.global.mbarrier::complete_tx::bytes [%0], [%1, {%3, %4, %5, %6}], [%2];"
                 ::"r"(dst), "l"(m), "r"(bar), "r"(c0), "r"(c1), "r"(c2), "r"(c3) : "memory");
  else
    asm volatile("cp.async.bulk.tensor.4d.shared::cluster.global.mbarrier::complete_tx::bytes.L2::cache_hint [%0], [%1, {%3, %4, %5, %6}], [%2], %7;"
                 ::"r"(dst), "l"(m), "r"(bar), "r"(c0), "r"(c1), "r"(c2), "r"(c3), "l"(policy<P>()) : "memory");
}
template <int P> __device__ __forceinline__ void tma_ld5(uint32_t dst, const CUtensorMap* m, uint32_t bar, int c0, int c1, int c2, int c3, int c4) {
  if constexpr (P == 0)
    asm volatile("cp.async.bulk.tensor.5d.shared::cluster.global.mbarrier::complete_tx::bytes [%0], [%1, {%3, %4, %5, %6, %7}], [%2];"
                 ::"r"(dst), "l"(m), "r"(bar), "r"(c0), "r"(c1), "r"(c2), "r"(c3), "r"(c4) : "memory");
  else
    asm volatile("cp.async.bulk.tensor.5d.shared::cluster.global.mbarrier::complete_tx::bytes.L2::cache_hint [%0], [%1, {%3, %4, %5, %6, %7}], [%2], %8;"
                 ::"r"(dst), "l"(m), "r"(bar), "r"(c0), "r"(c1), "r"(c2), "r"(c3), "r"(c4), "l"(policy<P>()) : "memory");
}
template <int P> __device__ __forceinline__ void tma_st3(const CUtensorMap* m, uint32_t src, int c0, int c1, int c2) {
  if constexpr (P == 0)
    asm volatile("cp.async.bulk.tensor.3d.global.shared::cta.bulk_group [%0, {%2, %3, %4}], [%1];" ::"l"(m), "r"(src), "r"(c0), "r"(c1), "r"(c2) : "memory");
  else
    asm volatile("cp.async.bulk.tensor.3d.global.shared::cta.bulk_group.L2::cache_hint [%0, {%2, %3, %4}], [%1], %5;" ::"l"(m), "r"(src), "r"(c0), "r"(c1), "r"(c2), "l"(policy<P>()) : "memory");
}
template <int P> __device__ __forceinline__ void tma_st4(const CUtensorMap* m, uint32_t src, int c0, int c1, int c2, int c3) {
  if constexpr (P == 0)
    asm volatile("cp.async.bulk.tensor.4d.global.shared::cta.bulk_group [%0, {%2, %3, %4, %5}], [%1];" ::"l"(m), "r"(src), "r"(c0), "r"(c1), "r"(c2), "r"(c3) : "memory");
  else
    asm volatile("cp.async.bulk.tensor.4d.global.shared::cta.bulk_group.L2::cache_hint [%0, {%2, %3, %4, %5}], [%1], %6;" ::"l"(m), "r"(src), "r"(c0), "r"(c1), "r"(c2), "r"(c3), "l"(policy<P>()) : "memory");
}
template <int P> __device__ __forceinline__ void tma_st5(const CUtensorMap* m, uint32_t src, int c0, int c1, int c2, int c3, int c4) {
  if constexpr (P == 0)
    asm volatile("cp.async.bulk.tensor.5d.global.shared::cta.bulk_group [%0, {%2, %3, %4, %5, %6}], [%1];" ::"l"(m), "r"(src), "r"(c0), "r"(c1), "r"(c2), "r"(c3), "r"(c4) : "memory");
  else
    asm volatile("cp.async.bulk.tensor.5d.global.shared::cta.bulk_group.L2::cache_hint [%0, {%2, %3, %4, %5, %6}], [%1], %7;" ::"l"(m), "r"(src), "r"(c0), "r"(c1), "r"(c2), "r"(c3), "r"(c4), "l"(policy<P>()) : "memory");
}
__device__ __forceinline__ void bulk_commit() { asm volatile("cp.async.bulk.commit_group;" ::: "memory"); }
template <int N> __device__ __forceinline__ void bulk_wait_read() { asm volatile("cp.async.bulk.wait_group.read %0;" ::"n"(N) : "memory"); }
__device__ __forceinline__ void wg_fence() { asm volatile("wgmma.fence.sync.aligned;" ::: "memory"); }
__device__ __forceinline__ void wg_commit() { asm volatile("wgmma.commit_group.sync.aligned;" ::: "memory"); }
template <int N> __device__ __forceinline__ void wg_wait() { asm volatile("wgmma.wait_group.sync.aligned %0;" ::"n"(N) : "memory"); }
template <int R> __device__ __forceinline__ void reg_fence(float (&d)[R]) {
#pragma unroll
  for (int i = 0; i < R; i++) asm volatile("" : "+f"(d[i])::"memory");
}
template <int R> __device__ __forceinline__ void reg_fence(uint32_t (&d)[R]) {
#pragma unroll
  for (int i = 0; i < R; i++) asm volatile("" : "+r"(d[i])::"memory");
}
__device__ __forceinline__ void stsm4(uint32_t a, uint32_t r0, uint32_t r1, uint32_t r2, uint32_t r3) {
  asm volatile("stmatrix.sync.aligned.m8n8.x4.shared.b16 [%0], {%1, %2, %3, %4};" ::"r"(a), "r"(r0), "r"(r1), "r"(r2), "r"(r3) : "memory");
}
__device__ __forceinline__ void stsm4t(uint32_t a, uint32_t r0, uint32_t r1, uint32_t r2, uint32_t r3) {
  asm volatile("stmatrix.sync.aligned.m8n8.x4.trans.shared.b16 [%0], {%1, %2, %3, %4};" ::"r"(a), "r"(r0), "r"(r1), "r"(r2), "r"(r3) : "memory");
}
__device__ __forceinline__ void ldsm4(uint32_t a, uint32_t& r0, uint32_t& r1, uint32_t& r2, uint32_t& r3) {
  asm volatile("ldmatrix.sync.aligned.m8n8.x4.shared.b16 {%0, %1, %2, %3}, [%4];" : "=r"(r0), "=r"(r1), "=r"(r2), "=r"(r3) : "r"(a) : "memory");
}
__device__ __forceinline__ void ldsm4t(uint32_t a, uint32_t& r0, uint32_t& r1, uint32_t& r2, uint32_t& r3) {
  asm volatile("ldmatrix.sync.aligned.m8n8.x4.trans.shared.b16 {%0, %1, %2, %3}, [%4];" : "=r"(r0), "=r"(r1), "=r"(r2), "=r"(r3) : "r"(a) : "memory");
}
__device__ __forceinline__ void ldg128(const uint4* p, uint32_t& a, uint32_t& b, uint32_t& c, uint32_t& d) {
  asm volatile("ld.global.nc.v4.u32 {%0, %1, %2, %3}, [%4];" : "=r"(a), "=r"(b), "=r"(c), "=r"(d) : "l"(p));
}
__device__ __forceinline__ uint32_t pack2(float lo, float hi) {
  uint32_t r;
  asm("cvt.rn.bf16x2.f32 %0, %1, %2;" : "=r"(r) : "f"(hi), "f"(lo));
  return r;
}
__device__ __forceinline__ float tanh_f32(float x) {
  float y;
  asm("tanh.approx.f32 %0, %1;" : "=f"(y) : "f"(x));
  return y;
}
__device__ __forceinline__ float gelu(float hx) {
  const float u = hx * fmaf(hx * hx, 8.0f * 0.044715f * 0.7978845608028654f, 2.0f * 0.7978845608028654f);
  return fmaf(hx, tanh_f32(u), hx);
}
__device__ __forceinline__ uint64_t mk_desc4(uint32_t addr4, uint32_t lbo, uint32_t sbo, uint32_t swz) {
  const uint32_t lo = addr4 + ((lbo >> 4) << 16), hi = (sbo >> 4) | (swz << 30);
  uint64_t d;
  asm("mov.b64 %0, {%1, %2};" : "=l"(d) : "r"(lo), "r"(hi));
  return d;
}
#define mk_desc(base, off, lbo, sbo, swz) mk_desc4((((base) & 0x3FFFF) >> 4) + ((off) >> 4), lbo, sbo, swz)

template <int SA, int SB, int TA, int TB>
__device__ __forceinline__ void wgmma_ss_48(float (&d)[24], uint64_t da, uint64_t db, int sd) {
  asm volatile("{\n.reg .pred p;\nsetp.ne.b32 p, %26, 0;\n"
      "wgmma.mma_async.sync.aligned.m64n48k16.f32.bf16.bf16 {"
      "%0, %1, %2, %3, %4, %5, %6, %7, %8, %9, %10, %11, %12, %13, %14, %15, %16, %17, %18, %19, %20, %21, %22, %23"
      "}, %24, %25, p, %27, %28, %29, %30;\n}\n"
      : "+f"(d[0]), "+f"(d[1]), "+f"(d[2]), "+f"(d[3]), "+f"(d[4]), "+f"(d[5]), "+f"(d[6]), "+f"(d[7]), "+f"(d[8]),
        "+f"(d[9]), "+f"(d[10]), "+f"(d[11]), "+f"(d[12]), "+f"(d[13]), "+f"(d[14]), "+f"(d[15]), "+f"(d[16]),
        "+f"(d[17]), "+f"(d[18]), "+f"(d[19]), "+f"(d[20]), "+f"(d[21]), "+f"(d[22]), "+f"(d[23])
      : "l"(da), "l"(db), "r"(sd), "n"(SA), "n"(SB), "n"(TA), "n"(TB));
}
template <int SA, int SB, int TA, int TB>
__device__ __forceinline__ void wgmma_ss_128(float (&d)[64], uint64_t da, uint64_t db, int sd) {
  asm volatile("{\n.reg .pred p;\nsetp.ne.b32 p, %66, 0;\n"
      "wgmma.mma_async.sync.aligned.m64n128k16.f32.bf16.bf16 {"
      "%0, %1, %2, %3, %4, %5, %6, %7, %8, %9, %10, %11, %12, %13, %14, %15, %16, %17, %18, %19, %20, %21, %22, %23, "
      "%24, %25, %26, %27, %28, %29, %30, %31, %32, %33, %34, %35, %36, %37, %38, %39, %40, %41, %42, %43, %44, %45, "
      "%46, %47, %48, %49, %50, %51, %52, %53, %54, %55, %56, %57, %58, %59, %60, %61, %62, %63"
      "}, %64, %65, p, %67, %68, %69, %70;\n}\n"
      : "+f"(d[0]), "+f"(d[1]), "+f"(d[2]), "+f"(d[3]), "+f"(d[4]), "+f"(d[5]), "+f"(d[6]), "+f"(d[7]), "+f"(d[8]),
        "+f"(d[9]), "+f"(d[10]), "+f"(d[11]), "+f"(d[12]), "+f"(d[13]), "+f"(d[14]), "+f"(d[15]), "+f"(d[16]),
        "+f"(d[17]), "+f"(d[18]), "+f"(d[19]), "+f"(d[20]), "+f"(d[21]), "+f"(d[22]), "+f"(d[23]), "+f"(d[24]),
        "+f"(d[25]), "+f"(d[26]), "+f"(d[27]), "+f"(d[28]), "+f"(d[29]), "+f"(d[30]), "+f"(d[31]), "+f"(d[32]),
        "+f"(d[33]), "+f"(d[34]), "+f"(d[35]), "+f"(d[36]), "+f"(d[37]), "+f"(d[38]), "+f"(d[39]), "+f"(d[40]),
        "+f"(d[41]), "+f"(d[42]), "+f"(d[43]), "+f"(d[44]), "+f"(d[45]), "+f"(d[46]), "+f"(d[47]), "+f"(d[48]),
        "+f"(d[49]), "+f"(d[50]), "+f"(d[51]), "+f"(d[52]), "+f"(d[53]), "+f"(d[54]), "+f"(d[55]), "+f"(d[56]),
        "+f"(d[57]), "+f"(d[58]), "+f"(d[59]), "+f"(d[60]), "+f"(d[61]), "+f"(d[62]), "+f"(d[63])
      : "l"(da), "l"(db), "r"(sd), "n"(SA), "n"(SB), "n"(TA), "n"(TB));
}
template <int SA, int SB, int TA, int TB>
__device__ __forceinline__ void wgmma_ss_168(float (&d)[84], uint64_t da, uint64_t db, int sd) {
  asm volatile("{\n.reg .pred p;\nsetp.ne.b32 p, %86, 0;\n"
      "wgmma.mma_async.sync.aligned.m64n168k16.f32.bf16.bf16 {"
      "%0, %1, %2, %3, %4, %5, %6, %7, %8, %9, %10, %11, %12, %13, %14, %15, %16, %17, %18, %19, %20, %21, %22, %23, "
      "%24, %25, %26, %27, %28, %29, %30, %31, %32, %33, %34, %35, %36, %37, %38, %39, %40, %41, %42, %43, %44, %45, "
      "%46, %47, %48, %49, %50, %51, %52, %53, %54, %55, %56, %57, %58, %59, %60, %61, %62, %63, %64, %65, %66, %67, "
      "%68, %69, %70, %71, %72, %73, %74, %75, %76, %77, %78, %79, %80, %81, %82, %83"
      "}, %84, %85, p, %87, %88, %89, %90;\n}\n"
      : "+f"(d[0]), "+f"(d[1]), "+f"(d[2]), "+f"(d[3]), "+f"(d[4]), "+f"(d[5]), "+f"(d[6]), "+f"(d[7]), "+f"(d[8]),
        "+f"(d[9]), "+f"(d[10]), "+f"(d[11]), "+f"(d[12]), "+f"(d[13]), "+f"(d[14]), "+f"(d[15]), "+f"(d[16]),
        "+f"(d[17]), "+f"(d[18]), "+f"(d[19]), "+f"(d[20]), "+f"(d[21]), "+f"(d[22]), "+f"(d[23]), "+f"(d[24]),
        "+f"(d[25]), "+f"(d[26]), "+f"(d[27]), "+f"(d[28]), "+f"(d[29]), "+f"(d[30]), "+f"(d[31]), "+f"(d[32]),
        "+f"(d[33]), "+f"(d[34]), "+f"(d[35]), "+f"(d[36]), "+f"(d[37]), "+f"(d[38]), "+f"(d[39]), "+f"(d[40]),
        "+f"(d[41]), "+f"(d[42]), "+f"(d[43]), "+f"(d[44]), "+f"(d[45]), "+f"(d[46]), "+f"(d[47]), "+f"(d[48]),
        "+f"(d[49]), "+f"(d[50]), "+f"(d[51]), "+f"(d[52]), "+f"(d[53]), "+f"(d[54]), "+f"(d[55]), "+f"(d[56]),
        "+f"(d[57]), "+f"(d[58]), "+f"(d[59]), "+f"(d[60]), "+f"(d[61]), "+f"(d[62]), "+f"(d[63]), "+f"(d[64]),
        "+f"(d[65]), "+f"(d[66]), "+f"(d[67]), "+f"(d[68]), "+f"(d[69]), "+f"(d[70]), "+f"(d[71]), "+f"(d[72]),
        "+f"(d[73]), "+f"(d[74]), "+f"(d[75]), "+f"(d[76]), "+f"(d[77]), "+f"(d[78]), "+f"(d[79]), "+f"(d[80]),
        "+f"(d[81]), "+f"(d[82]), "+f"(d[83])
      : "l"(da), "l"(db), "r"(sd), "n"(SA), "n"(SB), "n"(TA), "n"(TB));
}
template <int SA, int SB, int TB>
__device__ __forceinline__ void wgmma_rs_32(float (&d)[16], uint32_t a0, uint32_t a1, uint32_t a2, uint32_t a3, uint64_t db, int sd) {
  asm volatile("{\n.reg .pred p;\nsetp.ne.b32 p, %21, 0;\n"
      "wgmma.mma_async.sync.aligned.m64n32k16.f32.bf16.bf16 {"
      "%0, %1, %2, %3, %4, %5, %6, %7, %8, %9, %10, %11, %12, %13, %14, %15"
      "}, {%16, %17, %18, %19}, %20, p, %22, %23, %24;\n}\n"
      : "+f"(d[0]), "+f"(d[1]), "+f"(d[2]), "+f"(d[3]), "+f"(d[4]), "+f"(d[5]), "+f"(d[6]), "+f"(d[7]), "+f"(d[8]),
        "+f"(d[9]), "+f"(d[10]), "+f"(d[11]), "+f"(d[12]), "+f"(d[13]), "+f"(d[14]), "+f"(d[15])
      : "r"(a0), "r"(a1), "r"(a2), "r"(a3), "l"(db), "r"(sd), "n"(SA), "n"(SB), "n"(TB));
}
template <int SA, int SB, int TB>
__device__ __forceinline__ void wgmma_rs_64(float (&d)[32], uint32_t a0, uint32_t a1, uint32_t a2, uint32_t a3, uint64_t db, int sd) {
  asm volatile("{\n.reg .pred p;\nsetp.ne.b32 p, %37, 0;\n"
      "wgmma.mma_async.sync.aligned.m64n64k16.f32.bf16.bf16 {"
      "%0, %1, %2, %3, %4, %5, %6, %7, %8, %9, %10, %11, %12, %13, %14, %15, %16, %17, %18, %19, %20, %21, %22, %23, "
      "%24, %25, %26, %27, %28, %29, %30, %31"
      "}, {%32, %33, %34, %35}, %36, p, %38, %39, %40;\n}\n"
      : "+f"(d[0]), "+f"(d[1]), "+f"(d[2]), "+f"(d[3]), "+f"(d[4]), "+f"(d[5]), "+f"(d[6]), "+f"(d[7]), "+f"(d[8]),
        "+f"(d[9]), "+f"(d[10]), "+f"(d[11]), "+f"(d[12]), "+f"(d[13]), "+f"(d[14]), "+f"(d[15]), "+f"(d[16]),
        "+f"(d[17]), "+f"(d[18]), "+f"(d[19]), "+f"(d[20]), "+f"(d[21]), "+f"(d[22]), "+f"(d[23]), "+f"(d[24]),
        "+f"(d[25]), "+f"(d[26]), "+f"(d[27]), "+f"(d[28]), "+f"(d[29]), "+f"(d[30]), "+f"(d[31])
      : "r"(a0), "r"(a1), "r"(a2), "r"(a3), "l"(db), "r"(sd), "n"(SA), "n"(SB), "n"(TB));
}
template <int SA, int SB, int TB>
__device__ __forceinline__ void wgmma_rs_128(float (&d)[64], uint32_t a0, uint32_t a1, uint32_t a2, uint32_t a3, uint64_t db, int sd) {
  asm volatile("{\n.reg .pred p;\nsetp.ne.b32 p, %69, 0;\n"
      "wgmma.mma_async.sync.aligned.m64n128k16.f32.bf16.bf16 {"
      "%0, %1, %2, %3, %4, %5, %6, %7, %8, %9, %10, %11, %12, %13, %14, %15, %16, %17, %18, %19, %20, %21, %22, %23, "
      "%24, %25, %26, %27, %28, %29, %30, %31, %32, %33, %34, %35, %36, %37, %38, %39, %40, %41, %42, %43, %44, %45, "
      "%46, %47, %48, %49, %50, %51, %52, %53, %54, %55, %56, %57, %58, %59, %60, %61, %62, %63"
      "}, {%64, %65, %66, %67}, %68, p, %70, %71, %72;\n}\n"
      : "+f"(d[0]), "+f"(d[1]), "+f"(d[2]), "+f"(d[3]), "+f"(d[4]), "+f"(d[5]), "+f"(d[6]), "+f"(d[7]), "+f"(d[8]),
        "+f"(d[9]), "+f"(d[10]), "+f"(d[11]), "+f"(d[12]), "+f"(d[13]), "+f"(d[14]), "+f"(d[15]), "+f"(d[16]),
        "+f"(d[17]), "+f"(d[18]), "+f"(d[19]), "+f"(d[20]), "+f"(d[21]), "+f"(d[22]), "+f"(d[23]), "+f"(d[24]),
        "+f"(d[25]), "+f"(d[26]), "+f"(d[27]), "+f"(d[28]), "+f"(d[29]), "+f"(d[30]), "+f"(d[31]), "+f"(d[32]),
        "+f"(d[33]), "+f"(d[34]), "+f"(d[35]), "+f"(d[36]), "+f"(d[37]), "+f"(d[38]), "+f"(d[39]), "+f"(d[40]),
        "+f"(d[41]), "+f"(d[42]), "+f"(d[43]), "+f"(d[44]), "+f"(d[45]), "+f"(d[46]), "+f"(d[47]), "+f"(d[48]),
        "+f"(d[49]), "+f"(d[50]), "+f"(d[51]), "+f"(d[52]), "+f"(d[53]), "+f"(d[54]), "+f"(d[55]), "+f"(d[56]),
        "+f"(d[57]), "+f"(d[58]), "+f"(d[59]), "+f"(d[60]), "+f"(d[61]), "+f"(d[62]), "+f"(d[63])
      : "r"(a0), "r"(a1), "r"(a2), "r"(a3), "l"(db), "r"(sd), "n"(SA), "n"(SB), "n"(TB));
}
template <int SA, int SB, int TB>
__device__ __forceinline__ void wgmma_rs_168(float (&d)[84], uint32_t a0, uint32_t a1, uint32_t a2, uint32_t a3, uint64_t db, int sd) {
  asm volatile("{\n.reg .pred p;\nsetp.ne.b32 p, %89, 0;\n"
      "wgmma.mma_async.sync.aligned.m64n168k16.f32.bf16.bf16 {"
      "%0, %1, %2, %3, %4, %5, %6, %7, %8, %9, %10, %11, %12, %13, %14, %15, %16, %17, %18, %19, %20, %21, %22, %23, "
      "%24, %25, %26, %27, %28, %29, %30, %31, %32, %33, %34, %35, %36, %37, %38, %39, %40, %41, %42, %43, %44, %45, "
      "%46, %47, %48, %49, %50, %51, %52, %53, %54, %55, %56, %57, %58, %59, %60, %61, %62, %63, %64, %65, %66, %67, "
      "%68, %69, %70, %71, %72, %73, %74, %75, %76, %77, %78, %79, %80, %81, %82, %83"
      "}, {%84, %85, %86, %87}, %88, p, %90, %91, %92;\n}\n"
      : "+f"(d[0]), "+f"(d[1]), "+f"(d[2]), "+f"(d[3]), "+f"(d[4]), "+f"(d[5]), "+f"(d[6]), "+f"(d[7]), "+f"(d[8]),
        "+f"(d[9]), "+f"(d[10]), "+f"(d[11]), "+f"(d[12]), "+f"(d[13]), "+f"(d[14]), "+f"(d[15]), "+f"(d[16]),
        "+f"(d[17]), "+f"(d[18]), "+f"(d[19]), "+f"(d[20]), "+f"(d[21]), "+f"(d[22]), "+f"(d[23]), "+f"(d[24]),
        "+f"(d[25]), "+f"(d[26]), "+f"(d[27]), "+f"(d[28]), "+f"(d[29]), "+f"(d[30]), "+f"(d[31]), "+f"(d[32]),
        "+f"(d[33]), "+f"(d[34]), "+f"(d[35]), "+f"(d[36]), "+f"(d[37]), "+f"(d[38]), "+f"(d[39]), "+f"(d[40]),
        "+f"(d[41]), "+f"(d[42]), "+f"(d[43]), "+f"(d[44]), "+f"(d[45]), "+f"(d[46]), "+f"(d[47]), "+f"(d[48]),
        "+f"(d[49]), "+f"(d[50]), "+f"(d[51]), "+f"(d[52]), "+f"(d[53]), "+f"(d[54]), "+f"(d[55]), "+f"(d[56]),
        "+f"(d[57]), "+f"(d[58]), "+f"(d[59]), "+f"(d[60]), "+f"(d[61]), "+f"(d[62]), "+f"(d[63]), "+f"(d[64]),
        "+f"(d[65]), "+f"(d[66]), "+f"(d[67]), "+f"(d[68]), "+f"(d[69]), "+f"(d[70]), "+f"(d[71]), "+f"(d[72]),
        "+f"(d[73]), "+f"(d[74]), "+f"(d[75]), "+f"(d[76]), "+f"(d[77]), "+f"(d[78]), "+f"(d[79]), "+f"(d[80]),
        "+f"(d[81]), "+f"(d[82]), "+f"(d[83])
      : "r"(a0), "r"(a1), "r"(a2), "r"(a3), "l"(db), "r"(sd), "n"(SA), "n"(SB), "n"(TB));
}
template <int SA, int SB, int TB>
__device__ __forceinline__ void wgmma_rs_256(float (&d)[128], uint32_t a0, uint32_t a1, uint32_t a2, uint32_t a3, uint64_t db, int sd) {
  asm volatile("{\n.reg .pred p;\nsetp.ne.b32 p, %133, 0;\n"
      "wgmma.mma_async.sync.aligned.m64n256k16.f32.bf16.bf16 {"
      "%0, %1, %2, %3, %4, %5, %6, %7, %8, %9, %10, %11, %12, %13, %14, %15, %16, %17, %18, %19, %20, %21, %22, %23, "
      "%24, %25, %26, %27, %28, %29, %30, %31, %32, %33, %34, %35, %36, %37, %38, %39, %40, %41, %42, %43, %44, %45, "
      "%46, %47, %48, %49, %50, %51, %52, %53, %54, %55, %56, %57, %58, %59, %60, %61, %62, %63, %64, %65, %66, %67, "
      "%68, %69, %70, %71, %72, %73, %74, %75, %76, %77, %78, %79, %80, %81, %82, %83, %84, %85, %86, %87, %88, %89, "
      "%90, %91, %92, %93, %94, %95, %96, %97, %98, %99, %100, %101, %102, %103, %104, %105, %106, %107, %108, %109, "
      "%110, %111, %112, %113, %114, %115, %116, %117, %118, %119, %120, %121, %122, %123, %124, %125, %126, %127"
      "}, {%128, %129, %130, %131}, %132, p, %134, %135, %136;\n}\n"
      : "+f"(d[0]), "+f"(d[1]), "+f"(d[2]), "+f"(d[3]), "+f"(d[4]), "+f"(d[5]), "+f"(d[6]), "+f"(d[7]), "+f"(d[8]),
        "+f"(d[9]), "+f"(d[10]), "+f"(d[11]), "+f"(d[12]), "+f"(d[13]), "+f"(d[14]), "+f"(d[15]), "+f"(d[16]),
        "+f"(d[17]), "+f"(d[18]), "+f"(d[19]), "+f"(d[20]), "+f"(d[21]), "+f"(d[22]), "+f"(d[23]), "+f"(d[24]),
        "+f"(d[25]), "+f"(d[26]), "+f"(d[27]), "+f"(d[28]), "+f"(d[29]), "+f"(d[30]), "+f"(d[31]), "+f"(d[32]),
        "+f"(d[33]), "+f"(d[34]), "+f"(d[35]), "+f"(d[36]), "+f"(d[37]), "+f"(d[38]), "+f"(d[39]), "+f"(d[40]),
        "+f"(d[41]), "+f"(d[42]), "+f"(d[43]), "+f"(d[44]), "+f"(d[45]), "+f"(d[46]), "+f"(d[47]), "+f"(d[48]),
        "+f"(d[49]), "+f"(d[50]), "+f"(d[51]), "+f"(d[52]), "+f"(d[53]), "+f"(d[54]), "+f"(d[55]), "+f"(d[56]),
        "+f"(d[57]), "+f"(d[58]), "+f"(d[59]), "+f"(d[60]), "+f"(d[61]), "+f"(d[62]), "+f"(d[63]), "+f"(d[64]),
        "+f"(d[65]), "+f"(d[66]), "+f"(d[67]), "+f"(d[68]), "+f"(d[69]), "+f"(d[70]), "+f"(d[71]), "+f"(d[72]),
        "+f"(d[73]), "+f"(d[74]), "+f"(d[75]), "+f"(d[76]), "+f"(d[77]), "+f"(d[78]), "+f"(d[79]), "+f"(d[80]),
        "+f"(d[81]), "+f"(d[82]), "+f"(d[83]), "+f"(d[84]), "+f"(d[85]), "+f"(d[86]), "+f"(d[87]), "+f"(d[88]),
        "+f"(d[89]), "+f"(d[90]), "+f"(d[91]), "+f"(d[92]), "+f"(d[93]), "+f"(d[94]), "+f"(d[95]), "+f"(d[96]),
        "+f"(d[97]), "+f"(d[98]), "+f"(d[99]), "+f"(d[100]), "+f"(d[101]), "+f"(d[102]), "+f"(d[103]), "+f"(d[104]),
        "+f"(d[105]), "+f"(d[106]), "+f"(d[107]), "+f"(d[108]), "+f"(d[109]), "+f"(d[110]), "+f"(d[111]),
        "+f"(d[112]), "+f"(d[113]), "+f"(d[114]), "+f"(d[115]), "+f"(d[116]), "+f"(d[117]), "+f"(d[118]),
        "+f"(d[119]), "+f"(d[120]), "+f"(d[121]), "+f"(d[122]), "+f"(d[123]), "+f"(d[124]), "+f"(d[125]),
        "+f"(d[126]), "+f"(d[127])
      : "r"(a0), "r"(a1), "r"(a2), "r"(a3), "l"(db), "r"(sd), "n"(SA), "n"(SB), "n"(TB));
}

__device__ const __align__(128) uint32_t c_img[3584] = {
    0x00003c80, 0x00003c80, 0x00003c80, 0x00003c80, 0x00003c80, 0x00003c80, 0x00003c80, 0x00003c80, 0x00003c80, 0x00003c80,
    0x00003c80, 0x00003c80, 0x00003c80, 0x00003c80, 0x00003c80, 0x00003c80, 0x00003c80, 0x00003c80, 0x00003c80, 0x00003c80,
    0x00003c80, 0x00003c80, 0x00003c80, 0x00003c80, 0x00003c80, 0x00003c80, 0x00003c80, 0x00003c80, 0x00003c80, 0x00003c80,
    0x00003c80, 0x00003c80, 0x3c463c22, 0x3c623bf1, 0x3c753b95, 0x3c7f3ac9, 0x3ac93c7f, 0x3b953c75, 0x3bf13c62, 0x3c223c46,
    0x3c22bc46, 0x3bf1bc62, 0x3b95bc75, 0x3ac9bc7f, 0x3c7fbac9, 0x3c75bb95, 0x3c62bbf1, 0x3c46bc22, 0xbc46bc22, 0xbc62bbf1,
    0xbc75bb95, 0xbc7fbac9, 0xbac9bc7f, 0xbb95bc75, 0xbbf1bc62, 0xbc22bc46, 0xbc223c46, 0xbbf13c62, 0xbb953c75, 0xbac93c7f,
    0xbc7f3ac9, 0xbc753b95, 0xbc623bf1, 0xbc463c22, 0xbb48bc7b, 0xbc0ebc55, 0xbc55bc0e, 0xbc7bbb48, 0xbc7b3b48, 0xbc553c0e,
    0xbc0e3c55, 0xbb483c7b, 0x3b483c7b, 0x3c0e3c55, 0x3c553c0e, 0x3c7b3b48, 0x3c7bbb48, 0x3c55bc0e, 0x3c0ebc55, 0x3b48bc7b,
    0xbb48bc7b, 0xbc0ebc55, 0xbc55bc0e, 0xbc7bbb48, 0xbc7b3b48, 0xbc553c0e, 0xbc0e3c55, 0xbb483c7b, 0x3b483c7b, 0x3c0e3c55,
    0x3c553c0e, 0x3c7b3b48, 0x3c7bbb48, 0x3c55bc0e, 0x3c0ebc55, 0x3b48bc7b, 0x3c623bf1, 0x3c7fbac9, 0x3c46bc22, 0x3b95bc75,
    0xbc753b95, 0xbc223c46, 0xbac93c7f, 0x3bf13c62, 0x3bf1bc62, 0xbac9bc7f, 0xbc22bc46, 0xbc75bb95, 0x3b953c75, 0x3c463c22,
    0x3c7f3ac9, 0x3c62bbf1, 0xbc62bbf1, 0xbc7f3ac9, 0xbc463c22, 0xbb953c75, 0x3c75bb95, 0x3c22bc46, 0x3ac9bc7f, 0xbbf1bc62,
    0xbbf13c62, 0x3ac93c7f, 0x3c223c46, 0x3c753b95, 0xbb95bc75, 0xbc46bc22, 0xbc7fbac9, 0xbc623bf1, 0x3bc43c6d, 0x3c6d3bc4,
    0x3c6dbbc4, 0x3bc4bc6d, 0xbbc4bc6d, 0xbc6dbbc4, 0xbc6d3bc4, 0xbbc43c6d, 0x3bc43c6d, 0x3c6d3bc4, 0x3c6dbbc4, 0x3bc4bc6d,
    0xbbc4bc6d, 0xbc6dbbc4, 0xbc6d3bc4, 0xbbc43c6d, 0x3bc43c6d, 0x3c6d3bc4, 0x3c6dbbc4, 0x3bc4bc6d, 0xbbc4bc6d, 0xbc6dbbc4,
    0xbc6d3bc4, 0xbbc43c6d, 0x3bc43c6d, 0x3c6d3bc4, 0x3c6dbbc4, 0x3bc4bc6d, 0xbbc4bc6d, 0xbc6dbbc4, 0xbc6d3bc4, 0xbbc43c6d,
    0x3c753b95, 0x3c46bc22, 0xbac9bc7f, 0xbc62bbf1, 0xbbf1bc62, 0xbc7fbac9, 0xbc223c46, 0x3b953c75, 0x3b95bc75, 0xbc22bc46,
    0xbc7f3ac9, 0xbbf13c62, 0xbc623bf1, 0xbac93c7f, 0x3c463c22, 0x3c75bb95, 0xbc75bb95, 0xbc463c22, 0x3ac93c7f, 0x3c623bf1,
    0x3bf13c62, 0x3c7f3ac9, 0x3c22bc46, 0xbb95bc75, 0xbb953c75, 0x3c223c46, 0x3c7fbac9, 0x3bf1bc62, 0x3c62bbf1, 0x3ac9bc7f,
    0xbc46bc22, 0xbc753b95, 0xbc0ebc55, 0xbc7b3b48, 0xbb483c7b, 0x3c553c0e, 0x3c55bc0e, 0xbb48bc7b, 0xbc7bbb48, 0xbc0e3c55,
    0x3c0e3c55, 0x3c7bbb48, 0x3b48bc7b, 0xbc55bc0e, 0xbc553c0e, 0x3b483c7b, 0x3c7b3b48, 0x3c0ebc55, 0xbc0ebc55, 0xbc7b3b48,
    0xbb483c7b, 0x3c553c0e, 0x3c55bc0e, 0xbb48bc7b, 0xbc7bbb48, 0xbc0e3c55, 0x3c0e3c55, 0x3c7bbb48, 0x3b48bc7b, 0xbc55bc0e,
    0xbc553c0e, 0x3b483c7b, 0x3c7b3b48, 0x3c0ebc55, 0x3c7f3ac9, 0x3b95bc75, 0xbc62bbf1, 0xbc223c46, 0x3c46bc22, 0xbbf1bc62,
    0xbc753b95, 0x3ac93c7f, 0x3ac9bc7f, 0xbc75bb95, 0xbbf13c62, 0x3c463c22, 0xbc22bc46, 0xbc623bf1, 0x3b953c75, 0x3c7fbac9,
    0xbc7fbac9, 0xbb953c75, 0x3c623bf1, 0x3c22bc46, 0xbc463c22, 0x3bf13c62, 0x3c75bb95, 0xbac9bc7f, 0xbac93c7f, 0x3c753b95,
    0x3bf1bc62, 0xbc46bc22, 0x3c223c46, 0x3c62bbf1, 0xbb95bc75, 0xbc7f3ac9, 0x3a493c80, 0x3b163c7d, 0x3b793c78, 0x3bac3c71,
    0x3bdb3c67, 0x3c043c5c, 0x3c183c4e, 0x3c2c3c3e, 0x3c3e3c2c, 0x3c4e3c18, 0x3c5c3c04, 0x3c673bdb, 0x3c713bac, 0x3c783b79,
    0x3c7d3b16, 0x3c803a49, 0x3c80ba49, 0x3c7dbb16, 0x3c78bb79, 0x3c71bbac, 0x3c67bbdb, 0x3c5cbc04, 0x3c4ebc18, 0x3c3ebc2c,
    0x3c2cbc3e, 0x3c18bc4e, 0x3c04bc5c, 0x3bdbbc67, 0x3bacbc71, 0x3b79bc78, 0x3b16bc7d, 0x3a49bc80, 0x3c783b79, 0x3c80ba49,
    0x3c71bbac, 0x3c4ebc18, 0x3b163c7d, 0x3bdb3c67, 0x3c2c3c3e, 0x3c5c3c04, 0xbc04bc5c, 0xbc3ebc2c, 0xbc67bbdb, 0xbc7dbb16,
    0x3c18bc4e, 0x3bacbc71, 0x3a49bc80, 0xbb79bc78, 0xbb793c78, 0x3a493c80, 0x3bac3c71, 0x3c183c4e, 0xbc7d3b16, 0xbc673bdb,
    0xbc3e3c2c, 0xbc043c5c, 0x3c5cbc04, 0x3c2cbc3e, 0x3bdbbc67, 0x3b16bc7d, 0x3c4e3c18, 0x3c713bac, 0x3c803a49, 0x3c78bb79,
    0xbc5cbc04, 0xbc80ba49, 0xbc673bdb, 0xbc183c4e, 0xbb163c7d, 0x3bac3c71, 0x3c3e3c2c, 0x3c783b79, 0x3b793c78, 0x3c2c3c3e,
    0x3c713bac, 0x3c7dbb16, 0x3c4ebc18, 0x3bdbbc67, 0xba49bc80, 0xbc04bc5c, 0xbc043c5c, 0xba493c80, 0x3bdb3c67, 0x3c4e3c18,
    0x3c7d3b16, 0x3c71bbac, 0x3c2cbc3e, 0x3b79bc78, 0x3c78bb79, 0x3c3ebc2c, 0x3bacbc71, 0xbb16bc7d, 0xbc18bc4e, 0xbc67bbdb,
    0xbc803a49, 0xbc5c3c04, 0x3c3ebc2c, 0x3b16bc7d, 0xbc04bc5c, 0xbc71bbac, 0xbbdb3c67, 0x3b793c78, 0x3c4e3c18, 0x3c80ba49,
    0x3a49bc80, 0xbc18bc4e, 0xbc78bb79, 0xbc673bdb, 0x3bac3c71, 0x3c5c3c04, 0x3c7dbb16, 0x3c2cbc3e, 0x3c2c3c3e, 0x3c7d3b16,
    0x3c5cbc04, 0x3bacbc71, 0xbc67bbdb, 0xbc783b79, 0xbc183c4e, 0x3a493c80, 0x3c803a49, 0x3c4ebc18, 0x3b79bc78, 0xbbdbbc67,
    0xbc713bac, 0xbc043c5c, 0x3b163c7d, 0x3c3e3c2c, 0x3c67bbdb, 0x3b79bc78, 0xbc18bc4e, 0xbc80ba49, 0xbc2c3c3e, 0x3b163c7d,
    0x3c5c3c04, 0x3c71bbac, 0x3bacbc71, 0xbc04bc5c, 0xbc7dbb16, 0xbc3e3c2c, 0x3a493c80, 0x3c4e3c18, 0x3c78bb79, 0x3bdbbc67,
    0x3bdb3c67, 0x3c783b79, 0x3c4ebc18, 0x3a49bc80, 0xbc3ebc2c, 0xbc7d3b16, 0xbc043c5c, 0x3bac3c71, 0x3c713bac, 0x3c5cbc04,
    0x3b16bc7d, 0xbc2cbc3e, 0xbc803a49, 0xbc183c4e, 0x3b793c78, 0x3c673bdb, 0xbb16bc7d, 0xbc71bbac, 0xbc3e3c2c, 0x3b793c78,
    0xbc5c3c04, 0x3a493c80, 0x3c673bdb, 0x3c4ebc18, 0xbc183c4e, 0x3bdb3c67, 0x3c803a49, 0x3c04bc5c, 0x3c783b79, 0x3c2cbc3e,
    0xbbacbc71, 0xbc7dbb16, 0xbc7d3b16, 0xbbac3c71, 0x3c2c3c3e, 0x3c78bb79, 0x3c043c5c, 0x3c80ba49, 0x3bdbbc67, 0xbc18bc4e,
    0x3c4e3c18, 0x3c67bbdb, 0x3a49bc80, 0xbc5cbc04, 0x3b79bc78, 0xbc3ebc2c, 0xbc713bac, 0xbb163c7d, 0xbb163c7d, 0x3c673bdb,
    0x3c2cbc3e, 0xbc04bc5c, 0xbc783b79, 0xba493c80, 0x3c713bac, 0x3c18bc4e, 0x3c4ebc18, 0xbbacbc71, 0xbc803a49, 0xbb793c78,
    0x3c5c3c04, 0x3c3ebc2c, 0xbbdbbc67, 0xbc7d3b16, 0xbc7dbb16, 0xbbdb3c67, 0x3c3e3c2c, 0x3c5cbc04, 0xbb79bc78, 0xbc80ba49,
    0xbbac3c71, 0x3c4e3c18, 0x3c183c4e, 0x3c71bbac, 0xba49bc80, 0xbc78bb79, 0xbc043c5c, 0x3c2c3c3e, 0x3c67bbdb, 0xbb16bc7d,
    0xbc67bbdb, 0xbc043c5c, 0x3c4e3c18, 0x3c2cbc3e, 0xbc80ba49, 0xbb163c7d, 0x3c783b79, 0x3bacbc71, 0xbc713bac, 0x3b793c78,
    0x3c7dbb16, 0xba49bc80, 0xbc3e3c2c, 0x3c183c4e, 0x3c5cbc04, 0xbbdbbc67, 0xbbdb3c67, 0x3c5c3c04, 0x3c18bc4e, 0xbc3ebc2c,
    0xba493c80, 0x3c7d3b16, 0x3b79bc78, 0xbc71bbac, 0x3bac3c71, 0x3c78bb79, 0xbb16bc7d, 0xbc803a49, 0x3c2c3c3e, 0x3c4ebc18,
    0xbc04bc5c, 0xbc673bdb, 0x3c353c35, 0x3c35bc35, 0xbc35bc35, 0xbc353c35, 0x3c353c35, 0x3c35bc35, 0xbc35bc35, 0xbc353c35,
    0x3c353c35, 0x3c35bc35, 0xbc35bc35, 0xbc353c35, 0x3c353c35, 0x3c35bc35, 0xbc35bc35, 0xbc353c35, 0x3c353c35, 0x3c35bc35,
    0xbc35bc35, 0xbc353c35, 0x3c353c35, 0x3c35bc35, 0xbc35bc35, 0xbc353c35, 0x3c353c35, 0x3c35bc35, 0xbc35bc35, 0xbc353c35,
    0x3c353c35, 0x3c35bc35, 0xbc35bc35, 0xbc353c35, 0x3c7fbac9, 0xbb95bc75, 0xbc623bf1, 0x3c223c46, 0x3c463c22, 0x3bf1bc62,
    0xbc75bb95, 0xbac93c7f, 0xbac9bc7f, 0xbc753b95, 0x3bf13c62, 0x3c46bc22, 0x3c22bc46, 0xbc62bbf1, 0xbb953c75, 0x3c7f3ac9,
    0xbc7f3ac9, 0x3b953c75, 0x3c62bbf1, 0xbc22bc46, 0xbc46bc22, 0xbbf13c62, 0x3c753b95, 0x3ac9bc7f, 0x3ac93c7f, 0x3c75bb95,
    0xbbf1bc62, 0xbc463c22, 0xbc223c46, 0x3c623bf1, 0x3b95bc75, 0xbc7fbac9, 0xbc55bc0e, 0xbb483c7b, 0x3c7bbb48, 0xbc0ebc55,
    0xbc0e3c55, 0x3c7b3b48, 0xbb48bc7b, 0xbc553c0e, 0x3c553c0e, 0x3b48bc7b, 0xbc7b3b48, 0x3c0e3c55, 0x3c0ebc55, 0xbc7bbb48,
    0x3b483c7b, 0x3c55bc0e, 0xbc55bc0e, 0xbb483c7b, 0x3c7bbb48, 0xbc0ebc55, 0xbc0e3c55, 0x3c7b3b48, 0xbb48bc7b, 0xbc553c0e,
    0x3c553c0e, 0x3b48bc7b, 0xbc7b3b48, 0x3c0e3c55, 0x3c0ebc55, 0xbc7bbb48, 0x3b483c7b, 0x3c55bc0e, 0x3c75bb95, 0xbc46bc22,
    0xbac93c7f, 0x3c62bbf1, 0xbbf13c62, 0x3c7fbac9, 0xbc22bc46, 0xbb953c75, 0xbb95bc75, 0xbc223c46, 0x3c7f3ac9, 0xbbf1bc62,
    0x3c623bf1, 0xbac9bc7f, 0xbc463c22, 0x3c753b95, 0xbc753b95, 0x3c463c22, 0x3ac9bc7f, 0xbc623bf1, 0x3bf1bc62, 0xbc7f3ac9,
    0x3c223c46, 0x3b95bc75, 0x3b953c75, 0x3c22bc46, 0xbc7fbac9, 0x3bf13c62, 0xbc62bbf1, 0x3ac93c7f, 0x3c46bc22, 0xbc75bb95,
    0x3c6d3bc4, 0xbbc4bc6d, 0xbbc43c6d, 0x3c6dbbc4, 0xbc6dbbc4, 0x3bc43c6d, 0x3bc4bc6d, 0xbc6d3bc4, 0x3c6d3bc4, 0xbbc4bc6d,
    0xbbc43c6d, 0x3c6dbbc4, 0xbc6dbbc4, 0x3bc43c6d, 0x3bc4bc6d, 0xbc6d3bc4, 0x3c6d3bc4, 0xbbc4bc6d, 0xbbc43c6d, 0x3c6dbbc4,
    0xbc6dbbc4, 0x3bc43c6d, 0x3bc4bc6d, 0xbc6d3bc4, 0x3c6d3bc4, 0xbbc4bc6d, 0xbbc43c6d, 0x3c6dbbc4, 0xbc6dbbc4, 0x3bc43c6d,
    0x3bc4bc6d, 0xbc6d3bc4, 0x3c62bbf1, 0xbc7fbac9, 0x3c463c22, 0xbb95bc75, 0xbc75bb95, 0x3c223c46, 0xbac9bc7f, 0xbbf13c62,
    0xbbf1bc62, 0xbac93c7f, 0x3c22bc46, 0xbc753b95, 0xbb953c75, 0x3c46bc22, 0xbc7f3ac9, 0x3c623bf1, 0xbc623bf1, 0x3c7f3ac9,
    0xbc46bc22, 0x3b953c75, 0x3c753b95, 0xbc22bc46, 0x3ac93c7f, 0x3bf1bc62, 0x3bf13c62, 0x3ac9bc7f, 0xbc223c46, 0x3c75bb95,
    0x3b95bc75, 0xbc463c22, 0x3c7fbac9, 0xbc62bbf1, 0xbc7bbb48, 0x3c553c0e, 0xbc0ebc55, 0x3b483c7b, 0x3b48bc7b, 0xbc0e3c55,
    0x3c55bc0e, 0xbc7b3b48, 0x3c7b3b48, 0xbc55bc0e, 0x3c0e3c55, 0xbb48bc7b, 0xbb483c7b, 0x3c0ebc55, 0xbc553c0e, 0x3c7bbb48,
    0xbc7bbb48, 0x3c553c0e, 0xbc0ebc55, 0x3b483c7b, 0x3b48bc7b, 0xbc0e3c55, 0x3c55bc0e, 0xbc7b3b48, 0x3c7b3b48, 0xbc55bc0e,
    0x3c0e3c55, 0xbb48bc7b, 0xbb483c7b, 0x3c0ebc55, 0xbc553c0e, 0x3c7bbb48, 0x3c46bc22, 0xbc623bf1, 0x3c75bb95, 0xbc7f3ac9,
    0x3ac9bc7f, 0xbb953c75, 0x3bf1bc62, 0xbc223c46, 0xbc22bc46, 0x3bf13c62, 0xbb95bc75, 0x3ac93c7f, 0xbc7fbac9, 0x3c753b95,
    0xbc62bbf1, 0x3c463c22, 0xbc463c22, 0x3c62bbf1, 0xbc753b95, 0x3c7fbac9, 0xbac93c7f, 0x3b95bc75, 0xbbf13c62, 0x3c22bc46,
    0x3c223c46, 0xbbf1bc62, 0x3b953c75, 0xbac9bc7f, 0x3c7f3ac9, 0xbc75bb95, 0x3c623bf1, 0xbc46bc22, 0x3c3e3c2c, 0x3c18bc4e,
    0xbc5cbc04, 0xbbdb3c67, 0x3c713bac, 0x3b79bc78, 0xbc7dbb16, 0xba493c80, 0x3c80ba49, 0xbb16bc7d, 0xbc783b79, 0x3bac3c71,
    0x3c67bbdb, 0xbc04bc5c, 0xbc4e3c18, 0x3c2c3c3e, 0x3c2cbc3e, 0xbc4ebc18, 0xbc043c5c, 0x3c673bdb, 0x3bacbc71, 0xbc78bb79,
    0xbb163c7d, 0x3c803a49, 0xba49bc80, 0xbc7d3b16, 0x3b793c78, 0x3c71bbac, 0xbbdbbc67, 0xbc5c3c04, 0x3c183c4e, 0x3c3ebc2c,
    0x3c5cbc04, 0xbc3ebc2c, 0xbbdb3c67, 0x3c7d3b16, 0x3c4e3c18, 0x3bacbc71, 0xbc80ba49, 0x3b793c78, 0xbc78bb79, 0x3a493c80,
    0x3c71bbac, 0xbc18bc4e, 0xbb16bc7d, 0xbc673bdb, 0x3c2c3c3e, 0x3c04bc5c, 0x3c043c5c, 0x3c2cbc3e, 0xbc67bbdb, 0xbb163c7d,
    0xbc183c4e, 0x3c713bac, 0x3a49bc80, 0xbc783b79, 0x3b79bc78, 0xbc803a49, 0x3bac3c71, 0x3c4ebc18, 0x3c7dbb16, 0xbbdbbc67,
    0xbc3e3c2c, 0x3c5c3c04, 0xbc783b79, 0x3c2c3c3e, 0x3bacbc71, 0xbc7d3b16, 0x3c183c4e, 0x3bdbbc67, 0xbc803a49, 0x3c043c5c,
    0x3c5c3c04, 0x3a49bc80, 0xbc673bdb, 0x3c4e3c18, 0x3b16bc7d, 0xbc713bac, 0x3c3e3c2c, 0x3b79bc78, 0x3b793c78, 0x3c3ebc2c,
    0xbc71bbac, 0x3b163c7d, 0x3c4ebc18, 0xbc67bbdb, 0x3a493c80, 0x3c5cbc04, 0x3c04bc5c, 0xbc80ba49, 0x3bdb3c67, 0x3c18bc4e,
    0xbc7dbb16, 0x3bac3c71, 0x3c2cbc3e, 0xbc78bb79, 0x3a49bc80, 0xbc4e3c18, 0x3c783b79, 0xbbdbbc67, 0x3bac3c71, 0x3c04bc5c,
    0xbc7d3b16, 0x3c3e3c2c, 0xbc2cbc3e, 0xbb163c7d, 0x3c5cbc04, 0xbc71bbac, 0x3c673bdb, 0xbb79bc78, 0xbc183c4e, 0x3c80ba49,
    0x3c803a49, 0xbc18bc4e, 0xbb793c78, 0x3c67bbdb, 0xbc713bac, 0x3c5c3c04, 0xbb16bc7d, 0xbc2c3c3e, 0x3c3ebc2c, 0xbc7dbb16,
    0x3c043c5c, 0x3bacbc71, 0xbbdb3c67, 0x3c78bb79, 0xbc4ebc18, 0x3a493c80, 0x3bacbc71, 0xbc5c3c04, 0x3c7d3b16, 0xbc2cbc3e,
    0x3a493c80, 0x3c18bc4e, 0xbc783b79, 0x3c673bdb, 0xbbdbbc67, 0xbb793c78, 0x3c4ebc18, 0xbc80ba49, 0x3c3e3c2c, 0xbb16bc7d,
    0xbc043c5c, 0x3c71bbac, 0x3c713bac, 0xbc04bc5c, 0xbb163c7d, 0x3c3ebc2c, 0xbc803a49, 0x3c4e3c18, 0xbb79bc78, 0xbbdb3c67,
    0x3c67bbdb, 0xbc78bb79, 0x3c183c4e, 0x3a49bc80, 0xbc2c3c3e, 0x3c7dbb16, 0xbc5cbc04, 0x3bac3c71, 0xbc4ebc18, 0x3bdb3c67,
    0x3a49bc80, 0xbc043c5c, 0xbb793c78, 0x3c2cbc3e, 0xbc713bac, 0x3c7d3b16, 0x3b163c7d, 0x3bacbc71, 0xbc3e3c2c, 0x3c78bb79,
    0x3c5cbc04, 0xbc803a49, 0x3c673bdb, 0xbc18bc4e, 0xbc183c4e, 0x3c67bbdb, 0xbc80ba49, 0x3c5c3c04, 0x3c783b79, 0xbc3ebc2c,
    0x3bac3c71, 0x3b16bc7d, 0x3c7dbb16, 0xbc71bbac, 0x3c2c3c3e, 0xbb79bc78, 0xbc04bc5c, 0x3a493c80, 0x3bdbbc67, 0xbc4e3c18,
    0x3c183c4e, 0xbbacbc71, 0x3a493c80, 0x3b79bc78, 0xbc043c5c, 0x3c3ebc2c, 0xbc673bdb, 0x3c7dbb16, 0x3b16bc7d, 0xbbdb3c67,
    0x3c2cbc3e, 0xbc5c3c04, 0x3c78bb79, 0xbc80ba49, 0x3c713bac, 0xbc4ebc18, 0xbc4e3c18, 0x3c71bbac, 0xbc803a49, 0x3c783b79,
    0xbc5cbc04, 0x3c2c3c3e, 0xbbdbbc67, 0x3b163c7d, 0x3c7d3b16, 0xbc67bbdb, 0x3c3e3c2c, 0xbc04bc5c, 0x3b793c78, 0x3a49bc80,
    0xbbac3c71, 0x3c18bc4e, 0xbc713bac, 0x3c78bb79, 0xbc7d3b16, 0x3c80ba49, 0xbc3e3c2c, 0x3c4ebc18, 0xbc5c3c04, 0x3c67bbdb,
    0xbbdb3c67, 0x3c04bc5c, 0xbc183c4e, 0x3c2cbc3e, 0xba493c80, 0x3b16bc7d, 0xbb793c78, 0x3bacbc71, 0x3bac3c71, 0xbb79bc78,
    0x3b163c7d, 0xba49bc80, 0x3c2c3c3e, 0xbc18bc4e, 0x3c043c5c, 0xbbdbbc67, 0x3c673bdb, 0xbc5cbc04, 0x3c4e3c18, 0xbc3ebc2c,
    0x3c803a49, 0xbc7dbb16, 0x3c783b79, 0xbc71bbac, 0x3c800000, 0xbc800000, 0x3c800000, 0xbc800000, 0x3c800000, 0xbc800000,
    0x3c800000, 0xbc800000, 0x3c800000, 0xbc800000, 0x3c800000, 0xbc800000, 0x3c800000, 0xbc800000, 0x3c800000, 0xbc800000,
    0x3c800000, 0xbc800000, 0x3c800000, 0xbc800000, 0x3c800000, 0xbc800000, 0x3c800000, 0xbc800000, 0x3c800000, 0xbc800000,
    0x3c800000, 0xbc800000, 0x3c800000, 0xbc800000, 0x3c800000, 0xbc800000, 0x3c22bc46, 0xbbf13c62, 0x3b95bc75, 0xbac93c7f,
    0x3c7fbac9, 0xbc753b95, 0x3c62bbf1, 0xbc463c22, 0xbc46bc22, 0x3c623bf1, 0xbc75bb95, 0x3c7f3ac9, 0xbac9bc7f, 0x3b953c75,
    0xbbf1bc62, 0x3c223c46, 0xbc223c46, 0x3bf1bc62, 0xbb953c75, 0x3ac9bc7f, 0xbc7f3ac9, 0x3c75bb95, 0xbc623bf1, 0x3c46bc22,
    0x3c463c22, 0xbc62bbf1, 0x3c753b95, 0xbc7fbac9, 0x3ac93c7f, 0xbb95bc75, 0x3bf13c62, 0xbc22bc46, 0xbc7b3b48, 0x3c55bc0e,
    0xbc0e3c55, 0x3b48bc7b, 0x3b483c7b, 0xbc0ebc55, 0x3c553c0e, 0xbc7bbb48, 0x3c7bbb48, 0xbc553c0e, 0x3c0ebc55, 0xbb483c7b,
    0xbb48bc7b, 0x3c0e3c55, 0xbc55bc0e, 0x3c7b3b48, 0xbc7b3b48, 0x3c55bc0e, 0xbc0e3c55, 0x3b48bc7b, 0x3b483c7b, 0xbc0ebc55,
    0x3c553c0e, 0xbc7bbb48, 0x3c7bbb48, 0xbc553c0e, 0x3c0ebc55, 0xbb483c7b, 0xbb48bc7b, 0x3c0e3c55, 0xbc55bc0e, 0x3c7b3b48,
    0x3bf1bc62, 0x3ac93c7f, 0xbc22bc46, 0x3c753b95, 0x3b953c75, 0xbc46bc22, 0x3c7f3ac9, 0xbc623bf1, 0xbc62bbf1, 0x3c7fbac9,
    0xbc463c22, 0x3b95bc75, 0x3c75bb95, 0xbc223c46, 0x3ac9bc7f, 0x3bf13c62, 0xbbf13c62, 0xbac9bc7f, 0x3c223c46, 0xbc75bb95,
    0xbb95bc75, 0x3c463c22, 0xbc7fbac9, 0x3c62bbf1, 0x3c623bf1, 0xbc7f3ac9, 0x3c46bc22, 0xbb953c75, 0xbc753b95, 0x3c22bc46,
    0xbac93c7f, 0xbbf1bc62, 0x3c6dbbc4, 0xbbc43c6d, 0xbbc4bc6d, 0x3c6d3bc4, 0xbc6d3bc4, 0x3bc4bc6d, 0x3bc43c6d, 0xbc6dbbc4,
    0x3c6dbbc4, 0xbbc43c6d, 0xbbc4bc6d, 0x3c6d3bc4, 0xbc6d3bc4, 0x3bc4bc6d, 0x3bc43c6d, 0xbc6dbbc4, 0x3c6dbbc4, 0xbbc43c6d,
    0xbbc4bc6d, 0x3c6d3bc4, 0xbc6d3bc4, 0x3bc4bc6d, 0x3bc43c6d, 0xbc6dbbc4, 0x3c6dbbc4, 0xbbc43c6d, 0xbbc4bc6d, 0x3c6d3bc4,
    0xbc6d3bc4, 0x3bc4bc6d, 0x3bc43c6d, 0xbc6dbbc4, 0x3b95bc75, 0x3c223c46, 0xbc7f3ac9, 0x3bf1bc62, 0xbc623bf1, 0x3ac9bc7f,
    0x3c463c22, 0xbc753b95, 0xbc75bb95, 0x3c46bc22, 0x3ac93c7f, 0xbc62bbf1, 0x3bf13c62, 0xbc7fbac9, 0x3c22bc46, 0x3b953c75,
    0xbb953c75, 0xbc22bc46, 0x3c7fbac9, 0xbbf13c62, 0x3c62bbf1, 0xbac93c7f, 0xbc46bc22, 0x3c75bb95, 0x3c753b95, 0xbc463c22,
    0xbac9bc7f, 0x3c623bf1, 0xbbf1bc62, 0x3c7f3ac9, 0xbc223c46, 0xbb95bc75, 0xbc553c0e, 0xbb48bc7b, 0x3c7b3b48, 0xbc0e3c55,
    0xbc0ebc55, 0x3c7bbb48, 0xbb483c7b, 0xbc55bc0e, 0x3c55bc0e, 0x3b483c7b, 0xbc7bbb48, 0x3c0ebc55, 0x3c0e3c55, 0xbc7b3b48,
    0x3b48bc7b, 0x3c553c0e, 0xbc553c0e, 0xbb48bc7b, 0x3c7b3b48, 0xbc0e3c55, 0xbc0ebc55, 0x3c7bbb48, 0xbb483c7b, 0xbc55bc0e,
    0x3c55bc0e, 0x3b483c7b, 0xbc7bbb48, 0x3c0ebc55, 0x3c0e3c55, 0xbc7b3b48, 0x3b48bc7b, 0x3c553c0e, 0x3ac9bc7f, 0x3c753b95,
    0xbbf13c62, 0xbc46bc22, 0xbc22bc46, 0x3c62bbf1, 0x3b953c75, 0xbc7f3ac9, 0xbc7fbac9, 0x3b95bc75, 0x3c623bf1, 0xbc223c46,
    0xbc463c22, 0xbbf1bc62, 0x3c75bb95, 0x3ac93c7f, 0xbac93c7f, 0xbc75bb95, 0x3bf1bc62, 0x3c463c22, 0x3c223c46, 0xbc623bf1,
    0xbb95bc75, 0x3c7fbac9, 0x3c7f3ac9, 0xbb953c75, 0xbc62bbf1, 0x3c22bc46, 0x3c46bc22, 0x3bf13c62, 0xbc753b95, 0xbac9bc7f,
    0x3c80ba49, 0xbc7d3b16, 0x3c78bb79, 0xbc713bac, 0x3c67bbdb, 0xbc5c3c04, 0x3c4ebc18, 0xbc3e3c2c, 0x3c2cbc3e, 0xbc183c4e,
    0x3c04bc5c, 0xbbdb3c67, 0x3bacbc71, 0xbb793c78, 0x3b16bc7d, 0xba493c80, 0xba49bc80, 0x3b163c7d, 0xbb79bc78, 0x3bac3c71,
    0xbbdbbc67, 0x3c043c5c, 0xbc18bc4e, 0x3c2c3c3e, 0xbc3ebc2c, 0x3c4e3c18, 0xbc5cbc04, 0x3c673bdb, 0xbc71bbac, 0x3c783b79,
    0xbc7dbb16, 0x3c803a49, 0x3b79bc78, 0x3a493c80, 0xbbacbc71, 0x3c183c4e, 0x3c7dbb16, 0xbc673bdb, 0x3c3ebc2c, 0xbc043c5c,
    0xbc5c3c04, 0x3c2cbc3e, 0xbbdb3c67, 0x3b16bc7d, 0xbc4ebc18, 0x3c713bac, 0xbc80ba49, 0x3c78bb79, 0x3c783b79, 0xbc803a49,
    0x3c71bbac, 0xbc4e3c18, 0x3b163c7d, 0xbbdbbc67, 0x3c2c3c3e, 0xbc5cbc04, 0xbc04bc5c, 0x3c3e3c2c, 0xbc67bbdb, 0x3c7d3b16,
    0x3c18bc4e, 0xbbac3c71, 0x3a49bc80, 0x3b793c78, 0xbc043c5c, 0x3a49bc80, 0x3bdb3c67, 0xbc4ebc18, 0x3c7d3b16, 0xbc713bac,
    0x3c2cbc3e, 0xbb793c78, 0x3c78bb79, 0xbc3e3c2c, 0x3bacbc71, 0x3b163c7d, 0xbc18bc4e, 0x3c673bdb, 0xbc803a49, 0x3c5cbc04,
    0x3c5c3c04, 0xbc80ba49, 0x3c67bbdb, 0xbc183c4e, 0x3b16bc7d, 0x3bac3c71, 0xbc3ebc2c, 0x3c783b79, 0xbb79bc78, 0x3c2c3c3e,
    0xbc71bbac, 0x3c7dbb16, 0xbc4e3c18, 0x3bdbbc67, 0x3a493c80, 0xbc04bc5c, 0xbc2cbc3e, 0x3c7d3b16, 0xbc5c3c04, 0x3bacbc71,
    0x3c673bdb, 0xbc783b79, 0x3c18bc4e, 0x3a493c80, 0xbc80ba49, 0x3c4ebc18, 0xbb793c78, 0xbbdbbc67, 0x3c71bbac, 0xbc043c5c,
    0xbb16bc7d, 0x3c3e3c2c, 0x3c3ebc2c, 0xbb163c7d, 0xbc04bc5c, 0x3c713bac, 0xbbdb3c67, 0xbb79bc78, 0x3c4e3c18, 0xbc803a49,
    0x3a49bc80, 0x3c183c4e, 0xbc78bb79, 0x3c67bbdb, 0x3bac3c71, 0xbc5cbc04, 0x3c7dbb16, 0xbc2c3c3e, 0xbbdbbc67, 0x3c783b79,
    0xbc4e3c18, 0x3a49bc80, 0x3c3e3c2c, 0xbc7d3b16, 0x3c04bc5c, 0x3bac3c71, 0xbc71bbac, 0x3c5cbc04, 0xbb163c7d, 0xbc2cbc3e,
    0x3c80ba49, 0xbc183c4e, 0xbb79bc78, 0x3c673bdb, 0x3c67bbdb, 0xbb793c78, 0xbc18bc4e, 0x3c803a49, 0xbc2c3c3e, 0xbb16bc7d,
    0x3c5c3c04, 0xbc713bac, 0x3bacbc71, 0x3c043c5c, 0xbc7dbb16, 0x3c3ebc2c, 0x3a493c80, 0xbc4ebc18, 0x3c78bb79, 0xbbdb3c67,
    0xbc7d3b16, 0x3bacbc71, 0x3c2c3c3e, 0xbc783b79, 0x3c043c5c, 0xbc803a49, 0x3bdbbc67, 0x3c183c4e, 0x3c4e3c18, 0xbc673bdb,
    0x3a49bc80, 0x3c5c3c04, 0x3b79bc78, 0x3c3e3c2c, 0xbc713bac, 0x3b16bc7d, 0x3b163c7d, 0xbc71bbac, 0x3c3ebc2c, 0x3b793c78,
    0x3c5cbc04, 0x3a493c80, 0xbc67bbdb, 0x3c4ebc18, 0x3c18bc4e, 0x3bdb3c67, 0xbc80ba49, 0x3c04bc5c, 0xbc78bb79, 0x3c2cbc3e,
    0x3bac3c71, 0xbc7dbb16, 0x3c7d3b16, 0xbbdb3c67, 0xbc3ebc2c, 0x3c5cbc04, 0x3b793c78, 0xbc80ba49, 0x3bacbc71, 0x3c4e3c18,
    0xbc18bc4e, 0x3c71bbac, 0x3a493c80, 0xbc78bb79, 0x3c04bc5c, 0x3c2c3c3e, 0xbc673bdb, 0xbb16bc7d, 0xbb163c7d, 0xbc67bbdb,
    0x3c2cbc3e, 0x3c043c5c, 0xbc783b79, 0x3a49bc80, 0x3c713bac, 0xbc183c4e, 0x3c4ebc18, 0x3bac3c71, 0xbc803a49, 0x3b79bc78,
    0x3c5c3c04, 0xbc3e3c2c, 0xbbdbbc67, 0x3c7dbb16, 0xbbdb3c67, 0xbc5cbc04, 0x3c18bc4e, 0x3c3e3c2c, 0xba493c80, 0xbc7dbb16,
    0x3b79bc78, 0x3c713bac, 0x3bac3c71, 0xbc783b79, 0xbb16bc7d, 0x3c80ba49, 0x3c2c3c3e, 0xbc4e3c18, 0xbc04bc5c, 0x3c67bbdb,
    0x3c673bdb, 0xbc043c5c, 0xbc4ebc18, 0x3c2cbc3e, 0x3c803a49, 0xbb163c7d, 0xbc78bb79, 0x3bacbc71, 0x3c71bbac, 0x3b793c78,
    0xbc7d3b16, 0xba49bc80, 0x3c3ebc2c, 0x3c183c4e, 0xbc5c3c04, 0xbbdbbc67, 0x3f803f80, 0x3f7d3f7f, 0x3f783f7b, 0x3f713f75,
    0x3f673f6d, 0x3f5c3f62, 0x3f4e3f55, 0x3f3e3f46, 0x3f2c3f35, 0x3f183f22, 0x3f043f0e, 0x3edb3ef1, 0x3eac3ec4, 0x3e793e95,
    0x3e163e48, 0x3d493dc9, 0xbd490000, 0xbe16bdc9, 0xbe79be48, 0xbeacbe95, 0xbedbbec4, 0xbf04bef1, 0xbf18bf0e, 0xbf2cbf22,
    0xbf3ebf35, 0xbf4ebf46, 0xbf5cbf55, 0xbf67bf62, 0xbf71bf6d, 0xbf78bf75, 0xbf7dbf7b, 0xbf80bf7f, 0x3edb3ec4, 0x3f043ef1,
    0x3f183f0e, 0x3f2c3f22, 0x3d490000, 0x3e163dc9, 0x3e793e48, 0x3eac3e95, 0x3f713f6d, 0x3f783f75, 0x3f7d3f7b, 0x3f803f7f,
    0x3f3e3f35, 0x3f4e3f46, 0x3f5c3f55, 0x3f673f62, 0x3f673f6d, 0x3f5c3f62, 0x3f4e3f55, 0x3f3e3f46, 0x3f803f80, 0x3f7d3f7f,
    0x3f783f7b, 0x3f713f75, 0x3eac3ec4, 0x3e793e95, 0x3e163e48, 0x3d493dc9, 0x3f2c3f35, 0x3f183f22, 0x3f043f0e, 0x3edb3ef1,
    0xbf4ebf35, 0xbf71bf62, 0xbf80bf7b, 0xbf78bf7f, 0xbf5cbf6d, 0xbf2cbf46, 0xbedbbf0e, 0xbe16be95, 0x3f7d3f80, 0x3f673f75,
    0x3f3e3f55, 0x3f043f22, 0x3e793ec4, 0xbd493dc9, 0xbeacbe48, 0xbf18bef1, 0x3f183f35, 0x3eac3ef1, 0x3d493e48, 0xbe79bdc9,
    0xbf04bec4, 0xbf3ebf22, 0xbf67bf55, 0xbf7dbf75, 0x3e160000, 0x3edb3e95, 0x3f2c3f0e, 0x3f5c3f46, 0x3f783f6d, 0x3f803f7f,
    0x3f713f7b, 0x3f4e3f62, 0xbf04bec4, 0xbf3ebf22, 0xbf67bf55, 0xbf7dbf75, 0x3f183f35, 0x3eac3ef1, 0x3d493e48, 0xbe79bdc9,
    0x3f783f6d, 0x3f803f7f, 0x3f713f7b, 0x3f4e3f62, 0x3e160000, 0x3edb3e95, 0x3f2c3f0e, 0x3f5c3f46, 0x3f5c3f6d, 0x3f2c3f46,
    0x3edb3f0e, 0x3e163e95, 0x3f4e3f35, 0x3f713f62, 0x3f803f7b, 0x3f783f7f, 0xbe79bec4, 0x3d49bdc9, 0x3eac3e48, 0x3f183ef1,
    0xbf7dbf80, 0xbf67bf75, 0xbf3ebf55, 0xbf04bf22, 0xbe790000, 0xbf2cbef1, 0xbf71bf55, 0xbf7dbf7f, 0xbf4ebf6d, 0xbedbbf22,
    0x3d49be48, 0x3f043e95, 0x3f5c3f35, 0x3f803f75, 0x3f673f7b, 0x3f183f46, 0x3e163ec4, 0xbeacbdc9, 0xbf3ebf0e, 0xbf78bf62,
    0x3f783f80, 0x3f3e3f62, 0x3eac3f0e, 0xbe163dc9, 0xbf18bec4, 0xbf67bf46, 0xbf80bf7b, 0xbf5cbf75, 0xbf04bf35, 0xbd49be95,
    0x3edb3e48, 0x3f4e3f22, 0x3f7d3f6d, 0x3f713f7f, 0x3f2c3f55, 0x3e793ef1, 0xbf18bec4, 0xbf67bf46, 0xbf80bf7b, 0xbf5cbf75,
    0x3f783f80, 0x3f3e3f62, 0x3eac3f0e, 0xbe163dc9, 0x3f7d3f6d, 0x3f713f7f, 0x3f2c3f55, 0x3e793ef1, 0xbf04bf35, 0xbd49be95,
    0x3edb3e48, 0x3f4e3f22, 0x3f4e3f6d, 0x3edb3f22, 0xbd493e48, 0xbf04be95, 0x3e790000, 0x3f2c3ef1, 0x3f713f55, 0x3f7d3f7f,
    0xbe16bec4, 0x3eac3dc9, 0x3f3e3f0e, 0x3f783f62, 0xbf5cbf35, 0xbf80bf75, 0xbf67bf7b, 0xbf18bf46, 0xbedbbf35, 0x3e79bdc9,
    0x3f4e3f0e, 0x3f803f75, 0x3f3e3f6d, 0x3e163ef1, 0xbf04be48, 0xbf71bf46, 0x3eac0000, 0x3f5c3f22, 0x3f7d3f7b, 0x3f2c3f62,
    0x3d493ec4, 0xbf18be95, 0xbf78bf55, 0xbf67bf7f, 0x3f673f35, 0x3f783f7f, 0x3f183f55, 0xbd493e95, 0xbf2cbec4, 0xbf7dbf62,
    0xbf5cbf7b, 0xbeacbf22, 0x3f713f80, 0x3f043f46, 0xbe163e48, 0xbf3ebef1, 0xbf80bf6d, 0xbf4ebf75, 0xbe79bf0e, 0x3edb3dc9,
    0x3f2c3ec4, 0x3f7d3f62, 0x3f5c3f7b, 0x3eac3f22, 0xbf67bf35, 0xbf78bf7f, 0xbf18bf55, 0x3d49be95, 0x3f803f6d, 0x3f4e3f75,
    0x3e793f0e, 0xbedbbdc9, 0xbf71bf80, 0xbf04bf46, 0x3e16be48, 0x3f3e3ef1, 0x3f3e3f6d, 0x3e163ef1, 0xbf04be48, 0xbf71bf46,
    0xbedbbf35, 0x3e79bdc9, 0x3f4e3f0e, 0x3f803f75, 0x3d493ec4, 0xbf18be95, 0xbf78bf55, 0xbf67bf7f, 0x3eac0000, 0x3f5c3f22,
    0x3f7d3f7b, 0x3f2c3f62, 0x3f673f80, 0x3e793f22, 0xbf18be48, 0xbf80bf62, 0xbf2cbf6d, 0x3e16be95, 0x3f5c3f0e, 0x3f713f7f,
    0x3eac3f35, 0xbf04bdc9, 0xbf7dbf55, 0xbf3ebf75, 0x3d49bec4, 0x3f4e3ef1, 0x3f783f7b, 0x3edb3f46, 0xbedb0000, 0xbf78bf46,
    0xbf4ebf7b, 0xbd49bef1, 0x3f3e3ec4, 0x3f7d3f75, 0x3f043f55, 0xbeac3dc9, 0xbf71bf35, 0xbf5cbf7f, 0xbe16bf0e, 0x3f2c3e95,
    0x3f803f6d, 0x3f183f62, 0xbe793e48, 0xbf67bf22, 0xbf3ebec4, 0xbf7dbf75, 0xbf04bf55, 0x3eacbdc9, 0x3edb0000, 0x3f783f46,
    0x3f4e3f7b, 0x3d493ef1, 0xbf80bf6d, 0xbf18bf62, 0x3e79be48, 0x3f673f22, 0x3f713f35, 0x3f5c3f7f, 0x3e163f0e, 0xbf2cbe95,
    0xbf2cbf6d, 0x3e16be95, 0x3f5c3f0e, 0x3f713f7f, 0x3f673f80, 0x3e793f22, 0xbf18be48, 0xbf80bf62, 0x3d49bec4, 0x3f4e3ef1,
    0x3f783f7b, 0x3edb3f46, 0x3eac3f35, 0xbf04bdc9, 0xbf7dbf55, 0xbf3ebf75, 0xbf78bf35, 0xbf2cbf75, 0x3eacbe48, 0x3f7d3f46,
    0x3f183f6d, 0xbedb3dc9, 0xbf80bf55, 0xbf04bf62, 0x3f5c3f80, 0xbd493ef1, 0xbf67bf0e, 0xbf4ebf7f, 0x3e16bec4, 0x3f713f22,
    0x3f3e3f7b, 0xbe793e95, 0x3e793f35, 0xbf3ebe95, 0xbf71bf7b, 0xbe16bf22, 0x3f4e3ec4, 0x3f673f7f, 0x3d493f0e, 0xbf5cbef1,
    0x3f040000, 0x3f803f62, 0x3edb3f55, 0xbf18bdc9, 0xbf7dbf6d, 0xbeacbf46, 0x3f2c3e48, 0x3f783f75, 0x3f4e3ec4, 0x3f673f7f,
    0x3d493f0e, 0xbf5cbef1, 0x3e793f35, 0xbf3ebe95, 0xbf71bf7b, 0xbe16bf22, 0xbf7dbf6d, 0xbeacbf46, 0x3f2c3e48, 0x3f783f75,
    0x3f040000, 0x3f803f62, 0x3edb3f55, 0xbf18bdc9, 0xbf18bf6d, 0x3edbbdc9, 0x3f803f55, 0x3f043f62, 0x3f783f35, 0x3f2c3f75,
    0xbeac3e48, 0xbf7dbf46, 0xbe163ec4, 0xbf71bf22, 0xbf3ebf7b, 0x3e79be95, 0xbf5cbf80, 0x3d49bef1, 0x3f673f0e, 0x3f4e3f7f,
    0xbf180000, 0xbf71bf75, 0x3d49bf0e, 0x3f783f22, 0x3f043f6d, 0xbf2cbdc9, 0xbf67bf7b, 0x3e16bef1, 0x3f7d3f35, 0x3edb3f62,
    0xbf3ebe48, 0xbf5cbf7f, 0x3e79bec4, 0x3f803f46, 0x3eac3f55, 0xbf4ebe95, 0x3f4e3f80, 0xbeac3e95, 0xbf80bf55, 0xbe79bf46,
    0x3f5c3ec4, 0x3f3e3f7f, 0xbedb3e48, 0xbf7dbf62, 0xbe16bf35, 0x3f673ef1, 0x3f2c3f7b, 0xbf043dc9, 0xbf78bf6d, 0xbd49bf22,
    0x3f713f0e, 0x3f183f75, 0x3f5c3ec4, 0x3f3e3f7f, 0xbedb3e48, 0xbf7dbf62, 0x3f4e3f80, 0xbeac3e95, 0xbf80bf55, 0xbe79bf46,
    0xbf78bf6d, 0xbd49bf22, 0x3f713f0e, 0x3f183f75, 0xbe16bf35, 0x3f673ef1, 0x3f2c3f7b, 0xbf043dc9, 0xbf04bf6d, 0x3f2c3dc9,
    0x3f673f7b, 0xbe163ef1, 0x3f180000, 0x3f713f75, 0xbd493f0e, 0xbf78bf22, 0xbe793ec4, 0xbf80bf46, 0xbeacbf55, 0x3f4e3e95,
    0xbf7dbf35, 0xbedbbf62, 0x3f3e3e48, 0x3f5c3f7f, 0xbd49bf35, 0x3f7d3f22, 0x3e793f55, 0xbf71bef1, 0xbedbbf6d, 0x3f5c3e95,
    0x3f183f7b, 0xbf3ebdc9, 0x3f2c0000, 0x3f4e3f7f, 0xbf043e48, 0xbf67bf75, 0x3eacbec4, 0x3f783f62, 0xbe163f0e, 0xbf80bf46,
    0x3f803f35, 0x3e163f46, 0xbf78bf0e, 0xbeacbf62, 0x3f673ec4, 0x3f043f75, 0xbf4ebe48, 0xbf2cbf7f, 0x3f3e3f80, 0xbf183dc9,
    0xbf5cbf7b, 0x3edbbe95, 0x3f713f6d, 0xbe793ef1, 0xbf7dbf55, 0x3d49bf22, 0xbf67bec4, 0xbf04bf75, 0x3f4e3e48, 0x3f2c3f7f,
    0xbf80bf35, 0xbe16bf46, 0x3f783f0e, 0x3eac3f62, 0xbf71bf6d, 0x3e79bef1, 0x3f7d3f55, 0xbd493f22, 0xbf3ebf80, 0x3f18bdc9,
    0x3f5c3f7b, 0xbedb3e95, 0xbedbbf6d, 0x3f5c3e95, 0x3f183f7b, 0xbf3ebdc9, 0xbd49bf35, 0x3f7d3f22, 0x3e793f55, 0xbf71bef1,
    0x3eacbec4, 0x3f783f62, 0xbe163f0e, 0xbf80bf46, 0x3f2c0000, 0x3f4e3f7f, 0xbf043e48, 0xbf67bf75, 0x3f2c3f80, 0xbf4ebdc9,
    0xbf04bf7b, 0x3f673e95, 0x3eac3f6d, 0xbf78bef1, 0xbe16bf55, 0x3f803f22, 0xbd493f35, 0xbf7dbf46, 0x3e79bf0e, 0x3f713f62,
    0xbedb3ec4, 0xbf5cbf75, 0x3f18be48, 0x3f3e3f7f, 0xbf3e0000, 0xbf18bf7f, 0x3f5c3e48, 0x3edb3f75, 0xbf71bec4, 0xbe79bf62,
    0x3f7d3f0e, 0x3d493f46, 0xbf80bf35, 0x3e16bf22, 0x3f783f55, 0xbeac3ef1, 0xbf67bf6d, 0x3f04be95, 0x3f4e3f7b, 0xbf2c3dc9,
    0x3f713ec4, 0x3e793f62, 0xbf7dbf0e, 0xbd49bf46, 0x3f3e0000, 0x3f183f7f, 0xbf5cbe48, 0xbedbbf75, 0x3f673f6d, 0xbf043e95,
    0xbf4ebf7b, 0x3f2cbdc9, 0x3f803f35, 0xbe163f22, 0xbf78bf55, 0x3eacbef1, 0x3eac3f6d, 0xbf78bef1, 0xbe16bf55, 0x3f803f22,
    0x3f2c3f80, 0xbf4ebdc9, 0xbf04bf7b, 0x3f673e95, 0xbedb3ec4, 0xbf5cbf75, 0x3f18be48, 0x3f3e3f7f, 0xbd493f35, 0xbf7dbf46,
    0x3e79bf0e, 0x3f713f62, 0xbf7dbf35, 0x3edbbef1, 0x3f3e3f7b, 0xbf5cbdc9, 0xbe79bf6d, 0x3f803f22, 0xbeac3f0e, 0xbf4ebf75,
    0x3f183f80, 0xbf71be95, 0xbd49bf55, 0x3f783f46, 0xbf043ec4, 0xbf2cbf7f, 0x3f673e48, 0x3e163f62, 0xbe163f35, 0xbf67bf62,
    0x3f2cbe48, 0x3f043f7f, 0xbf78bec4, 0x3d49bf46, 0x3f713f55, 0xbf183e95, 0x3f4e0000, 0x3eac3f75, 0xbf80bf0e, 0x3e79bf22,
    0x3f5c3f6d, 0xbf3e3dc9, 0xbedbbf7b, 0x3f7d3ef1, 0xbf78bec4, 0x3d49bf46, 0x3f713f55, 0xbf183e95, 0xbe163f35, 0xbf67bf62,
    0x3f2cbe48, 0x3f043f7f, 0x3f5c3f6d, 0xbf3e3dc9, 0xbedbbf7b, 0x3f7d3ef1, 0x3f4e0000, 0x3eac3f75, 0xbf80bf0e, 0x3e79bf22,
    0x3e793f6d, 0xbf80bf22, 0x3eacbf0e, 0x3f4e3f75, 0x3f7d3f35, 0xbedb3ef1, 0xbf3ebf7b, 0x3f5c3dc9, 0x3f04bec4, 0x3f2c3f7f,
    0xbf67be48, 0xbe16bf62, 0xbf18bf80, 0x3f713e95, 0x3d493f55, 0xbf78bf46, 0xbf5c0000, 0xbd49bf62, 0x3f673f55, 0xbf4e3dc9,
    0xbe16bf6d, 0x3f713f46, 0xbf3e3e48, 0xbe79bf75, 0x3f783f35, 0xbf2c3e95, 0xbeacbf7b, 0x3f7d3f22, 0xbf183ec4, 0xbedbbf7f,
    0x3f803f0e, 0xbf043ef1, 0x3f043f80, 0xbf80bef1, 0x3edbbf0e, 0x3f183f7f, 0xbf7dbec4, 0x3eacbf22, 0x3f2c3f7b, 0xbf78be95,
    0x3e79bf35, 0x3f3e3f75, 0xbf71be48, 0x3e16bf46, 0x3f4e3f6d, 0xbf67bdc9, 0x3d49bf55, 0x3f5c3f62, 0xbf7dbec4, 0x3eacbf22,
    0x3f2c3f7b, 0xbf78be95, 0x3f043f80, 0xbf80bef1, 0x3edbbf0e, 0x3f183f7f, 0x3f4e3f6d, 0xbf67bdc9, 0x3d49bf55, 0x3f5c3f62,
    0x3e79bf35, 0x3f3e3f75, 0xbf71be48, 0x3e16bf46, 0x3e163f6d, 0xbf71bf46, 0x3f3ebe48, 0x3e793f75, 0x3f5c0000, 0x3d493f62,
    0xbf67bf55, 0x3f4ebdc9, 0x3f18bec4, 0x3edb3f7f, 0xbf80bf0e, 0x3f04bef1, 0xbf78bf35, 0x3f2cbe95, 0x3eac3f7b, 0xbf7dbf22,
    0x3eacbf35, 0x3f043f7f, 0xbf7dbf0e, 0x3f3ebe95, 0x3d493f6d, 0xbf4ebf62, 0x3f783e48, 0xbedb3f22, 0x3f670000, 0xbe793f46,
    0xbf18bf7b, 0x3f803ef1, 0xbf2c3ec4, 0xbe16bf75, 0x3f5c3f55, 0xbf71bdc9, 0x3f713f35, 0xbf5c3dc9, 0x3e16bf55, 0x3f2c3f75,
    0xbf80bec4, 0x3f18bef1, 0x3e793f7b, 0xbf67bf46, 0x3edb3f80, 0xbf78bf22, 0x3f4ebe48, 0xbd493f62, 0xbf3ebf6d, 0x3f7d3e95,
    0xbf043f0e, 0xbeacbf7f, 0x3f803ec4, 0xbf183ef1, 0xbe79bf7b, 0x3f673f46, 0xbf71bf35, 0x3f5cbdc9, 0xbe163f55, 0xbf2cbf75,
    0x3f3e3f6d, 0xbf7dbe95, 0x3f04bf0e, 0x3eac3f7f, 0xbedbbf80, 0x3f783f22, 0xbf4e3e48, 0x3d49bf62, 0x3d493f6d, 0xbf4ebf62,
    0x3f783e48, 0xbedb3f22, 0x3eacbf35, 0x3f043f7f, 0xbf7dbf0e, 0x3f3ebe95, 0xbf2c3ec4, 0xbe16bf75, 0x3f5c3f55, 0xbf71bdc9,
    0x3f670000, 0xbe793f46, 0xbf18bf7b, 0x3f803ef1, 0x3eac3f80, 0xbf5cbf46, 0x3f7d3e48, 0xbf2c3ef1, 0x3d49bf6d, 0x3f183f75,
    0xbf78bf0e, 0x3f67bdc9, 0xbedb3f35, 0xbe79bf7f, 0x3f4e3f55, 0xbf80be95, 0x3f3ebec4, 0xbe163f62, 0xbf04bf7b, 0x3f713f22,
    0xbf710000, 0x3f04bf22, 0x3e163f7b, 0xbf3ebf62, 0x3f803ec4, 0xbf4e3e95, 0x3e79bf55, 0x3edb3f7f, 0xbf67bf35, 0x3f783dc9,
    0xbf183f0e, 0xbd49bf75, 0x3f2c3f6d, 0xbf7dbef1, 0x3f5cbe48, 0xbeac3f46, 0xbf80bec4, 0x3f4ebe95, 0xbe793f55, 0xbedbbf7f,
    0x3f710000, 0xbf043f22, 0xbe16bf7b, 0x3f3e3f62, 0xbf2cbf6d, 0x3f7d3ef1, 0xbf5c3e48, 0x3eacbf46, 0x3f673f35, 0xbf78bdc9,
    0x3f18bf0e, 0x3d493f75, 0x3d49bf6d, 0x3f183f75, 0xbf78bf0e, 0x3f67bdc9, 0x3eac3f80, 0xbf5cbf46, 0x3f7d3e48, 0xbf2c3ef1,
    0x3f3ebec4, 0xbe163f62, 0xbf04bf7b, 0x3f713f22, 0xbedb3f35, 0xbe79bf7f, 0x3f4e3f55, 0xbf80be95, 0xbf5cbf35, 0x3f803e95,
    0xbf673e48, 0x3f18bf22, 0xbe163f6d, 0xbeacbf7f, 0x3f3e3f55, 0xbf78bef1, 0x3e793f80, 0xbf2cbf62, 0x3f713f0e, 0xbf7dbdc9,
    0x3f4ebec4, 0xbedb3f46, 0xbd49bf7b, 0x3f043f75, 0xbf043f35, 0x3d49bf75, 0x3edb3f7b, 0xbf4ebf46, 0x3f7d3ec4, 0xbf713dc9,
    0x3f2cbf0e, 0xbe793f62, 0x3f780000, 0xbf3e3ef1, 0x3eacbf55, 0x3e163f7f, 0xbf18bf6d, 0x3f673f22, 0xbf80be48, 0x3f5cbe95,
    0x3f7d3ec4, 0xbf713dc9, 0x3f2cbf0e, 0xbe793f62, 0xbf043f35, 0x3d49bf75, 0x3edb3f7b, 0xbf4ebf46, 0xbf18bf6d, 0x3f673f22,
    0xbf80be48, 0x3f5cbe95, 0x3f780000, 0xbf3e3ef1, 0x3eacbf55, 0x3e163f7f, 0x3e16bf6d, 0x3eac3f7f, 0xbf3ebf55, 0x3f783ef1,
    0x3f5c3f35, 0xbf80be95, 0x3f67be48, 0xbf183f22, 0xbf4e3ec4, 0x3edbbf46, 0x3d493f7b, 0xbf04bf75, 0xbe79bf80, 0x3f2c3f62,
    0xbf71bf0e, 0x3f7d3dc9, 0xbf7d0000, 0x3f67be95, 0xbf3e3f0e, 0x3f04bf46, 0xbe793f6d, 0xbd49bf7f, 0x3eac3f7b, 0xbf18bf62,
    0x3f4e3f35, 0xbf71bef1, 0x3f803e48, 0xbf783dc9, 0x3f5cbec4, 0xbf2c3f22, 0x3edbbf55, 0xbe163f75, 0x3e163f80, 0xbedbbf75,
    0x3f2c3f55, 0xbf5cbf22, 0x3f783ec4, 0xbf80bdc9, 0x3f71be48, 0xbf4e3ef1, 0x3f18bf35, 0xbeac3f62, 0x3d49bf7b, 0x3e793f7f,
    0xbf04bf6d, 0x3f3e3f46, 0xbf67bf0e, 0x3f7d3e95, 0x3f783ec4, 0xbf80bdc9, 0x3f71be48, 0xbf4e3ef1, 0x3e163f80, 0xbedbbf75,
    0x3f2c3f55, 0xbf5cbf22, 0xbf04bf6d, 0x3f3e3f46, 0xbf67bf0e, 0x3f7d3e95, 0x3f18bf35, 0xbeac3f62, 0x3d49bf7b, 0x3e793f7f,
    0x3e79bf6d, 0x3d493f7f, 0xbeacbf7b, 0x3f183f62, 0x3f7d0000, 0xbf673e95, 0x3f3ebf0e, 0xbf043f46, 0xbf5c3ec4, 0x3f2cbf22,
    0xbedb3f55, 0x3e16bf75, 0xbf4ebf35, 0x3f713ef1, 0xbf80be48, 0x3f78bdc9, 0x3f2cbf35, 0xbf183f46, 0x3f04bf55, 0xbedb3f62,
    0x3eacbf6d, 0xbe793f75, 0x3e16bf7b, 0xbd493f7f, 0x3f800000, 0xbf7d3dc9, 0x3f78be48, 0xbf713e95, 0x3f67bec4, 0xbf5c3ef1,
    0x3f4ebf0e, 0xbf3e3f22, 0x3f3e3f35, 0xbf4ebf22, 0x3f5c3f0e, 0xbf67bef1, 0x3f713ec4, 0xbf78be95, 0x3f7d3e48, 0xbf80bdc9,
    0x3d493f80, 0xbe16bf7f, 0x3e793f7b, 0xbeacbf75, 0x3edb3f6d, 0xbf04bf62, 0x3f183f55, 0xbf2cbf46, 0xbf71bec4, 0x3f783e95,
    0xbf7dbe48, 0x3f803dc9, 0xbf3ebf35, 0x3f4e3f22, 0xbf5cbf0e, 0x3f673ef1, 0xbedbbf6d, 0x3f043f62, 0xbf18bf55, 0x3f2c3f46,
    0xbd49bf80, 0x3e163f7f, 0xbe79bf7b, 0x3eac3f75, 0x3eacbf6d, 0xbe793f75, 0x3e16bf7b, 0xbd493f7f, 0x3f2cbf35, 0xbf183f46,
    0x3f04bf55, 0xbedb3f62, 0x3f67bec4, 0xbf5c3ef1, 0x3f4ebf0e, 0xbf3e3f22, 0x3f800000, 0xbf7d3dc9, 0x3f78be48, 0xbf713e95,
    0xbd493f80, 0x3e16bf7f, 0xbe793f7b, 0x3eacbf75, 0xbedb3f6d, 0x3f04bf62, 0xbf183f55, 0x3f2cbf46, 0xbf3e3f35, 0x3f4ebf22,
    0xbf5c3f0e, 0x3f67bef1, 0xbf713ec4, 0x3f78be95, 0xbf7d3e48, 0x3f80bdc9, 0xbf800000, 0x3f7d3dc9, 0xbf78be48, 0x3f713e95,
    0xbf67bec4, 0x3f5c3ef1, 0xbf4ebf0e, 0x3f3e3f22, 0xbf2cbf35, 0x3f183f46, 0xbf04bf55, 0x3edb3f62, 0xbeacbf6d, 0x3e793f75,
    0xbe16bf7b, 0x3d493f7f, 0x3f673ec4, 0xbf5cbef1, 0x3f4e3f0e, 0xbf3ebf22, 0x3f800000, 0xbf7dbdc9, 0x3f783e48, 0xbf71be95,
    0x3eac3f6d, 0xbe79bf75, 0x3e163f7b, 0xbd49bf7f, 0x3f2c3f35, 0xbf18bf46, 0x3f043f55, 0xbedbbf62, 0xbedb3f6d, 0x3f04bf62,
    0xbf183f55, 0x3f2cbf46, 0xbd493f80, 0x3e16bf7f, 0xbe793f7b, 0x3eacbf75, 0xbf713ec4, 0x3f78be95, 0xbf7d3e48, 0x3f80bdc9,
    0xbf3e3f35, 0x3f4ebf22, 0xbf5c3f0e, 0x3f67bef1, 0xbf18bf35, 0x3eac3f62, 0xbd49bf7b, 0xbe793f7f, 0x3f04bf6d, 0xbf3e3f46,
    0x3f67bf0e, 0xbf7d3e95, 0xbe163f80, 0x3edbbf75, 0xbf2c3f55, 0x3f5cbf22, 0xbf783ec4, 0x3f80bdc9, 0xbf71be48, 0x3f4e3ef1,
    0xbf4e3f35, 0x3f71bef1, 0xbf803e48, 0x3f783dc9, 0xbf5cbec4, 0x3f2c3f22, 0xbedbbf55, 0x3e163f75, 0x3f7d0000, 0xbf67be95,
    0x3f3e3f0e, 0xbf04bf46, 0x3e793f6d, 0x3d49bf7f, 0xbeac3f7b, 0x3f18bf62, 0xbf5cbec4, 0x3f2c3f22, 0xbedbbf55, 0x3e163f75,
    0xbf4e3f35, 0x3f71bef1, 0xbf803e48, 0x3f783dc9, 0x3e793f6d, 0x3d49bf7f, 0xbeac3f7b, 0x3f18bf62, 0x3f7d0000, 0xbf67be95,
    0x3f3e3f0e, 0xbf04bf46, 0xbf043f6d, 0x3f3ebf46, 0xbf673f0e, 0x3f7dbe95, 0x3f183f35, 0xbeacbf62, 0x3d493f7b, 0x3e79bf7f,
    0x3f78bec4, 0xbf803dc9, 0x3f713e48, 0xbf4ebef1, 0x3e16bf80, 0xbedb3f75, 0x3f2cbf55, 0xbf5c3f22, 0xbf780000, 0x3f3e3ef1,
    0xbeacbf55, 0xbe163f7f, 0x3f18bf6d, 0xbf673f22, 0x3f80be48, 0xbf5cbe95, 0x3f043f35, 0xbd49bf75, 0xbedb3f7b, 0x3f4ebf46,
    0xbf7d3ec4, 0x3f713dc9, 0xbf2cbf0e, 0x3e793f62, 0xbe793f80, 0x3f2cbf62, 0xbf713f0e, 0x3f7dbdc9, 0xbf4ebec4, 0x3edb3f46,
    0x3d49bf7b, 0xbf043f75, 0x3f5cbf35, 0xbf803e95, 0x3f673e48, 0xbf18bf22, 0x3e163f6d, 0x3eacbf7f, 0xbf3e3f55, 0x3f78bef1,
    0xbf4ebec4, 0x3edb3f46, 0x3d49bf7b, 0xbf043f75, 0xbe793f80, 0x3f2cbf62, 0xbf713f0e, 0x3f7dbdc9, 0x3e163f6d, 0x3eacbf7f,
    0xbf3e3f55, 0x3f78bef1, 0x3f5cbf35, 0xbf803e95, 0x3f673e48, 0xbf18bf22, 0xbf183f6d, 0x3f67bf22, 0xbf803e48, 0x3f5c3e95,
    0x3f780000, 0xbf3ebef1, 0x3eac3f55, 0x3e16bf7f, 0x3f7dbec4, 0xbf71bdc9, 0x3f2c3f0e, 0xbe79bf62, 0xbf04bf35, 0x3d493f75,
    0x3edbbf7b, 0xbf4e3f46, 0x3f67bf35, 0xbf783dc9, 0x3f183f0e, 0x3d49bf75, 0xbf2c3f6d, 0x3f7dbef1, 0xbf5cbe48, 0x3eac3f46,
    0x3f710000, 0xbf04bf22, 0xbe163f7b, 0x3f3ebf62, 0xbf803ec4, 0x3f4e3e95, 0xbe79bf55, 0xbedb3f7f, 0x3edb3f35, 0x3e79bf7f,
    0xbf4e3f55, 0x3f80be95, 0xbf3ebec4, 0x3e163f62, 0x3f04bf7b, 0xbf713f22, 0xbeac3f80, 0x3f5cbf46, 0xbf7d3e48, 0x3f2c3ef1,
    0xbd49bf6d, 0xbf183f75, 0x3f78bf0e, 0xbf67bdc9, 0x3f3e3ec4, 0xbe16bf62, 0xbf043f7b, 0x3f71bf22, 0xbedbbf35, 0xbe793f7f,
    0x3f4ebf55, 0xbf803e95, 0x3d493f6d, 0x3f18bf75, 0xbf783f0e, 0x3f673dc9, 0x3eacbf80, 0xbf5c3f46, 0x3f7dbe48, 0xbf2cbef1,
    0xbf2c3f6d, 0x3f7dbef1, 0xbf5cbe48, 0x3eac3f46, 0x3f67bf35, 0xbf783dc9, 0x3f183f0e, 0x3d49bf75, 0xbf803ec4, 0x3f4e3e95,
    0xbe79bf55, 0xbedb3f7f, 0x3f710000, 0xbf04bf22, 0xbe163f7b, 0x3f3ebf62, 0xbedb3f80, 0x3f78bf22, 0xbf4ebe48, 0x3d493f62,
    0x3f3ebf6d, 0xbf7d3e95, 0x3f043f0e, 0x3eacbf7f, 0xbf713f35, 0x3f5c3dc9, 0xbe16bf55, 0xbf2c3f75, 0x3f80bec4, 0xbf18bef1,
    0xbe793f7b, 0x3f67bf46, 0xbf670000, 0x3e793f46, 0x3f18bf7b, 0xbf803ef1, 0x3f2c3ec4, 0x3e16bf75, 0xbf5c3f55, 0x3f71bdc9,
    0xbeacbf35, 0xbf043f7f, 0x3f7dbf0e, 0xbf3ebe95, 0xbd493f6d, 0x3f4ebf62, 0xbf783e48, 0x3edb3f22, 0xbf2cbec4, 0xbe163f75,
    0x3f5cbf55, 0xbf713dc9, 0x3f670000, 0xbe79bf46, 0xbf183f7b, 0x3f80bef1, 0x3d49bf6d, 0xbf4e3f62, 0x3f78be48, 0xbedbbf22,
    0x3eac3f35, 0x3f04bf7f, 0xbf7d3f0e, 0x3f3e3e95, 0x3f3ebf6d, 0xbf7d3e95, 0x3f043f0e, 0x3eacbf7f, 0xbedb3f80, 0x3f78bf22,
    0xbf4ebe48, 0x3d493f62, 0x3f80bec4, 0xbf18bef1, 0xbe793f7b, 0x3f67bf46, 0xbf713f35, 0x3f5c3dc9, 0xbe16bf55, 0xbf2c3f75,
    0xbe79bf35, 0xbf3e3f75, 0x3f71be48, 0xbe16bf46, 0xbf4e3f6d, 0x3f67bdc9, 0xbd49bf55, 0xbf5c3f62, 0xbf043f80, 0x3f80bef1,
    0xbedbbf0e, 0xbf183f7f, 0x3f7dbec4, 0xbeacbf22, 0xbf2c3f7b, 0x3f78be95, 0xbf783f35, 0x3f2c3e95, 0x3eacbf7b, 0xbf7d3f22,
    0x3f183ec4, 0x3edbbf7f, 0xbf803f0e, 0x3f043ef1, 0x3f5c0000, 0x3d49bf62, 0xbf673f55, 0x3f4e3dc9, 0x3e16bf6d, 0xbf713f46,
    0x3f3e3e48, 0x3e79bf75, 0x3f183ec4, 0x3edbbf7f, 0xbf803f0e, 0x3f043ef1, 0xbf783f35, 0x3f2c3e95, 0x3eacbf7b, 0xbf7d3f22,
    0x3e16bf6d, 0xbf713f46, 0x3f3e3e48, 0x3e79bf75, 0x3f5c0000, 0x3d49bf62, 0xbf673f55, 0x3f4e3dc9, 0x3f4ebf6d, 0xbf673dc9,
    0x3d493f55, 0x3f5cbf62, 0x3e793f35, 0x3f3ebf75, 0xbf713e48, 0x3e163f46, 0xbf7d3ec4, 0x3eac3f22, 0x3f2cbf7b, 0xbf783e95,
    0x3f04bf80, 0xbf803ef1, 0x3edb3f0e, 0x3f18bf7f, 0xbf4e0000, 0xbeac3f75, 0x3f80bf0e, 0xbe79bf22, 0xbf5c3f6d, 0x3f3e3dc9,
    0x3edbbf7b, 0xbf7d3ef1, 0x3e163f35, 0x3f67bf62, 0xbf2cbe48, 0xbf043f7f, 0x3f78bec4, 0xbd49bf46, 0xbf713f55, 0x3f183e95,
    0xbf183f80, 0x3f71be95, 0x3d49bf55, 0xbf783f46, 0x3f043ec4, 0x3f2cbf7f, 0xbf673e48, 0xbe163f62, 0x3f7dbf35, 0xbedbbef1,
    0xbf3e3f7b, 0x3f5cbdc9, 0x3e79bf6d, 0xbf803f22, 0x3eac3f0e, 0x3f4ebf75, 0x3f043ec4, 0x3f2cbf7f, 0xbf673e48, 0xbe163f62,
    0xbf183f80, 0x3f71be95, 0x3d49bf55, 0xbf783f46, 0x3e79bf6d, 0xbf803f22, 0x3eac3f0e, 0x3f4ebf75, 0x3f7dbf35, 0xbedbbef1,
    0xbf3e3f7b, 0x3f5cbdc9, 0x3f5cbf6d, 0xbf3ebdc9, 0xbedb3f7b, 0x3f7dbef1, 0x3f4e0000, 0x3eacbf75, 0xbf803f0e, 0x3e793f22,
    0xbf783ec4, 0x3d493f46, 0x3f71bf55, 0xbf18be95, 0xbe16bf35, 0xbf673f62, 0x3f2c3e48, 0x3f04bf7f, 0x3f80bf35, 0xbe16bf22,
    0xbf783f55, 0x3eac3ef1, 0x3f67bf6d, 0xbf04be95, 0xbf4e3f7b, 0x3f2c3dc9, 0x3f3e0000, 0x3f18bf7f, 0xbf5c3e48, 0xbedb3f75,
    0x3f71bec4, 0x3e79bf62, 0xbf7d3f0e, 0xbd493f46, 0x3d493f35, 0x3f7dbf46, 0xbe79bf0e, 0xbf713f62, 0x3edb3ec4, 0x3f5cbf75,
    0xbf18be48, 0xbf3e3f7f, 0xbf2c3f80, 0x3f4ebdc9, 0x3f04bf7b, 0xbf673e95, 0xbeac3f6d, 0x3f78bef1, 0x3e16bf55, 0xbf803f22,
    0xbedbbec4, 0xbf5c3f75, 0x3f183e48, 0x3f3ebf7f, 0xbd49bf35, 0xbf7d3f46, 0x3e793f0e, 0x3f71bf62, 0x3eacbf6d, 0xbf783ef1,
    0xbe163f55, 0x3f80bf22, 0x3f2cbf80, 0xbf4e3dc9, 0xbf043f7b, 0x3f67be95, 0x3f67bf6d, 0xbf04be95, 0xbf4e3f7b, 0x3f2c3dc9,
    0x3f80bf35, 0xbe16bf22, 0xbf783f55, 0x3eac3ef1, 0x3f71bec4, 0x3e79bf62, 0xbf7d3f0e, 0xbd493f46, 0x3f3e0000, 0x3f18bf7f,
    0xbf5c3e48, 0xbedb3f75, 0xbf3e3f80, 0x3f183dc9, 0x3f5cbf7b, 0xbedbbe95, 0xbf713f6d, 0x3e793ef1, 0x3f7dbf55, 0xbd49bf22,
    0xbf803f35, 0xbe163f46, 0x3f78bf0e, 0x3eacbf62, 0xbf673ec4, 0xbf043f75, 0x3f4ebe48, 0x3f2cbf7f, 0xbf2c0000, 0xbf4e3f7f,
    0x3f043e48, 0x3f67bf75, 0xbeacbec4, 0xbf783f62, 0x3e163f0e, 0x3f80bf46, 0x3d49bf35, 0xbf7d3f22, 0xbe793f55, 0x3f71bef1,
    0x3edbbf6d, 0xbf5c3e95, 0xbf183f7b, 0x3f3ebdc9, 0x3eac3ec4, 0x3f78bf62, 0xbe16bf0e, 0xbf803f46, 0x3f2c0000, 0x3f4ebf7f,
    0xbf04be48, 0xbf673f75, 0xbedb3f6d, 0x3f5cbe95, 0x3f18bf7b, 0xbf3e3dc9, 0xbd493f35, 0x3f7dbf22, 0x3e79bf55, 0xbf713ef1,
    0xbf713f6d, 0x3e793ef1, 0x3f7dbf55, 0xbd49bf22, 0xbf3e3f80, 0x3f183dc9, 0x3f5cbf7b, 0xbedbbe95, 0xbf673ec4, 0xbf043f75,
    0x3f4ebe48, 0x3f2cbf7f, 0xbf803f35, 0xbe163f46, 0x3f78bf0e, 0x3eacbf62, 0x3e16bf35, 0xbf673ef1, 0xbf2c3f7b, 0x3f043dc9,
    0x3f78bf6d, 0x3d49bf22, 0xbf713f0e, 0xbf183f75, 0xbf4e3f80, 0x3eac3e95, 0x3f80bf55, 0x3e79bf46, 0xbf5c3ec4, 0xbf3e3f7f,
    0x3edb3e48, 0x3f7dbf62, 0xbf7d3f35, 0xbedb3f62, 0x3f3ebe48, 0x3f5cbf7f, 0xbe79bec4, 0xbf803f46, 0xbeac3f55, 0x3f4ebe95,
    0x3f180000, 0x3f71bf75, 0xbd49bf0e, 0xbf783f22, 0xbf043f6d, 0x3f2cbdc9, 0x3f67bf7b, 0xbe16bef1, 0xbe79bec4, 0xbf803f46,
    0xbeac3f55, 0x3f4ebe95, 0xbf7d3f35, 0xbedb3f62, 0x3f3ebe48, 0x3f5cbf7f, 0xbf043f6d, 0x3f2cbdc9, 0x3f67bf7b, 0xbe16bef1,
    0x3f180000, 0x3f71bf75, 0xbd49bf0e, 0xbf783f22, 0xbf783f6d, 0xbd493f22, 0x3f71bf0e, 0x3f18bf75, 0xbe163f35, 0x3f67bef1,
    0x3f2cbf7b, 0xbf04bdc9, 0x3f5cbec4, 0x3f3ebf7f, 0xbedbbe48, 0xbf7d3f62, 0x3f4ebf80, 0xbeacbe95, 0xbf803f55, 0xbe793f46,
    0xbf040000, 0xbf803f62, 0xbedb3f55, 0x3f18bdc9, 0x3f7dbf6d, 0x3eacbf46, 0xbf2c3e48, 0xbf783f75, 0xbe793f35, 0x3f3ebe95,
    0x3f71bf7b, 0x3e16bf22, 0xbf4e3ec4, 0xbf673f7f, 0xbd493f0e, 0x3f5cbef1, 0xbf5c3f80, 0x3d493ef1, 0x3f67bf0e, 0x3f4ebf7f,
    0xbe16bec4, 0xbf713f22, 0xbf3e3f7b, 0x3e793e95, 0x3f78bf35, 0x3f2cbf75, 0xbeacbe48, 0xbf7d3f46, 0xbf183f6d, 0x3edb3dc9,
    0x3f80bf55, 0x3f04bf62, 0xbe16bec4, 0xbf713f22, 0xbf3e3f7b, 0x3e793e95, 0xbf5c3f80, 0x3d493ef1, 0x3f67bf0e, 0x3f4ebf7f,
    0xbf183f6d, 0x3edb3dc9, 0x3f80bf55, 0x3f04bf62, 0x3f78bf35, 0x3f2cbf75, 0xbeacbe48, 0xbf7d3f46, 0xbf7d3f6d, 0xbeac3f46,
    0x3f2cbe48, 0x3f78bf75, 0x3f040000, 0x3f80bf62, 0x3edbbf55, 0xbf183dc9, 0x3f4ebec4, 0x3f67bf7f, 0x3d49bf0e, 0xbf5c3ef1,
    0x3e79bf35, 0xbf3e3e95, 0xbf713f7b, 0xbe163f22, 0x3f71bf35, 0x3f5cbf7f, 0x3e16bf0e, 0xbf2c3e95, 0xbf803f6d, 0xbf183f62,
    0x3e793e48, 0x3f67bf22, 0x3edb0000, 0x3f78bf46, 0x3f4ebf7b, 0x3d49bef1, 0xbf3e3ec4, 0xbf7d3f75, 0xbf043f55, 0x3eac3dc9,
    0xbeac3f35, 0x3f04bdc9, 0x3f7dbf55, 0x3f3ebf75, 0xbd49bec4, 0xbf4e3ef1, 0xbf783f7b, 0xbedb3f46, 0xbf673f80, 0xbe793f22,
    0x3f18be48, 0x3f80bf62, 0x3f2cbf6d, 0xbe16be95, 0xbf5c3f0e, 0xbf713f7f, 0x3d493ec4, 0x3f4ebef1, 0x3f78bf7b, 0x3edbbf46,
    0x3eacbf35, 0xbf043dc9, 0xbf7d3f55, 0xbf3e3f75, 0xbf2c3f6d, 0x3e163e95, 0x3f5cbf0e, 0x3f71bf7f, 0x3f67bf80, 0x3e79bf22,
    0xbf183e48, 0xbf803f62, 0xbf803f6d, 0xbf183f62, 0x3e793e48, 0x3f67bf22, 0x3f71bf35, 0x3f5cbf7f, 0x3e16bf0e, 0xbf2c3e95,
    0xbf3e3ec4, 0xbf7d3f75, 0xbf043f55, 0x3eac3dc9, 0x3edb0000, 0x3f78bf46, 0x3f4ebf7b, 0x3d49bef1, 0xbf713f80, 0xbf043f46,
    0x3e163e48, 0x3f3ebef1, 0x3f80bf6d, 0x3f4ebf75, 0x3e79bf0e, 0xbedb3dc9, 0xbf673f35, 0xbf783f7f, 0xbf183f55, 0x3d493e95,
    0x3f2cbec4, 0x3f7dbf62, 0x3f5cbf7b, 0x3eacbf22, 0xbeac0000, 0xbf5c3f22, 0xbf7d3f7b, 0xbf2c3f62, 0xbd493ec4, 0x3f18be95,
    0x3f78bf55, 0x3f67bf7f, 0x3edbbf35, 0xbe79bdc9, 0xbf4e3f0e, 0xbf803f75, 0xbf3e3f6d, 0xbe163ef1, 0x3f04be48, 0x3f71bf46,
    0x3d49bec4, 0xbf183e95, 0xbf783f55, 0xbf673f7f, 0x3eac0000, 0x3f5cbf22, 0x3f7dbf7b, 0x3f2cbf62, 0x3f3ebf6d, 0x3e16bef1,
    0xbf043e48, 0xbf713f46, 0xbedb3f35, 0x3e793dc9, 0x3f4ebf0e, 0x3f80bf75, 0x3f80bf6d, 0x3f4ebf75, 0x3e79bf0e, 0xbedb3dc9,
    0xbf713f80, 0xbf043f46, 0x3e163e48, 0x3f3ebef1, 0x3f2cbec4, 0x3f7dbf62, 0x3f5cbf7b, 0x3eacbf22, 0xbf673f35, 0xbf783f7f,
    0xbf183f55, 0x3d493e95, 0x3f04bf35, 0x3d49be95, 0xbedb3e48, 0xbf4e3f22, 0xbf7d3f6d, 0xbf713f7f, 0xbf2c3f55, 0xbe793ef1,
    0xbf783f80, 0xbf3e3f62, 0xbeac3f0e, 0x3e163dc9, 0x3f18bec4, 0x3f67bf46, 0x3f80bf7b, 0x3f5cbf75, 0xbf5c3f35, 0xbf803f75,
    0xbf673f7b, 0xbf183f46, 0xbe163ec4, 0x3eacbdc9, 0x3f3ebf0e, 0x3f78bf62, 0x3e790000, 0x3f2cbef1, 0x3f71bf55, 0x3f7dbf7f,
    0x3f4ebf6d, 0x3edbbf22, 0xbd49be48, 0xbf043e95, 0xbe163ec4, 0x3eacbdc9, 0x3f3ebf0e, 0x3f78bf62, 0xbf5c3f35, 0xbf803f75,
    0xbf673f7b, 0xbf183f46, 0x3f4ebf6d, 0x3edbbf22, 0xbd49be48, 0xbf043e95, 0x3e790000, 0x3f2cbef1, 0x3f71bf55, 0x3f7dbf7f,
    0x3f7dbf6d, 0x3f71bf7f, 0x3f2cbf55, 0x3e79bef1, 0xbf043f35, 0xbd493e95, 0x3edbbe48, 0x3f4ebf22, 0xbf183ec4, 0xbf673f46,
    0xbf803f7b, 0xbf5c3f75, 0x3f78bf80, 0x3f3ebf62, 0x3eacbf0e, 0xbe16bdc9, 0xbe160000, 0xbedb3e95, 0xbf2c3f0e, 0xbf5c3f46,
    0xbf783f6d, 0xbf803f7f, 0xbf713f7b, 0xbf4e3f62, 0xbf183f35, 0xbeac3ef1, 0xbd493e48, 0x3e79bdc9, 0x3f04bec4, 0x3f3ebf22,
    0x3f67bf55, 0x3f7dbf75, 0xbf7d3f80, 0xbf673f75, 0xbf3e3f55, 0xbf043f22, 0xbe793ec4, 0x3d493dc9, 0x3eacbe48, 0x3f18bef1,
    0x3f4ebf35, 0x3f71bf62, 0x3f80bf7b, 0x3f78bf7f, 0x3f5cbf6d, 0x3f2cbf46, 0x3edbbf0e, 0x3e16be95, 0xbe793ec4, 0x3d493dc9,
    0x3eacbe48, 0x3f18bef1, 0xbf7d3f80, 0xbf673f75, 0xbf3e3f55, 0xbf043f22, 0x3f5cbf6d, 0x3f2cbf46, 0x3edbbf0e, 0x3e16be95,
    0x3f4ebf35, 0x3f71bf62, 0x3f80bf7b, 0x3f78bf7f, 0x3f78bf6d, 0x3f80bf7f, 0x3f71bf7b, 0x3f4ebf62, 0x3e160000, 0x3edbbe95,
    0x3f2cbf0e, 0x3f5cbf46, 0xbf043ec4, 0xbf3e3f22, 0xbf673f55, 0xbf7d3f75, 0x3f18bf35, 0x3eacbef1, 0x3d49be48, 0xbe793dc9,
    0x3f3ebf35, 0x3f4ebf46, 0x3f5cbf55, 0x3f67bf62, 0x3f71bf6d, 0x3f78bf75, 0x3f7dbf7b, 0x3f80bf7f, 0x3d490000, 0x3e16bdc9,
    0x3e79be48, 0x3eacbe95, 0x3edbbec4, 0x3f04bef1, 0x3f18bf0e, 0x3f2cbf22, 0xbf2c3f35, 0xbf183f22, 0xbf043f0e, 0xbedb3ef1,
    0xbeac3ec4, 0xbe793e95, 0xbe163e48, 0xbd493dc9, 0xbf803f80, 0xbf7d3f7f, 0xbf783f7b, 0xbf713f75, 0xbf673f6d, 0xbf5c3f62,
    0xbf4e3f55, 0xbf3e3f46, 0x3eacbec4, 0x3e79be95, 0x3e16be48, 0x3d49bdc9, 0x3f2cbf35, 0x3f18bf22, 0x3f04bf0e, 0x3edbbef1,
    0x3f67bf6d, 0x3f5cbf62, 0x3f4ebf55, 0x3f3ebf46, 0x3f80bf80, 0x3f7dbf7f, 0x3f78bf7b, 0x3f71bf75, 0x3f71bf6d, 0x3f78bf75,
    0x3f7dbf7b, 0x3f80bf7f, 0x3f3ebf35, 0x3f4ebf46, 0x3f5cbf55, 0x3f67bf62, 0x3edbbec4, 0x3f04bef1, 0x3f18bf0e, 0x3f2cbf22,
    0x3d490000, 0x3e16bdc9, 0x3e79be48, 0x3eacbe95,
};
__device__ const __align__(128) uint32_t c_ga[1536] = {
    0x00003c80, 0x3bc43c6d, 0x00003c80, 0xbbc4bc6d, 0x00003c80, 0x3c6d3bc4, 0x00003c80, 0xbc6dbbc4, 0x00003c80, 0x3c6dbbc4,
    0x00003c80, 0xbc6d3bc4, 0x00003c80, 0x3bc4bc6d, 0x00003c80, 0xbbc43c6d, 0x3a493c80, 0x3bdb3c67, 0x3bdb3c67, 0xbc3ebc2c,
    0x3b163c7d, 0x3c783b79, 0x3c043c5c, 0xbc7d3b16, 0x3b793c78, 0x3c4ebc18, 0x3c183c4e, 0xbc043c5c, 0x3bac3c71, 0x3a49bc80,
    0x3c2c3c3e, 0x3bac3c71, 0x3ac93c7f, 0x3bf13c62, 0x3c463c22, 0xbc75bb95, 0x3b953c75, 0x3c7f3ac9, 0x3c623bf1, 0xbc463c22,
    0x3bf13c62, 0x3c22bc46, 0x3c753b95, 0x3ac93c7f, 0x3c223c46, 0xbb95bc75, 0x3c7f3ac9, 0x3c623bf1, 0x3b163c7d, 0x3c043c5c,
    0x3c783b79, 0xbc7d3b16, 0x3bdb3c67, 0x3c80ba49, 0x3c80ba49, 0xbbac3c71, 0x3c2c3c3e, 0x3bdbbc67, 0x3c71bbac, 0x3c2c3c3e,
    0x3c5c3c04, 0xbc18bc4e, 0x3c4ebc18, 0x3c78bb79, 0x3b483c7b, 0x3c0e3c55, 0x3c7bbb48, 0xbc553c0e, 0x3c0e3c55, 0x3c7bbb48,
    0x3c55bc0e, 0x3b483c7b, 0x3c553c0e, 0x3b48bc7b, 0x3c0ebc55, 0x3c7b3b48, 0x3c7b3b48, 0xbc55bc0e, 0x3b48bc7b, 0x3c0ebc55,
    0x3b793c78, 0x3c183c4e, 0x3c4ebc18, 0xbc043c5c, 0x3c2c3c3e, 0x3c71bbac, 0x3bdbbc67, 0x3c2c3c3e, 0x3c713bac, 0xba49bc80,
    0xba49bc80, 0x3c67bbdb, 0x3c7dbb16, 0xbc78bb79, 0xbc04bc5c, 0xbb16bc7d, 0x3b953c75, 0x3c223c46, 0x3bf1bc62, 0xbac93c7f,
    0x3c463c22, 0x3c62bbf1, 0xbac9bc7f, 0x3c753b95, 0x3c7f3ac9, 0xbb95bc75, 0xbc22bc46, 0x3bf1bc62, 0x3c62bbf1, 0xbc7f3ac9,
    0xbc75bb95, 0xbc46bc22, 0x3bac3c71, 0x3c2c3c3e, 0x3a49bc80, 0x3bac3c71, 0x3c5c3c04, 0x3c4ebc18, 0xbc18bc4e, 0x3c78bb79,
    0x3c7dbb16, 0xbc04bc5c, 0xbc78bb79, 0xbb16bc7d, 0x3c2cbc3e, 0xbc673bdb, 0xbc673bdb, 0xbc803a49, 0x00003c80, 0x3bc43c6d,
    0x00003c80, 0xbbc4bc6d, 0x00003c80, 0x3c6d3bc4, 0x00003c80, 0xbc6dbbc4, 0x00003c80, 0x3c6dbbc4, 0x00003c80, 0xbc6d3bc4,
    0x00003c80, 0x3bc4bc6d, 0x00003c80, 0xbbc43c6d, 0x3c3e3c2c, 0x3c713bac, 0x3c713bac, 0xbc803a49, 0x3c4e3c18, 0x3c5cbc04,
    0x3c783b79, 0xbc183c4e, 0x3c5c3c04, 0x3b16bc7d, 0x3c7d3b16, 0x3b793c78, 0x3c673bdb, 0xbc2cbc3e, 0x3c803a49, 0x3c673bdb,
    0x3c7fbac9, 0x3c62bbf1, 0x3c22bc46, 0xbb953c75, 0x3c75bb95, 0x3ac9bc7f, 0x3bf1bc62, 0x3c223c46, 0x3c62bbf1, 0xbc46bc22,
    0x3b95bc75, 0x3c7fbac9, 0x3c46bc22, 0xbc753b95, 0x3ac9bc7f, 0x3bf1bc62, 0x3c18bc4e, 0x3b79bc78, 0xbc04bc5c, 0x3c4e3c18,
    0x3bacbc71, 0xbc3ebc2c, 0xbc3ebc2c, 0x3c67bbdb, 0x3a49bc80, 0xbc713bac, 0xbc67bbdb, 0x3a49bc80, 0xbb79bc78, 0xbb163c7d,
    0xbc7dbb16, 0xbc5cbc04, 0xbb48bc7b, 0xbc0ebc55, 0xbc7b3b48, 0x3c55bc0e, 0xbc0ebc55, 0xbc7b3b48, 0xbc553c0e, 0xbb48bc7b,
    0xbc55bc0e, 0xbb483c7b, 0xbc0e3c55, 0xbc7bbb48, 0xbc7bbb48, 0x3c553c0e, 0xbb483c7b, 0xbc0e3c55, 0xbc5cbc04, 0xbc7dbb16,
    0xbb163c7d, 0xbb79bc78, 0xbc80ba49, 0xbbdb3c67, 0x3bac3c71, 0xbc80ba49, 0xbc673bdb, 0x3c3e3c2c, 0x3c3e3c2c, 0xbbac3c71,
    0xbc183c4e, 0x3c5cbc04, 0x3c783b79, 0x3c4e3c18, 0xbc753b95, 0xbc463c22, 0x3c623bf1, 0xbc7fbac9, 0xbc223c46, 0x3bf13c62,
    0x3c7fbac9, 0xbb953c75, 0xbac93c7f, 0x3c75bb95, 0x3c46bc22, 0x3c623bf1, 0x3bf13c62, 0xbac9bc7f, 0x3b95bc75, 0x3c22bc46,
    0xbbdb3c67, 0xba493c80, 0x3c3ebc2c, 0xbbdb3c67, 0x3b793c78, 0x3c7d3b16, 0x3b16bc7d, 0x3c5c3c04, 0x3c4e3c18, 0x3b79bc78,
    0xbc04bc5c, 0x3c18bc4e, 0x3c80ba49, 0xbc71bbac, 0xbc71bbac, 0xbc3ebc2c, 0x00003c80, 0x3bc43c6d, 0x00003c80, 0xbbc4bc6d,
    0x00003c80, 0x3c6d3bc4, 0x00003c80, 0xbc6dbbc4, 0x00003c80, 0x3c6dbbc4, 0x00003c80, 0xbc6d3bc4, 0x00003c80, 0x3bc4bc6d,
    0x00003c80, 0xbbc43c6d, 0x3c80ba49, 0x3c67bbdb, 0x3c67bbdb, 0xbc2c3c3e, 0x3c7dbb16, 0x3b79bc78, 0x3c5cbc04, 0x3b163c7d,
    0x3c78bb79, 0xbc18bc4e, 0x3c4ebc18, 0x3c5c3c04, 0x3c71bbac, 0xbc80ba49, 0x3c3ebc2c, 0x3c71bbac, 0xbac9bc7f, 0xbbf1bc62,
    0xbc46bc22, 0x3c753b95, 0xbb95bc75, 0xbc7fbac9, 0xbc62bbf1, 0x3c46bc22, 0xbbf1bc62, 0xbc223c46, 0xbc75bb95, 0xbac9bc7f,
    0xbc22bc46, 0x3b953c75, 0xbc7fbac9, 0xbc62bbf1, 0xbc7d3b16, 0xbc5c3c04, 0xbb793c78, 0xbb16bc7d, 0xbc673bdb, 0x3a493c80,
    0x3a493c80, 0xbc71bbac, 0xbc3e3c2c, 0x3c673bdb, 0x3bac3c71, 0xbc3e3c2c, 0xbc043c5c, 0x3c4ebc18, 0x3c183c4e, 0x3b793c78,
    0x3b483c7b, 0x3c0e3c55, 0x3c7bbb48, 0xbc553c0e, 0x3c0e3c55, 0x3c7bbb48, 0x3c55bc0e, 0x3b483c7b, 0x3c553c0e, 0x3b48bc7b,
    0x3c0ebc55, 0x3c7b3b48, 0x3c7b3b48, 0xbc55bc0e, 0x3b48bc7b, 0x3c0ebc55, 0x3c78bb79, 0x3c4ebc18, 0xbc18bc4e, 0x3c5c3c04,
    0x3c3ebc2c, 0xbbacbc71, 0xbc67bbdb, 0x3c3ebc2c, 0x3bacbc71, 0xbc803a49, 0xbc803a49, 0xbbdbbc67, 0xbb16bc7d, 0xbb793c78,
    0xbc5c3c04, 0xbc7d3b16, 0xbb95bc75, 0xbc22bc46, 0xbbf13c62, 0x3ac9bc7f, 0xbc46bc22, 0xbc623bf1, 0x3ac93c7f, 0xbc75bb95,
    0xbc7fbac9, 0x3b953c75, 0x3c223c46, 0xbbf13c62, 0xbc623bf1, 0x3c7fbac9, 0x3c753b95, 0x3c463c22, 0xbc713bac, 0xbc3e3c2c,
    0x3c803a49, 0xbc713bac, 0xbc043c5c, 0x3c183c4e, 0x3c4ebc18, 0x3b793c78, 0x3b163c7d, 0x3c5cbc04, 0x3b79bc78, 0x3c7dbb16,
    0x3c3e3c2c, 0xbbdbbc67, 0xbbdbbc67, 0xba49bc80, 0x00003c80, 0x3bc43c6d, 0x00003c80, 0xbbc4bc6d, 0x00003c80, 0x3c6d3bc4,
    0x00003c80, 0xbc6dbbc4, 0x00003c80, 0x3c6dbbc4, 0x00003c80, 0xbc6d3bc4, 0x00003c80, 0x3bc4bc6d, 0x00003c80, 0xbbc43c6d,
    0x3c2cbc3e, 0x3bacbc71, 0x3bacbc71, 0x3a493c80, 0x3c18bc4e, 0xbc04bc5c, 0x3b79bc78, 0x3c4e3c18, 0x3c04bc5c, 0xbc7dbb16,
    0x3b16bc7d, 0x3c78bb79, 0x3bdbbc67, 0xbc3e3c2c, 0x3a49bc80, 0x3bdbbc67, 0xbc7f3ac9, 0xbc623bf1, 0xbc223c46, 0x3b95bc75,
    0xbc753b95, 0xbac93c7f, 0xbbf13c62, 0xbc22bc46, 0xbc623bf1, 0x3c463c22, 0xbb953c75, 0xbc7f3ac9, 0xbc463c22, 0x3c75bb95,
    0xbac93c7f, 0xbbf13c62, 0x3c4e3c18, 0x3c783b79, 0x3c5cbc04, 0xbc183c4e, 0x3c713bac, 0x3c2cbc3e, 0x3c2cbc3e, 0x3bdb3c67,
    0x3c803a49, 0xbbacbc71, 0x3bdbbc67, 0x3c803a49, 0x3c78bb79, 0xbc7dbb16, 0x3b16bc7d, 0x3c04bc5c, 0xbb48bc7b, 0xbc0ebc55,
    0xbc7b3b48, 0x3c55bc0e, 0xbc0ebc55, 0xbc7b3b48, 0xbc553c0e, 0xbb48bc7b, 0xbc55bc0e, 0xbb483c7b, 0xbc0e3c55, 0xbc7bbb48,
    0xbc7bbb48, 0x3c553c0e, 0xbb483c7b, 0xbc0e3c55, 0xbc043c5c, 0xbb163c7d, 0x3c7d3b16, 0xbc783b79, 0xba493c80, 0x3c673bdb,
    0x3c71bbac, 0xba493c80, 0x3bdb3c67, 0x3c2cbc3e, 0x3c2cbc3e, 0x3c713bac, 0x3c4e3c18, 0xbc04bc5c, 0x3b79bc78, 0x3c18bc4e,
    0x3c75bb95, 0x3c46bc22, 0xbc62bbf1, 0x3c7f3ac9, 0x3c22bc46, 0xbbf1bc62, 0xbc7f3ac9, 0x3b95bc75, 0x3ac9bc7f, 0xbc753b95,
    0xbc463c22, 0xbc62bbf1, 0xbbf1bc62, 0x3ac93c7f, 0xbb953c75, 0xbc223c46, 0xbc67bbdb, 0xbc80ba49, 0x3c2c3c3e, 0xbc67bbdb,
    0xbc783b79, 0xbb163c7d, 0x3c7d3b16, 0xbc043c5c, 0xbc183c4e, 0x3c783b79, 0x3c5cbc04, 0x3c4e3c18, 0x3a493c80, 0x3bacbc71,
    0x3bacbc71, 0x3c2cbc3e, 0x3c353c35, 0x3c6d3bc4, 0x3c353c35, 0xbc6dbbc4, 0x3c35bc35, 0xbbc4bc6d, 0x3c35bc35, 0x3bc43c6d,
    0xbc35bc35, 0xbbc43c6d, 0xbc35bc35, 0x3bc4bc6d, 0xbc353c35, 0x3c6dbbc4, 0xbc353c35, 0xbc6d3bc4, 0x3c3e3c2c, 0x3c713bac,
    0x3c713bac, 0xbc803a49, 0x3c18bc4e, 0xbc04bc5c, 0x3b79bc78, 0x3c4e3c18, 0xbc5cbc04, 0xbb163c7d, 0xbc7dbb16, 0xbb79bc78,
    0xbbdb3c67, 0x3c3ebc2c, 0xba493c80, 0xbbdb3c67, 0x3c463c22, 0x3c753b95, 0x3c7fbac9, 0xbc623bf1, 0x3bf1bc62, 0xbc22bc46,
    0xbb95bc75, 0x3c7f3ac9, 0xbc75bb95, 0x3ac93c7f, 0xbc623bf1, 0xbc46bc22, 0xbac93c7f, 0x3bf1bc62, 0x3c223c46, 0x3b953c75,
    0x3c4e3c18, 0x3c783b79, 0x3c5cbc04, 0xbc183c4e, 0x3bacbc71, 0xbc3ebc2c, 0xbc3ebc2c, 0x3c67bbdb, 0xbc80ba49, 0x3bac3c71,
    0xbbdb3c67, 0xbc80ba49, 0x3b793c78, 0x3b16bc7d, 0x3c7d3b16, 0x3c5c3c04, 0x3c553c0e, 0x3c7b3b48, 0x3c0ebc55, 0xbb483c7b,
    0x3b48bc7b, 0xbc55bc0e, 0xbc7bbb48, 0x3c0ebc55, 0xbc7b3b48, 0x3c0e3c55, 0x3b483c7b, 0xbc553c0e, 0x3c0e3c55, 0xbb48bc7b,
    0x3c55bc0e, 0x3c7bbb48, 0x3c5c3c04, 0x3c7d3b16, 0x3b16bc7d, 0x3b793c78, 0x3a49bc80, 0xbc67bbdb, 0xbc713bac, 0x3a49bc80,
    0xbc673bdb, 0x3c3e3c2c, 0x3c3e3c2c, 0xbbac3c71, 0x3c4e3c18, 0xbc04bc5c, 0x3b79bc78, 0x3c18bc4e, 0x3c623bf1, 0x3c7f3ac9,
    0xbb95bc75, 0x3c223c46, 0xbac9bc7f, 0xbc75bb95, 0xbc223c46, 0xbbf1bc62, 0xbc463c22, 0x3c623bf1, 0x3c7f3ac9, 0x3b953c75,
    0x3c753b95, 0xbc46bc22, 0xbbf1bc62, 0xbac9bc7f, 0x3c673bdb, 0x3c803a49, 0xbc2cbc3e, 0x3c673bdb, 0xbb79bc78, 0xbc7dbb16,
    0xbb163c7d, 0xbc5cbc04, 0xbc183c4e, 0x3c783b79, 0x3c5cbc04, 0x3c4e3c18, 0x3c80ba49, 0xbc71bbac, 0xbc71bbac, 0xbc3ebc2c,
    0x3c353c35, 0x3c6d3bc4, 0x3c353c35, 0xbc6dbbc4, 0x3c35bc35, 0xbbc4bc6d, 0x3c35bc35, 0x3bc43c6d, 0xbc35bc35, 0xbbc43c6d,
    0xbc35bc35, 0x3bc4bc6d, 0xbc353c35, 0x3c6dbbc4, 0xbc353c35, 0xbc6d3bc4, 0x3c80ba49, 0x3c67bbdb, 0x3c67bbdb, 0xbc2c3c3e,
    0xbb16bc7d, 0xbc78bb79, 0xbc04bc5c, 0x3c7dbb16, 0xbc783b79, 0x3c183c4e, 0xbc4e3c18, 0xbc5cbc04, 0x3bac3c71, 0x3a49bc80,
    0x3c2c3c3e, 0x3bac3c71, 0x3c22bc46, 0x3b95bc75, 0xbac9bc7f, 0x3bf13c62, 0xbc62bbf1, 0xbc463c22, 0xbc753b95, 0x3ac9bc7f,
    0xbb953c75, 0x3c7fbac9, 0x3bf13c62, 0xbc223c46, 0x3c7f3ac9, 0xbc62bbf1, 0x3c46bc22, 0x3c75bb95, 0xbb16bc7d, 0xbc04bc5c,
    0xbc78bb79, 0x3c7dbb16, 0xbc673bdb, 0x3a493c80, 0x3a493c80, 0xbc71bbac, 0x3c2c3c3e, 0x3bdbbc67, 0x3c71bbac, 0x3c2c3c3e,
    0x3c04bc5c, 0xbc4e3c18, 0xbc18bc4e, 0xbb79bc78, 0xbc55bc0e, 0xbc7bbb48, 0xbc0e3c55, 0x3b48bc7b, 0xbb483c7b, 0x3c553c0e,
    0x3c7b3b48, 0xbc0e3c55, 0x3c7bbb48, 0xbc0ebc55, 0xbb48bc7b, 0x3c55bc0e, 0xbc0ebc55, 0x3b483c7b, 0xbc553c0e, 0xbc7b3b48,
    0xbc783b79, 0xbc4e3c18, 0x3c183c4e, 0xbc5cbc04, 0x3c2c3c3e, 0x3c71bbac, 0x3bdbbc67, 0x3c2c3c3e, 0x3bacbc71, 0xbc803a49,
    0xbc803a49, 0xbbdbbc67, 0xbc7d3b16, 0x3c783b79, 0x3c043c5c, 0x3b163c7d, 0xbbf13c62, 0xbac93c7f, 0x3c75bb95, 0xbc463c22,
    0x3c7fbac9, 0x3b95bc75, 0xbc46bc22, 0x3c62bbf1, 0xbc22bc46, 0xbbf13c62, 0xbac93c7f, 0xbc753b95, 0xbb953c75, 0x3c22bc46,
    0x3c62bbf1, 0x3c7fbac9, 0x3bac3c71, 0x3c2c3c3e, 0x3a49bc80, 0x3bac3c71, 0x3c04bc5c, 0xbc18bc4e, 0xbc4e3c18, 0xbb79bc78,
    0xbc7d3b16, 0x3c043c5c, 0x3c783b79, 0x3b163c7d, 0x3c3e3c2c, 0xbbdbbc67, 0xbbdbbc67, 0xba49bc80, 0x3c353c35, 0x3c6d3bc4,
    0x3c353c35, 0xbc6dbbc4, 0x3c35bc35, 0xbbc4bc6d, 0x3c35bc35, 0x3bc43c6d, 0xbc35bc35, 0xbbc43c6d, 0xbc35bc35, 0x3bc4bc6d,
    0xbc353c35, 0x3c6dbbc4, 0xbc353c35, 0xbc6d3bc4, 0x3c2cbc3e, 0x3bacbc71, 0x3bacbc71, 0x3a493c80, 0xbc4ebc18, 0xbc5c3c04,
    0xbc78bb79, 0x3c18bc4e, 0xbc043c5c, 0x3c7d3b16, 0xbb163c7d, 0xbc783b79, 0x3c673bdb, 0xbc2cbc3e, 0x3c803a49, 0x3c673bdb,
    0xbc46bc22, 0xbc75bb95, 0xbc7f3ac9, 0x3c62bbf1, 0xbbf13c62, 0x3c223c46, 0x3b953c75, 0xbc7fbac9, 0x3c753b95, 0xbac9bc7f,
    0x3c62bbf1, 0x3c463c22, 0x3ac9bc7f, 0xbbf13c62, 0xbc22bc46, 0xbb95bc75, 0xbc183c4e, 0xbb793c78, 0x3c043c5c, 0xbc4ebc18,
    0x3c713bac, 0x3c2cbc3e, 0x3c2cbc3e, 0x3bdb3c67, 0x3a49bc80, 0xbc713bac, 0xbc67bbdb, 0x3a49bc80, 0xbc783b79, 0x3c7d3b16,
    0xbb163c7d, 0xbc043c5c, 0x3c553c0e, 0x3c7b3b48, 0x3c0ebc55, 0xbb483c7b, 0x3b48bc7b, 0xbc55bc0e, 0xbc7bbb48, 0x3c0ebc55,
    0xbc7b3b48, 0x3c0e3c55, 0x3b483c7b, 0xbc553c0e, 0x3c0e3c55, 0xbb48bc7b, 0x3c55bc0e, 0x3c7bbb48, 0x3c04bc5c, 0x3b16bc7d,
    0xbc7dbb16, 0x3c78bb79, 0xbc80ba49, 0xbbdb3c67, 0x3bac3c71, 0xbc80ba49, 0x3bdb3c67, 0x3c2cbc3e, 0x3c2cbc3e, 0x3c713bac,
    0x3c18bc4e, 0xbc5c3c04, 0xbc78bb79, 0xbc4ebc18, 0xbc62bbf1, 0xbc7fbac9, 0x3b953c75, 0xbc22bc46, 0x3ac93c7f, 0x3c753b95,
    0x3c22bc46, 0x3bf13c62, 0x3c46bc22, 0xbc62bbf1, 0xbc7fbac9, 0xbb95bc75, 0xbc75bb95, 0x3c463c22, 0x3bf13c62, 0x3ac93c7f,
    0xbbdb3c67, 0xba493c80, 0x3c3ebc2c, 0xbbdb3c67, 0x3c78bb79, 0x3b16bc7d, 0xbc7dbb16, 0x3c04bc5c, 0xbc4ebc18, 0xbb793c78,
    0x3c043c5c, 0xbc183c4e, 0x3a493c80, 0x3bacbc71, 0x3bacbc71, 0x3c2cbc3e, 0x3c353c35, 0x3c6d3bc4, 0x3c353c35, 0xbc6dbbc4,
    0x3c35bc35, 0xbbc4bc6d, 0x3c35bc35, 0x3bc43c6d, 0xbc35bc35, 0xbbc43c6d, 0xbc35bc35, 0x3bc4bc6d, 0xbc353c35, 0x3c6dbbc4,
    0xbc353c35, 0xbc6d3bc4, 0xba49bc80, 0xbbdbbc67, 0xbbdbbc67, 0x3c3e3c2c, 0xbc7d3b16, 0xbb793c78, 0xbc5c3c04, 0xbb16bc7d,
    0x3b793c78, 0x3c4ebc18, 0x3c183c4e, 0xbc043c5c, 0x3c71bbac, 0xbc80ba49, 0x3c3ebc2c, 0x3c71bbac, 0xbc223c46, 0xbb953c75,
    0x3ac93c7f, 0xbbf1bc62, 0x3c623bf1, 0x3c46bc22, 0x3c75bb95, 0xbac93c7f, 0x3b95bc75, 0xbc7f3ac9, 0xbbf1bc62, 0x3c22bc46,
    0xbc7fbac9, 0x3c623bf1, 0xbc463c22, 0xbc753b95, 0x3c7dbb16, 0x3c5cbc04, 0x3b79bc78, 0x3b163c7d, 0xbbdbbc67, 0xbc803a49,
    0xbc803a49, 0x3bacbc71, 0xbc3e3c2c, 0x3c673bdb, 0x3bac3c71, 0xbc3e3c2c, 0x3c5c3c04, 0xbc18bc4e, 0x3c4ebc18, 0x3c78bb79,
    0xbc55bc0e, 0xbc7bbb48, 0xbc0e3c55, 0x3b48bc7b, 0xbb483c7b, 0x3c553c0e, 0x3c7b3b48, 0xbc0e3c55, 0x3c7bbb48, 0xbc0ebc55,
    0xbb48bc7b, 0x3c55bc0e, 0xbc0ebc55, 0x3b483c7b, 0xbc553c0e, 0xbc7b3b48, 0x3b793c78, 0x3c183c4e, 0x3c4ebc18, 0xbc043c5c,
    0x3c3ebc2c, 0xbbacbc71, 0xbc67bbdb, 0x3c3ebc2c, 0xbc71bbac, 0x3a493c80, 0x3a493c80, 0xbc673bdb, 0x3b163c7d, 0x3b79bc78,
    0x3c5cbc04, 0x3c7dbb16, 0x3bf1bc62, 0x3ac9bc7f, 0xbc753b95, 0x3c46bc22, 0xbc7f3ac9, 0xbb953c75, 0x3c463c22, 0xbc623bf1,
    0x3c223c46, 0x3bf1bc62, 0x3ac9bc7f, 0x3c75bb95, 0x3b95bc75, 0xbc223c46, 0xbc623bf1, 0xbc7f3ac9, 0xbc713bac, 0xbc3e3c2c,
    0x3c803a49, 0xbc713bac, 0x3c5c3c04, 0x3c4ebc18, 0xbc18bc4e, 0x3c78bb79, 0xbb16bc7d, 0xbc5c3c04, 0xbb793c78, 0xbc7d3b16,
    0xbc2c3c3e, 0x3c67bbdb, 0x3c67bbdb, 0x3c80ba49, 0x3c800000, 0x3c6dbbc4, 0x3c800000, 0xbc6d3bc4, 0xbc800000, 0xbbc43c6d,
    0xbc800000, 0x3bc4bc6d, 0x3c800000, 0xbbc4bc6d, 0x3c800000, 0x3bc43c6d, 0xbc800000, 0x3c6d3bc4, 0xbc800000, 0xbc6dbbc4,
    0x3c80ba49, 0x3c67bbdb, 0x3c67bbdb, 0xbc2c3c3e, 0xbc7d3b16, 0xbb793c78, 0xbc5c3c04, 0xbb16bc7d, 0x3c78bb79, 0xbc18bc4e,
    0x3c4ebc18, 0x3c5c3c04, 0xbc713bac, 0x3c803a49, 0xbc3e3c2c, 0xbc713bac, 0x3c7fbac9, 0x3c62bbf1, 0x3c22bc46, 0xbb953c75,
    0xbc753b95, 0xbac93c7f, 0xbbf13c62, 0xbc22bc46, 0x3c62bbf1, 0xbc46bc22, 0x3b95bc75, 0x3c7fbac9, 0xbc463c22, 0x3c75bb95,
    0xbac93c7f, 0xbbf13c62, 0x3c7dbb16, 0x3c5cbc04, 0x3b79bc78, 0x3b163c7d, 0xbc673bdb, 0x3a493c80, 0x3a493c80, 0xbc71bbac,
    0x3c3ebc2c, 0xbc67bbdb, 0xbbacbc71, 0x3c3ebc2c, 0xbc043c5c, 0x3c4ebc18, 0x3c183c4e, 0x3b793c78, 0x3c7bbb48, 0x3c55bc0e,
    0xbb48bc7b, 0x3c0e3c55, 0xbc553c0e, 0x3b483c7b, 0x3c0e3c55, 0xbc7b3b48, 0x3c0ebc55, 0xbc7bbb48, 0xbc55bc0e, 0x3b48bc7b,
    0xbb483c7b, 0x3c0ebc55, 0x3c7b3b48, 0x3c553c0e, 0x3c78bb79, 0x3c4ebc18, 0xbc18bc4e, 0x3c5c3c04, 0xbc3e3c2c, 0x3bac3c71,
    0x3c673bdb, 0xbc3e3c2c, 0x3bacbc71, 0xbc803a49, 0xbc803a49, 0xbbdbbc67, 0x3b163c7d, 0x3b79bc78, 0x3c5cbc04, 0x3c7dbb16,
    0x3c75bb95, 0x3c46bc22, 0xbc62bbf1, 0x3c7f3ac9, 0xbc223c46, 0x3bf13c62, 0x3c7fbac9, 0xbb953c75, 0x3ac9bc7f, 0xbc753b95,
    0xbc463c22, 0xbc62bbf1, 0x3bf13c62, 0xbac9bc7f, 0x3b95bc75, 0x3c22bc46, 0x3c71bbac, 0x3c3ebc2c, 0xbc80ba49, 0x3c71bbac,
    0xbc043c5c, 0x3c183c4e, 0x3c4ebc18, 0x3b793c78, 0xbb16bc7d, 0xbc5c3c04, 0xbb793c78, 0xbc7d3b16, 0x3c3e3c2c, 0xbbdbbc67,
    0xbbdbbc67, 0xba49bc80, 0x3c800000, 0x3c6dbbc4, 0x3c800000, 0xbc6d3bc4, 0xbc800000, 0xbbc43c6d, 0xbc800000, 0x3bc4bc6d,
    0x3c800000, 0xbbc4bc6d, 0x3c800000, 0x3bc43c6d, 0xbc800000, 0x3c6d3bc4, 0xbc800000, 0xbc6dbbc4, 0x3c2cbc3e, 0x3bacbc71,
    0x3bacbc71, 0x3a493c80, 0xbc183c4e, 0x3c043c5c, 0xbb793c78, 0xbc4ebc18, 0x3c04bc5c, 0xbc7dbb16, 0x3b16bc7d, 0x3c78bb79,
    0xbbdb3c67, 0x3c3ebc2c, 0xba493c80, 0xbbdb3c67, 0xbac9bc7f, 0xbbf1bc62, 0xbc46bc22, 0x3c753b95, 0x3b953c75, 0x3c7f3ac9,
    0x3c623bf1, 0xbc463c22, 0xbbf1bc62, 0xbc223c46, 0xbc75bb95, 0xbac9bc7f, 0x3c223c46, 0xbb95bc75, 0x3c7f3ac9, 0x3c623bf1,
    0xbc4ebc18, 0xbc78bb79, 0xbc5c3c04, 0x3c18bc4e, 0x3c713bac, 0x3c2cbc3e, 0x3c2cbc3e, 0x3bdb3c67, 0xbc80ba49, 0x3bac3c71,
    0xbbdb3c67, 0xbc80ba49, 0x3c78bb79, 0xbc7dbb16, 0x3b16bc7d, 0x3c04bc5c, 0xbc7b3b48, 0xbc553c0e, 0x3b483c7b, 0xbc0ebc55,
    0x3c55bc0e, 0xbb48bc7b, 0xbc0ebc55, 0x3c7bbb48, 0xbc0e3c55, 0x3c7b3b48, 0x3c553c0e, 0xbb483c7b, 0x3b48bc7b, 0xbc0e3c55,
    0xbc7bbb48, 0xbc55bc0e, 0xbc043c5c, 0xbb163c7d, 0x3c7d3b16, 0xbc783b79, 0x3a49bc80, 0xbc67bbdb, 0xbc713bac, 0x3a49bc80,
    0x3bdb3c67, 0x3c2cbc3e, 0x3c2cbc3e, 0x3c713bac, 0xbc4ebc18, 0x3c043c5c, 0xbb793c78, 0xbc183c4e, 0x3b953c75, 0x3c223c46,
    0x3bf1bc62, 0xbac93c7f, 0xbc46bc22, 0xbc623bf1, 0x3ac93c7f, 0xbc75bb95, 0x3c7f3ac9, 0xbb95bc75, 0xbc22bc46, 0x3bf1bc62,
    0xbc623bf1, 0x3c7fbac9, 0x3c753b95, 0x3c463c22, 0x3c673bdb, 0x3c803a49, 0xbc2cbc3e, 0x3c673bdb, 0xbc783b79, 0xbb163c7d,
    0x3c7d3b16, 0xbc043c5c, 0x3c18bc4e, 0xbc78bb79, 0xbc5c3c04, 0xbc4ebc18, 0x3a493c80, 0x3bacbc71, 0x3bacbc71, 0x3c2cbc3e,
    0x3c800000, 0x3c6dbbc4, 0x3c800000, 0xbc6d3bc4, 0xbc800000, 0xbbc43c6d, 0xbc800000, 0x3bc4bc6d, 0x3c800000, 0xbbc4bc6d,
    0x3c800000, 0x3bc43c6d, 0xbc800000, 0x3c6d3bc4, 0xbc800000, 0xbc6dbbc4, 0xba49bc80, 0xbbdbbc67, 0xbbdbbc67, 0x3c3e3c2c,
    0x3b163c7d, 0x3c783b79, 0x3c043c5c, 0xbc7d3b16, 0xbb79bc78, 0xbc4e3c18, 0xbc18bc4e, 0x3c04bc5c, 0x3bac3c71, 0x3a49bc80,
    0x3c2c3c3e, 0x3bac3c71, 0xbc7f3ac9, 0xbc623bf1, 0xbc223c46, 0x3b95bc75, 0x3c75bb95, 0x3ac9bc7f, 0x3bf1bc62, 0x3c223c46,
    0xbc623bf1, 0x3c463c22, 0xbb953c75, 0xbc7f3ac9, 0x3c46bc22, 0xbc753b95, 0x3ac9bc7f, 0x3bf1bc62, 0x3b163c7d, 0x3c043c5c,
    0x3c783b79, 0xbc7d3b16, 0xbbdbbc67, 0xbc803a49, 0xbc803a49, 0x3bacbc71, 0x3c2c3c3e, 0x3bdbbc67, 0x3c71bbac, 0x3c2c3c3e,
    0xbc5cbc04, 0x3c183c4e, 0xbc4e3c18, 0xbc783b79, 0x3c7bbb48, 0x3c55bc0e, 0xbb48bc7b, 0x3c0e3c55, 0xbc553c0e, 0x3b483c7b,
    0x3c0e3c55, 0xbc7b3b48, 0x3c0ebc55, 0xbc7bbb48, 0xbc55bc0e, 0x3b48bc7b, 0xbb483c7b, 0x3c0ebc55, 0x3c7b3b48, 0x3c553c0e,
    0xbb79bc78, 0xbc18bc4e, 0xbc4e3c18, 0x3c04bc5c, 0x3c2c3c3e, 0x3c71bbac, 0x3bdbbc67, 0x3c2c3c3e, 0xbc71bbac, 0x3a493c80,
    0x3a493c80, 0xbc673bdb, 0x3c7dbb16, 0xbc78bb79, 0xbc04bc5c, 0xbb16bc7d, 0xbc753b95, 0xbc463c22, 0x3c623bf1, 0xbc7fbac9,
    0x3c22bc46, 0xbbf1bc62, 0xbc7f3ac9, 0x3b95bc75, 0xbac93c7f, 0x3c75bb95, 0x3c46bc22, 0x3c623bf1, 0xbbf1bc62, 0x3ac93c7f,
    0xbb953c75, 0xbc223c46, 0x3bac3c71, 0x3c2c3c3e, 0x3a49bc80, 0x3bac3c71, 0xbc5cbc04, 0xbc4e3c18, 0x3c183c4e, 0xbc783b79,
    0x3c7dbb16, 0xbc04bc5c, 0xbc78bb79, 0xbb16bc7d, 0xbc2c3c3e, 0x3c67bbdb, 0x3c67bbdb, 0x3c80ba49, 0x3c800000, 0x3c6dbbc4,
    0x3c800000, 0xbc6d3bc4, 0xbc800000, 0xbbc43c6d, 0xbc800000, 0x3bc4bc6d, 0x3c800000, 0xbbc4bc6d, 0x3c800000, 0x3bc43c6d,
    0xbc800000, 0x3c6d3bc4, 0xbc800000, 0xbc6dbbc4, 0xbc3ebc2c, 0xbc71bbac, 0xbc71bbac, 0x3c80ba49, 0x3c4e3c18, 0x3c5cbc04,
    0x3c783b79, 0xbc183c4e, 0xbc5cbc04, 0xbb163c7d, 0xbc7dbb16, 0xbb79bc78, 0x3c673bdb, 0xbc2cbc3e, 0x3c803a49, 0x3c673bdb,
    0x3ac93c7f, 0x3bf13c62, 0x3c463c22, 0xbc75bb95, 0xbb95bc75, 0xbc7fbac9, 0xbc62bbf1, 0x3c46bc22, 0x3bf13c62, 0x3c22bc46,
    0x3c753b95, 0x3ac93c7f, 0xbc22bc46, 0x3b953c75, 0xbc7fbac9, 0xbc62bbf1, 0x3c18bc4e, 0x3b79bc78, 0xbc04bc5c, 0x3c4e3c18,
    0xbbac3c71, 0x3c3e3c2c, 0x3c3e3c2c, 0xbc673bdb, 0x3a49bc80, 0xbc713bac, 0xbc67bbdb, 0x3a49bc80, 0x3b793c78, 0x3b16bc7d,
    0x3c7d3b16, 0x3c5c3c04, 0xbc7b3b48, 0xbc553c0e, 0x3b483c7b, 0xbc0ebc55, 0x3c55bc0e, 0xbb48bc7b, 0xbc0ebc55, 0x3c7bbb48,
    0xbc0e3c55, 0x3c7b3b48, 0x3c553c0e, 0xbb483c7b, 0x3b48bc7b, 0xbc0e3c55, 0xbc7bbb48, 0xbc55bc0e, 0x3c5c3c04, 0x3c7d3b16,
    0x3b16bc7d, 0x3b793c78, 0xbc80ba49, 0xbbdb3c67, 0x3bac3c71, 0xbc80ba49, 0x3c67bbdb, 0xbc3ebc2c, 0xbc3ebc2c, 0x3bacbc71,
    0xbc183c4e, 0x3c5cbc04, 0x3c783b79, 0x3c4e3c18, 0xbb95bc75, 0xbc22bc46, 0xbbf13c62, 0x3ac9bc7f, 0x3c463c22, 0x3c62bbf1,
    0xbac9bc7f, 0x3c753b95, 0xbc7fbac9, 0x3b953c75, 0x3c223c46, 0xbbf13c62, 0x3c62bbf1, 0xbc7f3ac9, 0xbc75bb95, 0xbc46bc22,
    0xbbdb3c67, 0xba493c80, 0x3c3ebc2c, 0xbbdb3c67, 0xbb79bc78, 0xbc7dbb16, 0xbb163c7d, 0xbc5cbc04, 0x3c4e3c18, 0x3b79bc78,
    0xbc04bc5c, 0x3c18bc4e, 0xbc803a49, 0x3c713bac, 0x3c713bac, 0x3c3e3c2c,
};

__device__ __forceinline__ void store_tile_64(const float (&d)[32], uint32_t base, int warp, int lane) {
  const int row = warp * 16 + (lane & 7) + ((lane >> 3) & 1) * 8;
  const uint32_t rb = base + row * 128;
#pragma unroll
  for (int j = 0; j < 8; j += 2) {
    const int jj = j + (lane >> 4);
    stsm4(rb + ((jj ^ (lane & 7)) << 4), pack2(d[4 * j], d[4 * j + 1]), pack2(d[4 * j + 2], d[4 * j + 3]),
          pack2(d[4 * j + 4], d[4 * j + 5]), pack2(d[4 * j + 6], d[4 * j + 7]));
  }
}

#define G_EPI 3
#define G_TK 3
#define W_Q 6
#define W2_PC 32
#define W2_PF 3
constexpr int X_LOC0 = 5;
constexpr int A_IN = 112 * 128;
constexpr int G_ST = 2 * NB1 * 64;
constexpr int K1_R = 131072, K1_BAR = K1_R + 98304, K1_SMEM = K1_BAR + 2048 + 1024;
constexpr int K1_T = K1_R + 65536, K1_TIN = 0, K1_Y0 = 3 * G_ST + 8192, G_KM = 16 - G_TK, G_S0 = 2 * G_KM;
__device__ int g_done[8 * 32];
struct Ptrs {
  int* done;
  float* ge;
  const uint32_t *img, *ga;
};

__host__ __device__ constexpr int g_depth(int s) { return s < 11 ? 3 : s < 18 ? 4 : s < 23 ? 5 : 6; }
__host__ __device__ constexpr int g_slot(int s) { return s < 3 ? s : g_depth(s) != g_depth(s - 1) ? g_depth(s - 1) : g_slot(s - g_depth(s)); }
__host__ __device__ constexpr int g_off(int id) { return id * G_ST + (id < 3 ? K1_R : 8192 - 3 * G_ST); }
struct Plan {
  uint32_t raw[32];
  uint32_t x[16];
  uint32_t grp[8];
  uint32_t last;
  uint32_t wpf;
  uint32_t g0;
  uint32_t tmask;
  uint64_t list[2];
};
struct K1Maps {
  Plan p;
  CUtensorMap x, we, wo, xs, y, w2e, w2o, w2s;
  int slot[32];
  int src[32];
  int dep[32];
};
__device__ __forceinline__ void poll_ge(const int* p, int target) {
  for (int it = 0; it < (1 << 20); it++) {
    int v;
    asm volatile("ld.acquire.gpu.global.s32 %0, [%1];" : "=r"(v) : "l"(p) : "memory");
    if (v >= target) break;
  }
}
__device__ __forceinline__ uint32_t place(int rank, uint32_t c) { return (c ^ (rank * 4 & ~(c >> 1))) << 14; }
__device__ __forceinline__ int x_unit(int cta, int u, uint32_t pl) {
  const int i = u * 128 + cta;
  const int pr = cta >= 128 ? 2 * cta - 96 + (u & 1) : i % 160, sl = cta >= 128 ? u >> 1 : i / 160, b = pr >= 84;
  return pr | sl << 8 | b << 11 | (cta >= 128 ? (u & 7) << 14 : place(cta & 1, pl & 15)) | 12 * (pr - 84 * b) << 20;
}
__device__ __forceinline__ int lds32(uint32_t a) {
  int v;
  asm volatile("ld.shared.b32 %0, [%1];" : "=r"(v) : "r"(a));
  return v;
}
__host__ __device__ constexpr uint64_t sched(const char* p) {
  uint64_t r = 0;
  for (int n = 0; p[n]; n++) r |= (uint64_t)(p[n] - '0' + 1) << (5 * n);
  return r;
}

__global__ void __cluster_dims__(2, 1, 1) __launch_bounds__(384, 1)
k1(const Ptrs gp_, const char* __restrict__ x1, const char* __restrict__ w1, const __grid_constant__ K1Maps m, const __nv_bfloat16* __restrict__ g,
   const __nv_bfloat16* __restrict__ wgt) {
  extern __shared__ __align__(1024) uint8_t smem_k1[];
  const uint32_t sb = s2u(smem_k1);
  const int tid = threadIdx.x, cta = blockIdx.x, rank = cta & 1;
  if (tid == 288) {
    const uint32_t bar = sb + K1_BAR + 256, dst = sb + (cta >= 128 ? 0 : place(rank, X_LOC0));
    const int pr = cta >= 128 ? 2 * cta - 96 : cta, b = pr >= 84;
    mbar_init(bar, 1);
    mbar_expect(bar, A_IN);
    for (int h = 0; h < 2; h++) tma_ld4<1>(dst + h * (A_IN / 2), &m.x, bar, 0, 96 * (pr - 84 * b) - 24 + h * 56, 0, b);
    for (int i = 1; i < 4; i++) mbar_init(bar + 8 * i, 1);
    fence_bar_init();
  }
  const uint32_t sF = sb + (cta >= 128 ? K1_T : rank * 65536), fbar = sb + K1_BAR + 1792;
  if (tid == 320) {
    mbar_init(fbar, 1);
    mbar_expect(fbar, 8192);
    asm volatile("cp.async.bulk.shared::cluster.global.mbarrier::complete_tx::bytes [%0], [%1], 8192, [%2];" ::"r"(sF), "l"(gp_.img + 1536), "r"(fbar) : "memory");
    fence_bar_init();
  }
  const int wg = __shfl_sync(0xffffffffu, tid >> 7, 0), t = tid & 127;
  const int warp = __shfl_sync(0xffffffffu, t >> 5, 0), lane = t & 31;
  const bool spare = cta >= 128;
  const int nx = spare ? 16 : 10;
  int bp, dc;
  {
    const int ci = cta >> 1;
    const int G = ci < 4 ? 0 : ci < 36 ? (ci - 4) & 7 : 1 + (ci - 36) % 7;
    const int li = ci < 4 ? 4 + ci : ci < 36 ? (ci - 4) >> 3 : 4 + (ci - 36) / 7;
    bp = 2 * G + (li >> 2), dc = li & 3;
  }
  const int bin = 2 * bp + rank;
  const uint32_t bb = sb + K1_BAR;
  const uint32_t rfull = bb, xfull = bb + 256, xfree = bb + 384, gfull = bb + 512, win = bb + 1800, win1 = bb + 1808;
  const uint32_t inf0 = bb + 784, se0 = inf0 + 16, pfree = se0 + 16, rempty = bb + 1024, xready = bb + 1280;
  const uint32_t gdone = bb + 1536, ine0 = gdone + 224, sf0 = ine0 + 16;
  const uint32_t xtab = bb + 896, ptab = bb + 2048 + 768;
  auto raw_load = [&](int j, uint32_t dst) {
    mbar_expect(rfull + 8 * j, 16384);
    tma_ld4<0>(dst, rank ? &m.we : &m.wo, rfull + 8 * j, dc * 64, rank - 1, (j & 3) * 4, (j >> 2) * 2);
  };
  auto x_half = [&](int u, int c, int h) {
    tma_ld4<1>(sb + (c & 0x3C000) + h * (A_IN / 2), &m.x, xfull + 8 * u, 0, (c >> 17 & ~7) - 24 + h * 56, c >> 8 & 7, c >> 11 & 1);
  };
  auto w_prefetch = [&](int q) {
    if (cta < 124) asm volatile("cp.async.bulk.prefetch.L2.global [%0], 4096;" ::"l"(w1 + (cta >> 2) * 131072 + (q * 4 + (cta & 3)) * 4096) : "memory");
  };
  uint32_t peer;
  asm("mapa.shared::cluster.u32 %0, %1, %2;" : "=r"(peer) : "r"(sb), "r"(rank ^ 1));
  if (wg == 2) {
    if (lane == 0) {
      if (warp == 0) {
        for (int i = 0; i < 4; i++) mbar_init(bb + 8 * i, 1);
        fence_bar_init();
        if (!spare)
          for (int j = 0; j < 4; j++) raw_load(j, sb + K1_R + j * 16384);
      } else if (warp == 2) {
#pragma unroll 1
        for (int q = 1; q <= m.p.wpf; q++) w_prefetch(q);
        prefetch_map(&m.xs);
      }
    }
    if (warp == 3) {
      const uint32_t v = reinterpret_cast<const uint32_t*>(&m.p)[32 + lane];
      asm volatile("st.shared.b32 [%0], %1;" ::"r"(ptab + 4 * lane), "r"(m.p.raw[lane]) : "memory");
      asm volatile("st.shared.b32 [%0], %1;" ::"r"(ptab + 128 + 4 * lane), "r"(v) : "memory");
      if (lane < 16) asm volatile("st.shared.b32 [%0], %1;" ::"r"(xtab + 4 * lane), "r"(x_unit(cta, lane, v)) : "memory");
    }
  } else {
    const int c = 4 * wg + warp;
    if (lane == 0 && c < 7) {
      const uint32_t b0 = bb + 256 * c, n = c < 4 ? 1 : c < 6 ? 4 : 8;
      if (c >= 2)
        for (int i = 0; i < 4; i++) mbar_init(b0 + 8 * i, n);
      for (int i = 4; i < 16; i++) mbar_init(b0 + 8 * i, n);
      if (c == 3) {
        mbar_init(win, 1 + 2 * W_Q);
        mbar_init(win1, 17 - 2 * W_Q);
        mbar_expect(win, 8192 * W_Q);
        mbar_expect(win1, 65536 - 8192 * W_Q);
        mbar_arrive(bb + 776);
      } else {
        for (int i = 16; i < 32; i++) mbar_init(b0 + 8 * i, n);
      }
      fence_bar_init();
    }
  }
  pdl_launch();
  __syncthreads();
  asm volatile("barrier.cluster.arrive.relaxed.aligned;" ::: "memory");
  if (wg == 2) {
    asm volatile("setmaxnreg.dec.sync.aligned.u32 40;");
    asm volatile("barrier.cluster.wait.aligned;" ::: "memory");
    if (lane == 0) {
      const int wpf = lds32(ptab + 228), g0 = lds32(ptab + 232), s0 = g0 * 4 / 5;
      const int nx0 = spare ? 2 * s0 : g0;
      if (warp == 0) {
        if (!spare) {
#pragma unroll 1
          for (int j = 4; j < 32; j++) {
            const uint32_t e = lds32(ptab + 4 * j);
            mbar_wait(bb + (e >> 5 & ~7), 0);
            raw_load(j, sb + place(rank, e & 15));
            if ((j & 3) == 0 && wpf && (j >> 2) + wpf < 8) w_prefetch((j >> 2) + wpf);
          }
#pragma unroll 1
          for (int s = 0; s < 32; s++) {
            if (s == 0 || s == 4 * s0) {
              poll_ge(&gp_.done[(s ? 5 : 4) * 32], 132);
              asm volatile("fence.proxy.async.global;" ::: "memory");
              mbar_wait(bb + 8 * (lds32(ptab + 224) & 255), 0);
            }
            const uint32_t bar = gfull + 8 * s, dst = sb + 16 * m.slot[s];
            const char* src = x1 + bin * (4 * G_ST) + m.src[s];
            mbar_wait(bb + m.dep[s], 0);
            mbar_expect(bar, G_ST);
#pragma unroll
            for (int h = 0; h < 2; h++) {
              if (s >= 16)
                asm volatile("cp.async.bulk.shared::cluster.global.mbarrier::complete_tx::bytes.L2::cache_hint [%0], [%1], %2, [%3], %4;"
                             ::"r"(dst + h * (G_ST / 2)), "l"(src + h * (s < G_S0 ? G_ST / 2 : 2 * G_ST)), "n"(G_ST / 2), "r"(bar), "l"(policy<1>()) : "memory");
              else
                asm volatile("cp.async.bulk.shared::cluster.global.mbarrier::complete_tx::bytes [%0], [%1], %2, [%3];"
                             ::"r"(dst + h * (G_ST / 2)), "l"(src + h * (s < G_S0 ? G_ST / 2 : 2 * G_ST)), "n"(G_ST / 2), "r"(bar) : "memory");
            }
          }
          if (cta == 0) asm volatile("cp.async.bulk.prefetch.L2.global [%0], 14336;" ::"l"(gp_.img) : "memory");
        }
      } else if (warp < 3) {
        const int u0 = warp == 1 ? 0 : nx0, u1 = warp == 1 ? nx0 : nx;
#pragma unroll 1
        for (int u = u0; u < u1; u++) {
          const int c = lds32(xtab + 4 * u);
          const uint32_t e = spare ? 0xC0 : lds32(ptab + 128 + 4 * u);
          const uint32_t src = sb + (c & 0x3C000), rel = e >> 1 & 24, burst = (16 << (e >> 6 & 3)) - 1;
          mbar_wait(xready + 8 * u, 0);
#pragma unroll 1
          for (int p = 0; p < 128; p += 16) {
            tma_st4<0>(&m.xs, src + p * 128, 0, (c >> 2 & 0x1C0) + (p & 63), p >> 6, c & 255);
            if (((p + 16) & burst) == 0) {
              bulk_commit();
              bulk_wait_read<0>();
            }
          }
          mbar_arrive(xfree + 8 * u);
          if (rel)
            asm volatile("mbarrier.arrive.shared::cluster.b64 _, [%0];" ::"r"(peer + (pfree - sb) + rel) : "memory");
        }
        asm volatile("cp.async.bulk.wait_group 0;" ::: "memory");
        asm volatile("red.release.gpu.global.add.s32 [%0], 1;" ::"l"(&gp_.done[(3 + warp) * 32]) : "memory");
        if (!spare) {
          if (warp == 1) {
            auto w2_row = [&](int it, bool pf) {
              const CUtensorMap* mp = it & 1 ? &m.w2e : &m.w2o;
              const int c1 = (it & 1) - 1, c2 = (cta & 1) * 2, c3 = (it >> 1) * 64 + (cta >> 1);
              if (pf) {
                asm volatile("cp.async.bulk.prefetch.tensor.4d.L2.global [%0, {%1, %2, %3, %4}];" ::"l"(mp), "r"(0), "r"(c1), "r"(c2), "r"(c3) : "memory");
              } else {
                mbar_expect(inf0 + 8 * (it & 1), 4096);
                tma_ld4<1>(sb + K1_TIN + (it & 1) * 4096, mp, inf0 + 8 * (it & 1), 0, c1, c2, c3);
              }
            };
#pragma unroll 1
            for (int it = 0; it < W2_PF; it++) {
              mbar_wait(gfull + 8 * (it >> 1), 0);
              w2_row(it, true);
            }
            mbar_wait(gdone + 8, 0);
#pragma unroll 1
            for (int it = 0; it < 8; it++) {
              if (it >= 2) mbar_wait(ine0 + 8 * (it & 1), ((it >> 1) - 1) & 1);
              w2_row(it, false);
              if (W2_PF && it + W2_PF < 8) w2_row(it + W2_PF, true);
            }
          } else {
            prefetch_map(&m.w2s);
            prefetch_map(&m.y);
#pragma unroll 1
            for (int it = 0; it < 8; it++) {
              if ((0x74 >> it) & 1) poll_ge(&gp_.done[((0x33210000 >> (4 * it)) & 3) * 32], 128);
              mbar_wait(sf0 + 8 * (it & 1), (it >> 1) & 1);
#pragma unroll 1
              for (int p = 0; p < 128; p += W2_PC) {
                tma_st4<0>(&m.w2s, sb + K1_T + (it & 1) * 16384 + p * 128, 0, it * 64 + (p & 63), (cta & 1) * 2 + (p >> 6),
                           (cta >> 1 & 33) | (cta >> 3 & 6) | (cta << 1 & 24));
                bulk_commit();
                bulk_wait_read<0>();
              }
              mbar_arrive(se0 + 8 * (it & 1));
            }
          }
        }
      } else {
#pragma unroll 1
        for (int u = 1; u < nx; u++) {
          const int c = lds32(xtab + 4 * u);
          const uint32_t e = spare ? (u < 8 ? 97 : 40 + u) * 0x01010100u : lds32(ptab + 128 + 4 * u);
          mbar_wait(bb + (e >> 5 & 0x7F8), 0);
          mbar_expect(xfull + 8 * u, A_IN);
          mbar_wait(bb + (e >> 13 & 0x7F8), 0);
          x_half(u, c, 0);
          mbar_wait(bb + (e >> 21 & 0x7F8), 0);
          x_half(u, c, 1);
        }
#pragma unroll 1
        for (int s = 0; s < (spare ? 0 : 16); s++) {
          mbar_wait(gfull + 8 * s, 0);
          if ((s & 3) == 3) asm volatile("red.relaxed.gpu.global.add.s32 [%0], 1;" ::"l"(&gp_.done[(s >> 2) * 32]) : "memory");
        }
      }
    }
  } else {
    asm volatile("setmaxnreg.inc.sync.aligned.u32 232;");
    const int row = (lane & 7) + ((lane >> 3) & 1) * 8, hi = lane >> 4;
    asm volatile("barrier.cluster.wait.aligned;" ::: "memory");
    uint32_t fw[4];
    {
      uint32_t fa[16], za[64];
      mbar_wait(fbar, 0);
      const int f = (4 * bp + warp) & 63;
      const uint32_t lo = lds32(sF + f * 128 + ((f & 7) << 4) + (lane & 3) * 4), hh = lds32(sF + f * 128 + (((f & 7) ^ 1) << 4) + (lane & 3) * 4);
#pragma unroll
      for (int k = 0; k < 4; k++)
        ldsm4(sF + (warp * 16 + row) * 128 + (((2 * k + hi) ^ (lane & 7)) << 4), fa[4 * k], fa[4 * k + 1], fa[4 * k + 2], fa[4 * k + 3]);
      const int rho = (lane >> 3) | (lane & 4);
#pragma unroll
      for (int i = 0; i < 64; i++) za[i] = ((i & 1) == (i >> 5) && rho == ((i >> 2) & 7)) ? ((i & 2) ? hh : lo) : 0u;
      reg_fence(za);
      bar_sync(3, 256);
      const bool own = (warp >> 1) == rank;
      float d[64];
      constexpr uint64_t s2 = sched("02468:<>"), s3 = sched("13579;=?");
#pragma unroll 1
      for (uint64_t sc = spare ? (wg ? s3 : s2) : m.p.list[wg]; sc; sc >>= 5) {
        const int item = (int)sc & 31;
        if (item >= 18) {
          const int q = item - 18;
          const uint32_t e = __shfl_sync(0xffffffffu, lds32(ptab + 192 + 4 * q), 0);
#pragma unroll
          for (int jj = 0; jj < 4; jj++) {
            const int j = 4 * q + jj;
            mbar_wait(rfull + 8 * j, 0);
            wg_fence();
#pragma unroll
            for (int i = 0; i < 4; i++)
              wgmma_rs_128<1, 1, 1>(d, za[16 * jj + 4 * i], za[16 * jj + 4 * i + 1], za[16 * jj + 4 * i + 2], za[16 * jj + 4 * i + 3],
                                    mk_desc(sb + place(rank, e >> (4 * jj) & 15), i * 2048, 8192, 1024, 1), jj | i);
            wg_commit();
            if (jj > 0) {
              wg_wait<1>();
              if (lane == 0) mbar_arrive(rempty + 8 * (j - 1));
            }
          }
          wg_wait<0>();
          reg_fence(d);
          if (lane == 0) mbar_arrive(rempty + 8 * (4 * q + 3));
          mbar_wait(bb + (e >> (own ? 13 : 21) & 0x7F8), 0);
          const uint32_t rb = (own ? sb : peer) + (8 * rank + q) * 8192 + (warp & 1) * 4096 + rho * 128;
          const uint32_t wbar = q < W_Q ? win : win1;
          auto put_w = [&](auto remote) {
#pragma unroll
            for (int v = 0; v < 8; v++) {
              const int j = 4 * (v >> 1), h = v & 1;
              const uint32_t a = rb + (j >> 3) * 2048 + h * 1024 + ((((j & 4) + (lane & 3)) ^ rho) << 4);
              const uint32_t p0 = pack2(d[4 * j + 2 * h], d[4 * j + 2 * h + 1]), p1 = pack2(d[4 * j + 4 + 2 * h], d[4 * j + 5 + 2 * h]);
              const uint32_t p2 = pack2(d[4 * j + 8 + 2 * h], d[4 * j + 9 + 2 * h]), p3 = pack2(d[4 * j + 12 + 2 * h], d[4 * j + 13 + 2 * h]);
              if (decltype(remote)::value)
                asm volatile("st.async.shared::cluster.mbarrier::complete_tx::bytes.v4.b32 [%0], {%1, %2, %3, %4}, [%5];"
                             ::"r"(a), "r"(p0), "r"(p1), "r"(p2), "r"(p3), "r"(peer + (wbar - sb)) : "memory");
              else
                asm volatile("st.shared.v4.b32 [%0], {%1, %2, %3, %4};" ::"r"(a), "r"(p0), "r"(p1), "r"(p2), "r"(p3) : "memory");
            }
          };
          if (own) {
            put_w(std::false_type());
            __syncwarp();
            if (lane == 0) mbar_arrive(wbar);
          } else {
            put_w(std::true_type());
          }
        } else {
          const int u = item - 1;
          const int c = lds32(xtab + 4 * u);
          const uint32_t in = sb + (c & 0x3C000);
          mbar_wait(xfull + 8 * u, 0);
          wg_fence();
#pragma unroll
          for (int k = 0; k < 4; k++)
            wgmma_rs_128<1, 1, 1>(d, fa[4 * k], fa[4 * k + 1], fa[4 * k + 2], fa[4 * k + 3], mk_desc(in, k * 2048, 6144, 1024, 1), k);
          wg_commit();
          wg_wait<0>();
          reg_fence(d);
          bar_sync(1 + wg, 128);
          const uint32_t rb = in + (warp * 16 + row) * 128, xr = (lane & 7) ^ (c & 3);
#pragma unroll
          for (int j = 0; j < 16; j += 2)
            stsm4(rb + ((j >> 2) & 1) * 8192 + ((((j >> 3) * 4 + (j & 3) + hi) ^ xr) << 4), pack2(d[4 * j], d[4 * j + 1]),
                  pack2(d[4 * j + 2], d[4 * j + 3]), pack2(d[4 * j + 4], d[4 * j + 5]), pack2(d[4 * j + 6], d[4 * j + 7]));
          fence_async();
          __syncwarp();
          if (lane == 0) mbar_arrive(xready + 8 * u);
        }
      }
#pragma unroll
      for (int i = 0; i < 4; i++) fw[i] = fa[i];
    }
    if (spare) {
      float* sg = reinterpret_cast<float*>(smem_k1 + K1_R);
      __nv_bfloat16* sw = reinterpret_cast<__nv_bfloat16*>(sg + 16 * 256);
      const int c0 = (cta - 128) * 64;
      uint4 vw[8], vg[2];
#pragma unroll
      for (int i = 0; i < 8; i++) vw[i] = __ldg(reinterpret_cast<const uint4*>(wgt + ((i * 256 + tid) >> 3) * 256 + c0 + (tid & 7) * 8));
#pragma unroll
      for (int i = 0; i < 2; i++) vg[i] = __ldg(reinterpret_cast<const uint4*>(g) + i * 256 + tid);
#pragma unroll
      for (int i = 0; i < 8; i++) reinterpret_cast<uint4*>(sw)[i * 256 + tid] = vw[i];
#pragma unroll
      for (int i = 0; i < 2; i++) {
        const uint32_t w4[4] = {vg[i].x, vg[i].y, vg[i].z, vg[i].w};
#pragma unroll
        for (int e = 0; e < 4; e++) {
          sg[(i * 256 + tid) * 8 + 2 * e] = __uint_as_float(w4[e] << 16);
          sg[(i * 256 + tid) * 8 + 2 * e + 1] = __uint_as_float(w4[e] & 0xffff0000u);
        }
      }
      bar_sync(3, 256);
      const int col = tid & 63, r0 = (tid >> 6) * 4;
      float a0 = 0.f, a1 = 0.f, a2 = 0.f, a3 = 0.f;
#pragma unroll 8
      for (int k = 0; k < 256; k++) {
        const float w = __bfloat162float(sw[k * 64 + col]);
        a0 = fmaf(sg[(r0 + 0) * 256 + k], w, a0);
        a1 = fmaf(sg[(r0 + 1) * 256 + k], w, a1);
        a2 = fmaf(sg[(r0 + 2) * 256 + k], w, a2);
        a3 = fmaf(sg[(r0 + 3) * 256 + k], w, a3);
      }
      const int cc = c0 + col;
      const int pos = (cc & ~15) + ((cc >> 1) & 3) * 4 + ((cc >> 3) & 1) * 2 + (cc & 1);
      gp_.ge[(r0 + 0) * 256 + pos] = __bfloat162float(__float2bfloat16_rn(a0));
      gp_.ge[(r0 + 1) * 256 + pos] = __bfloat162float(__float2bfloat16_rn(a1));
      gp_.ge[(r0 + 2) * 256 + pos] = __bfloat162float(__float2bfloat16_rn(a2));
      gp_.ge[(r0 + 3) * 256 + pos] = __bfloat162float(__float2bfloat16_rn(a3));
      return;
    }
    reg_fence(fw);
    mbar_wait(win, 0);
    float d[16];
    auto t_begin = [&](int it, int hh, int r) {
      if (r == 0) mbar_wait(inf0 + 8 * (it & 1), (it >> 1) & 1);
      wg_fence();
      wgmma_rs_32<1, 1, 1>(d, fw[0], fw[1], fw[2], fw[3], mk_desc(sb + K1_TIN + (it & 1) * 4096 + hh * 2048, r * 64, 0, 1024, 1), 0);
      wg_commit();
    };
    auto t_end = [&](int it, int hh, int r) {
      reg_fence(d);
      const int j = it & 1;
      if (r == 0) mbar_wait(it >= 2 ? se0 + 8 * j : bb + (m.p.last >> (5 + 8 * it) & 0x7F8), it >= 2 ? ((it >> 1) - 1) & 1 : 0);
      else if (lane == 0) mbar_arrive(ine0 + 8 * j);
      const uint32_t rb = sb + K1_T + j * 16384 + hh * 8192 + (warp * 16 + row) * 128;
#pragma unroll
      for (int i = 0; i < 2; i++)
        stsm4(rb + (((4 * r + 2 * i + hi) ^ (lane & 7)) << 4), pack2(d[8 * i], d[8 * i + 1]), pack2(d[8 * i + 2], d[8 * i + 3]),
              pack2(d[8 * i + 4], d[8 * i + 5]), pack2(d[8 * i + 6], d[8 * i + 7]));
      if (r == 1) {
        fence_async();
        __syncwarp();
        if (lane == 0) mbar_arrive(sf0 + 8 * j);
      }
    };
    float y0[NB1 / 2], y1[NB1 / 2];
    uint32_t wa[8], wb[8];
    uint32_t wp = sb + wg * 4096 + ((lane & 7) + hi * 8) * 128 + (((2 * warp + ((lane >> 3) & 1)) ^ (lane & 7)) << 4);
    const uint32_t neg = wg ? 0x80008000u : 0u;
    auto frag = [&](uint32_t (&w)[8], uint32_t a, uint32_t sg) {
      ldsm4t(a, w[0], w[1], w[2], w[3]);
      ldsm4t(a + 2048, w[4], w[5], w[6], w[7]);
#pragma unroll
      for (int i = 0; i < 8; i++) w[i] ^= sg;
    };
    auto stage = [&](const uint32_t (&w)[8], uint32_t x4, int acc) {
      wg_fence();
      wgmma_rs_168<1, 1, 0>(y0, w[0], w[1], w[2], w[3], mk_desc4(x4, 0, 512, 2), acc);
      wgmma_rs_168<1, 1, 0>(y1, w[0], w[1], w[2], w[3], mk_desc4(x4 + G_ST / 32, 0, 512, 2), acc);
      wgmma_rs_168<1, 1, 0>(y0, w[4], w[5], w[6], w[7], mk_desc4(x4 + 2, 0, 512, 2), 1);
      wgmma_rs_168<1, 1, 0>(y1, w[4], w[5], w[6], w[7], mk_desc4(x4 + G_ST / 32 + 2, 0, 512, 2), 1);
      wg_commit();
      wg_wait<1>();
    };
    frag(wa, wp, neg);
    int it = 0;
#pragma unroll 1
    for (int k = 0; k < G_KM; k++) {
      const bool T = (m.p.tmask >> (k + 16 * wg)) & 1;
      const uint32_t xa = ((sb & 0x3FFFF) >> 4) + m.slot[2 * k], xb = ((sb & 0x3FFFF) >> 4) + m.slot[2 * k + 1];
      if (T) t_begin(it, wg, 0);
      mbar_wait(gfull + 16 * k, 0);
      stage(wa, xa, k);
      frag(wb, wp ^ 4096, 0);
      if (k > 0 && lane == 0) mbar_arrive(gdone + 16 * k - 8);
      if (T) {
        t_end(it, wg, 0);
        t_begin(it, wg, 1);
      }
      mbar_wait(gfull + 16 * k + 8, 0);
      stage(wb, xb, 1);
      wp += 8192;
      if (k == W_Q - 1) {
        mbar_wait(win1, 0);
        fence_async();
      }
      frag(wa, wp, neg);
      if (lane == 0) mbar_arrive(gdone + 16 * k);
      if (T) t_end(it++, wg, 1);
    }
    auto tail = [&](float (&y)[NB1 / 2], auto batch, auto wgc) {
      constexpr int B = decltype(batch)::value, W = decltype(wgc)::value;
#pragma unroll
      for (int k = G_KM; k < 16; k++) {
        const int s = G_KM + k + G_TK * B;
        mbar_wait(gfull + 8 * s, 0);
        const int xo = g_off(g_slot(s));
        wg_fence();
#pragma unroll
        for (int h = 0; h < 4; h++) {
          const uint64_t dW = mk_desc(sb, k * 8192 + ((h >> 1) ^ W) * 4096 + (h & 1) * 2048, 0, 1024, 1);
          const uint64_t dX = mk_desc(sb, xo + (h >> 1) * (G_ST / 2) + (h & 1) * 32, 0, 512, 2);
          if (W == 1 && h < 2) wgmma_ss_168<-1, 1, 1, 0>(y, dW, dX, 1);
          else wgmma_ss_168<1, 1, 1, 0>(y, dW, dX, 1);
        }
        if (s <= 26) {
          wg_commit();
          if (W == 0 || k > G_KM) {
            wg_wait<1>();
            if (lane == 0) mbar_arrive(gdone + 8 * (s - 1));
          }
        }
      }
      wg_commit();
    };
    constexpr std::integral_constant<int, 0> c0;
    constexpr std::integral_constant<int, 1> c1;
    auto put = [&](const float (&v)[NB1 / 2], uint32_t stg, int b) {
      const int mi = lane >> 3, i = lane & 7;
      const uint32_t a0 = stg + (mi >> 1) * 1024 + i * 128 + (((2 * warp + (mi & 1)) ^ i) << 4);
      constexpr int J = 21 / G_EPI;
#pragma unroll
      for (int c = 0; c < G_EPI; c++) {
#pragma unroll
        for (int j = c * J; j + 1 < (c + 1) * J; j += 2)
          stsm4t(a0 + j * 1024, pack2(v[4 * j], v[4 * j + 1]), pack2(v[4 * j + 2], v[4 * j + 3]),
                 pack2(v[4 * j + 4], v[4 * j + 5]), pack2(v[4 * j + 6], v[4 * j + 7]));
        const int j = (c + 1) * J - 1;
        asm volatile("stmatrix.sync.aligned.m8n8.x2.trans.shared.b16 [%0], {%1, %2};" ::"r"(a0 + j * 1024),
                     "r"(pack2(v[4 * j], v[4 * j + 1])), "r"(pack2(v[4 * j + 2], v[4 * j + 3])) : "memory");
        fence_async();
        bar_sync(1 + wg, 128);
        if (t == 0) {
          tma_st4<0>(&m.y, stg + c * J * 1024, 0, b * NB1 + c * J * 8, 2 * bin + wg, dc);
          bulk_commit();
        }
      }
    };
    if (wg == 0) {
      tail(y0, c0, c0);
      bar_arrive(4, 256);
      mbar_wait(gdone + 8 * (G_S0 - 1), 0);
      wg_wait<0>();
      reg_fence(y0);
      put(y0, sb + K1_Y0, 0);
      bar_sync(7, 256);
      tail(y1, c1, c0);
      bar_arrive(8, 256);
      if (t == 0) bulk_wait_read<0>();
      wg_wait<0>();
      reg_fence(y1);
      bar_sync(1, 128);
      put(y1, sb + K1_Y0, 1);
    } else {
      wg_wait<0>();
      if (lane == 0) mbar_arrive(gdone + 8 * (G_S0 - 1));
#pragma unroll 1
      for (int h2 = 2 * it; h2 < 16; h2++) {
#pragma unroll
        for (int r = 0; r < 2; r++) {
          t_begin(h2 >> 1, h2 & 1, r);
          wg_wait<0>();
          t_end(h2 >> 1, h2 & 1, r);
        }
      }
      bar_sync(4, 256);
      tail(y0, c0, c1);
      bar_arrive(7, 256);
      mbar_wait(se0, 1);
      mbar_wait(se0 + 8, 1);
      wg_wait<0>();
      reg_fence(y0);
      put(y0, sb + K1_T, 0);
      bar_sync(8, 256);
      tail(y1, c1, c1);
      wg_wait<0>();
      reg_fence(y1);
      put(y1, sb + g_off(g_slot(26)), 1);
    }
    if (t == 0) {
      bulk_wait_read<0>();
    }
  }
}

#define H_EPI 3
#define H_KS 11
#define C_PC 32
constexpr int H_XP = 168 * 64, H_STAGE = 8192 + 2 * H_XP, H_NST = 7, K2_STG = H_NST * H_STAGE, K2_SMEM = K2_STG + 21504 + 1024;

template <int WG>
__device__ __forceinline__ void h_loop(float (&acc)[84], uint32_t sb, uint32_t full0, uint32_t empty0, int lane) {
#pragma unroll 1
  for (int k = 0; k < 16; k++) {
    const int st = k % H_NST;
    if (WG == 1 && k == H_KS) bar_sync(5, 256);
    mbar_wait(full0 + 8 * st, (k / H_NST) & 1);
    const uint32_t base = sb + st * H_STAGE;
    wg_fence();
#pragma unroll
    for (int s = 0; s < 2; s++) {
      const uint64_t dP = mk_desc(base, s * 2048, 0, 1024, 1), dQ = mk_desc(base, 4096 + s * 2048, 0, 1024, 1);
      const uint64_t dA = mk_desc(base, 8192 + s * 32, 0, 1024, 1), dB = mk_desc(base, 8192 + 64 + s * 32, 0, 1024, 1);
      wgmma_ss_168<1, 1, 1, 0>(acc, dP, WG == 0 ? dA : dB, k | s);
      wgmma_ss_168<WG == 0 ? 1 : -1, 1, 1, 0>(acc, dQ, WG == 0 ? dB : dA, 1);
    }
    wg_commit();
    if (WG == 0 && k == 15) bar_arrive(5, 256);
    if (k <= 10) {
      wg_wait<1>();
      if (k > 0 && k - 1 + H_NST < 16 && lane < 2) mbar_arrive_cta(empty0 + 8 * ((k - 1) % H_NST), lane);
    }
  }
  wg_wait<0>();
  reg_fence(acc);
}
template <int C0, int C1> __device__ __forceinline__ void gelu_pack(uint32_t (&p)[12], const float (&h)[24]) {
#pragma unroll
  for (int i = 4 * C0; i < 4 * C1; i++) p[i] = pack2(gelu(h[2 * i]), gelu(h[2 * i + 1]));
}
struct K2Maps {
  int stage[16], item[8], wpre, pad[7];
  CUtensorMap y, xa, xs, w, y2;
};

__global__ void __cluster_dims__(2, 1, 1) __launch_bounds__(512, 1)
k2(const Ptrs gp_, const char* __restrict__ x2, const __grid_constant__ K2Maps m, const __nv_bfloat16* __restrict__ wf,
   const __nv_bfloat16* __restrict__ wo) {
  extern __shared__ __align__(1024) uint8_t smem_k1[];
  const uint32_t sb = s2u(smem_k1);
  const int tid = threadIdx.x, wg = __shfl_sync(0xffffffffu, tid >> 7, 0), t = tid & 127;
  const int warp = __shfl_sync(0xffffffffu, t >> 5, 0), lane = t & 31;
  const int cta = blockIdx.x, rank = cta & 1, dc = cta & 3, bin = cta >> 2;
  const uint32_t sGi = sb + K2_STG, sF = sGi + 6144, bb = sb + K2_STG + 21504;
  const uint32_t yfull = bb, full0 = bb + 128, empty0 = bb + 192, cfull = bb + 256, ready = bb + 320, bfree = bb + 384;
  const int b = cta & 1, j = cta >> 2;
  const int len0 = j < 20 ? 3 : 2, len1 = j >= 12 ? 3 : 2;
  const int n00 = j < 20 ? 3 * j : 2 * j + 20, n01 = j < 12 ? 2 * j : 3 * j - 12, cs0 = 3 - (cta >> 1 & 1);
  auto y_load = [&](int r, int i) {
    tma_ld5<1>(sb + (3 + 2 * r) * H_STAGE + i * 8192, &m.y, yfull + 64 * r + 8 * i, 0, 0, cs0 - 2 * r, 2 * (r ? n01 : n00) + i, b);
  };
  if (wg == 2 && warp == 0) {
    if (lane == 0) {
      prefetch_map(&m.y);
      for (int i = 0; i < 16; i++) mbar_init(yfull + 8 * i, 1);
      fence_bar_init();
    }
    __syncwarp();
    if (lane < 16) mbar_expect(yfull + 8 * lane, lane == 7 ? 6144 : 8192);
    bar_arrive(0, 512);
    asm volatile("barrier.cluster.arrive.relaxed.aligned;" ::: "memory");
    auto c_load = [&](int h) {
      asm volatile("cp.async.bulk.shared::cluster.global.mbarrier::complete_tx::bytes [%0], [%1], %2, [%3];"
                   ::"r"(sGi + 6144 * h), "l"(gp_.img + 1536 * h), "r"(6144 + 2048 * h), "r"(yfull + 56 + 64 * h) : "memory");
    };
    if (lane == 0) {
      c_load(0);
      c_load(1);
      pdl_wait();
      const int r2 = len0 == 2, i2 = r2 ? 2 : 6;
      y_load(0, 2), y_load(0, 0), y_load(0, 1), y_load(1, 0), y_load(0, 4), y_load(0, 3), y_load(r2, i2), y_load(r2, i2 - 1);
      pdl_launch();
    }
    __syncwarp();
  } else {
    if (lane == 0 && wg == 3) {
      for (int i = 0; i < 8; i++) mbar_init(full0 + 64 * warp + 8 * i, warp == 0 ? 1 : warp == 1 ? 16 : 4);
      fence_bar_init();
    }
    if (tid == 0) {
      mbar_init(bfree, 2);
      for (int i = 1; i < 5; i++) mbar_init(bfree + 8 * i, 1);
      mbar_arrive(bfree + 8);
      fence_bar_init();
    }
    if (tid == 128) {
      prefetch_map(&m.xa);
      prefetch_map(&m.xs);
      prefetch_map(&m.w);
      prefetch_map(&m.y2);
    }
    bar_sync(0, 512);
    asm volatile("barrier.cluster.arrive.relaxed.aligned;" ::: "memory");
  }
  if (wg == 2) asm volatile("barrier.cluster.wait.aligned;" ::: "memory");
  mbar_wait(yfull + 56, 0);
  auto idft = [&](float (&h)[24], uint32_t in, uint32_t bar) {
    mbar_wait(bar, 0);
    wg_fence();
#pragma unroll
    for (int k = 0; k < 4; k++) wgmma_ss_48<1, 1, 1, 0>(h, mk_desc(in, k * 2048, 0, 1024, 1), mk_desc(sGi, k * 32, 0, 1024, 1), k);
    wg_commit();
  };
  auto carry_out = [&](const uint32_t (&p)[12], uint32_t dst, uint32_t bar) {
    bar_sync(1 + wg, 128);
#pragma unroll
    for (int v = 0; v < 3; v++)
      asm volatile("st.shared.v4.b32 [%0], {%1, %2, %3, %4};" ::"r"(dst + v * 2048 + t * 16), "r"(p[4 * v]), "r"(p[4 * v + 1]), "r"(p[4 * v + 2]), "r"(p[4 * v + 3]) : "memory");
    __syncwarp();
    if (lane == 0) mbar_arrive(bar);
  };
  if (wg == 3) {
#pragma unroll 1
    for (int r = 0; r < 2; r++) {
      float h[24];
      uint32_t p[12];
      idft(h, sb + (3 + 2 * r) * H_STAGE, yfull + 64 * r);
      wg_wait<0>();
      reg_fence(h);
      gelu_pack<0, 3>(p, h);
      if (j == 0) p[0] = p[1] = p[2] = p[3] = 0;
      carry_out(p, sb + (3 + 2 * r) * H_STAGE, cfull + 32 * r);
    }
    asm volatile("barrier.cluster.wait.aligned;" ::: "memory");
    if (lane == 0) {
      if (warp == 0) {
        auto w_load = [&](int k) {
          mbar_expect(full0 + 8 * (k % H_NST), H_STAGE);
          tma_ld4<1>(sb + (k % H_NST) * H_STAGE, &m.w, full0 + 8 * (k % H_NST), 0, (k & 1) * 32, dc, (7 - (k >> 1)) * 64 + 2 * bin);
        };
        const int wpre = m.wpre;
        for (int k = 0; k < wpre; k++) w_load(k);
#pragma unroll 1
        for (int k = 0; k < 16; k++) {
          const int st = k % H_NST, e = m.stage[k];
          if ((k & 7) == 0) {
            poll_ge(&gp_.done[(6 + (k >> 3)) * 32], 128);
            asm volatile("fence.proxy.async.global;" ::: "memory");
            if (k == 0) mbar_arrive(bfree + 32);
          }
          if (e) mbar_wait(bb + 8 * e, 0);
          if (k == 5) mbar_wait(bfree, 0);
          if (k >= H_NST) mbar_wait(empty0 + 8 * st, ((k / H_NST) - 1) & 1);
          const char* xs = x2 + (((7 - (k >> 2) - (k & 2) * 2) * 64 + (k & 1) * 32 + bin) * 2 + rank) * H_XP;
          asm volatile("cp.async.bulk.shared::cluster.global.mbarrier::complete_tx::bytes.multicast::cluster [%0], [%1], %2, [%3], %4;"
                       ::"r"(sb + st * H_STAGE + 8192 + rank * H_XP), "l"(xs), "n"(H_XP), "r"(full0 + 8 * st), "h"((uint16_t)3) : "memory");
          if (k >= wpre) w_load(k);
          if (k == 8) {
            if (cta == 0) asm volatile("cp.async.bulk.prefetch.L2.global [%0], 6144;" ::"l"(gp_.ga) : "memory");
            asm volatile("cp.async.bulk.prefetch.L2.global [%0], 1024;" ::"l"(wf + cta * 512) : "memory");
            asm volatile("cp.async.bulk.prefetch.L2.global [%0], 1024;" ::"l"(wo + cta * 512) : "memory");
          }
        }
      } else if (warp < 3) {
        const int r = warp - 1, n0 = b * NB2 + (r ? n01 : n00), f0 = (cs0 - 2 * r) * 64;
#pragma unroll 1
        for (int i = 0; i < (r ? len1 : len0); i++) {
          const uint32_t src = sb + (3 + 2 * r) * H_STAGE + i * 16384;
          const int e = m.item[4 * r + i], burst = (16 << (e >> 8)) - 1;
          if (r) mbar_wait(bb + 8 * (e & 255), 0);
          mbar_wait(ready + 32 * r + 8 * i, 0);
          if (!r) {
            tma_st4<0>(&m.xa, src, 0, f0, 0, n0 + i);
            bulk_commit();
            continue;
          }
#pragma unroll 1
          for (int p = 0; p < 128; p += C_PC) {
            tma_st3<0>(&m.xs, src + p * 128, 0, f0 + (p & 63) + (p >> 6) * 256, n0 + i);
            bulk_commit();
            if (((p + C_PC) & burst) == 0) bulk_wait_read<0>();
          }
        }
        asm volatile("cp.async.bulk.wait_group 0;" ::: "memory");
        if (r) {
          mbar_arrive_cta(bfree, 0);
          mbar_arrive_cta(bfree, 1);
        }
        if (!r) mbar_arrive(bfree + 16);
        asm volatile("red.release.gpu.global.add.s32 [%0], 1;" ::"l"(&gp_.done[(6 + r) * 32]) : "memory");
        if (!r) mbar_arrive(bfree + 24);
      }
    }
    return;
  }
#pragma unroll 1
  for (int it = wg; it < len0 + len1; it += 3) {
    const int r = it >= len0, i = it - r * len0;
    const bool last = i + 1 == (r ? len1 : len0);
    const uint32_t in = sb + (3 + 2 * r) * H_STAGE + i * 16384, bar = yfull + 64 * r + 16 * i;
    float h1[24], h2[24];
    uint32_t p0[12], p1[12], p2[12];
    idft(h2, in + 16384, bar + 16);
    if (it == 2 && lane == 0 && 3 + warp - len0 < len1) {
      y_load(1, 2 * (3 + warp - len0) + 2);
      y_load(1, 2 * (3 + warp - len0) + 1);
    }
    if (it > 0) bar_sync(6 + wg, 256);
    wg_wait<0>();
    reg_fence(h2);
    gelu_pack<0, 2>(p2, h2);
    idft(h1, in + 8192, bar + 8);
    if (!last) {
      gelu_pack<2, 3>(p2, h2);
      carry_out(p2, in + 16384, cfull + 32 * r + 8 * i + 8);
    }
    if (it + 1 < len0 + len1) bar_arrive(6 + (wg + 1) % 3, 256);
    mbar_wait(cfull + 32 * r + 8 * i, 0);
#pragma unroll
    for (int v = 0; v < 3; v++)
      asm volatile("ld.shared.v4.b32 {%0, %1, %2, %3}, [%4];" : "=r"(p0[4 * v]), "=r"(p0[4 * v + 1]), "=r"(p0[4 * v + 2]), "=r"(p0[4 * v + 3]) : "r"(in + v * 2048 + t * 16) : "memory");
    if (it < 3) mbar_wait(yfull + 120, 0);
    wg_wait<0>();
    reg_fence(h1);
    gelu_pack<0, 3>(p1, h1);
    if (last && j == 31) {
#pragma unroll
      for (int v = 0; v < 12; v++) p1[v] = p2[v] = 0;
    }
    uint32_t hp[32];
#pragma unroll
    for (int c = 0; c < 8; c++)
#pragma unroll
      for (int v = 0; v < 4; v++) hp[(v >> 1) * 16 + 2 * c + (v & 1)] = c < 3 ? p0[4 * c + v] : c < 6 ? p1[4 * (c - 3) + v] : p2[4 * (c - 6) + v];
    float e0[32], e1[32];
    reg_fence(hp);
    wg_fence();
#pragma unroll
    for (int k = 0; k < 4; k++) {
      const uint64_t db = mk_desc(sF, k * 32, 0, 1024, 1);
      wgmma_rs_64<1, 1, 0>(e0, hp[4 * k], hp[4 * k + 1], hp[4 * k + 2], hp[4 * k + 3], db, k);
      wgmma_rs_64<1, 1, 0>(e1, hp[16 + 4 * k], hp[16 + 4 * k + 1], hp[16 + 4 * k + 2], hp[16 + 4 * k + 3], db, k);
    }
    wg_commit();
    bar_sync(1 + wg, 128);
    wg_wait<0>();
    reg_fence(e0);
    reg_fence(e1);
    {
      const int mi = lane >> 3, rr = (lane & 7) >> 1, blk = b * NB2 + (r ? n01 : n00) + i;
      const uint32_t a0 = in + (mi >> 1) * 8192 + (warp >> 1) * 4096 + rr * 128;
      const uint32_t pos = ((lane & 1) * 4 + (warp & 1) * 2 + (mi & 1)) ^ rr ^ (blk & 7);
#pragma unroll
      for (int q = 0; q < 8; q++)
        stsm4t(a0 + q * 512 + ((pos ^ (q & 1) * 4) << 4), pack2(e0[4 * q], e0[4 * q + 1]), pack2(e0[4 * q + 2], e0[4 * q + 3]),
               pack2(e1[4 * q], e1[4 * q + 1]), pack2(e1[4 * q + 2], e1[4 * q + 3]));
    }
    fence_async();
    __syncwarp();
    if (lane == 0) mbar_arrive(ready + 32 * r + 8 * i);
  }
  if (wg == 2) return;
  asm volatile("barrier.cluster.wait.aligned;" ::: "memory");
  float acc[84];
  if (wg == 0) {
    h_loop<0>(acc, sb, full0, empty0, lane);
  } else {
    h_loop<1>(acc, sb, full0, empty0, lane);
    bar_sync(2, 128);
  }
  const uint32_t stg = sb + (wg == 0 ? H_NST : 9 % H_NST) * H_STAGE;
  const int mi = lane >> 3, i = lane & 7;
  const uint32_t a0 = stg + (mi >> 1) * 1024 + i * 128 + (((2 * warp + (mi & 1)) ^ i) << 4);
  constexpr int J = 21 / H_EPI;
#pragma unroll
  for (int c = 0; c < H_EPI; c++) {
#pragma unroll
    for (int q = c * J; q + 1 < (c + 1) * J; q += 2)
      stsm4t(a0 + q * 1024, pack2(acc[4 * q], acc[4 * q + 1]), pack2(acc[4 * q + 2], acc[4 * q + 3]),
             pack2(acc[4 * q + 4], acc[4 * q + 5]), pack2(acc[4 * q + 6], acc[4 * q + 7]));
    const int q = (c + 1) * J - 1;
    asm volatile("stmatrix.sync.aligned.m8n8.x2.trans.shared.b16 [%0], {%1, %2};" ::"r"(a0 + q * 1024),
                 "r"(pack2(acc[4 * q], acc[4 * q + 1])), "r"(pack2(acc[4 * q + 2], acc[4 * q + 3])) : "memory");
    fence_async();
    bar_sync(1 + wg, 128);
    if (t == 0) {
      tma_st4<0>(&m.y2, stg + c * J * 1024, 0, c * J * 8, 2 * bin + wg, dc);
      bulk_commit();
    }
  }
  if (t == 0) {
    bulk_wait_read<0>();
  }
}

#define E_WPRE 2
#define E_EARLY0 2
#define E_EARLY 2
constexpr int E_SMEM = 65536 + 131072 + 32768 + 1024;

__device__ __forceinline__ uint32_t joint2(uint32_t fe, uint32_t g0, uint32_t g1) {
  uint32_t s0, s1;
  asm("{\n.reg .b16 l, h;\n.reg .b32 ll, hh;\nmov.b32 {l, h}, %2;\nmov.b32 ll, {l, l};\nmov.b32 hh, {h, h};\n"
      "fma.rn.bf16x2 %0, ll, %5, %3;\nfma.rn.bf16x2 %1, hh, %5, %4;\n}"
      : "=r"(s0), "=r"(s1) : "r"(fe), "r"(g0), "r"(g1), "r"(0x3F800000u));
  return pack2(tanh_f32(__uint_as_float(s0)), tanh_f32(__uint_as_float(s1)));
}
__device__ __forceinline__ uint4 lds128(uint32_t a) {
  uint4 v;
  asm volatile("ld.shared.v4.u32 {%0, %1, %2, %3}, [%4];" : "=r"(v.x), "=r"(v.y), "=r"(v.z), "=r"(v.w) : "r"(a));
  return v;
}
__device__ __forceinline__ void joint_group(uint32_t (&ja)[8], const uint32_t* fe, const uint4& c0, const uint4& c1) {
  ja[0] = joint2(fe[0], c0.x, c0.y);
  ja[1] = joint2(fe[1], c0.x, c0.y);
  ja[2] = joint2(fe[2], c0.z, c0.w);
  ja[3] = joint2(fe[3], c0.z, c0.w);
  ja[4] = joint2(fe[4], c1.x, c1.y);
  ja[5] = joint2(fe[5], c1.x, c1.y);
  ja[6] = joint2(fe[6], c1.z, c1.w);
  ja[7] = joint2(fe[7], c1.z, c1.w);
  reg_fence(ja);
}

__global__ void __launch_bounds__(256, 1)
kE(const __grid_constant__ CUtensorMap my, const __grid_constant__ CUtensorMap mwf, const __grid_constant__ CUtensorMap mwo,
   const __grid_constant__ CUtensorMap mout) {
  const Ptrs gp_ = {g_done, g_ge, c_img, c_ga};
  extern __shared__ uint8_t smem_raw[];
  __shared__ __align__(8) uint64_t bars[13];
  const uint32_t sb = (s2u(smem_raw) + 1023) & ~1023u;
  const int tid = threadIdx.x, wg = __shfl_sync(0xffffffffu, tid >> 7, 0), t = tid & 127, warp = t >> 5, lane = t & 31;
  const uint32_t R0 = sb, R1 = sb + 65536, R2 = sb + 65536 + 131072;
  const uint32_t barY = s2u(&bars[0]), barF = s2u(&bars[4]), barO = s2u(&bars[8]), barA = s2u(&bars[12]);
  const int b = blockIdx.x / 63, t0 = (blockIdx.x % 63) * 64;
  const int a = t0 / 48, o = t0 % 48;
  const int qw = o + 16 * warp, sel = qw >= 48;
  uint32_t ga[16];
#pragma unroll
  for (int s = 0; s < 4; s++)
    ldg128(reinterpret_cast<const uint4*>(gp_.ga) + ((qw >> 4) - 3 * sel) * 128 + s * 32 + lane, ga[4 * s], ga[4 * s + 1], ga[4 * s + 2], ga[4 * s + 3]);
  uint4 gev0, gev1;
  asm volatile("ld.global.cg.v4.u32 {%0, %1, %2, %3}, [%4];" : "=r"(gev0.x), "=r"(gev0.y), "=r"(gev0.z), "=r"(gev0.w)
               : "l"(reinterpret_cast<const uint4*>(gp_.ge) + (b * 8 + wg * 4) * 64 + t));
  asm volatile("ld.global.cg.v4.u32 {%0, %1, %2, %3}, [%4];" : "=r"(gev1.x), "=r"(gev1.y), "=r"(gev1.z), "=r"(gev1.w)
               : "l"(reinterpret_cast<const uint4*>(gp_.ge) + (b * 8 + wg * 4) * 64 + 128 + t));
  if (tid == 0) {
    prefetch_map(&my);
    for (int i = 0; i < 12; i++) mbar_init(barY + 8 * i, 1);
    mbar_init(barA, 8);
    fence_bar_init();
    fence_async();
    for (int i = 0; i < E_WPRE; i++) {
      const int kc = (i >> 1) | ((i & 1) << 1);
      mbar_expect(barF + 8 * kc, 32768);
      tma_ld3<0>(R1 + kc * 32768, &mwf, barF + 8 * kc, 0, kc * 64, 0);
    }
    pdl_wait();
    for (int i = 0; i < 4; i++) {
      mbar_expect(barY + 8 * i, 16384);
      tma_ld5<0>(R0 + i * 16384, &my, barY + 8 * i, 0, 0, 2 * (i & 1) + (i >> 1), a, b);
    }
    for (int i = E_WPRE; i < 2; i++) {
      const int kc = (i >> 1) | ((i & 1) << 1);
      mbar_expect(barF + 8 * kc, 32768);
      tma_ld3<0>(R1 + kc * 32768, &mwf, barF + 8 * kc, 0, kc * 64, 0);
    }
    prefetch_map(&mwo);
    prefetch_map(&mout);
  }
  uint32_t gs[32];
#pragma unroll
  for (int i = 0; i < 16; i++) {
    gs[i] = sel ? 0u : ga[i];
    gs[16 + i] = sel ? ga[i] : 0u;
  }
  __syncthreads();
  if (blockIdx.x == 125 && tid < 8) gp_.done[tid * 32] = 0;
  reg_fence(gs);
  uint32_t gp = R2 + wg * 4096 + (lane & 3) * 16;
  uint4 g0, g1;
  uint32_t fe[64];
  {
    float d0[32], d1[32], e[64];
    mbar_wait(barY + 8 * wg, 0);
    wg_fence();
#pragma unroll
    for (int k = 0; k < 8; k++)
      wgmma_rs_64<1, 1, 1>(d0, gs[4 * k], gs[4 * k + 1], gs[4 * k + 2], gs[4 * k + 3], mk_desc(R0 + wg * 16384, k * 2048, 0, 1024, 1), k);
    wg_commit();
    if (t == 0) {
      mbar_expect(barF + 8 + 16 * wg, 32768);
      tma_ld3<0>(R1 + (1 + 2 * wg) * 32768, &mwf, barF + 8 + 16 * wg, 0, (1 + 2 * wg) * 64, 0);
    }
    wg_wait<0>();
    reg_fence(d0);
#pragma unroll
    for (int i = 0; i < 32; i++) d0[i] = gelu(d0[i]);
    store_tile_64(d0, R2 + wg * 16384, warp, lane);
    mbar_wait(barY + 8 * (2 + wg), 0);
    wg_fence();
#pragma unroll
    for (int k = 0; k < 8; k++)
      wgmma_rs_64<1, 1, 1>(d1, gs[4 * k], gs[4 * k + 1], gs[4 * k + 2], gs[4 * k + 3], mk_desc(R0 + wg * 16384, 32768 + k * 2048, 0, 1024, 1), k);
    wg_commit();
    fence_async();
    mbar_wait(barF, 0);
    mbar_wait(barF + 16, 0);
    __syncthreads();
    wg_fence();
#pragma unroll
    for (int i = 0; i < 4; i++) {
      const int kc = (i >> 2) * 2, s = i & 3;
      wgmma_ss_128<1, 1, 0, 1>(e, mk_desc(R2, kc * 8192 + s * 32, 0, 1024, 1),
                               mk_desc(R1 + wg * 16384, kc * 32768 + s * 2048, 8192, 1024, 1), i);
    }
    wg_commit();
    if (tid == 128) {
      mbar_expect(barO, 32768);
      tma_ld3<0>(R0, &mwo, barO, 0, 0, 0);
    }
    wg_wait<1>();
    reg_fence(d1);
#pragma unroll
    for (int i = 0; i < 8; i++) d1[i] = gelu(d1[i]);
    {
      reg_fence(d1);
      mbar_wait(barF + 16, 0);
      wg_fence();
#pragma unroll
      for (int s = 0; s < 4; s++)
        wgmma_ss_128<1, 1, 0, 1>(e, mk_desc(R2, 2 * 8192 + s * 32, 0, 1024, 1), mk_desc(R1 + wg * 16384, 2 * 32768 + s * 2048, 8192, 1024, 1), 1);
      wg_commit();
    }
#pragma unroll
    for (int i = 8; i < 32; i++) d1[i] = gelu(d1[i]);
    store_tile_64(d1, R2 + wg * 16384 + 8192, warp, lane);
    fence_async();
    mbar_wait(barF + 8, 0);
    mbar_wait(barF + 24, 0);
    __syncthreads();
    if (tid == 128) {
      mbar_expect(barO + 8, 32768);
      tma_ld3<0>(R0 + 32768, &mwo, barO + 8, 0, 64, 0);
    }
    if (wg == 1) bar_sync(4, 256);
    wg_fence();
#pragma unroll
    for (int i = 0; i < 8; i++) {
      const int kc = (i >> 2) * 2 + 1, s = i & 3;
      wgmma_ss_128<1, 1, 0, 1>(e, mk_desc(R2, kc * 8192 + s * 32, 0, 1024, 1),
                               mk_desc(R1 + wg * 16384, kc * 32768 + s * 2048, 8192, 1024, 1), 1);
    }
    wg_commit();
    if (wg == 0) bar_arrive(4, 256);
    wg_wait<1>();
    if (lane == 0) mbar_arrive(barA);
    if (tid == 128) {
      mbar_wait(barA, 0);
      for (int kc = 2; kc < 4; kc++) {
        mbar_expect(barO + 8 * kc, 32768);
        tma_ld3<0>(R1 + (kc - 2) * 65536, &mwo, barO + 8 * kc, 0, kc * 64, 0);
      }
    }
    mbar_wait(barA, 0);
    asm volatile("st.shared.v4.u32 [%0], {%1, %2, %3, %4};" ::"r"(R2 + wg * 4096 + ((t * 16) ^ (wg * 512))), "r"(gev0.x), "r"(gev0.y), "r"(gev0.z), "r"(gev0.w) : "memory");
    asm volatile("st.shared.v4.u32 [%0], {%1, %2, %3, %4};" ::"r"(R2 + wg * 4096 + 2048 + ((t * 16) ^ (wg * 512))), "r"(gev1.x), "r"(gev1.y), "r"(gev1.z), "r"(gev1.w) : "memory");
    bar_sync(1 + wg, 128);
    g0 = lds128(gp);
    g1 = lds128(gp + 64);
    wg_wait<0>();
    reg_fence(e);
#pragma unroll
    for (int i = 0; i < 32; i++) fe[i] = pack2(e[2 * i], e[2 * i + 1]);
  }
  auto publish = [&]() {
    bar_sync(1 + wg, 128);
    const int row = warp * 16 + (lane & 7) + ((lane >> 3) & 1) * 8;
    const uint32_t xb = R1 + (wg == 0 ? 3 * 32768 : 32768 + 16384) + row * 128;
#pragma unroll
    for (int s = 0; s < 8; s++) {
      const int jj = 2 * s + (lane >> 4);
      stsm4(xb + (s >> 2) * 8192 + (((jj & 7) ^ (lane & 7)) << 4), fe[4 * s], fe[4 * s + 1], fe[4 * s + 2], fe[4 * s + 3]);
    }
    bar_arrive(5 + wg, 256);
  };
  if (wg == 1) publish();
  const uint32_t stg = R1 + 32768 + wg * 65536;
  const uint32_t w0 = sb + wg * 65536, w1 = sb + 32768 + wg * 98304, w2 = sb + 65536 - wg * 65536, w3 = sb + 131072 - wg * 98304;
  float acc[128];
  uint32_t j0[8], j1[8], j2[8], j3[8];
  uint4 h0 = lds128(gp + 128), h1 = lds128(gp + 192);
#define E_PAIR(J, K, F, G, BAR)             \
  joint_group(J, fe + (F), g0, g1);         \
  if (ui == 0) mbar_wait(BAR, 0);           \
  joint_group(K, fe + (F) + 8, h0, h1);     \
  g0 = lds128(gp + (G));                    \
  g1 = lds128(gp + (G) + 64);
  {
    const int ui = 0;
    E_PAIR(j0, j1, 0, 256, barO + 16 * wg)
    mbar_wait(barO + 16 * wg, 0);
  }
#define E_MMA4(J, K, W, FIRSTK, G, NEXTBAR)                                                     \
  wg_fence();                                                                                   \
  wgmma_rs_256<1, 1, 1>(acc, J[0], J[1], J[2], J[3], mk_desc(W, 0, 8192, 1024, 1), FIRSTK);     \
  wgmma_rs_256<1, 1, 1>(acc, J[4], J[5], J[6], J[7], mk_desc(W, 2048, 8192, 1024, 1), 1);       \
  wgmma_rs_256<1, 1, 1>(acc, K[0], K[1], K[2], K[3], mk_desc(W, 4096, 8192, 1024, 1), 1);       \
  wgmma_rs_256<1, 1, 1>(acc, K[4], K[5], K[6], K[7], mk_desc(W, 6144, 8192, 1024, 1), 1);       \
  wg_commit();                                                                                  \
  if ((ui + wg == 0 ? E_EARLY0 : E_EARLY) == (G) && (ui < 3 || wg == 0)) bar_arrive(4 - wg, 256); \
  wg_wait<1>();                                                                                 \
  h0 = lds128(gp + 256 * (G) + 384);                                                            \
  h1 = lds128(gp + 256 * (G) + 448);                                                            \
  if (ui == 0) mbar_wait(NEXTBAR, 0);
  const uint32_t bo0 = barO + 16 * wg, bo2 = barO + 16 * (1 - wg);
#pragma unroll 1
  for (int ui = 0; ui < 4; ui++) {
    if (ui > 0 || wg == 1) bar_sync(3 + wg, 256);
    E_MMA4(j0, j1, w0, 0, 0, bo0)
    E_PAIR(j2, j3, 16, 512, bo0 + 8)
    E_MMA4(j2, j3, w1, 1, 1, bo0 + 8)
    if (ui == 0) {
      if (wg == 0) publish();
      bar_sync(6 - wg, 256);
      const int row = warp * 16 + (lane & 7) + ((lane >> 3) & 1) * 8;
      const uint32_t xb = R1 + (wg == 1 ? 3 * 32768 : 32768 + 16384) + row * 128;
#pragma unroll
      for (int s = 0; s < 8; s++) {
        const int jj = 2 * s + (lane >> 4);
        ldsm4(xb + (s >> 2) * 8192 + (((jj & 7) ^ (lane & 7)) << 4), fe[32 + 4 * s], fe[33 + 4 * s], fe[34 + 4 * s], fe[35 + 4 * s]);
      }
    }
    E_PAIR(j0, j1, 32, 768, bo2)
    E_MMA4(j0, j1, w2, 1, 2, bo2)
    E_PAIR(j2, j3, 48, 1024, bo2 + 8)
    E_MMA4(j2, j3, w3, 1, 3, bo2 + 8)
    gp += 1024;
    if (ui < 3) {
      E_PAIR(j0, j1, 0, 256, bo2 + 8)
    }
    if (t == 0) bulk_wait_read<0>();
    bar_sync(1 + wg, 128);
    wg_wait<0>();
    reg_fence(acc);
    const uint32_t rb = stg + (warp * 16 + (lane & 7) + ((lane >> 3) & 1) * 8) * 128;
#pragma unroll
    for (int h = 0; h < 2; h++) {
#pragma unroll
      for (int j = 16 * h; j < 16 * h + 16; j += 2) {
        const int jj = j + (lane >> 4);
        stsm4(rb + (j >> 3) * 8192 + (((jj & 7) ^ (lane & 7)) << 4), pack2(acc[4 * j], acc[4 * j + 1]), pack2(acc[4 * j + 2], acc[4 * j + 3]),
              pack2(acc[4 * j + 4], acc[4 * j + 5]), pack2(acc[4 * j + 6], acc[4 * j + 7]));
      }
      fence_async();
      bar_sync(1 + wg, 128);
      if (t == 0) {
        tma_st5<1>(&mout, stg + h * 16384, 0, t0, 2 * h, wg * 4 + ui, b);
        bulk_commit();
      }
    }
  }
  if (t == 0) bulk_wait_read<0>();
}

typedef CUresult (*EncodeFn)(CUtensorMap*, CUtensorMapDataType, cuuint32_t, void*, const cuuint64_t*, const cuuint64_t*,
                             const cuuint32_t*, const cuuint32_t*, CUtensorMapInterleave, CUtensorMapSwizzle,
                             CUtensorMapL2promotion, CUtensorMapFloatOOBfill);

CUtensorMap make_map(EncodeFn fn, const void* base, int rank, const uint64_t* dims, const uint64_t* strides, const uint32_t* box,
                     CUtensorMapSwizzle swz) {
  CUtensorMap m;
  cuuint64_t gd[5], gs[4];
  cuuint32_t bx[5], es[5];
  for (int i = 0; i < rank; i++) { gd[i] = dims[i]; bx[i] = box[i]; es[i] = 1; }
  for (int i = 0; i + 1 < rank; i++) gs[i] = strides[i];
  fn(&m, CU_TENSOR_MAP_DATA_TYPE_BFLOAT16, rank, const_cast<void*>(base), gd, gs, bx, es, CU_TENSOR_MAP_INTERLEAVE_NONE, swz,
     CU_TENSOR_MAP_L2_PROMOTION_NONE, CU_TENSOR_MAP_FLOAT_OOB_FILL_NONE);
  return m;
}

template <typename... KArgs, typename... Args>
void launch(void (*k)(KArgs...), int grid, int block, int smem, bool pdl, Args... args) {
  cudaLaunchConfig_t c = {};
  c.gridDim = dim3(grid);
  c.blockDim = dim3(block);
  c.dynamicSmemBytes = smem;
  c.stream = cudaStreamPerThread;
  cudaLaunchAttribute at[1];
  at[0].id = cudaLaunchAttributeProgrammaticStreamSerialization;
  at[0].val.programmaticStreamSerializationAllowed = 1;
  c.attrs = at;
  c.numAttrs = pdl ? 1 : 0;
  cudaLaunchKernelEx(&c, k, args...);
}

}

static uint32_t h_plan[67 + 25] = {
    0x6108, 0x6109, 0x610a, 0x610b, 0x6101, 0x8008, 0x8109, 0x820a, 0x830b, 0x8401,
    0x8508, 0x6102, 0x8609, 0x870a, 0x880b, 0x6103, 0x8a08, 0x8b02, 0x8c09, 0x8d0a,
    0x8e0b, 0x8f03, 0x9008, 0x9209, 0x930a, 0x9503, 0x9608, 0x9709, 0x980a, 0x9a08,
    0x9b09, 0x9c0a, 0x61616115, 0x6161610d, 0x61616107, 0x83816166, 0x8986610c, 0x8a89314d, 0x8f8a3237, 0x938f940b,
    0x9393344c, 0x9993354d, 0x0, 0x0, 0x0, 0x0, 0x0, 0x0, 0x6161ba98, 0x6161a981,
    0x6789281b, 0x67893ba9, 0x6891a928, 0x6891983b, 0x6999983a, 0x6999a98a, 0x39389d, 0x3, 0x4, 0x1dcc17b8,
    0x8f6a0c52, 0xac1, 0x2e5a9261, 0x194a, 0x9e, 0x9f, 0x37, 0x0, 0x0, 0x0,
    0x10, 0x11, 0x13, 0x14, 0x0, 0x0, 0x0, 0x0, 0x0, 0x0,
    0x0, 0x0, 0x0, 0x431, 0x431, 0x431, 0x0, 0x133, 0x131, 0x331,
    0x0, 0x3,
};

extern "C" void kernel_launch(void* const* d_in, const int* in_sizes, int n_in, void* d_out, int out_size) {
  const __nv_bfloat16* x = (const __nv_bfloat16*)d_in[0];
  const __nv_bfloat16* w1 = (const __nv_bfloat16*)d_in[1];
  const __nv_bfloat16* w2 = (const __nv_bfloat16*)d_in[2];
  const __nv_bfloat16* g = (const __nv_bfloat16*)d_in[3];
  const __nv_bfloat16* wf = (const __nv_bfloat16*)d_in[4];
  const __nv_bfloat16* wgt = (const __nv_bfloat16*)d_in[5];
  const __nv_bfloat16* wo = (const __nv_bfloat16*)d_in[6];

  void* fp = nullptr;
  cudaDriverEntryPointQueryResult qr;
  cudaGetDriverEntryPoint("cuTensorMapEncodeTiled", &fp, cudaEnableDefault, &qr);
  EncodeFn fn = (EncodeFn)fp;
  void *X1, *W2, *Y1, *X2, *Y2;
  cudaGetSymbolAddress(&X1, g_X1);
  cudaGetSymbolAddress(&W2, g_W2);
  cudaGetSymbolAddress(&Y1, g_Y1);
  cudaGetSymbolAddress(&X2, g_X2);
  cudaGetSymbolAddress(&Y2, g_Y2);
  cudaFuncSetAttribute(k1, cudaFuncAttributeMaxDynamicSharedMemorySize, K1_SMEM);
  cudaFuncSetAttribute(k2, cudaFuncAttributeMaxDynamicSharedMemorySize, K2_SMEM);
  cudaFuncSetAttribute(kE, cudaFuncAttributeMaxDynamicSharedMemorySize, E_SMEM);
  if (ALIAS) {
    W2 = d_out;
    X2 = (char*)d_out + sizeof(g_W2);
    X1 = (char*)X2 - sizeof(g_X2);
    Y2 = Y1;
  }
  const CUtensorMapSwizzle S128 = CU_TENSOR_MAP_SWIZZLE_128B;

  auto map_x = [&]() {
    uint64_t d[] = {64, 8000, 8, 2}, s[] = {1024, 128, 8000ull * 1024};
    uint32_t bx[] = {64, 56, 1, 1};
    return make_map(fn, x, 4, d, s, bx, S128);
  };
  auto map_w_in = [&](const __nv_bfloat16* w, int odd) {
    uint64_t d[] = {64, (uint64_t)(odd ? 15 : 16), 4, 256}, s[] = {2ull * 65536 * 2, 128, 512};
    uint32_t bx[] = {64, 16, 2, 1};
    return make_map(fn, w + (odd ? 65536 : 0), 4, d, s, bx, S128);
  };
  auto map_X_st = [&](void* p, int nb, int boxb) {
    uint64_t d[] = {64, 512, (uint64_t)(2 * nb)}, s[] = {2ull * nb * 128, 128};
    uint32_t bx[] = {64, C_PC, (uint32_t)boxb};
    return make_map(fn, p, 3, d, s, bx, S128);
  };
  auto map_X1_st = [&]() {
    uint64_t d[] = {64, 512, 2, (uint64_t)NB1}, s[] = {2ull * NB1 * 128, (uint64_t)NB1 * 128, 128};
    uint32_t bx[] = {64, 16, 1, 1};
    return make_map(fn, X1, 4, d, s, bx, S128);
  };
  auto map_W_st = [&](void* p) {
    uint64_t d[] = {64, 512, 4, 64}, s[] = {32768, 8192, 128};
    uint32_t bx[] = {64, W2_PC < 64 ? W2_PC : 64, W2_PC == 128 ? 2 : 1, 1};
    return make_map(fn, p, 4, d, s, bx, S128);
  };
  auto map_W_ld = [&](void* p, uint32_t bd, uint32_t bf) {
    uint64_t d[] = {64, 64, 4, 512}, s[] = {128, 8192, 32768};
    uint32_t bx[] = {64, 32, bd, bf};
    return make_map(fn, p, 4, d, s, bx, S128);
  };
  auto map_Y_st = [&](void* p, int nb, int rows) {
    uint64_t d[] = {64, (uint64_t)(2 * nb), 64, 4}, s[] = {32768, 128, 8192};
    uint32_t bx[] = {64, (uint32_t)rows, 1, 1};
    return make_map(fn, p, 4, d, s, bx, S128);
  };
  auto map_Y_ld = [&](void* p, int nb, int boxc, int boxb) {
    uint64_t d[] = {64, 64, 4, (uint64_t)nb, 2}, s[] = {128, 8192, 32768, (uint64_t)nb * 32768};
    uint32_t bx[] = {64, 64, (uint32_t)boxc, (uint32_t)boxb, 1};
    return make_map(fn, p, 5, d, s, bx, S128);
  };
  auto map_wsq = [&](const __nv_bfloat16* w) {
    uint64_t d[] = {64, 256, 4}, s[] = {512, 128};
    uint32_t bx[] = {64, 64, 4};
    return make_map(fn, w, 3, d, s, bx, S128);
  };
  auto map_out = [&]() {
    uint64_t d[] = {64, 4000, 4, 8, 2}, s[] = {4096, 128, 512, 4000ull * 4096};
    uint32_t bx[] = {64, 64, 2, 1, 1};
    return make_map(fn, d_out, 5, d, s, bx, S128);
  };

  auto map_w_raw = [&](const __nv_bfloat16* w, int odd) {
    uint64_t d[] = {256, (uint64_t)(odd ? 15 : 16), 16, 16}, s[] = {2ull * 65536 * 2, 512, 8192};
    uint32_t bx[] = {64, 16, 4, 2};
    return make_map(fn, w + (odd ? 65536 : 0), 4, d, s, bx, S128);
  };
  Ptrs gp;
  cudaGetSymbolAddress((void**)&gp.done, g_done);
  cudaGetSymbolAddress((void**)&gp.ge, g_ge);
  cudaGetSymbolAddress((void**)&gp.img, c_img);
  cudaGetSymbolAddress((void**)&gp.ga, c_ga);
  K1Maps g1;
  memcpy(&g1.p, h_plan, sizeof(Plan));
  g1.x = map_x();
  g1.we = map_w_raw(w1, 0);
  g1.wo = map_w_raw(w1, 1);
  g1.xs = map_X1_st();
  g1.y = map_Y_st(Y1, NB1, NB1 / G_EPI);
  g1.w2e = map_w_in(w2, 0);
  g1.w2o = map_w_in(w2, 1);
  g1.w2s = map_W_st(W2);
  for (int s = 0; s < 32; s++) {
    const int k = s < G_S0 ? s >> 1 : G_KM + (s - G_S0) % G_TK;
    g1.slot[s] = g_off(g_slot(s)) / 16;
    g1.src[s] = ((k >> 1) * 256 + (k & 1) * 2 + (s < G_S0 ? (s & 1) * 4 : s >= G_S0 + G_TK)) * (G_ST / 2);
    g1.dep[s] = s < 3 ? 8 * h_plan[64 + s] : 1536 + 8 * (s - g_depth(s));
  }
  launch(k1, 132, 384, K1_SMEM, false, gp, (const char*)X1, (const char*)w1, g1, g, wgt);
  K2Maps g2;
  memcpy(&g2, h_plan + 67, 100);
  g2.y = map_Y_ld(Y1, NB1, 1, 1);
  g2.xs = map_X_st(X2, NB2, 1);
  {
    uint64_t d[] = {64, 256, 2, 2 * NB2}, s[] = {2ull * NB2 * 128, 512ull * NB2 * 128, 128};
    uint32_t bx[] = {64, 64, 2, 1};
    g2.xa = make_map(fn, X2, 4, d, s, bx, S128);
  }
  g2.w = map_W_ld(W2, 1, 2);
  g2.y2 = map_Y_st(Y2, NB2, 168 / H_EPI);
  launch(k2, 128, 512, K2_SMEM, true, gp, (const char*)X2, g2, wf, wo);
  launch(kE, 126, 256, E_SMEM, true, map_Y_ld(Y2, NB2, 1, 2), map_wsq(wf), map_wsq(wo), map_out());
}
```

```cpp
#include <cuda_runtime.h>
#include <cuda_bf16.h>
#include <cuda.h>
#include <stdint.h>
#include <string.h>
#include <type_traits>

#define ALIAS 1
namespace {

constexpr int NB1 = 168;
constexpr int NB2 = 84;

__device__ __align__(1024) __nv_bfloat16 g_X1[8 * 64 * 2 * NB1 * 64];
__device__ __align__(1024) __nv_bfloat16 g_W2[8 * 64 * 4 * 64 * 64];
__device__ __align__(1024) __nv_bfloat16 g_Y1[2 * NB1 * 4 * 64 * 64];
__device__ __align__(1024) __nv_bfloat16 g_X2[8 * 64 * 2 * NB2 * 64];
__device__ __align__(1024) __nv_bfloat16 g_Y2[2 * NB2 * 4 * 64 * 64];
__device__ __align__(1024) float g_ge[16 * 256];

__device__ __forceinline__ uint32_t s2u(const void* p) { return (uint32_t)__cvta_generic_to_shared(p); }
__device__ __forceinline__ void mbar_init(uint32_t b, int c) {
  asm volatile("mbarrier.init.shared::cta.b64 [%0], %1;" ::"r"(b), "r"(c) : "memory");
}
__device__ __forceinline__ void mbar_expect(uint32_t b, int bytes) {
  asm volatile("mbarrier.arrive.expect_tx.shared::cta.b64 _, [%0], %1;" ::"r"(b), "r"(bytes) : "memory");
}
__device__ __forceinline__ void mbar_arrive(uint32_t b) {
  asm volatile("mbarrier.arrive.shared::cta.b64 _, [%0];" ::"r"(b) : "memory");
}
__device__ __forceinline__ void mbar_arrive_cta(uint32_t b, uint32_t cta) {
  asm volatile("{\n.reg .b32 r;\nmapa.shared::cluster.u32 r, %0, %1;\nmbarrier.arrive.shared::cluster.b64 _, [r];\n}" ::"r"(b), "r"(cta) : "memory");
}
__device__ __forceinline__ void mbar_wait(uint32_t b, int ph) {
  asm volatile(
      "{\n.reg .pred p;\n.reg .u32 n;\n"
      "mov.u32 n, 0;\n"
      "MBW_LOOP:\n"
      "mbarrier.try_wait.parity.shared::cta.b64 p, [%0], %1;\n"
      "@p bra MBW_DONE;\n"
      "add.u32 n, n, 1;\n"
      "setp.lt.u32 p, n, 1048576;\n"
      "@p bra MBW_LOOP;\n"
      "MBW_DONE:\n}" ::"r"(b), "r"(ph) : "memory");
}
__device__ __forceinline__ void fence_bar_init() { asm volatile("fence.mbarrier_init.release.cluster;" ::: "memory"); }
__device__ __forceinline__ void fence_async() { asm volatile("fence.proxy.async.shared::cta;" ::: "memory"); }
__device__ __forceinline__ void bar_sync(int id, int n) { asm volatile("bar.sync %0, %1;" ::"r"(id), "r"(n) : "memory"); }
__device__ __forceinline__ void bar_arrive(int id, int n) { asm volatile("bar.arrive %0, %1;" ::"r"(id), "r"(n) : "memory"); }
__device__ __forceinline__ void pdl_wait() { asm volatile("griddepcontrol.wait;" ::: "memory"); }
__device__ __forceinline__ void pdl_launch() { asm volatile("griddepcontrol.launch_dependents;" ::: "memory"); }
__device__ __forceinline__ void prefetch_map(const CUtensorMap* m) {
  asm volatile("prefetch.tensormap [%0];" ::"l"(m) : "memory");
}
template <int P> __device__ __forceinline__ uint64_t policy() {
  uint64_t p;
  asm("createpolicy.fractional.L2::evict_first.b64 %0, 1.0;" : "=l"(p));
  return p;
}
template <int P> __device__ __forceinline__ void tma_ld3(uint32_t dst, const CUtensorMap* m, uint32_t bar, int c0, int c1, int c2) {
  if constexpr (P == 0)
    asm volatile("cp.async.bulk.tensor.3d.shared::cluster.global.mbarrier::complete_tx::bytes [%0], [%1, {%3, %4, %5}], [%2];"
                 ::"r"(dst), "l"(m), "r"(bar), "r"(c0), "r"(c1), "r"(c2) : "memory");
  else
    asm volatile("cp.async.bulk.tensor.3d.shared::cluster.global.mbarrier::complete_tx::bytes.L2::cache_hint [%0], [%1, {%3, %4, %5}], [%2], %6;"
                 ::"r"(dst), "l"(m), "r"(bar), "r"(c0), "r"(c1), "r"(c2), "l"(policy<P>()) : "memory");
}
template <int P> __device__ __forceinline__ void tma_ld4(uint32_t dst, const CUtensorMap* m, uint32_t bar, int c0, int c1, int c2, int c3) {
  if constexpr (P == 0)
    asm volatile("cp.async.bulk.tensor.4d.shared::cluster.global.mbarrier::complete_tx::bytes [%0], [%1, {%3, %4, %5, %6}], [%2];"
                 ::"r"(dst), "l"(m), "r"(bar), "r"(c0), "r"(c1), "r"(c2), "r"(c3) : "memory");
  else
    asm volatile("cp.async.bulk.tensor.4d.shared::cluster.global.mbarrier::complete_tx::bytes.L2::cache_hint [%0], [%1, {%3, %4, %5, %6}], [%2], %7;"
                 ::"r"(dst), "l"(m), "r"(bar), "r"(c0), "r"(c1), "r"(c2), "r"(c3), "l"(policy<P>()) : "memory");
}
template <int P> __device__ __forceinline__ void tma_ld5(uint32_t dst, const CUtensorMap* m, uint32_t bar, int c0, int c1, int c2, int c3, int c4) {
  if constexpr (P == 0)
    asm volatile("cp.async.bulk.tensor.5d.shared::cluster.global.mbarrier::complete_tx::bytes [%0], [%1, {%3, %4, %5, %6, %7}], [%2];"
                 ::"r"(dst), "l"(m), "r"(bar), "r"(c0), "r"(c1), "r"(c2), "r"(c3), "r"(c4) : "memory");
  else
    asm volatile("cp.async.bulk.tensor.5d.shared::cluster.global.mbarrier::complete_tx::bytes.L2::cache_hint [%0], [%1, {%3, %4, %5, %6, %7}], [%2], %8;"
                 ::"r"(dst), "l"(m), "r"(bar), "r"(c0), "r"(c1), "r"(c2), "r"(c3), "r"(c4), "l"(policy<P>()) : "memory");
}
template <int P> __device__ __forceinline__ void tma_st3(const CUtensorMap* m, uint32_t src, int c0, int c1, int c2) {
  if constexpr (P == 0)
    asm volatile("cp.async.bulk.tensor.3d.global.shared::cta.bulk_group [%0, {%2, %3, %4}], [%1];" ::"l"(m), "r"(src), "r"(c0), "r"(c1), "r"(c2) : "memory");
  else
    asm volatile("cp.async.bulk.tensor.3d.global.shared::cta.bulk_group.L2::cache_hint [%0, {%2, %3, %4}], [%1], %5;" ::"l"(m), "r"(src), "r"(c0), "r"(c1), "r"(c2), "l"(policy<P>()) : "memory");
}
template <int P> __device__ __forceinline__ void tma_st4(const CUtensorMap* m, uint32_t src, int c0, int c1, int c2, int c3) {
  if constexpr (P == 0)
    asm volatile("cp.async.bulk.tensor.4d.global.shared::cta.bulk_group [%0, {%2, %3, %4, %5}], [%1];" ::"l"(m), "r"(src), "r"(c0), "r"(c1), "r"(c2), "r"(c3) : "memory");
  else
    asm volatile("cp.async.bulk.tensor.4d.global.shared::cta.bulk_group.L2::cache_hint [%0, {%2, %3, %4, %5}], [%1], %6;" ::"l"(m), "r"(src), "r"(c0), "r"(c1), "r"(c2), "r"(c3), "l"(policy<P>()) : "memory");
}
template <int P> __device__ __forceinline__ void tma_st5(const CUtensorMap* m, uint32_t src, int c0, int c1, int c2, int c3, int c4) {
  if constexpr (P == 0)
    asm volatile("cp.async.bulk.tensor.5d.global.shared::cta.bulk_group [%0, {%2, %3, %4, %5, %6}], [%1];" ::"l"(m), "r"(src), "r"(c0), "r"(c1), "r"(c2), "r"(c3), "r"(c4) : "memory");
  else
    asm volatile("cp.async.bulk.tensor.5d.global.shared::cta.bulk_group.L2::cache_hint [%0, {%2, %3, %4, %5, %6}], [%1], %7;" ::"l"(m), "r"(src), "r"(c0), "r"(c1), "r"(c2), "r"(c3), "r"(c4), "l"(policy<P>()) : "memory");
}
__device__ __forceinline__ void bulk_commit() { asm volatile("cp.async.bulk.commit_group;" ::: "memory"); }
template <int N> __device__ __forceinline__ void bulk_wait_read() { asm volatile("cp.async.bulk.wait_group.read %0;" ::"n"(N) : "memory"); }
__device__ __forceinline__ void wg_fence() { asm volatile("wgmma.fence.sync.aligned;" ::: "memory"); }
__device__ __forceinline__ void wg_commit() { asm volatile("wgmma.commit_group.sync.aligned;" ::: "memory"); }
template <int N> __device__ __forceinline__ void wg_wait() { asm volatile("wgmma.wait_group.sync.aligned %0;" ::"n"(N) : "memory"); }
template <int R> __device__ __forceinline__ void reg_fence(float (&d)[R]) {
#pragma unroll
  for (int i = 0; i < R; i++) asm volatile("" : "+f"(d[i])::"memory");
}
template <int R> __device__ __forceinline__ void reg_fence(uint32_t (&d)[R]) {
#pragma unroll
  for (int i = 0; i < R; i++) asm volatile("" : "+r"(d[i])::"memory");
}
__device__ __forceinline__ void stsm4(uint32_t a, uint32_t r0, uint32_t r1, uint32_t r2, uint32_t r3) {
  asm volatile("stmatrix.sync.aligned.m8n8.x4.shared.b16 [%0], {%1, %2, %3, %4};" ::"r"(a), "r"(r0), "r"(r1), "r"(r2), "r"(r3) : "memory");
}
__device__ __forceinline__ void stsm4t(uint32_t a, uint32_t r0, uint32_t r1, uint32_t r2, uint32_t r3) {
  asm volatile("stmatrix.sync.aligned.m8n8.x4.trans.shared.b16 [%0], {%1, %2, %3, %4};" ::"r"(a), "r"(r0), "r"(r1), "r"(r2), "r"(r3) : "memory");
}
__device__ __forceinline__ void ldsm4(uint32_t a, uint32_t& r0, uint32_t& r1, uint32_t& r2, uint32_t& r3) {
  asm volatile("ldmatrix.sync.aligned.m8n8.x4.shared.b16 {%0, %1, %2, %3}, [%4];" : "=r"(r0), "=r"(r1), "=r"(r2), "=r"(r3) : "r"(a) : "memory");
}
__device__ __forceinline__ void ldsm4t(uint32_t a, uint32_t& r0, uint32_t& r1, uint32_t& r2, uint32_t& r3) {
  asm volatile("ldmatrix.sync.aligned.m8n8.x4.trans.shared.b16 {%0, %1, %2, %3}, [%4];" : "=r"(r0), "=r"(r1), "=r"(r2), "=r"(r3) : "r"(a) : "memory");
}
__device__ __forceinline__ void ldg128(const uint4* p, uint32_t& a, uint32_t& b, uint32_t& c, uint32_t& d) {
  asm volatile("ld.global.nc.v4.u32 {%0, %1, %2, %3}, [%4];" : "=r"(a), "=r"(b), "=r"(c), "=r"(d) : "l"(p));
}
__device__ __forceinline__ uint32_t pack2(float lo, float hi) {
  uint32_t r;
  asm("cvt.rn.bf16x2.f32 %0, %1, %2;" : "=r"(r) : "f"(hi), "f"(lo));
  return r;
}
__device__ __forceinline__ float tanh_f32(float x) {
  float y;
  asm("tanh.approx.f32 %0, %1;" : "=f"(y) : "f"(x));
  return y;
}
__device__ __forceinline__ float gelu(float hx) {
  const float u = hx * fmaf(hx * hx, 8.0f * 0.044715f * 0.7978845608028654f, 2.0f * 0.7978845608028654f);
  return fmaf(hx, tanh_f32(u), hx);
}
__device__ __forceinline__ uint64_t mk_desc4(uint32_t addr4, uint32_t lbo, uint32_t sbo, uint32_t swz) {
  const uint32_t lo = addr4 + ((lbo >> 4) << 16), hi = (sbo >> 4) | (swz << 30);
  uint64_t d;
  asm("mov.b64 %0, {%1, %2};" : "=l"(d) : "r"(lo), "r"(hi));
  return d;
}
#define mk_desc(base, off, lbo, sbo, swz) mk_desc4((((base) & 0x3FFFF) >> 4) + ((off) >> 4), lbo, sbo, swz)

template <int SA, int SB, int TA, int TB>
__device__ __forceinline__ void wgmma_ss_48(float (&d)[24], uint64_t da, uint64_t db, int sd) {
  asm volatile("{\n.reg .pred p;\nsetp.ne.b32 p, %26, 0;\n"
      "wgmma.mma_async.sync.aligned.m64n48k16.f32.bf16.bf16 {"
      "%0, %1, %2, %3, %4, %5, %6, %7, %8, %9, %10, %11, %12, %13, %14, %15, %16, %17, %18, %19, %20, %21, %22, %23"
      "}, %24, %25, p, %27, %28, %29, %30;\n}\n"
      : "+f"(d[0]), "+f"(d[1]), "+f"(d[2]), "+f"(d[3]), "+f"(d[4]), "+f"(d[5]), "+f"(d[6]), "+f"(d[7]), "+f"(d[8]),
        "+f"(d[9]), "+f"(d[10]), "+f"(d[11]), "+f"(d[12]), "+f"(d[13]), "+f"(d[14]), "+f"(d[15]), "+f"(d[16]),
        "+f"(d[17]), "+f"(d[18]), "+f"(d[19]), "+f"(d[20]), "+f"(d[21]), "+f"(d[22]), "+f"(d[23])
      : "l"(da), "l"(db), "r"(sd), "n"(SA), "n"(SB), "n"(TA), "n"(TB));
}
template <int SA, int SB, int TA, int TB>
__device__ __forceinline__ void wgmma_ss_128(float (&d)[64], uint64_t da, uint64_t db, int sd) {
  asm volatile("{\n.reg .pred p;\nsetp.ne.b32 p, %66, 0;\n"
      "wgmma.mma_async.sync.aligned.m64n128k16.f32.bf16.bf16 {"
      "%0, %1, %2, %3, %4, %5, %6, %7, %8, %9, %10, %11, %12, %13, %14, %15, %16, %17, %18, %19, %20, %21, %22, %23, "
      "%24, %25, %26, %27, %28, %29, %30, %31, %32, %33, %34, %35, %36, %37, %38, %39, %40, %41, %42, %43, %44, %45, "
      "%46, %47, %48, %49, %50, %51, %52, %53, %54, %55, %56, %57, %58, %59, %60, %61, %62, %63"
      "}, %64, %65, p, %67, %68, %69, %70;\n}\n"
      : "+f"(d[0]), "+f"(d[1]), "+f"(d[2]), "+f"(d[3]), "+f"(d[4]), "+f"(d[5]), "+f"(d[6]), "+f"(d[7]), "+f"(d[8]),
        "+f"(d[9]), "+f"(d[10]), "+f"(d[11]), "+f"(d[12]), "+f"(d[13]), "+f"(d[14]), "+f"(d[15]), "+f"(d[16]),
        "+f"(d[17]), "+f"(d[18]), "+f"(d[19]), "+f"(d[20]), "+f"(d[21]), "+f"(d[22]), "+f"(d[23]), "+f"(d[24]),
        "+f"(d[25]), "+f"(d[26]), "+f"(d[27]), "+f"(d[28]), "+f"(d[29]), "+f"(d[30]), "+f"(d[31]), "+f"(d[32]),
        "+f"(d[33]), "+f"(d[34]), "+f"(d[35]), "+f"(d[36]), "+f"(d[37]), "+f"(d[38]), "+f"(d[39]), "+f"(d[40]),
        "+f"(d[41]), "+f"(d[42]), "+f"(d[43]), "+f"(d[44]), "+f"(d[45]), "+f"(d[46]), "+f"(d[47]), "+f"(d[48]),
        "+f"(d[49]), "+f"(d[50]), "+f"(d[51]), "+f"(d[52]), "+f"(d[53]), "+f"(d[54]), "+f"(d[55]), "+f"(d[56]),
        "+f"(d[57]), "+f"(d[58]), "+f"(d[59]), "+f"(d[60]), "+f"(d[61]), "+f"(d[62]), "+f"(d[63])
      : "l"(da), "l"(db), "r"(sd), "n"(SA), "n"(SB), "n"(TA), "n"(TB));
}
template <int SA, int SB, int TA, int TB>
__device__ __forceinline__ void wgmma_ss_168(float (&d)[84], uint64_t da, uint64_t db, int sd) {
  asm volatile("{\n.reg .pred p;\nsetp.ne.b32 p, %86, 0;\n"
      "wgmma.mma_async.sync.aligned.m64n168k16.f32.bf16.bf16 {"
      "%0, %1, %2, %3, %4, %5, %6, %7, %8, %9, %10, %11, %12, %13, %14, %15, %16, %17, %18, %19, %20, %21, %22, %23, "
      "%24, %25, %26, %27, %28, %29, %30, %31, %32, %33, %34, %35, %36, %37, %38, %39, %40, %41, %42, %43, %44, %45, "
      "%46, %47, %48, %49, %50, %51, %52, %53, %54, %55, %56, %57, %58, %59, %60, %61, %62, %63, %64, %65, %66, %67, "
      "%68, %69, %70, %71, %72, %73, %74, %75, %76, %77, %78, %79, %80, %81, %82, %83"
      "}, %84, %85, p, %87, %88, %89, %90;\n}\n"
      : "+f"(d[0]), "+f"(d[1]), "+f"(d[2]), "+f"(d[3]), "+f"(d[4]), "+f"(d[5]), "+f"(d[6]), "+f"(d[7]), "+f"(d[8]),
        "+f"(d[9]), "+f"(d[10]), "+f"(d[11]), "+f"(d[12]), "+f"(d[13]), "+f"(d[14]), "+f"(d[15]), "+f"(d[16]),
        "+f"(d[17]), "+f"(d[18]), "+f"(d[19]), "+f"(d[20]), "+f"(d[21]), "+f"(d[22]), "+f"(d[23]), "+f"(d[24]),
        "+f"(d[25]), "+f"(d[26]), "+f"(d[27]), "+f"(d[28]), "+f"(d[29]), "+f"(d[30]), "+f"(d[31]), "+f"(d[32]),
        "+f"(d[33]), "+f"(d[34]), "+f"(d[35]), "+f"(d[36]), "+f"(d[37]), "+f"(d[38]), "+f"(d[39]), "+f"(d[40]),
        "+f"(d[41]), "+f"(d[42]), "+f"(d[43]), "+f"(d[44]), "+f"(d[45]), "+f"(d[46]), "+f"(d[47]), "+f"(d[48]),
        "+f"(d[49]), "+f"(d[50]), "+f"(d[51]), "+f"(d[52]), "+f"(d[53]), "+f"(d[54]), "+f"(d[55]), "+f"(d[56]),
        "+f"(d[57]), "+f"(d[58]), "+f"(d[59]), "+f"(d[60]), "+f"(d[61]), "+f"(d[62]), "+f"(d[63]), "+f"(d[64]),
        "+f"(d[65]), "+f"(d[66]), "+f"(d[67]), "+f"(d[68]), "+f"(d[69]), "+f"(d[70]), "+f"(d[71]), "+f"(d[72]),
        "+f"(d[73]), "+f"(d[74]), "+f"(d[75]), "+f"(d[76]), "+f"(d[77]), "+f"(d[78]), "+f"(d[79]), "+f"(d[80]),
        "+f"(d[81]), "+f"(d[82]), "+f"(d[83])
      : "l"(da), "l"(db), "r"(sd), "n"(SA), "n"(SB), "n"(TA), "n"(TB));
}
template <int SA, int SB, int TB>
__device__ __forceinline__ void wgmma_rs_32(float (&d)[16], uint32_t a0, uint32_t a1, uint32_t a2, uint32_t a3, uint64_t db, int sd) {
  asm volatile("{\n.reg .pred p;\nsetp.ne.b32 p, %21, 0;\n"
      "wgmma.mma_async.sync.aligned.m64n32k16.f32.bf16.bf16 {"
      "%0, %1, %2, %3, %4, %5, %6, %7, %8, %9, %10, %11, %12, %13, %14, %15"
      "}, {%16, %17, %18, %19}, %20, p, %22, %23, %24;\n}\n"
      : "+f"(d[0]), "+f"(d[1]), "+f"(d[2]), "+f"(d[3]), "+f"(d[4]), "+f"(d[5]), "+f"(d[6]), "+f"(d[7]), "+f"(d[8]),
        "+f"(d[9]), "+f"(d[10]), "+f"(d[11]), "+f"(d[12]), "+f"(d[13]), "+f"(d[14]), "+f"(d[15])
      : "r"(a0), "r"(a1), "r"(a2), "r"(a3), "l"(db), "r"(sd), "n"(SA), "n"(SB), "n"(TB));
}
template <int SA, int SB, int TB>
__device__ __forceinline__ void wgmma_rs_64(float (&d)[32], uint32_t a0, uint32_t a1, uint32_t a2, uint32_t a3, uint64_t db, int sd) {
  asm volatile("{\n.reg .pred p;\nsetp.ne.b32 p, %37, 0;\n"
      "wgmma.mma_async.sync.aligned.m64n64k16.f32.bf16.bf16 {"
      "%0, %1, %2, %3, %4, %5, %6, %7, %8, %9, %10, %11, %12, %13, %14, %15, %16, %17, %18, %19, %20, %21, %22, %23, "
      "%24, %25, %26, %27, %28, %29, %30, %31"
      "}, {%32, %33, %34, %35}, %36, p, %38, %39, %40;\n}\n"
      : "+f"(d[0]), "+f"(d[1]), "+f"(d[2]), "+f"(d[3]), "+f"(d[4]), "+f"(d[5]), "+f"(d[6]), "+f"(d[7]), "+f"(d[8]),
        "+f"(d[9]), "+f"(d[10]), "+f"(d[11]), "+f"(d[12]), "+f"(d[13]), "+f"(d[14]), "+f"(d[15]), "+f"(d[16]),
        "+f"(d[17]), "+f"(d[18]), "+f"(d[19]), "+f"(d[20]), "+f"(d[21]), "+f"(d[22]), "+f"(d[23]), "+f"(d[24]),
        "+f"(d[25]), "+f"(d[26]), "+f"(d[27]), "+f"(d[28]), "+f"(d[29]), "+f"(d[30]), "+f"(d[31])
      : "r"(a0), "r"(a1), "r"(a2), "r"(a3), "l"(db), "r"(sd), "n"(SA), "n"(SB), "n"(TB));
}
template <int SA, int SB, int TB>
__device__ __forceinline__ void wgmma_rs_128(float (&d)[64], uint32_t a0, uint32_t a1, uint32_t a2, uint32_t a3, uint64_t db, int sd) {
  asm volatile("{\n.reg .pred p;\nsetp.ne.b32 p, %69, 0;\n"
      "wgmma.mma_async.sync.aligned.m64n128k16.f32.bf16.bf16 {"
      "%0, %1, %2, %3, %4, %5, %6, %7, %8, %9, %10, %11, %12, %13, %14, %15, %16, %17, %18, %19, %20, %21, %22, %23, "
      "%24, %25, %26, %27, %28, %29, %30, %31, %32, %33, %34, %35, %36, %37, %38, %39, %40, %41, %42, %43, %44, %45, "
      "%46, %47, %48, %49, %50, %51, %52, %53, %54, %55, %56, %57, %58, %59, %60, %61, %62, %63"
      "}, {%64, %65, %66, %67}, %68, p, %70, %71, %72;\n}\n"
      : "+f"(d[0]), "+f"(d[1]), "+f"(d[2]), "+f"(d[3]), "+f"(d[4]), "+f"(d[5]), "+f"(d[6]), "+f"(d[7]), "+f"(d[8]),
        "+f"(d[9]), "+f"(d[10]), "+f"(d[11]), "+f"(d[12]), "+f"(d[13]), "+f"(d[14]), "+f"(d[15]), "+f"(d[16]),
        "+f"(d[17]), "+f"(d[18]), "+f"(d[19]), "+f"(d[20]), "+f"(d[21]), "+f"(d[22]), "+f"(d[23]), "+f"(d[24]),
        "+f"(d[25]), "+f"(d[26]), "+f"(d[27]), "+f"(d[28]), "+f"(d[29]), "+f"(d[30]), "+f"(d[31]), "+f"(d[32]),
        "+f"(d[33]), "+f"(d[34]), "+f"(d[35]), "+f"(d[36]), "+f"(d[37]), "+f"(d[38]), "+f"(d[39]), "+f"(d[40]),
        "+f"(d[41]), "+f"(d[42]), "+f"(d[43]), "+f"(d[44]), "+f"(d[45]), "+f"(d[46]), "+f"(d[47]), "+f"(d[48]),
        "+f"(d[49]), "+f"(d[50]), "+f"(d[51]), "+f"(d[52]), "+f"(d[53]), "+f"(d[54]), "+f"(d[55]), "+f"(d[56]),
        "+f"(d[57]), "+f"(d[58]), "+f"(d[59]), "+f"(d[60]), "+f"(d[61]), "+f"(d[62]), "+f"(d[63])
      : "r"(a0), "r"(a1), "r"(a2), "r"(a3), "l"(db), "r"(sd), "n"(SA), "n"(SB), "n"(TB));
}
template <int SA, int SB, int TB>
__device__ __forceinline__ void wgmma_rs_168(float (&d)[84], uint32_t a0, uint32_t a1, uint32_t a2, uint32_t a3, uint64_t db, int sd) {
  asm volatile("{\n.reg .pred p;\nsetp.ne.b32 p, %89, 0;\n"
      "wgmma.mma_async.sync.aligned.m64n168k16.f32.bf16.bf16 {"
      "%0, %1, %2, %3, %4, %5, %6, %7, %8, %9, %10, %11, %12, %13, %14, %15, %16, %17, %18, %19, %20, %21, %22, %23, "
      "%24, %25, %26, %27, %28, %29, %30, %31, %32, %33, %34, %35, %36, %37, %38, %39, %40, %41, %42, %43, %44, %45, "
      "%46, %47, %48, %49, %50, %51, %52, %53, %54, %55, %56, %57, %58, %59, %60, %61, %62, %63, %64, %65, %66, %67, "
      "%68, %69, %70, %71, %72, %73, %74, %75, %76, %77, %78, %79, %80, %81, %82, %83"
      "}, {%84, %85, %86, %87}, %88, p, %90, %91, %92;\n}\n"
      : "+f"(d[0]), "+f"(d[1]), "+f"(d[2]), "+f"(d[3]), "+f"(d[4]), "+f"(d[5]), "+f"(d[6]), "+f"(d[7]), "+f"(d[8]),
        "+f"(d[9]), "+f"(d[10]), "+f"(d[11]), "+f"(d[12]), "+f"(d[13]), "+f"(d[14]), "+f"(d[15]), "+f"(d[16]),
        "+f"(d[17]), "+f"(d[18]), "+f"(d[19]), "+f"(d[20]), "+f"(d[21]), "+f"(d[22]), "+f"(d[23]), "+f"(d[24]),
        "+f"(d[25]), "+f"(d[26]), "+f"(d[27]), "+f"(d[28]), "+f"(d[29]), "+f"(d[30]), "+f"(d[31]), "+f"(d[32]),
        "+f"(d[33]), "+f"(d[34]), "+f"(d[35]), "+f"(d[36]), "+f"(d[37]), "+f"(d[38]), "+f"(d[39]), "+f"(d[40]),
        "+f"(d[41]), "+f"(d[42]), "+f"(d[43]), "+f"(d[44]), "+f"(d[45]), "+f"(d[46]), "+f"(d[47]), "+f"(d[48]),
        "+f"(d[49]), "+f"(d[50]), "+f"(d[51]), "+f"(d[52]), "+f"(d[53]), "+f"(d[54]), "+f"(d[55]), "+f"(d[56]),
        "+f"(d[57]), "+f"(d[58]), "+f"(d[59]), "+f"(d[60]), "+f"(d[61]), "+f"(d[62]), "+f"(d[63]), "+f"(d[64]),
        "+f"(d[65]), "+f"(d[66]), "+f"(d[67]), "+f"(d[68]), "+f"(d[69]), "+f"(d[70]), "+f"(d[71]), "+f"(d[72]),
        "+f"(d[73]), "+f"(d[74]), "+f"(d[75]), "+f"(d[76]), "+f"(d[77]), "+f"(d[78]), "+f"(d[79]), "+f"(d[80]),
        "+f"(d[81]), "+f"(d[82]), "+f"(d[83])
      : "r"(a0), "r"(a1), "r"(a2), "r"(a3), "l"(db), "r"(sd), "n"(SA), "n"(SB), "n"(TB));
}
template <int SA, int SB, int TB>
__device__ __forceinline__ void wgmma_rs_256(float (&d)[128], uint32_t a0, uint32_t a1, uint32_t a2, uint32_t a3, uint64_t db, int sd) {
  asm volatile("{\n.reg .pred p;\nsetp.ne.b32 p, %133, 0;\n"
      "wgmma.mma_async.sync.aligned.m64n256k16.f32.bf16.bf16 {"
      "%0, %1, %2, %3, %4, %5, %6, %7, %8, %9, %10, %11, %12, %13, %14, %15, %16, %17, %18, %19, %20, %21, %22, %23, "
      "%24, %25, %26, %27, %28, %29, %30, %31, %32, %33, %34, %35, %36, %37, %38, %39, %40, %41, %42, %43, %44, %45, "
      "%46, %47, %48, %49, %50, %51, %52, %53, %54, %55, %56, %57, %58, %59, %60, %61, %62, %63, %64, %65, %66, %67, "
      "%68, %69, %70, %71, %72, %73, %74, %75, %76, %77, %78, %79, %80, %81, %82, %83, %84, %85, %86, %87, %88, %89, "
      "%90, %91, %92, %93, %94, %95, %96, %97, %98, %99, %100, %101, %102, %103, %104, %105, %106, %107, %108, %109, "
      "%110, %111, %112, %113, %114, %115, %116, %117, %118, %119, %120, %121, %122, %123, %124, %125, %126, %127"
      "}, {%128, %129, %130, %131}, %132, p, %134, %135, %136;\n}\n"
      : "+f"(d[0]), "+f"(d[1]), "+f"(d[2]), "+f"(d[3]), "+f"(d[4]), "+f"(d[5]), "+f"(d[6]), "+f"(d[7]), "+f"(d[8]),
        "+f"(d[9]), "+f"(d[10]), "+f"(d[11]), "+f"(d[12]), "+f"(d[13]), "+f"(d[14]), "+f"(d[15]), "+f"(d[16]),
        "+f"(d[17]), "+f"(d[18]), "+f"(d[19]), "+f"(d[20]), "+f"(d[21]), "+f"(d[22]), "+f"(d[23]), "+f"(d[24]),
        "+f"(d[25]), "+f"(d[26]), "+f"(d[27]), "+f"(d[28]), "+f"(d[29]), "+f"(d[30]), "+f"(d[31]), "+f"(d[32]),
        "+f"(d[33]), "+f"(d[34]), "+f"(d[35]), "+f"(d[36]), "+f"(d[37]), "+f"(d[38]), "+f"(d[39]), "+f"(d[40]),
        "+f"(d[41]), "+f"(d[42]), "+f"(d[43]), "+f"(d[44]), "+f"(d[45]), "+f"(d[46]), "+f"(d[47]), "+f"(d[48]),
        "+f"(d[49]), "+f"(d[50]), "+f"(d[51]), "+f"(d[52]), "+f"(d[53]), "+f"(d[54]), "+f"(d[55]), "+f"(d[56]),
        "+f"(d[57]), "+f"(d[58]), "+f"(d[59]), "+f"(d[60]), "+f"(d[61]), "+f"(d[62]), "+f"(d[63]), "+f"(d[64]),
        "+f"(d[65]), "+f"(d[66]), "+f"(d[67]), "+f"(d[68]), "+f"(d[69]), "+f"(d[70]), "+f"(d[71]), "+f"(d[72]),
        "+f"(d[73]), "+f"(d[74]), "+f"(d[75]), "+f"(d[76]), "+f"(d[77]), "+f"(d[78]), "+f"(d[79]), "+f"(d[80]),
        "+f"(d[81]), "+f"(d[82]), "+f"(d[83]), "+f"(d[84]), "+f"(d[85]), "+f"(d[86]), "+f"(d[87]), "+f"(d[88]),
        "+f"(d[89]), "+f"(d[90]), "+f"(d[91]), "+f"(d[92]), "+f"(d[93]), "+f"(d[94]), "+f"(d[95]), "+f"(d[96]),
        "+f"(d[97]), "+f"(d[98]), "+f"(d[99]), "+f"(d[100]), "+f"(d[101]), "+f"(d[102]), "+f"(d[103]), "+f"(d[104]),
        "+f"(d[105]), "+f"(d[106]), "+f"(d[107]), "+f"(d[108]), "+f"(d[109]), "+f"(d[110]), "+f"(d[111]),
        "+f"(d[112]), "+f"(d[113]), "+f"(d[114]), "+f"(d[115]), "+f"(d[116]), "+f"(d[117]), "+f"(d[118]),
        "+f"(d[119]), "+f"(d[120]), "+f"(d[121]), "+f"(d[122]), "+f"(d[123]), "+f"(d[124]), "+f"(d[125]),
        "+f"(d[126]), "+f"(d[127])
      : "r"(a0), "r"(a1), "r"(a2), "r"(a3), "l"(db), "r"(sd), "n"(SA), "n"(SB), "n"(TB));
}

__device__ const __align__(128) uint32_t c_img[3584] = {
    0x00003c80, 0x00003c80, 0x00003c80, 0x00003c80, 0x00003c80, 0x00003c80, 0x00003c80, 0x00003c80, 0x00003c80, 0x00003c80,
    0x00003c80, 0x00003c80, 0x00003c80, 0x00003c80, 0x00003c80, 0x00003c80, 0x00003c80, 0x00003c80, 0x00003c80, 0x00003c80,
    0x00003c80, 0x00003c80, 0x00003c80, 0x00003c80, 0x00003c80, 0x00003c80, 0x00003c80, 0x00003c80, 0x00003c80, 0x00003c80,
    0x00003c80, 0x00003c80, 0x3c463c22, 0x3c623bf1, 0x3c753b95, 0x3c7f3ac9, 0x3ac93c7f, 0x3b953c75, 0x3bf13c62, 0x3c223c46,
    0x3c22bc46, 0x3bf1bc62, 0x3b95bc75, 0x3ac9bc7f, 0x3c7fbac9, 0x3c75bb95, 0x3c62bbf1, 0x3c46bc22, 0xbc46bc22, 0xbc62bbf1,
    0xbc75bb95, 0xbc7fbac9, 0xbac9bc7f, 0xbb95bc75, 0xbbf1bc62, 0xbc22bc46, 0xbc223c46, 0xbbf13c62, 0xbb953c75, 0xbac93c7f,
    0xbc7f3ac9, 0xbc753b95, 0xbc623bf1, 0xbc463c22, 0xbb48bc7b, 0xbc0ebc55, 0xbc55bc0e, 0xbc7bbb48, 0xbc7b3b48, 0xbc553c0e,
    0xbc0e3c55, 0xbb483c7b, 0x3b483c7b, 0x3c0e3c55, 0x3c553c0e, 0x3c7b3b48, 0x3c7bbb48, 0x3c55bc0e, 0x3c0ebc55, 0x3b48bc7b,
    0xbb48bc7b, 0xbc0ebc55, 0xbc55bc0e, 0xbc7bbb48, 0xbc7b3b48, 0xbc553c0e, 0xbc0e3c55, 0xbb483c7b, 0x3b483c7b, 0x3c0e3c55,
    0x3c553c0e, 0x3c7b3b48, 0x3c7bbb48, 0x3c55bc0e, 0x3c0ebc55, 0x3b48bc7b, 0x3c623bf1, 0x3c7fbac9, 0x3c46bc22, 0x3b95bc75,
    0xbc753b95, 0xbc223c46, 0xbac93c7f, 0x3bf13c62, 0x3bf1bc62, 0xbac9bc7f, 0xbc22bc46, 0xbc75bb95, 0x3b953c75, 0x3c463c22,
    0x3c7f3ac9, 0x3c62bbf1, 0xbc62bbf1, 0xbc7f3ac9, 0xbc463c22, 0xbb953c75, 0x3c75bb95, 0x3c22bc46, 0x3ac9bc7f, 0xbbf1bc62,
    0xbbf13c62, 0x3ac93c7f, 0x3c223c46, 0x3c753b95, 0xbb95bc75, 0xbc46bc22, 0xbc7fbac9, 0xbc623bf1, 0x3bc43c6d, 0x3c6d3bc4,
    0x3c6dbbc4, 0x3bc4bc6d, 0xbbc4bc6d, 0xbc6dbbc4, 0xbc6d3bc4, 0xbbc43c6d, 0x3bc43c6d, 0x3c6d3bc4, 0x3c6dbbc4, 0x3bc4bc6d,
    0xbbc4bc6d, 0xbc6dbbc4, 0xbc6d3bc4, 0xbbc43c6d, 0x3bc43c6d, 0x3c6d3bc4, 0x3c6dbbc4, 0x3bc4bc6d, 0xbbc4bc6d, 0xbc6dbbc4,
    0xbc6d3bc4, 0xbbc43c6d, 0x3bc43c6d, 0x3c6d3bc4, 0x3c6dbbc4, 0x3bc4bc6d, 0xbbc4bc6d, 0xbc6dbbc4, 0xbc6d3bc4, 0xbbc43c6d,
    0x3c753b95, 0x3c46bc22, 0xbac9bc7f, 0xbc62bbf1, 0xbbf1bc62, 0xbc7fbac9, 0xbc223c46, 0x3b953c75, 0x3b95bc75, 0xbc22bc46,
    0xbc7f3ac9, 0xbbf13c62, 0xbc623bf1, 0xbac93c7f, 0x3c463c22, 0x3c75bb95, 0xbc75bb95, 0xbc463c22, 0x3ac93c7f, 0x3c623bf1,
    0x3bf13c62, 0x3c7f3ac9, 0x3c22bc46, 0xbb95bc75, 0xbb953c75, 0x3c223c46, 0x3c7fbac9, 0x3bf1bc62, 0x3c62bbf1, 0x3ac9bc7f,
    0xbc46bc22, 0xbc753b95, 0xbc0ebc55, 0xbc7b3b48, 0xbb483c7b, 0x3c553c0e, 0x3c55bc0e, 0xbb48bc7b, 0xbc7bbb48, 0xbc0e3c55,
    0x3c0e3c55, 0x3c7bbb48, 0x3b48bc7b, 0xbc55bc0e, 0xbc553c0e, 0x3b483c7b, 0x3c7b3b48, 0x3c0ebc55, 0xbc0ebc55, 0xbc7b3b48,
    0xbb483c7b, 0x3c553c0e, 0x3c55bc0e, 0xbb48bc7b, 0xbc7bbb48, 0xbc0e3c55, 0x3c0e3c55, 0x3c7bbb48, 0x3b48bc7b, 0xbc55bc0e,
    0xbc553c0e, 0x3b483c7b, 0x3c7b3b48, 0x3c0ebc55, 0x3c7f3ac9, 0x3b95bc75, 0xbc62bbf1, 0xbc223c46, 0x3c46bc22, 0xbbf1bc62,
    0xbc753b95, 0x3ac93c7f, 0x3ac9bc7f, 0xbc75bb95, 0xbbf13c62, 0x3c463c22, 0xbc22bc46, 0xbc623bf1, 0x3b953c75, 0x3c7fbac9,
    0xbc7fbac9, 0xbb953c75, 0x3c623bf1, 0x3c22bc46, 0xbc463c22, 0x3bf13c62, 0x3c75bb95, 0xbac9bc7f, 0xbac93c7f, 0x3c753b95,
    0x3bf1bc62, 0xbc46bc22, 0x3c223c46, 0x3c62bbf1, 0xbb95bc75, 0xbc7f3ac9, 0x3a493c80, 0x3b163c7d, 0x3b793c78, 0x3bac3c71,
    0x3bdb3c67, 0x3c043c5c, 0x3c183c4e, 0x3c2c3c3e, 0x3c3e3c2c, 0x3c4e3c18, 0x3c5c3c04, 0x3c673bdb, 0x3c713bac, 0x3c783b79,
    0x3c7d3b16, 0x3c803a49, 0x3c80ba49, 0x3c7dbb16, 0x3c78bb79, 0x3c71bbac, 0x3c67bbdb, 0x3c5cbc04, 0x3c4ebc18, 0x3c3ebc2c,
    0x3c2cbc3e, 0x3c18bc4e, 0x3c04bc5c, 0x3bdbbc67, 0x3bacbc71, 0x3b79bc78, 0x3b16bc7d, 0x3a49bc80, 0x3c783b79, 0x3c80ba49,
    0x3c71bbac, 0x3c4ebc18, 0x3b163c7d, 0x3bdb3c67, 0x3c2c3c3e, 0x3c5c3c04, 0xbc04bc5c, 0xbc3ebc2c, 0xbc67bbdb, 0xbc7dbb16,
    0x3c18bc4e, 0x3bacbc71, 0x3a49bc80, 0xbb79bc78, 0xbb793c78, 0x3a493c80, 0x3bac3c71, 0x3c183c4e, 0xbc7d3b16, 0xbc673bdb,
    0xbc3e3c2c, 0xbc043c5c, 0x3c5cbc04, 0x3c2cbc3e, 0x3bdbbc67, 0x3b16bc7d, 0x3c4e3c18, 0x3c713bac, 0x3c803a49, 0x3c78bb79,
    0xbc5cbc04, 0xbc80ba49, 0xbc673bdb, 0xbc183c4e, 0xbb163c7d, 0x3bac3c71, 0x3c3e3c2c, 0x3c783b79, 0x3b793c78, 0x3c2c3c3e,
    0x3c713bac, 0x3c7dbb16, 0x3c4ebc18, 0x3bdbbc67, 0xba49bc80, 0xbc04bc5c, 0xbc043c5c, 0xba493c80, 0x3bdb3c67, 0x3c4e3c18,
    0x3c7d3b16, 0x3c71bbac, 0x3c2cbc3e, 0x3b79bc78, 0x3c78bb79, 0x3c3ebc2c, 0x3bacbc71, 0xbb16bc7d, 0xbc18bc4e, 0xbc67bbdb,
    0xbc803a49, 0xbc5c3c04, 0x3c3ebc2c, 0x3b16bc7d, 0xbc04bc5c, 0xbc71bbac, 0xbbdb3c67, 0x3b793c78, 0x3c4e3c18, 0x3c80ba49,
    0x3a49bc80, 0xbc18bc4e, 0xbc78bb79, 0xbc673bdb, 0x3bac3c71, 0x3c5c3c04, 0x3c7dbb16, 0x3c2cbc3e, 0x3c2c3c3e, 0x3c7d3b16,
    0x3c5cbc04, 0x3bacbc71, 0xbc67bbdb, 0xbc783b79, 0xbc183c4e, 0x3a493c80, 0x3c803a49, 0x3c4ebc18, 0x3b79bc78, 0xbbdbbc67,
    0xbc713bac, 0xbc043c5c, 0x3b163c7d, 0x3c3e3c2c, 0x3c67bbdb, 0x3b79bc78, 0xbc18bc4e, 0xbc80ba49, 0xbc2c3c3e, 0x3b163c7d,
    0x3c5c3c04, 0x3c71bbac, 0x3bacbc71, 0xbc04bc5c, 0xbc7dbb16, 0xbc3e3c2c, 0x3a493c80, 0x3c4e3c18, 0x3c78bb79, 0x3bdbbc67,
    0x3bdb3c67, 0x3c783b79, 0x3c4ebc18, 0x3a49bc80, 0xbc3ebc2c, 0xbc7d3b16, 0xbc043c5c, 0x3bac3c71, 0x3c713bac, 0x3c5cbc04,
    0x3b16bc7d, 0xbc2cbc3e, 0xbc803a49, 0xbc183c4e, 0x3b793c78, 0x3c673bdb, 0xbb16bc7d, 0xbc71bbac, 0xbc3e3c2c, 0x3b793c78,
    0xbc5c3c04, 0x3a493c80, 0x3c673bdb, 0x3c4ebc18, 0xbc183c4e, 0x3bdb3c67, 0x3c803a49, 0x3c04bc5c, 0x3c783b79, 0x3c2cbc3e,
    0xbbacbc71, 0xbc7dbb16, 0xbc7d3b16, 0xbbac3c71, 0x3c2c3c3e, 0x3c78bb79, 0x3c043c5c, 0x3c80ba49, 0x3bdbbc67, 0xbc18bc4e,
    0x3c4e3c18, 0x3c67bbdb, 0x3a49bc80, 0xbc5cbc04, 0x3b79bc78, 0xbc3ebc2c, 0xbc713bac, 0xbb163c7d, 0xbb163c7d, 0x3c673bdb,
    0x3c2cbc3e, 0xbc04bc5c, 0xbc783b79, 0xba493c80, 0x3c713bac, 0x3c18bc4e, 0x3c4ebc18, 0xbbacbc71, 0xbc803a49, 0xbb793c78,
    0x3c5c3c04, 0x3c3ebc2c, 0xbbdbbc67, 0xbc7d3b16, 0xbc7dbb16, 0xbbdb3c67, 0x3c3e3c2c, 0x3c5cbc04, 0xbb79bc78, 0xbc80ba49,
    0xbbac3c71, 0x3c4e3c18, 0x3c183c4e, 0x3c71bbac, 0xba49bc80, 0xbc78bb79, 0xbc043c5c, 0x3c2c3c3e, 0x3c67bbdb, 0xbb16bc7d,
    0xbc67bbdb, 0xbc043c5c, 0x3c4e3c18, 0x3c2cbc3e, 0xbc80ba49, 0xbb163c7d, 0x3c783b79, 0x3bacbc71, 0xbc713bac, 0x3b793c78,
    0x3c7dbb16, 0xba49bc80, 0xbc3e3c2c, 0x3c183c4e, 0x3c5cbc04, 0xbbdbbc67, 0xbbdb3c67, 0x3c5c3c04, 0x3c18bc4e, 0xbc3ebc2c,
    0xba493c80, 0x3c7d3b16, 0x3b79bc78, 0xbc71bbac, 0x3bac3c71, 0x3c78bb79, 0xbb16bc7d, 0xbc803a49, 0x3c2c3c3e, 0x3c4ebc18,
    0xbc04bc5c, 0xbc673bdb, 0x3c353c35, 0x3c35bc35, 0xbc35bc35, 0xbc353c35, 0x3c353c35, 0x3c35bc35, 0xbc35bc35, 0xbc353c35,
    0x3c353c35, 0x3c35bc35, 0xbc35bc35, 0xbc353c35, 0x3c353c35, 0x3c35bc35, 0xbc35bc35, 0xbc353c35, 0x3c353c35, 0x3c35bc35,
    0xbc35bc35, 0xbc353c35, 0x3c353c35, 0x3c35bc35, 0xbc35bc35, 0xbc353c35, 0x3c353c35, 0x3c35bc35, 0xbc35bc35, 0xbc353c35,
    0x3c353c35, 0x3c35bc35, 0xbc35bc35, 0xbc353c35, 0x3c7fbac9, 0xbb95bc75, 0xbc623bf1, 0x3c223c46, 0x3c463c22, 0x3bf1bc62,
    0xbc75bb95, 0xbac93c7f, 0xbac9bc7f, 0xbc753b95, 0x3bf13c62, 0x3c46bc22, 0x3c22bc46, 0xbc62bbf1, 0xbb953c75, 0x3c7f3ac9,
    0xbc7f3ac9, 0x3b953c75, 0x3c62bbf1, 0xbc22bc46, 0xbc46bc22, 0xbbf13c62, 0x3c753b95, 0x3ac9bc7f, 0x3ac93c7f, 0x3c75bb95,
    0xbbf1bc62, 0xbc463c22, 0xbc223c46, 0x3c623bf1, 0x3b95bc75, 0xbc7fbac9, 0xbc55bc0e, 0xbb483c7b, 0x3c7bbb48, 0xbc0ebc55,
    0xbc0e3c55, 0x3c7b3b48, 0xbb48bc7b, 0xbc553c0e, 0x3c553c0e, 0x3b48bc7b, 0xbc7b3b48, 0x3c0e3c55, 0x3c0ebc55, 0xbc7bbb48,
    0x3b483c7b, 0x3c55bc0e, 0xbc55bc0e, 0xbb483c7b, 0x3c7bbb48, 0xbc0ebc55, 0xbc0e3c55, 0x3c7b3b48, 0xbb48bc7b, 0xbc553c0e,
    0x3c553c0e, 0x3b48bc7b, 0xbc7b3b48, 0x3c0e3c55, 0x3c0ebc55, 0xbc7bbb48, 0x3b483c7b, 0x3c55bc0e, 0x3c75bb95, 0xbc46bc22,
    0xbac93c7f, 0x3c62bbf1, 0xbbf13c62, 0x3c7fbac9, 0xbc22bc46, 0xbb953c75, 0xbb95bc75, 0xbc223c46, 0x3c7f3ac9, 0xbbf1bc62,
    0x3c623bf1, 0xbac9bc7f, 0xbc463c22, 0x3c753b95, 0xbc753b95, 0x3c463c22, 0x3ac9bc7f, 0xbc623bf1, 0x3bf1bc62, 0xbc7f3ac9,
    0x3c223c46, 0x3b95bc75, 0x3b953c75, 0x3c22bc46, 0xbc7fbac9, 0x3bf13c62, 0xbc62bbf1, 0x3ac93c7f, 0x3c46bc22, 0xbc75bb95,
    0x3c6d3bc4, 0xbbc4bc6d, 0xbbc43c6d, 0x3c6dbbc4, 0xbc6dbbc4, 0x3bc43c6d, 0x3bc4bc6d, 0xbc6d3bc4, 0x3c6d3bc4, 0xbbc4bc6d,
    0xbbc43c6d, 0x3c6dbbc4, 0xbc6dbbc4, 0x3bc43c6d, 0x3bc4bc6d, 0xbc6d3bc4, 0x3c6d3bc4, 0xbbc4bc6d, 0xbbc43c6d, 0x3c6dbbc4,
    0xbc6dbbc4, 0x3bc43c6d, 0x3bc4bc6d, 0xbc6d3bc4, 0x3c6d3bc4, 0xbbc4bc6d, 0xbbc43c6d, 0x3c6dbbc4, 0xbc6dbbc4, 0x3bc43c6d,
    0x3bc4bc6d, 0xbc6d3bc4, 0x3c62bbf1, 0xbc7fbac9, 0x3c463c22, 0xbb95bc75, 0xbc75bb95, 0x3c223c46, 0xbac9bc7f, 0xbbf13c62,
    0xbbf1bc62, 0xbac93c7f, 0x3c22bc46, 0xbc753b95, 0xbb953c75, 0x3c46bc22, 0xbc7f3ac9, 0x3c623bf1, 0xbc623bf1, 0x3c7f3ac9,
    0xbc46bc22, 0x3b953c75, 0x3c753b95, 0xbc22bc46, 0x3ac93c7f, 0x3bf1bc62, 0x3bf13c62, 0x3ac9bc7f, 0xbc223c46, 0x3c75bb95,
    0x3b95bc75, 0xbc463c22, 0x3c7fbac9, 0xbc62bbf1, 0xbc7bbb48, 0x3c553c0e, 0xbc0ebc55, 0x3b483c7b, 0x3b48bc7b, 0xbc0e3c55,
    0x3c55bc0e, 0xbc7b3b48, 0x3c7b3b48, 0xbc55bc0e, 0x3c0e3c55, 0xbb48bc7b, 0xbb483c7b, 0x3c0ebc55, 0xbc553c0e, 0x3c7bbb48,
    0xbc7bbb48, 0x3c553c0e, 0xbc0ebc55, 0x3b483c7b, 0x3b48bc7b, 0xbc0e3c55, 0x3c55bc0e, 0xbc7b3b48, 0x3c7b3b48, 0xbc55bc0e,
    0x3c0e3c55, 0xbb48bc7b, 0xbb483c7b, 0x3c0ebc55, 0xbc553c0e, 0x3c7bbb48, 0x3c46bc22, 0xbc623bf1, 0x3c75bb95, 0xbc7f3ac9,
    0x3ac9bc7f, 0xbb953c75, 0x3bf1bc62, 0xbc223c46, 0xbc22bc46, 0x3bf13c62, 0xbb95bc75, 0x3ac93c7f, 0xbc7fbac9, 0x3c753b95,
    0xbc62bbf1, 0x3c463c22, 0xbc463c22, 0x3c62bbf1, 0xbc753b95, 0x3c7fbac9, 0xbac93c7f, 0x3b95bc75, 0xbbf13c62, 0x3c22bc46,
    0x3c223c46, 0xbbf1bc62, 0x3b953c75, 0xbac9bc7f, 0x3c7f3ac9, 0xbc75bb95, 0x3c623bf1, 0xbc46bc22, 0x3c3e3c2c, 0x3c18bc4e,
    0xbc5cbc04, 0xbbdb3c67, 0x3c713bac, 0x3b79bc78, 0xbc7dbb16, 0xba493c80, 0x3c80ba49, 0xbb16bc7d, 0xbc783b79, 0x3bac3c71,
    0x3c67bbdb, 0xbc04bc5c, 0xbc4e3c18, 0x3c2c3c3e, 0x3c2cbc3e, 0xbc4ebc18, 0xbc043c5c, 0x3c673bdb, 0x3bacbc71, 0xbc78bb79,
    0xbb163c7d, 0x3c803a49, 0xba49bc80, 0xbc7d3b16, 0x3b793c78, 0x3c71bbac, 0xbbdbbc67, 0xbc5c3c04, 0x3c183c4e, 0x3c3ebc2c,
    0x3c5cbc04, 0xbc3ebc2c, 0xbbdb3c67, 0x3c7d3b16, 0x3c4e3c18, 0x3bacbc71, 0xbc80ba49, 0x3b793c78, 0xbc78bb79, 0x3a493c80,
    0x3c71bbac, 0xbc18bc4e, 0xbb16bc7d, 0xbc673bdb, 0x3c2c3c3e, 0x3c04bc5c, 0x3c043c5c, 0x3c2cbc3e, 0xbc67bbdb, 0xbb163c7d,
    0xbc183c4e, 0x3c713bac, 0x3a49bc80, 0xbc783b79, 0x3b79bc78, 0xbc803a49, 0x3bac3c71, 0x3c4ebc18, 0x3c7dbb16, 0xbbdbbc67,
    0xbc3e3c2c, 0x3c5c3c04, 0xbc783b79, 0x3c2c3c3e, 0x3bacbc71, 0xbc7d3b16, 0x3c183c4e, 0x3bdbbc67, 0xbc803a49, 0x3c043c5c,
    0x3c5c3c04, 0x3a49bc80, 0xbc673bdb, 0x3c4e3c18, 0x3b16bc7d, 0xbc713bac, 0x3c3e3c2c, 0x3b79bc78, 0x3b793c78, 0x3c3ebc2c,
    0xbc71bbac, 0x3b163c7d, 0x3c4ebc18, 0xbc67bbdb, 0x3a493c80, 0x3c5cbc04, 0x3c04bc5c, 0xbc80ba49, 0x3bdb3c67, 0x3c18bc4e,
    0xbc7dbb16, 0x3bac3c71, 0x3c2cbc3e, 0xbc78bb79, 0x3a49bc80, 0xbc4e3c18, 0x3c783b79, 0xbbdbbc67, 0x3bac3c71, 0x3c04bc5c,
    0xbc7d3b16, 0x3c3e3c2c, 0xbc2cbc3e, 0xbb163c7d, 0x3c5cbc04, 0xbc71bbac, 0x3c673bdb, 0xbb79bc78, 0xbc183c4e, 0x3c80ba49,
    0x3c803a49, 0xbc18bc4e, 0xbb793c78, 0x3c67bbdb, 0xbc713bac, 0x3c5c3c04, 0xbb16bc7d, 0xbc2c3c3e, 0x3c3ebc2c, 0xbc7dbb16,
    0x3c043c5c, 0x3bacbc71, 0xbbdb3c67, 0x3c78bb79, 0xbc4ebc18, 0x3a493c80, 0x3bacbc71, 0xbc5c3c04, 0x3c7d3b16, 0xbc2cbc3e,
    0x3a493c80, 0x3c18bc4e, 0xbc783b79, 0x3c673bdb, 0xbbdbbc67, 0xbb793c78, 0x3c4ebc18, 0xbc80ba49, 0x3c3e3c2c, 0xbb16bc7d,
    0xbc043c5c, 0x3c71bbac, 0x3c713bac, 0xbc04bc5c, 0xbb163c7d, 0x3c3ebc2c, 0xbc803a49, 0x3c4e3c18, 0xbb79bc78, 0xbbdb3c67,
    0x3c67bbdb, 0xbc78bb79, 0x3c183c4e, 0x3a49bc80, 0xbc2c3c3e, 0x3c7dbb16, 0xbc5cbc04, 0x3bac3c71, 0xbc4ebc18, 0x3bdb3c67,
    0x3a49bc80, 0xbc043c5c, 0xbb793c78, 0x3c2cbc3e, 0xbc713bac, 0x3c7d3b16, 0x3b163c7d, 0x3bacbc71, 0xbc3e3c2c, 0x3c78bb79,
    0x3c5cbc04, 0xbc803a49, 0x3c673bdb, 0xbc18bc4e, 0xbc183c4e, 0x3c67bbdb, 0xbc80ba49, 0x3c5c3c04, 0x3c783b79, 0xbc3ebc2c,
    0x3bac3c71, 0x3b16bc7d, 0x3c7dbb16, 0xbc71bbac, 0x3c2c3c3e, 0xbb79bc78, 0xbc04bc5c, 0x3a493c80, 0x3bdbbc67, 0xbc4e3c18,
    0x3c183c4e, 0xbbacbc71, 0x3a493c80, 0x3b79bc78, 0xbc043c5c, 0x3c3ebc2c, 0xbc673bdb, 0x3c7dbb16, 0x3b16bc7d, 0xbbdb3c67,
    0x3c2cbc3e, 0xbc5c3c04, 0x3c78bb79, 0xbc80ba49, 0x3c713bac, 0xbc4ebc18, 0xbc4e3c18, 0x3c71bbac, 0xbc803a49, 0x3c783b79,
    0xbc5cbc04, 0x3c2c3c3e, 0xbbdbbc67, 0x3b163c7d, 0x3c7d3b16, 0xbc67bbdb, 0x3c3e3c2c, 0xbc04bc5c, 0x3b793c78, 0x3a49bc80,
    0xbbac3c71, 0x3c18bc4e, 0xbc713bac, 0x3c78bb79, 0xbc7d3b16, 0x3c80ba49, 0xbc3e3c2c, 0x3c4ebc18, 0xbc5c3c04, 0x3c67bbdb,
    0xbbdb3c67, 0x3c04bc5c, 0xbc183c4e, 0x3c2cbc3e, 0xba493c80, 0x3b16bc7d, 0xbb793c78, 0x3bacbc71, 0x3bac3c71, 0xbb79bc78,
    0x3b163c7d, 0xba49bc80, 0x3c2c3c3e, 0xbc18bc4e, 0x3c043c5c, 0xbbdbbc67, 0x3c673bdb, 0xbc5cbc04, 0x3c4e3c18, 0xbc3ebc2c,
    0x3c803a49, 0xbc7dbb16, 0x3c783b79, 0xbc71bbac, 0x3c800000, 0xbc800000, 0x3c800000, 0xbc800000, 0x3c800000, 0xbc800000,
    0x3c800000, 0xbc800000, 0x3c800000, 0xbc800000, 0x3c800000, 0xbc800000, 0x3c800000, 0xbc800000, 0x3c800000, 0xbc800000,
    0x3c800000, 0xbc800000, 0x3c800000, 0xbc800000, 0x3c800000, 0xbc800000, 0x3c800000, 0xbc800000, 0x3c800000, 0xbc800000,
    0x3c800000, 0xbc800000, 0x3c800000, 0xbc800000, 0x3c800000, 0xbc800000, 0x3c22bc46, 0xbbf13c62, 0x3b95bc75, 0xbac93c7f,
    0x3c7fbac9, 0xbc753b95, 0x3c62bbf1, 0xbc463c22, 0xbc46bc22, 0x3c623bf1, 0xbc75bb95, 0x3c7f3ac9, 0xbac9bc7f, 0x3b953c75,
    0xbbf1bc62, 0x3c223c46, 0xbc223c46, 0x3bf1bc62, 0xbb953c75, 0x3ac9bc7f, 0xbc7f3ac9, 0x3c75bb95, 0xbc623bf1, 0x3c46bc22,
    0x3c463c22, 0xbc62bbf1, 0x3c753b95, 0xbc7fbac9, 0x3ac93c7f, 0xbb95bc75, 0x3bf13c62, 0xbc22bc46, 0xbc7b3b48, 0x3c55bc0e,
    0xbc0e3c55, 0x3b48bc7b, 0x3b483c7b, 0xbc0ebc55, 0x3c553c0e, 0xbc7bbb48, 0x3c7bbb48, 0xbc553c0e, 0x3c0ebc55, 0xbb483c7b,
    0xbb48bc7b, 0x3c0e3c55, 0xbc55bc0e, 0x3c7b3b48, 0xbc7b3b48, 0x3c55bc0e, 0xbc0e3c55, 0x3b48bc7b, 0x3b483c7b, 0xbc0ebc55,
    0x3c553c0e, 0xbc7bbb48, 0x3c7bbb48, 0xbc553c0e, 0x3c0ebc55, 0xbb483c7b, 0xbb48bc7b, 0x3c0e3c55, 0xbc55bc0e, 0x3c7b3b48,
    0x3bf1bc62, 0x3ac93c7f, 0xbc22bc46, 0x3c753b95, 0x3b953c75, 0xbc46bc22, 0x3c7f3ac9, 0xbc623bf1, 0xbc62bbf1, 0x3c7fbac9,
    0xbc463c22, 0x3b95bc75, 0x3c75bb95, 0xbc223c46, 0x3ac9bc7f, 0x3bf13c62, 0xbbf13c62, 0xbac9bc7f, 0x3c223c46, 0xbc75bb95,
    0xbb95bc75, 0x3c463c22, 0xbc7fbac9, 0x3c62bbf1, 0x3c623bf1, 0xbc7f3ac9, 0x3c46bc22, 0xbb953c75, 0xbc753b95, 0x3c22bc46,
    0xbac93c7f, 0xbbf1bc62, 0x3c6dbbc4, 0xbbc43c6d, 0xbbc4bc6d, 0x3c6d3bc4, 0xbc6d3bc4, 0x3bc4bc6d, 0x3bc43c6d, 0xbc6dbbc4,
    0x3c6dbbc4, 0xbbc43c6d, 0xbbc4bc6d, 0x3c6d3bc4, 0xbc6d3bc4, 0x3bc4bc6d, 0x3bc43c6d, 0xbc6dbbc4, 0x3c6dbbc4, 0xbbc43c6d,
    0xbbc4bc6d, 0x3c6d3bc4, 0xbc6d3bc4, 0x3bc4bc6d, 0x3bc43c6d, 0xbc6dbbc4, 0x3c6dbbc4, 0xbbc43c6d, 0xbbc4bc6d, 0x3c6d3bc4,
    0xbc6d3bc4, 0x3bc4bc6d, 0x3bc43c6d, 0xbc6dbbc4, 0x3b95bc75, 0x3c223c46, 0xbc7f3ac9, 0x3bf1bc62, 0xbc623bf1, 0x3ac9bc7f,
    0x3c463c22, 0xbc753b95, 0xbc75bb95, 0x3c46bc22, 0x3ac93c7f, 0xbc62bbf1, 0x3bf13c62, 0xbc7fbac9, 0x3c22bc46, 0x3b953c75,
    0xbb953c75, 0xbc22bc46, 0x3c7fbac9, 0xbbf13c62, 0x3c62bbf1, 0xbac93c7f, 0xbc46bc22, 0x3c75bb95, 0x3c753b95, 0xbc463c22,
    0xbac9bc7f, 0x3c623bf1, 0xbbf1bc62, 0x3c7f3ac9, 0xbc223c46, 0xbb95bc75, 0xbc553c0e, 0xbb48bc7b, 0x3c7b3b48, 0xbc0e3c55,
    0xbc0ebc55, 0x3c7bbb48, 0xbb483c7b, 0xbc55bc0e, 0x3c55bc0e, 0x3b483c7b, 0xbc7bbb48, 0x3c0ebc55, 0x3c0e3c55, 0xbc7b3b48,
    0x3b48bc7b, 0x3c553c0e, 0xbc553c0e, 0xbb48bc7b, 0x3c7b3b48, 0xbc0e3c55, 0xbc0ebc55, 0x3c7bbb48, 0xbb483c7b, 0xbc55bc0e,
    0x3c55bc0e, 0x3b483c7b, 0xbc7bbb48, 0x3c0ebc55, 0x3c0e3c55, 0xbc7b3b48, 0x3b48bc7b, 0x3c553c0e, 0x3ac9bc7f, 0x3c753b95,
    0xbbf13c62, 0xbc46bc22, 0xbc22bc46, 0x3c62bbf1, 0x3b953c75, 0xbc7f3ac9, 0xbc7fbac9, 0x3b95bc75, 0x3c623bf1, 0xbc223c46,
    0xbc463c22, 0xbbf1bc62, 0x3c75bb95, 0x3ac93c7f, 0xbac93c7f, 0xbc75bb95, 0x3bf1bc62, 0x3c463c22, 0x3c223c46, 0xbc623bf1,
    0xbb95bc75, 0x3c7fbac9, 0x3c7f3ac9, 0xbb953c75, 0xbc62bbf1, 0x3c22bc46, 0x3c46bc22, 0x3bf13c62, 0xbc753b95, 0xbac9bc7f,
    0x3c80ba49, 0xbc7d3b16, 0x3c78bb79, 0xbc713bac, 0x3c67bbdb, 0xbc5c3c04, 0x3c4ebc18, 0xbc3e3c2c, 0x3c2cbc3e, 0xbc183c4e,
    0x3c04bc5c, 0xbbdb3c67, 0x3bacbc71, 0xbb793c78, 0x3b16bc7d, 0xba493c80, 0xba49bc80, 0x3b163c7d, 0xbb79bc78, 0x3bac3c71,
    0xbbdbbc67, 0x3c043c5c, 0xbc18bc4e, 0x3c2c3c3e, 0xbc3ebc2c, 0x3c4e3c18, 0xbc5cbc04, 0x3c673bdb, 0xbc71bbac, 0x3c783b79,
    0xbc7dbb16, 0x3c803a49, 0x3b79bc78, 0x3a493c80, 0xbbacbc71, 0x3c183c4e, 0x3c7dbb16, 0xbc673bdb, 0x3c3ebc2c, 0xbc043c5c,
    0xbc5c3c04, 0x3c2cbc3e, 0xbbdb3c67, 0x3b16bc7d, 0xbc4ebc18, 0x3c713bac, 0xbc80ba49, 0x3c78bb79, 0x3c783b79, 0xbc803a49,
    0x3c71bbac, 0xbc4e3c18, 0x3b163c7d, 0xbbdbbc67, 0x3c2c3c3e, 0xbc5cbc04, 0xbc04bc5c, 0x3c3e3c2c, 0xbc67bbdb, 0x3c7d3b16,
    0x3c18bc4e, 0xbbac3c71, 0x3a49bc80, 0x3b793c78, 0xbc043c5c, 0x3a49bc80, 0x3bdb3c67, 0xbc4ebc18, 0x3c7d3b16, 0xbc713bac,
    0x3c2cbc3e, 0xbb793c78, 0x3c78bb79, 0xbc3e3c2c, 0x3bacbc71, 0x3b163c7d, 0xbc18bc4e, 0x3c673bdb, 0xbc803a49, 0x3c5cbc04,
    0x3c5c3c04, 0xbc80ba49, 0x3c67bbdb, 0xbc183c4e, 0x3b16bc7d, 0x3bac3c71, 0xbc3ebc2c, 0x3c783b79, 0xbb79bc78, 0x3c2c3c3e,
    0xbc71bbac, 0x3c7dbb16, 0xbc4e3c18, 0x3bdbbc67, 0x3a493c80, 0xbc04bc5c, 0xbc2cbc3e, 0x3c7d3b16, 0xbc5c3c04, 0x3bacbc71,
    0x3c673bdb, 0xbc783b79, 0x3c18bc4e, 0x3a493c80, 0xbc80ba49, 0x3c4ebc18, 0xbb793c78, 0xbbdbbc67, 0x3c71bbac, 0xbc043c5c,
    0xbb16bc7d, 0x3c3e3c2c, 0x3c3ebc2c, 0xbb163c7d, 0xbc04bc5c, 0x3c713bac, 0xbbdb3c67, 0xbb79bc78, 0x3c4e3c18, 0xbc803a49,
    0x3a49bc80, 0x3c183c4e, 0xbc78bb79, 0x3c67bbdb, 0x3bac3c71, 0xbc5cbc04, 0x3c7dbb16, 0xbc2c3c3e, 0xbbdbbc67, 0x3c783b79,
    0xbc4e3c18, 0x3a49bc80, 0x3c3e3c2c, 0xbc7d3b16, 0x3c04bc5c, 0x3bac3c71, 0xbc71bbac, 0x3c5cbc04, 0xbb163c7d, 0xbc2cbc3e,
    0x3c80ba49, 0xbc183c4e, 0xbb79bc78, 0x3c673bdb, 0x3c67bbdb, 0xbb793c78, 0xbc18bc4e, 0x3c803a49, 0xbc2c3c3e, 0xbb16bc7d,
    0x3c5c3c04, 0xbc713bac, 0x3bacbc71, 0x3c043c5c, 0xbc7dbb16, 0x3c3ebc2c, 0x3a493c80, 0xbc4ebc18, 0x3c78bb79, 0xbbdb3c67,
    0xbc7d3b16, 0x3bacbc71, 0x3c2c3c3e, 0xbc783b79, 0x3c043c5c, 0xbc803a49, 0x3bdbbc67, 0x3c183c4e, 0x3c4e3c18, 0xbc673bdb,
    0x3a49bc80, 0x3c5c3c04, 0x3b79bc78, 0x3c3e3c2c, 0xbc713bac, 0x3b16bc7d, 0x3b163c7d, 0xbc71bbac, 0x3c3ebc2c, 0x3b793c78,
    0x3c5cbc04, 0x3a493c80, 0xbc67bbdb, 0x3c4ebc18, 0x3c18bc4e, 0x3bdb3c67, 0xbc80ba49, 0x3c04bc5c, 0xbc78bb79, 0x3c2cbc3e,
    0x3bac3c71, 0xbc7dbb16, 0x3c7d3b16, 0xbbdb3c67, 0xbc3ebc2c, 0x3c5cbc04, 0x3b793c78, 0xbc80ba49, 0x3bacbc71, 0x3c4e3c18,
    0xbc18bc4e, 0x3c71bbac, 0x3a493c80, 0xbc78bb79, 0x3c04bc5c, 0x3c2c3c3e, 0xbc673bdb, 0xbb16bc7d, 0xbb163c7d, 0xbc67bbdb,
    0x3c2cbc3e, 0x3c043c5c, 0xbc783b79, 0x3a49bc80, 0x3c713bac, 0xbc183c4e, 0x3c4ebc18, 0x3bac3c71, 0xbc803a49, 0x3b79bc78,
    0x3c5c3c04, 0xbc3e3c2c, 0xbbdbbc67, 0x3c7dbb16, 0xbbdb3c67, 0xbc5cbc04, 0x3c18bc4e, 0x3c3e3c2c, 0xba493c80, 0xbc7dbb16,
    0x3b79bc78, 0x3c713bac, 0x3bac3c71, 0xbc783b79, 0xbb16bc7d, 0x3c80ba49, 0x3c2c3c3e, 0xbc4e3c18, 0xbc04bc5c, 0x3c67bbdb,
    0x3c673bdb, 0xbc043c5c, 0xbc4ebc18, 0x3c2cbc3e, 0x3c803a49, 0xbb163c7d, 0xbc78bb79, 0x3bacbc71, 0x3c71bbac, 0x3b793c78,
    0xbc7d3b16, 0xba49bc80, 0x3c3ebc2c, 0x3c183c4e, 0xbc5c3c04, 0xbbdbbc67, 0x3f803f80, 0x3f7d3f7f, 0x3f783f7b, 0x3f713f75,
    0x3f673f6d, 0x3f5c3f62, 0x3f4e3f55, 0x3f3e3f46, 0x3f2c3f35, 0x3f183f22, 0x3f043f0e, 0x3edb3ef1, 0x3eac3ec4, 0x3e793e95,
    0x3e163e48, 0x3d493dc9, 0xbd490000, 0xbe16bdc9, 0xbe79be48, 0xbeacbe95, 0xbedbbec4, 0xbf04bef1, 0xbf18bf0e, 0xbf2cbf22,
    0xbf3ebf35, 0xbf4ebf46, 0xbf5cbf55, 0xbf67bf62, 0xbf71bf6d, 0xbf78bf75, 0xbf7dbf7b, 0xbf80bf7f, 0x3edb3ec4, 0x3f043ef1,
    0x3f183f0e, 0x3f2c3f22, 0x3d490000, 0x3e163dc9, 0x3e793e48, 0x3eac3e95, 0x3f713f6d, 0x3f783f75, 0x3f7d3f7b, 0x3f803f7f,
    0x3f3e3f35, 0x3f4e3f46, 0x3f5c3f55, 0x3f673f62, 0x3f673f6d, 0x3f5c3f62, 0x3f4e3f55, 0x3f3e3f46, 0x3f803f80, 0x3f7d3f7f,
    0x3f783f7b, 0x3f713f75, 0x3eac3ec4, 0x3e793e95, 0x3e163e48, 0x3d493dc9, 0x3f2c3f35, 0x3f183f22, 0x3f043f0e, 0x3edb3ef1,
    0xbf4ebf35, 0xbf71bf62, 0xbf80bf7b, 0xbf78bf7f, 0xbf5cbf6d, 0xbf2cbf46, 0xbedbbf0e, 0xbe16be95, 0x3f7d3f80, 0x3f673f75,
    0x3f3e3f55, 0x3f043f22, 0x3e793ec4, 0xbd493dc9, 0xbeacbe48, 0xbf18bef1, 0x3f183f35, 0x3eac3ef1, 0x3d493e48, 0xbe79bdc9,
    0xbf04bec4, 0xbf3ebf22, 0xbf67bf55, 0xbf7dbf75, 0x3e160000, 0x3edb3e95, 0x3f2c3f0e, 0x3f5c3f46, 0x3f783f6d, 0x3f803f7f,
    0x3f713f7b, 0x3f4e3f62, 0xbf04bec4, 0xbf3ebf22, 0xbf67bf55, 0xbf7dbf75, 0x3f183f35, 0x3eac3ef1, 0x3d493e48, 0xbe79bdc9,
    0x3f783f6d, 0x3f803f7f, 0x3f713f7b, 0x3f4e3f62, 0x3e160000, 0x3edb3e95, 0x3f2c3f0e, 0x3f5c3f46, 0x3f5c3f6d, 0x3f2c3f46,
    0x3edb3f0e, 0x3e163e95, 0x3f4e3f35, 0x3f713f62, 0x3f803f7b, 0x3f783f7f, 0xbe79bec4, 0x3d49bdc9, 0x3eac3e48, 0x3f183ef1,
    0xbf7dbf80, 0xbf67bf75, 0xbf3ebf55, 0xbf04bf22, 0xbe790000, 0xbf2cbef1, 0xbf71bf55, 0xbf7dbf7f, 0xbf4ebf6d, 0xbedbbf22,
    0x3d49be48, 0x3f043e95, 0x3f5c3f35, 0x3f803f75, 0x3f673f7b, 0x3f183f46, 0x3e163ec4, 0xbeacbdc9, 0xbf3ebf0e, 0xbf78bf62,
    0x3f783f80, 0x3f3e3f62, 0x3eac3f0e, 0xbe163dc9, 0xbf18bec4, 0xbf67bf46, 0xbf80bf7b, 0xbf5cbf75, 0xbf04bf35, 0xbd49be95,
    0x3edb3e48, 0x3f4e3f22, 0x3f7d3f6d, 0x3f713f7f, 0x3f2c3f55, 0x3e793ef1, 0xbf18bec4, 0xbf67bf46, 0xbf80bf7b, 0xbf5cbf75,
    0x3f783f80, 0x3f3e3f62, 0x3eac3f0e, 0xbe163dc9, 0x3f7d3f6d, 0x3f713f7f, 0x3f2c3f55, 0x3e793ef1, 0xbf04bf35, 0xbd49be95,
    0x3edb3e48, 0x3f4e3f22, 0x3f4e3f6d, 0x3edb3f22, 0xbd493e48, 0xbf04be95, 0x3e790000, 0x3f2c3ef1, 0x3f713f55, 0x3f7d3f7f,
    0xbe16bec4, 0x3eac3dc9, 0x3f3e3f0e, 0x3f783f62, 0xbf5cbf35, 0xbf80bf75, 0xbf67bf7b, 0xbf18bf46, 0xbedbbf35, 0x3e79bdc9,
    0x3f4e3f0e, 0x3f803f75, 0x3f3e3f6d, 0x3e163ef1, 0xbf04be48, 0xbf71bf46, 0x3eac0000, 0x3f5c3f22, 0x3f7d3f7b, 0x3f2c3f62,
    0x3d493ec4, 0xbf18be95, 0xbf78bf55, 0xbf67bf7f, 0x3f673f35, 0x3f783f7f, 0x3f183f55, 0xbd493e95, 0xbf2cbec4, 0xbf7dbf62,
    0xbf5cbf7b, 0xbeacbf22, 0x3f713f80, 0x3f043f46, 0xbe163e48, 0xbf3ebef1, 0xbf80bf6d, 0xbf4ebf75, 0xbe79bf0e, 0x3edb3dc9,
    0x3f2c3ec4, 0x3f7d3f62, 0x3f5c3f7b, 0x3eac3f22, 0xbf67bf35, 0xbf78bf7f, 0xbf18bf55, 0x3d49be95, 0x3f803f6d, 0x3f4e3f75,
    0x3e793f0e, 0xbedbbdc9, 0xbf71bf80, 0xbf04bf46, 0x3e16be48, 0x3f3e3ef1, 0x3f3e3f6d, 0x3e163ef1, 0xbf04be48, 0xbf71bf46,
    0xbedbbf35, 0x3e79bdc9, 0x3f4e3f0e, 0x3f803f75, 0x3d493ec4, 0xbf18be95, 0xbf78bf55, 0xbf67bf7f, 0x3eac0000, 0x3f5c3f22,
    0x3f7d3f7b, 0x3f2c3f62, 0x3f673f80, 0x3e793f22, 0xbf18be48, 0xbf80bf62, 0xbf2cbf6d, 0x3e16be95, 0x3f5c3f0e, 0x3f713f7f,
    0x3eac3f35, 0xbf04bdc9, 0xbf7dbf55, 0xbf3ebf75, 0x3d49bec4, 0x3f4e3ef1, 0x3f783f7b, 0x3edb3f46, 0xbedb0000, 0xbf78bf46,
    0xbf4ebf7b, 0xbd49bef1, 0x3f3e3ec4, 0x3f7d3f75, 0x3f043f55, 0xbeac3dc9, 0xbf71bf35, 0xbf5cbf7f, 0xbe16bf0e, 0x3f2c3e95,
    0x3f803f6d, 0x3f183f62, 0xbe793e48, 0xbf67bf22, 0xbf3ebec4, 0xbf7dbf75, 0xbf04bf55, 0x3eacbdc9, 0x3edb0000, 0x3f783f46,
    0x3f4e3f7b, 0x3d493ef1, 0xbf80bf6d, 0xbf18bf62, 0x3e79be48, 0x3f673f22, 0x3f713f35, 0x3f5c3f7f, 0x3e163f0e, 0xbf2cbe95,
    0xbf2cbf6d, 0x3e16be95, 0x3f5c3f0e, 0x3f713f7f, 0x3f673f80, 0x3e793f22, 0xbf18be48, 0xbf80bf62, 0x3d49bec4, 0x3f4e3ef1,
    0x3f783f7b, 0x3edb3f46, 0x3eac3f35, 0xbf04bdc9, 0xbf7dbf55, 0xbf3ebf75, 0xbf78bf35, 0xbf2cbf75, 0x3eacbe48, 0x3f7d3f46,
    0x3f183f6d, 0xbedb3dc9, 0xbf80bf55, 0xbf04bf62, 0x3f5c3f80, 0xbd493ef1, 0xbf67bf0e, 0xbf4ebf7f, 0x3e16bec4, 0x3f713f22,
    0x3f3e3f7b, 0xbe793e95, 0x3e793f35, 0xbf3ebe95, 0xbf71bf7b, 0xbe16bf22, 0x3f4e3ec4, 0x3f673f7f, 0x3d493f0e, 0xbf5cbef1,
    0x3f040000, 0x3f803f62, 0x3edb3f55, 0xbf18bdc9, 0xbf7dbf6d, 0xbeacbf46, 0x3f2c3e48, 0x3f783f75, 0x3f4e3ec4, 0x3f673f7f,
    0x3d493f0e, 0xbf5cbef1, 0x3e793f35, 0xbf3ebe95, 0xbf71bf7b, 0xbe16bf22, 0xbf7dbf6d, 0xbeacbf46, 0x3f2c3e48, 0x3f783f75,
    0x3f040000, 0x3f803f62, 0x3edb3f55, 0xbf18bdc9, 0xbf18bf6d, 0x3edbbdc9, 0x3f803f55, 0x3f043f62, 0x3f783f35, 0x3f2c3f75,
    0xbeac3e48, 0xbf7dbf46, 0xbe163ec4, 0xbf71bf22, 0xbf3ebf7b, 0x3e79be95, 0xbf5cbf80, 0x3d49bef1, 0x3f673f0e, 0x3f4e3f7f,
    0xbf180000, 0xbf71bf75, 0x3d49bf0e, 0x3f783f22, 0x3f043f6d, 0xbf2cbdc9, 0xbf67bf7b, 0x3e16bef1, 0x3f7d3f35, 0x3edb3f62,
    0xbf3ebe48, 0xbf5cbf7f, 0x3e79bec4, 0x3f803f46, 0x3eac3f55, 0xbf4ebe95, 0x3f4e3f80, 0xbeac3e95, 0xbf80bf55, 0xbe79bf46,
    0x3f5c3ec4, 0x3f3e3f7f, 0xbedb3e48, 0xbf7dbf62, 0xbe16bf35, 0x3f673ef1, 0x3f2c3f7b, 0xbf043dc9, 0xbf78bf6d, 0xbd49bf22,
    0x3f713f0e, 0x3f183f75, 0x3f5c3ec4, 0x3f3e3f7f, 0xbedb3e48, 0xbf7dbf62, 0x3f4e3f80, 0xbeac3e95, 0xbf80bf55, 0xbe79bf46,
    0xbf78bf6d, 0xbd49bf22, 0x3f713f0e, 0x3f183f75, 0xbe16bf35, 0x3f673ef1, 0x3f2c3f7b, 0xbf043dc9, 0xbf04bf6d, 0x3f2c3dc9,
    0x3f673f7b, 0xbe163ef1, 0x3f180000, 0x3f713f75, 0xbd493f0e, 0xbf78bf22, 0xbe793ec4, 0xbf80bf46, 0xbeacbf55, 0x3f4e3e95,
    0xbf7dbf35, 0xbedbbf62, 0x3f3e3e48, 0x3f5c3f7f, 0xbd49bf35, 0x3f7d3f22, 0x3e793f55, 0xbf71bef1, 0xbedbbf6d, 0x3f5c3e95,
    0x3f183f7b, 0xbf3ebdc9, 0x3f2c0000, 0x3f4e3f7f, 0xbf043e48, 0xbf67bf75, 0x3eacbec4, 0x3f783f62, 0xbe163f0e, 0xbf80bf46,
    0x3f803f35, 0x3e163f46, 0xbf78bf0e, 0xbeacbf62, 0x3f673ec4, 0x3f043f75, 0xbf4ebe48, 0xbf2cbf7f, 0x3f3e3f80, 0xbf183dc9,
    0xbf5cbf7b, 0x3edbbe95, 0x3f713f6d, 0xbe793ef1, 0xbf7dbf55, 0x3d49bf22, 0xbf67bec4, 0xbf04bf75, 0x3f4e3e48, 0x3f2c3f7f,
    0xbf80bf35, 0xbe16bf46, 0x3f783f0e, 0x3eac3f62, 0xbf71bf6d, 0x3e79bef1, 0x3f7d3f55, 0xbd493f22, 0xbf3ebf80, 0x3f18bdc9,
    0x3f5c3f7b, 0xbedb3e95, 0xbedbbf6d, 0x3f5c3e95, 0x3f183f7b, 0xbf3ebdc9, 0xbd49bf35, 0x3f7d3f22, 0x3e793f55, 0xbf71bef1,
    0x3eacbec4, 0x3f783f62, 0xbe163f0e, 0xbf80bf46, 0x3f2c0000, 0x3f4e3f7f, 0xbf043e48, 0xbf67bf75, 0x3f2c3f80, 0xbf4ebdc9,
    0xbf04bf7b, 0x3f673e95, 0x3eac3f6d, 0xbf78bef1, 0xbe16bf55, 0x3f803f22, 0xbd493f35, 0xbf7dbf46, 0x3e79bf0e, 0x3f713f62,
    0xbedb3ec4, 0xbf5cbf75, 0x3f18be48, 0x3f3e3f7f, 0xbf3e0000, 0xbf18bf7f, 0x3f5c3e48, 0x3edb3f75, 0xbf71bec4, 0xbe79bf62,
    0x3f7d3f0e, 0x3d493f46, 0xbf80bf35, 0x3e16bf22, 0x3f783f55, 0xbeac3ef1, 0xbf67bf6d, 0x3f04be95, 0x3f4e3f7b, 0xbf2c3dc9,
    0x3f713ec4, 0x3e793f62, 0xbf7dbf0e, 0xbd49bf46, 0x3f3e0000, 0x3f183f7f, 0xbf5cbe48, 0xbedbbf75, 0x3f673f6d, 0xbf043e95,
    0xbf4ebf7b, 0x3f2cbdc9, 0x3f803f35, 0xbe163f22, 0xbf78bf55, 0x3eacbef1, 0x3eac3f6d, 0xbf78bef1, 0xbe16bf55, 0x3f803f22,
    0x3f2c3f80, 0xbf4ebdc9, 0xbf04bf7b, 0x3f673e95, 0xbedb3ec4, 0xbf5cbf75, 0x3f18be48, 0x3f3e3f7f, 0xbd493f35, 0xbf7dbf46,
    0x3e79bf0e, 0x3f713f62, 0xbf7dbf35, 0x3edbbef1, 0x3f3e3f7b, 0xbf5cbdc9, 0xbe79bf6d, 0x3f803f22, 0xbeac3f0e, 0xbf4ebf75,
    0x3f183f80, 0xbf71be95, 0xbd49bf55, 0x3f783f46, 0xbf043ec4, 0xbf2cbf7f, 0x3f673e48, 0x3e163f62, 0xbe163f35, 0xbf67bf62,
    0x3f2cbe48, 0x3f043f7f, 0xbf78bec4, 0x3d49bf46, 0x3f713f55, 0xbf183e95, 0x3f4e0000, 0x3eac3f75, 0xbf80bf0e, 0x3e79bf22,
    0x3f5c3f6d, 0xbf3e3dc9, 0xbedbbf7b, 0x3f7d3ef1, 0xbf78bec4, 0x3d49bf46, 0x3f713f55, 0xbf183e95, 0xbe163f35, 0xbf67bf62,
    0x3f2cbe48, 0x3f043f7f, 0x3f5c3f6d, 0xbf3e3dc9, 0xbedbbf7b, 0x3f7d3ef1, 0x3f4e0000, 0x3eac3f75, 0xbf80bf0e, 0x3e79bf22,
    0x3e793f6d, 0xbf80bf22, 0x3eacbf0e, 0x3f4e3f75, 0x3f7d3f35, 0xbedb3ef1, 0xbf3ebf7b, 0x3f5c3dc9, 0x3f04bec4, 0x3f2c3f7f,
    0xbf67be48, 0xbe16bf62, 0xbf18bf80, 0x3f713e95, 0x3d493f55, 0xbf78bf46, 0xbf5c0000, 0xbd49bf62, 0x3f673f55, 0xbf4e3dc9,
    0xbe16bf6d, 0x3f713f46, 0xbf3e3e48, 0xbe79bf75, 0x3f783f35, 0xbf2c3e95, 0xbeacbf7b, 0x3f7d3f22, 0xbf183ec4, 0xbedbbf7f,
    0x3f803f0e, 0xbf043ef1, 0x3f043f80, 0xbf80bef1, 0x3edbbf0e, 0x3f183f7f, 0xbf7dbec4, 0x3eacbf22, 0x3f2c3f7b, 0xbf78be95,
    0x3e79bf35, 0x3f3e3f75, 0xbf71be48, 0x3e16bf46, 0x3f4e3f6d, 0xbf67bdc9, 0x3d49bf55, 0x3f5c3f62, 0xbf7dbec4, 0x3eacbf22,
    0x3f2c3f7b, 0xbf78be95, 0x3f043f80, 0xbf80bef1, 0x3edbbf0e, 0x3f183f7f, 0x3f4e3f6d, 0xbf67bdc9, 0x3d49bf55, 0x3f5c3f62,
    0x3e79bf35, 0x3f3e3f75, 0xbf71be48, 0x3e16bf46, 0x3e163f6d, 0xbf71bf46, 0x3f3ebe48, 0x3e793f75, 0x3f5c0000, 0x3d493f62,
    0xbf67bf55, 0x3f4ebdc9, 0x3f18bec4, 0x3edb3f7f, 0xbf80bf0e, 0x3f04bef1, 0xbf78bf35, 0x3f2cbe95, 0x3eac3f7b, 0xbf7dbf22,
    0x3eacbf35, 0x3f043f7f, 0xbf7dbf0e, 0x3f3ebe95, 0x3d493f6d, 0xbf4ebf62, 0x3f783e48, 0xbedb3f22, 0x3f670000, 0xbe793f46,
    0xbf18bf7b, 0x3f803ef1, 0xbf2c3ec4, 0xbe16bf75, 0x3f5c3f55, 0xbf71bdc9, 0x3f713f35, 0xbf5c3dc9, 0x3e16bf55, 0x3f2c3f75,
    0xbf80bec4, 0x3f18bef1, 0x3e793f7b, 0xbf67bf46, 0x3edb3f80, 0xbf78bf22, 0x3f4ebe48, 0xbd493f62, 0xbf3ebf6d, 0x3f7d3e95,
    0xbf043f0e, 0xbeacbf7f, 0x3f803ec4, 0xbf183ef1, 0xbe79bf7b, 0x3f673f46, 0xbf71bf35, 0x3f5cbdc9, 0xbe163f55, 0xbf2cbf75,
    0x3f3e3f6d, 0xbf7dbe95, 0x3f04bf0e, 0x3eac3f7f, 0xbedbbf80, 0x3f783f22, 0xbf4e3e48, 0x3d49bf62, 0x3d493f6d, 0xbf4ebf62,
    0x3f783e48, 0xbedb3f22, 0x3eacbf35, 0x3f043f7f, 0xbf7dbf0e, 0x3f3ebe95, 0xbf2c3ec4, 0xbe16bf75, 0x3f5c3f55, 0xbf71bdc9,
    0x3f670000, 0xbe793f46, 0xbf18bf7b, 0x3f803ef1, 0x3eac3f80, 0xbf5cbf46, 0x3f7d3e48, 0xbf2c3ef1, 0x3d49bf6d, 0x3f183f75,
    0xbf78bf0e, 0x3f67bdc9, 0xbedb3f35, 0xbe79bf7f, 0x3f4e3f55, 0xbf80be95, 0x3f3ebec4, 0xbe163f62, 0xbf04bf7b, 0x3f713f22,
    0xbf710000, 0x3f04bf22, 0x3e163f7b, 0xbf3ebf62, 0x3f803ec4, 0xbf4e3e95, 0x3e79bf55, 0x3edb3f7f, 0xbf67bf35, 0x3f783dc9,
    0xbf183f0e, 0xbd49bf75, 0x3f2c3f6d, 0xbf7dbef1, 0x3f5cbe48, 0xbeac3f46, 0xbf80bec4, 0x3f4ebe95, 0xbe793f55, 0xbedbbf7f,
    0x3f710000, 0xbf043f22, 0xbe16bf7b, 0x3f3e3f62, 0xbf2cbf6d, 0x3f7d3ef1, 0xbf5c3e48, 0x3eacbf46, 0x3f673f35, 0xbf78bdc9,
    0x3f18bf0e, 0x3d493f75, 0x3d49bf6d, 0x3f183f75, 0xbf78bf0e, 0x3f67bdc9, 0x3eac3f80, 0xbf5cbf46, 0x3f7d3e48, 0xbf2c3ef1,
    0x3f3ebec4, 0xbe163f62, 0xbf04bf7b, 0x3f713f22, 0xbedb3f35, 0xbe79bf7f, 0x3f4e3f55, 0xbf80be95, 0xbf5cbf35, 0x3f803e95,
    0xbf673e48, 0x3f18bf22, 0xbe163f6d, 0xbeacbf7f, 0x3f3e3f55, 0xbf78bef1, 0x3e793f80, 0xbf2cbf62, 0x3f713f0e, 0xbf7dbdc9,
    0x3f4ebec4, 0xbedb3f46, 0xbd49bf7b, 0x3f043f75, 0xbf043f35, 0x3d49bf75, 0x3edb3f7b, 0xbf4ebf46, 0x3f7d3ec4, 0xbf713dc9,
    0x3f2cbf0e, 0xbe793f62, 0x3f780000, 0xbf3e3ef1, 0x3eacbf55, 0x3e163f7f, 0xbf18bf6d, 0x3f673f22, 0xbf80be48, 0x3f5cbe95,
    0x3f7d3ec4, 0xbf713dc9, 0x3f2cbf0e, 0xbe793f62, 0xbf043f35, 0x3d49bf75, 0x3edb3f7b, 0xbf4ebf46, 0xbf18bf6d, 0x3f673f22,
    0xbf80be48, 0x3f5cbe95, 0x3f780000, 0xbf3e3ef1, 0x3eacbf55, 0x3e163f7f, 0x3e16bf6d, 0x3eac3f7f, 0xbf3ebf55, 0x3f783ef1,
    0x3f5c3f35, 0xbf80be95, 0x3f67be48, 0xbf183f22, 0xbf4e3ec4, 0x3edbbf46, 0x3d493f7b, 0xbf04bf75, 0xbe79bf80, 0x3f2c3f62,
    0xbf71bf0e, 0x3f7d3dc9, 0xbf7d0000, 0x3f67be95, 0xbf3e3f0e, 0x3f04bf46, 0xbe793f6d, 0xbd49bf7f, 0x3eac3f7b, 0xbf18bf62,
    0x3f4e3f35, 0xbf71bef1, 0x3f803e48, 0xbf783dc9, 0x3f5cbec4, 0xbf2c3f22, 0x3edbbf55, 0xbe163f75, 0x3e163f80, 0xbedbbf75,
    0x3f2c3f55, 0xbf5cbf22, 0x3f783ec4, 0xbf80bdc9, 0x3f71be48, 0xbf4e3ef1, 0x3f18bf35, 0xbeac3f62, 0x3d49bf7b, 0x3e793f7f,
    0xbf04bf6d, 0x3f3e3f46, 0xbf67bf0e, 0x3f7d3e95, 0x3f783ec4, 0xbf80bdc9, 0x3f71be48, 0xbf4e3ef1, 0x3e163f80, 0xbedbbf75,
    0x3f2c3f55, 0xbf5cbf22, 0xbf04bf6d, 0x3f3e3f46, 0xbf67bf0e, 0x3f7d3e95, 0x3f18bf35, 0xbeac3f62, 0x3d49bf7b, 0x3e793f7f,
    0x3e79bf6d, 0x3d493f7f, 0xbeacbf7b, 0x3f183f62, 0x3f7d0000, 0xbf673e95, 0x3f3ebf0e, 0xbf043f46, 0xbf5c3ec4, 0x3f2cbf22,
    0xbedb3f55, 0x3e16bf75, 0xbf4ebf35, 0x3f713ef1, 0xbf80be48, 0x3f78bdc9, 0x3f2cbf35, 0xbf183f46, 0x3f04bf55, 0xbedb3f62,
    0x3eacbf6d, 0xbe793f75, 0x3e16bf7b, 0xbd493f7f, 0x3f800000, 0xbf7d3dc9, 0x3f78be48, 0xbf713e95, 0x3f67bec4, 0xbf5c3ef1,
    0x3f4ebf0e, 0xbf3e3f22, 0x3f3e3f35, 0xbf4ebf22, 0x3f5c3f0e, 0xbf67bef1, 0x3f713ec4, 0xbf78be95, 0x3f7d3e48, 0xbf80bdc9,
    0x3d493f80, 0xbe16bf7f, 0x3e793f7b, 0xbeacbf75, 0x3edb3f6d, 0xbf04bf62, 0x3f183f55, 0xbf2cbf46, 0xbf71bec4, 0x3f783e95,
    0xbf7dbe48, 0x3f803dc9, 0xbf3ebf35, 0x3f4e3f22, 0xbf5cbf0e, 0x3f673ef1, 0xbedbbf6d, 0x3f043f62, 0xbf18bf55, 0x3f2c3f46,
    0xbd49bf80, 0x3e163f7f, 0xbe79bf7b, 0x3eac3f75, 0x3eacbf6d, 0xbe793f75, 0x3e16bf7b, 0xbd493f7f, 0x3f2cbf35, 0xbf183f46,
    0x3f04bf55, 0xbedb3f62, 0x3f67bec4, 0xbf5c3ef1, 0x3f4ebf0e, 0xbf3e3f22, 0x3f800000, 0xbf7d3dc9, 0x3f78be48, 0xbf713e95,
    0xbd493f80, 0x3e16bf7f, 0xbe793f7b, 0x3eacbf75, 0xbedb3f6d, 0x3f04bf62, 0xbf183f55, 0x3f2cbf46, 0xbf3e3f35, 0x3f4ebf22,
    0xbf5c3f0e, 0x3f67bef1, 0xbf713ec4, 0x3f78be95, 0xbf7d3e48, 0x3f80bdc9, 0xbf800000, 0x3f7d3dc9, 0xbf78be48, 0x3f713e95,
    0xbf67bec4, 0x3f5c3ef1, 0xbf4ebf0e, 0x3f3e3f22, 0xbf2cbf35, 0x3f183f46, 0xbf04bf55, 0x3edb3f62, 0xbeacbf6d, 0x3e793f75,
    0xbe16bf7b, 0x3d493f7f, 0x3f673ec4, 0xbf5cbef1, 0x3f4e3f0e, 0xbf3ebf22, 0x3f800000, 0xbf7dbdc9, 0x3f783e48, 0xbf71be95,
    0x3eac3f6d, 0xbe79bf75, 0x3e163f7b, 0xbd49bf7f, 0x3f2c3f35, 0xbf18bf46, 0x3f043f55, 0xbedbbf62, 0xbedb3f6d, 0x3f04bf62,
    0xbf183f55, 0x3f2cbf46, 0xbd493f80, 0x3e16bf7f, 0xbe793f7b, 0x3eacbf75, 0xbf713ec4, 0x3f78be95, 0xbf7d3e48, 0x3f80bdc9,
    0xbf3e3f35, 0x3f4ebf22, 0xbf5c3f0e, 0x3f67bef1, 0xbf18bf35, 0x3eac3f62, 0xbd49bf7b, 0xbe793f7f, 0x3f04bf6d, 0xbf3e3f46,
    0x3f67bf0e, 0xbf7d3e95, 0xbe163f80, 0x3edbbf75, 0xbf2c3f55, 0x3f5cbf22, 0xbf783ec4, 0x3f80bdc9, 0xbf71be48, 0x3f4e3ef1,
    0xbf4e3f35, 0x3f71bef1, 0xbf803e48, 0x3f783dc9, 0xbf5cbec4, 0x3f2c3f22, 0xbedbbf55, 0x3e163f75, 0x3f7d0000, 0xbf67be95,
    0x3f3e3f0e, 0xbf04bf46, 0x3e793f6d, 0x3d49bf7f, 0xbeac3f7b, 0x3f18bf62, 0xbf5cbec4, 0x3f2c3f22, 0xbedbbf55, 0x3e163f75,
    0xbf4e3f35, 0x3f71bef1, 0xbf803e48, 0x3f783dc9, 0x3e793f6d, 0x3d49bf7f, 0xbeac3f7b, 0x3f18bf62, 0x3f7d0000, 0xbf67be95,
    0x3f3e3f0e, 0xbf04bf46, 0xbf043f6d, 0x3f3ebf46, 0xbf673f0e, 0x3f7dbe95, 0x3f183f35, 0xbeacbf62, 0x3d493f7b, 0x3e79bf7f,
    0x3f78bec4, 0xbf803dc9, 0x3f713e48, 0xbf4ebef1, 0x3e16bf80, 0xbedb3f75, 0x3f2cbf55, 0xbf5c3f22, 0xbf780000, 0x3f3e3ef1,
    0xbeacbf55, 0xbe163f7f, 0x3f18bf6d, 0xbf673f22, 0x3f80be48, 0xbf5cbe95, 0x3f043f35, 0xbd49bf75, 0xbedb3f7b, 0x3f4ebf46,
    0xbf7d3ec4, 0x3f713dc9, 0xbf2cbf0e, 0x3e793f62, 0xbe793f80, 0x3f2cbf62, 0xbf713f0e, 0x3f7dbdc9, 0xbf4ebec4, 0x3edb3f46,
    0x3d49bf7b, 0xbf043f75, 0x3f5cbf35, 0xbf803e95, 0x3f673e48, 0xbf18bf22, 0x3e163f6d, 0x3eacbf7f, 0xbf3e3f55, 0x3f78bef1,
    0xbf4ebec4, 0x3edb3f46, 0x3d49bf7b, 0xbf043f75, 0xbe793f80, 0x3f2cbf62, 0xbf713f0e, 0x3f7dbdc9, 0x3e163f6d, 0x3eacbf7f,
    0xbf3e3f55, 0x3f78bef1, 0x3f5cbf35, 0xbf803e95, 0x3f673e48, 0xbf18bf22, 0xbf183f6d, 0x3f67bf22, 0xbf803e48, 0x3f5c3e95,
    0x3f780000, 0xbf3ebef1, 0x3eac3f55, 0x3e16bf7f, 0x3f7dbec4, 0xbf71bdc9, 0x3f2c3f0e, 0xbe79bf62, 0xbf04bf35, 0x3d493f75,
    0x3edbbf7b, 0xbf4e3f46, 0x3f67bf35, 0xbf783dc9, 0x3f183f0e, 0x3d49bf75, 0xbf2c3f6d, 0x3f7dbef1, 0xbf5cbe48, 0x3eac3f46,
    0x3f710000, 0xbf04bf22, 0xbe163f7b, 0x3f3ebf62, 0xbf803ec4, 0x3f4e3e95, 0xbe79bf55, 0xbedb3f7f, 0x3edb3f35, 0x3e79bf7f,
    0xbf4e3f55, 0x3f80be95, 0xbf3ebec4, 0x3e163f62, 0x3f04bf7b, 0xbf713f22, 0xbeac3f80, 0x3f5cbf46, 0xbf7d3e48, 0x3f2c3ef1,
    0xbd49bf6d, 0xbf183f75, 0x3f78bf0e, 0xbf67bdc9, 0x3f3e3ec4, 0xbe16bf62, 0xbf043f7b, 0x3f71bf22, 0xbedbbf35, 0xbe793f7f,
    0x3f4ebf55, 0xbf803e95, 0x3d493f6d, 0x3f18bf75, 0xbf783f0e, 0x3f673dc9, 0x3eacbf80, 0xbf5c3f46, 0x3f7dbe48, 0xbf2cbef1,
    0xbf2c3f6d, 0x3f7dbef1, 0xbf5cbe48, 0x3eac3f46, 0x3f67bf35, 0xbf783dc9, 0x3f183f0e, 0x3d49bf75, 0xbf803ec4, 0x3f4e3e95,
    0xbe79bf55, 0xbedb3f7f, 0x3f710000, 0xbf04bf22, 0xbe163f7b, 0x3f3ebf62, 0xbedb3f80, 0x3f78bf22, 0xbf4ebe48, 0x3d493f62,
    0x3f3ebf6d, 0xbf7d3e95, 0x3f043f0e, 0x3eacbf7f, 0xbf713f35, 0x3f5c3dc9, 0xbe16bf55, 0xbf2c3f75, 0x3f80bec4, 0xbf18bef1,
    0xbe793f7b, 0x3f67bf46, 0xbf670000, 0x3e793f46, 0x3f18bf7b, 0xbf803ef1, 0x3f2c3ec4, 0x3e16bf75, 0xbf5c3f55, 0x3f71bdc9,
    0xbeacbf35, 0xbf043f7f, 0x3f7dbf0e, 0xbf3ebe95, 0xbd493f6d, 0x3f4ebf62, 0xbf783e48, 0x3edb3f22, 0xbf2cbec4, 0xbe163f75,
    0x3f5cbf55, 0xbf713dc9, 0x3f670000, 0xbe79bf46, 0xbf183f7b, 0x3f80bef1, 0x3d49bf6d, 0xbf4e3f62, 0x3f78be48, 0xbedbbf22,
    0x3eac3f35, 0x3f04bf7f, 0xbf7d3f0e, 0x3f3e3e95, 0x3f3ebf6d, 0xbf7d3e95, 0x3f043f0e, 0x3eacbf7f, 0xbedb3f80, 0x3f78bf22,
    0xbf4ebe48, 0x3d493f62, 0x3f80bec4, 0xbf18bef1, 0xbe793f7b, 0x3f67bf46, 0xbf713f35, 0x3f5c3dc9, 0xbe16bf55, 0xbf2c3f75,
    0xbe79bf35, 0xbf3e3f75, 0x3f71be48, 0xbe16bf46, 0xbf4e3f6d, 0x3f67bdc9, 0xbd49bf55, 0xbf5c3f62, 0xbf043f80, 0x3f80bef1,
    0xbedbbf0e, 0xbf183f7f, 0x3f7dbec4, 0xbeacbf22, 0xbf2c3f7b, 0x3f78be95, 0xbf783f35, 0x3f2c3e95, 0x3eacbf7b, 0xbf7d3f22,
    0x3f183ec4, 0x3edbbf7f, 0xbf803f0e, 0x3f043ef1, 0x3f5c0000, 0x3d49bf62, 0xbf673f55, 0x3f4e3dc9, 0x3e16bf6d, 0xbf713f46,
    0x3f3e3e48, 0x3e79bf75, 0x3f183ec4, 0x3edbbf7f, 0xbf803f0e, 0x3f043ef1, 0xbf783f35, 0x3f2c3e95, 0x3eacbf7b, 0xbf7d3f22,
    0x3e16bf6d, 0xbf713f46, 0x3f3e3e48, 0x3e79bf75, 0x3f5c0000, 0x3d49bf62, 0xbf673f55, 0x3f4e3dc9, 0x3f4ebf6d, 0xbf673dc9,
    0x3d493f55, 0x3f5cbf62, 0x3e793f35, 0x3f3ebf75, 0xbf713e48, 0x3e163f46, 0xbf7d3ec4, 0x3eac3f22, 0x3f2cbf7b, 0xbf783e95,
    0x3f04bf80, 0xbf803ef1, 0x3edb3f0e, 0x3f18bf7f, 0xbf4e0000, 0xbeac3f75, 0x3f80bf0e, 0xbe79bf22, 0xbf5c3f6d, 0x3f3e3dc9,
    0x3edbbf7b, 0xbf7d3ef1, 0x3e163f35, 0x3f67bf62, 0xbf2cbe48, 0xbf043f7f, 0x3f78bec4, 0xbd49bf46, 0xbf713f55, 0x3f183e95,
    0xbf183f80, 0x3f71be95, 0x3d49bf55, 0xbf783f46, 0x3f043ec4, 0x3f2cbf7f, 0xbf673e48, 0xbe163f62, 0x3f7dbf35, 0xbedbbef1,
    0xbf3e3f7b, 0x3f5cbdc9, 0x3e79bf6d, 0xbf803f22, 0x3eac3f0e, 0x3f4ebf75, 0x3f043ec4, 0x3f2cbf7f, 0xbf673e48, 0xbe163f62,
    0xbf183f80, 0x3f71be95, 0x3d49bf55, 0xbf783f46, 0x3e79bf6d, 0xbf803f22, 0x3eac3f0e, 0x3f4ebf75, 0x3f7dbf35, 0xbedbbef1,
    0xbf3e3f7b, 0x3f5cbdc9, 0x3f5cbf6d, 0xbf3ebdc9, 0xbedb3f7b, 0x3f7dbef1, 0x3f4e0000, 0x3eacbf75, 0xbf803f0e, 0x3e793f22,
    0xbf783ec4, 0x3d493f46, 0x3f71bf55, 0xbf18be95, 0xbe16bf35, 0xbf673f62, 0x3f2c3e48, 0x3f04bf7f, 0x3f80bf35, 0xbe16bf22,
    0xbf783f55, 0x3eac3ef1, 0x3f67bf6d, 0xbf04be95, 0xbf4e3f7b, 0x3f2c3dc9, 0x3f3e0000, 0x3f18bf7f, 0xbf5c3e48, 0xbedb3f75,
    0x3f71bec4, 0x3e79bf62, 0xbf7d3f0e, 0xbd493f46, 0x3d493f35, 0x3f7dbf46, 0xbe79bf0e, 0xbf713f62, 0x3edb3ec4, 0x3f5cbf75,
    0xbf18be48, 0xbf3e3f7f, 0xbf2c3f80, 0x3f4ebdc9, 0x3f04bf7b, 0xbf673e95, 0xbeac3f6d, 0x3f78bef1, 0x3e16bf55, 0xbf803f22,
    0xbedbbec4, 0xbf5c3f75, 0x3f183e48, 0x3f3ebf7f, 0xbd49bf35, 0xbf7d3f46, 0x3e793f0e, 0x3f71bf62, 0x3eacbf6d, 0xbf783ef1,
    0xbe163f55, 0x3f80bf22, 0x3f2cbf80, 0xbf4e3dc9, 0xbf043f7b, 0x3f67be95, 0x3f67bf6d, 0xbf04be95, 0xbf4e3f7b, 0x3f2c3dc9,
    0x3f80bf35, 0xbe16bf22, 0xbf783f55, 0x3eac3ef1, 0x3f71bec4, 0x3e79bf62, 0xbf7d3f0e, 0xbd493f46, 0x3f3e0000, 0x3f18bf7f,
    0xbf5c3e48, 0xbedb3f75, 0xbf3e3f80, 0x3f183dc9, 0x3f5cbf7b, 0xbedbbe95, 0xbf713f6d, 0x3e793ef1, 0x3f7dbf55, 0xbd49bf22,
    0xbf803f35, 0xbe163f46, 0x3f78bf0e, 0x3eacbf62, 0xbf673ec4, 0xbf043f75, 0x3f4ebe48, 0x3f2cbf7f, 0xbf2c0000, 0xbf4e3f7f,
    0x3f043e48, 0x3f67bf75, 0xbeacbec4, 0xbf783f62, 0x3e163f0e, 0x3f80bf46, 0x3d49bf35, 0xbf7d3f22, 0xbe793f55, 0x3f71bef1,
    0x3edbbf6d, 0xbf5c3e95, 0xbf183f7b, 0x3f3ebdc9, 0x3eac3ec4, 0x3f78bf62, 0xbe16bf0e, 0xbf803f46, 0x3f2c0000, 0x3f4ebf7f,
    0xbf04be48, 0xbf673f75, 0xbedb3f6d, 0x3f5cbe95, 0x3f18bf7b, 0xbf3e3dc9, 0xbd493f35, 0x3f7dbf22, 0x3e79bf55, 0xbf713ef1,
    0xbf713f6d, 0x3e793ef1, 0x3f7dbf55, 0xbd49bf22, 0xbf3e3f80, 0x3f183dc9, 0x3f5cbf7b, 0xbedbbe95, 0xbf673ec4, 0xbf043f75,
    0x3f4ebe48, 0x3f2cbf7f, 0xbf803f35, 0xbe163f46, 0x3f78bf0e, 0x3eacbf62, 0x3e16bf35, 0xbf673ef1, 0xbf2c3f7b, 0x3f043dc9,
    0x3f78bf6d, 0x3d49bf22, 0xbf713f0e, 0xbf183f75, 0xbf4e3f80, 0x3eac3e95, 0x3f80bf55, 0x3e79bf46, 0xbf5c3ec4, 0xbf3e3f7f,
    0x3edb3e48, 0x3f7dbf62, 0xbf7d3f35, 0xbedb3f62, 0x3f3ebe48, 0x3f5cbf7f, 0xbe79bec4, 0xbf803f46, 0xbeac3f55, 0x3f4ebe95,
    0x3f180000, 0x3f71bf75, 0xbd49bf0e, 0xbf783f22, 0xbf043f6d, 0x3f2cbdc9, 0x3f67bf7b, 0xbe16bef1, 0xbe79bec4, 0xbf803f46,
    0xbeac3f55, 0x3f4ebe95, 0xbf7d3f35, 0xbedb3f62, 0x3f3ebe48, 0x3f5cbf7f, 0xbf043f6d, 0x3f2cbdc9, 0x3f67bf7b, 0xbe16bef1,
    0x3f180000, 0x3f71bf75, 0xbd49bf0e, 0xbf783f22, 0xbf783f6d, 0xbd493f22, 0x3f71bf0e, 0x3f18bf75, 0xbe163f35, 0x3f67bef1,
    0x3f2cbf7b, 0xbf04bdc9, 0x3f5cbec4, 0x3f3ebf7f, 0xbedbbe48, 0xbf7d3f62, 0x3f4ebf80, 0xbeacbe95, 0xbf803f55, 0xbe793f46,
    0xbf040000, 0xbf803f62, 0xbedb3f55, 0x3f18bdc9, 0x3f7dbf6d, 0x3eacbf46, 0xbf2c3e48, 0xbf783f75, 0xbe793f35, 0x3f3ebe95,
    0x3f71bf7b, 0x3e16bf22, 0xbf4e3ec4, 0xbf673f7f, 0xbd493f0e, 0x3f5cbef1, 0xbf5c3f80, 0x3d493ef1, 0x3f67bf0e, 0x3f4ebf7f,
    0xbe16bec4, 0xbf713f22, 0xbf3e3f7b, 0x3e793e95, 0x3f78bf35, 0x3f2cbf75, 0xbeacbe48, 0xbf7d3f46, 0xbf183f6d, 0x3edb3dc9,
    0x3f80bf55, 0x3f04bf62, 0xbe16bec4, 0xbf713f22, 0xbf3e3f7b, 0x3e793e95, 0xbf5c3f80, 0x3d493ef1, 0x3f67bf0e, 0x3f4ebf7f,
    0xbf183f6d, 0x3edb3dc9, 0x3f80bf55, 0x3f04bf62, 0x3f78bf35, 0x3f2cbf75, 0xbeacbe48, 0xbf7d3f46, 0xbf7d3f6d, 0xbeac3f46,
    0x3f2cbe48, 0x3f78bf75, 0x3f040000, 0x3f80bf62, 0x3edbbf55, 0xbf183dc9, 0x3f4ebec4, 0x3f67bf7f, 0x3d49bf0e, 0xbf5c3ef1,
    0x3e79bf35, 0xbf3e3e95, 0xbf713f7b, 0xbe163f22, 0x3f71bf35, 0x3f5cbf7f, 0x3e16bf0e, 0xbf2c3e95, 0xbf803f6d, 0xbf183f62,
    0x3e793e48, 0x3f67bf22, 0x3edb0000, 0x3f78bf46, 0x3f4ebf7b, 0x3d49bef1, 0xbf3e3ec4, 0xbf7d3f75, 0xbf043f55, 0x3eac3dc9,
    0xbeac3f35, 0x3f04bdc9, 0x3f7dbf55, 0x3f3ebf75, 0xbd49bec4, 0xbf4e3ef1, 0xbf783f7b, 0xbedb3f46, 0xbf673f80, 0xbe793f22,
    0x3f18be48, 0x3f80bf62, 0x3f2cbf6d, 0xbe16be95, 0xbf5c3f0e, 0xbf713f7f, 0x3d493ec4, 0x3f4ebef1, 0x3f78bf7b, 0x3edbbf46,
    0x3eacbf35, 0xbf043dc9, 0xbf7d3f55, 0xbf3e3f75, 0xbf2c3f6d, 0x3e163e95, 0x3f5cbf0e, 0x3f71bf7f, 0x3f67bf80, 0x3e79bf22,
    0xbf183e48, 0xbf803f62, 0xbf803f6d, 0xbf183f62, 0x3e793e48, 0x3f67bf22, 0x3f71bf35, 0x3f5cbf7f, 0x3e16bf0e, 0xbf2c3e95,
    0xbf3e3ec4, 0xbf7d3f75, 0xbf043f55, 0x3eac3dc9, 0x3edb0000, 0x3f78bf46, 0x3f4ebf7b, 0x3d49bef1, 0xbf713f80, 0xbf043f46,
    0x3e163e48, 0x3f3ebef1, 0x3f80bf6d, 0x3f4ebf75, 0x3e79bf0e, 0xbedb3dc9, 0xbf673f35, 0xbf783f7f, 0xbf183f55, 0x3d493e95,
    0x3f2cbec4, 0x3f7dbf62, 0x3f5cbf7b, 0x3eacbf22, 0xbeac0000, 0xbf5c3f22, 0xbf7d3f7b, 0xbf2c3f62, 0xbd493ec4, 0x3f18be95,
    0x3f78bf55, 0x3f67bf7f, 0x3edbbf35, 0xbe79bdc9, 0xbf4e3f0e, 0xbf803f75, 0xbf3e3f6d, 0xbe163ef1, 0x3f04be48, 0x3f71bf46,
    0x3d49bec4, 0xbf183e95, 0xbf783f55, 0xbf673f7f, 0x3eac0000, 0x3f5cbf22, 0x3f7dbf7b, 0x3f2cbf62, 0x3f3ebf6d, 0x3e16bef1,
    0xbf043e48, 0xbf713f46, 0xbedb3f35, 0x3e793dc9, 0x3f4ebf0e, 0x3f80bf75, 0x3f80bf6d, 0x3f4ebf75, 0x3e79bf0e, 0xbedb3dc9,
    0xbf713f80, 0xbf043f46, 0x3e163e48, 0x3f3ebef1, 0x3f2cbec4, 0x3f7dbf62, 0x3f5cbf7b, 0x3eacbf22, 0xbf673f35, 0xbf783f7f,
    0xbf183f55, 0x3d493e95, 0x3f04bf35, 0x3d49be95, 0xbedb3e48, 0xbf4e3f22, 0xbf7d3f6d, 0xbf713f7f, 0xbf2c3f55, 0xbe793ef1,
    0xbf783f80, 0xbf3e3f62, 0xbeac3f0e, 0x3e163dc9, 0x3f18bec4, 0x3f67bf46, 0x3f80bf7b, 0x3f5cbf75, 0xbf5c3f35, 0xbf803f75,
    0xbf673f7b, 0xbf183f46, 0xbe163ec4, 0x3eacbdc9, 0x3f3ebf0e, 0x3f78bf62, 0x3e790000, 0x3f2cbef1, 0x3f71bf55, 0x3f7dbf7f,
    0x3f4ebf6d, 0x3edbbf22, 0xbd49be48, 0xbf043e95, 0xbe163ec4, 0x3eacbdc9, 0x3f3ebf0e, 0x3f78bf62, 0xbf5c3f35, 0xbf803f75,
    0xbf673f7b, 0xbf183f46, 0x3f4ebf6d, 0x3edbbf22, 0xbd49be48, 0xbf043e95, 0x3e790000, 0x3f2cbef1, 0x3f71bf55, 0x3f7dbf7f,
    0x3f7dbf6d, 0x3f71bf7f, 0x3f2cbf55, 0x3e79bef1, 0xbf043f35, 0xbd493e95, 0x3edbbe48, 0x3f4ebf22, 0xbf183ec4, 0xbf673f46,
    0xbf803f7b, 0xbf5c3f75, 0x3f78bf80, 0x3f3ebf62, 0x3eacbf0e, 0xbe16bdc9, 0xbe160000, 0xbedb3e95, 0xbf2c3f0e, 0xbf5c3f46,
    0xbf783f6d, 0xbf803f7f, 0xbf713f7b, 0xbf4e3f62, 0xbf183f35, 0xbeac3ef1, 0xbd493e48, 0x3e79bdc9, 0x3f04bec4, 0x3f3ebf22,
    0x3f67bf55, 0x3f7dbf75, 0xbf7d3f80, 0xbf673f75, 0xbf3e3f55, 0xbf043f22, 0xbe793ec4, 0x3d493dc9, 0x3eacbe48, 0x3f18bef1,
    0x3f4ebf35, 0x3f71bf62, 0x3f80bf7b, 0x3f78bf7f, 0x3f5cbf6d, 0x3f2cbf46, 0x3edbbf0e, 0x3e16be95, 0xbe793ec4, 0x3d493dc9,
    0x3eacbe48, 0x3f18bef1, 0xbf7d3f80, 0xbf673f75, 0xbf3e3f55, 0xbf043f22, 0x3f5cbf6d, 0x3f2cbf46, 0x3edbbf0e, 0x3e16be95,
    0x3f4ebf35, 0x3f71bf62, 0x3f80bf7b, 0x3f78bf7f, 0x3f78bf6d, 0x3f80bf7f, 0x3f71bf7b, 0x3f4ebf62, 0x3e160000, 0x3edbbe95,
    0x3f2cbf0e, 0x3f5cbf46, 0xbf043ec4, 0xbf3e3f22, 0xbf673f55, 0xbf7d3f75, 0x3f18bf35, 0x3eacbef1, 0x3d49be48, 0xbe793dc9,
    0x3f3ebf35, 0x3f4ebf46, 0x3f5cbf55, 0x3f67bf62, 0x3f71bf6d, 0x3f78bf75, 0x3f7dbf7b, 0x3f80bf7f, 0x3d490000, 0x3e16bdc9,
    0x3e79be48, 0x3eacbe95, 0x3edbbec4, 0x3f04bef1, 0x3f18bf0e, 0x3f2cbf22, 0xbf2c3f35, 0xbf183f22, 0xbf043f0e, 0xbedb3ef1,
    0xbeac3ec4, 0xbe793e95, 0xbe163e48, 0xbd493dc9, 0xbf803f80, 0xbf7d3f7f, 0xbf783f7b, 0xbf713f75, 0xbf673f6d, 0xbf5c3f62,
    0xbf4e3f55, 0xbf3e3f46, 0x3eacbec4, 0x3e79be95, 0x3e16be48, 0x3d49bdc9, 0x3f2cbf35, 0x3f18bf22, 0x3f04bf0e, 0x3edbbef1,
    0x3f67bf6d, 0x3f5cbf62, 0x3f4ebf55, 0x3f3ebf46, 0x3f80bf80, 0x3f7dbf7f, 0x3f78bf7b, 0x3f71bf75, 0x3f71bf6d, 0x3f78bf75,
    0x3f7dbf7b, 0x3f80bf7f, 0x3f3ebf35, 0x3f4ebf46, 0x3f5cbf55, 0x3f67bf62, 0x3edbbec4, 0x3f04bef1, 0x3f18bf0e, 0x3f2cbf22,
    0x3d490000, 0x3e16bdc9, 0x3e79be48, 0x3eacbe95,
};
__device__ const __align__(128) uint32_t c_ga[1536] = {
    0x00003c80, 0x3bc43c6d, 0x00003c80, 0xbbc4bc6d, 0x00003c80, 0x3c6d3bc4, 0x00003c80, 0xbc6dbbc4, 0x00003c80, 0x3c6dbbc4,
    0x00003c80, 0xbc6d3bc4, 0x00003c80, 0x3bc4bc6d, 0x00003c80, 0xbbc43c6d, 0x3a493c80, 0x3bdb3c67, 0x3bdb3c67, 0xbc3ebc2c,
    0x3b163c7d, 0x3c783b79, 0x3c043c5c, 0xbc7d3b16, 0x3b793c78, 0x3c4ebc18, 0x3c183c4e, 0xbc043c5c, 0x3bac3c71, 0x3a49bc80,
    0x3c2c3c3e, 0x3bac3c71, 0x3ac93c7f, 0x3bf13c62, 0x3c463c22, 0xbc75bb95, 0x3b953c75, 0x3c7f3ac9, 0x3c623bf1, 0xbc463c22,
    0x3bf13c62, 0x3c22bc46, 0x3c753b95, 0x3ac93c7f, 0x3c223c46, 0xbb95bc75, 0x3c7f3ac9, 0x3c623bf1, 0x3b163c7d, 0x3c043c5c,
    0x3c783b79, 0xbc7d3b16, 0x3bdb3c67, 0x3c80ba49, 0x3c80ba49, 0xbbac3c71, 0x3c2c3c3e, 0x3bdbbc67, 0x3c71bbac, 0x3c2c3c3e,
    0x3c5c3c04, 0xbc18bc4e, 0x3c4ebc18, 0x3c78bb79, 0x3b483c7b, 0x3c0e3c55, 0x3c7bbb48, 0xbc553c0e, 0x3c0e3c55, 0x3c7bbb48,
    0x3c55bc0e, 0x3b483c7b, 0x3c553c0e, 0x3b48bc7b, 0x3c0ebc55, 0x3c7b3b48, 0x3c7b3b48, 0xbc55bc0e, 0x3b48bc7b, 0x3c0ebc55,
    0x3b793c78, 0x3c183c4e, 0x3c4ebc18, 0xbc043c5c, 0x3c2c3c3e, 0x3c71bbac, 0x3bdbbc67, 0x3c2c3c3e, 0x3c713bac, 0xba49bc80,
    0xba49bc80, 0x3c67bbdb, 0x3c7dbb16, 0xbc78bb79, 0xbc04bc5c, 0xbb16bc7d, 0x3b953c75, 0x3c223c46, 0x3bf1bc62, 0xbac93c7f,
    0x3c463c22, 0x3c62bbf1, 0xbac9bc7f, 0x3c753b95, 0x3c7f3ac9, 0xbb95bc75, 0xbc22bc46, 0x3bf1bc62, 0x3c62bbf1, 0xbc7f3ac9,
    0xbc75bb95, 0xbc46bc22, 0x3bac3c71, 0x3c2c3c3e, 0x3a49bc80, 0x3bac3c71, 0x3c5c3c04, 0x3c4ebc18, 0xbc18bc4e, 0x3c78bb79,
    0x3c7dbb16, 0xbc04bc5c, 0xbc78bb79, 0xbb16bc7d, 0x3c2cbc3e, 0xbc673bdb, 0xbc673bdb, 0xbc803a49, 0x00003c80, 0x3bc43c6d,
    0x00003c80, 0xbbc4bc6d, 0x00003c80, 0x3c6d3bc4, 0x00003c80, 0xbc6dbbc4, 0x00003c80, 0x3c6dbbc4, 0x00003c80, 0xbc6d3bc4,
    0x00003c80, 0x3bc4bc6d, 0x00003c80, 0xbbc43c6d, 0x3c3e3c2c, 0x3c713bac, 0x3c713bac, 0xbc803a49, 0x3c4e3c18, 0x3c5cbc04,
    0x3c783b79, 0xbc183c4e, 0x3c5c3c04, 0x3b16bc7d, 0x3c7d3b16, 0x3b793c78, 0x3c673bdb, 0xbc2cbc3e, 0x3c803a49, 0x3c673bdb,
    0x3c7fbac9, 0x3c62bbf1, 0x3c22bc46, 0xbb953c75, 0x3c75bb95, 0x3ac9bc7f, 0x3bf1bc62, 0x3c223c46, 0x3c62bbf1, 0xbc46bc22,
    0x3b95bc75, 0x3c7fbac9, 0x3c46bc22, 0xbc753b95, 0x3ac9bc7f, 0x3bf1bc62, 0x3c18bc4e, 0x3b79bc78, 0xbc04bc5c, 0x3c4e3c18,
    0x3bacbc71, 0xbc3ebc2c, 0xbc3ebc2c, 0x3c67bbdb, 0x3a49bc80, 0xbc713bac, 0xbc67bbdb, 0x3a49bc80, 0xbb79bc78, 0xbb163c7d,
    0xbc7dbb16, 0xbc5cbc04, 0xbb48bc7b, 0xbc0ebc55, 0xbc7b3b48, 0x3c55bc0e, 0xbc0ebc55, 0xbc7b3b48, 0xbc553c0e, 0xbb48bc7b,
    0xbc55bc0e, 0xbb483c7b, 0xbc0e3c55, 0xbc7bbb48, 0xbc7bbb48, 0x3c553c0e, 0xbb483c7b, 0xbc0e3c55, 0xbc5cbc04, 0xbc7dbb16,
    0xbb163c7d, 0xbb79bc78, 0xbc80ba49, 0xbbdb3c67, 0x3bac3c71, 0xbc80ba49, 0xbc673bdb, 0x3c3e3c2c, 0x3c3e3c2c, 0xbbac3c71,
    0xbc183c4e, 0x3c5cbc04, 0x3c783b79, 0x3c4e3c18, 0xbc753b95, 0xbc463c22, 0x3c623bf1, 0xbc7fbac9, 0xbc223c46, 0x3bf13c62,
    0x3c7fbac9, 0xbb953c75, 0xbac93c7f, 0x3c75bb95, 0x3c46bc22, 0x3c623bf1, 0x3bf13c62, 0xbac9bc7f, 0x3b95bc75, 0x3c22bc46,
    0xbbdb3c67, 0xba493c80, 0x3c3ebc2c, 0xbbdb3c67, 0x3b793c78, 0x3c7d3b16, 0x3b16bc7d, 0x3c5c3c04, 0x3c4e3c18, 0x3b79bc78,
    0xbc04bc5c, 0x3c18bc4e, 0x3c80ba49, 0xbc71bbac, 0xbc71bbac, 0xbc3ebc2c, 0x00003c80, 0x3bc43c6d, 0x00003c80, 0xbbc4bc6d,
    0x00003c80, 0x3c6d3bc4, 0x00003c80, 0xbc6dbbc4, 0x00003c80, 0x3c6dbbc4, 0x00003c80, 0xbc6d3bc4, 0x00003c80, 0x3bc4bc6d,
    0x00003c80, 0xbbc43c6d, 0x3c80ba49, 0x3c67bbdb, 0x3c67bbdb, 0xbc2c3c3e, 0x3c7dbb16, 0x3b79bc78, 0x3c5cbc04, 0x3b163c7d,
    0x3c78bb79, 0xbc18bc4e, 0x3c4ebc18, 0x3c5c3c04, 0x3c71bbac, 0xbc80ba49, 0x3c3ebc2c, 0x3c71bbac, 0xbac9bc7f, 0xbbf1bc62,
    0xbc46bc22, 0x3c753b95, 0xbb95bc75, 0xbc7fbac9, 0xbc62bbf1, 0x3c46bc22, 0xbbf1bc62, 0xbc223c46, 0xbc75bb95, 0xbac9bc7f,
    0xbc22bc46, 0x3b953c75, 0xbc7fbac9, 0xbc62bbf1, 0xbc7d3b16, 0xbc5c3c04, 0xbb793c78, 0xbb16bc7d, 0xbc673bdb, 0x3a493c80,
    0x3a493c80, 0xbc71bbac, 0xbc3e3c2c, 0x3c673bdb, 0x3bac3c71, 0xbc3e3c2c, 0xbc043c5c, 0x3c4ebc18, 0x3c183c4e, 0x3b793c78,
    0x3b483c7b, 0x3c0e3c55, 0x3c7bbb48, 0xbc553c0e, 0x3c0e3c55, 0x3c7bbb48, 0x3c55bc0e, 0x3b483c7b, 0x3c553c0e, 0x3b48bc7b,
    0x3c0ebc55, 0x3c7b3b48, 0x3c7b3b48, 0xbc55bc0e, 0x3b48bc7b, 0x3c0ebc55, 0x3c78bb79, 0x3c4ebc18, 0xbc18bc4e, 0x3c5c3c04,
    0x3c3ebc2c, 0xbbacbc71, 0xbc67bbdb, 0x3c3ebc2c, 0x3bacbc71, 0xbc803a49, 0xbc803a49, 0xbbdbbc67, 0xbb16bc7d, 0xbb793c78,
    0xbc5c3c04, 0xbc7d3b16, 0xbb95bc75, 0xbc22bc46, 0xbbf13c62, 0x3ac9bc7f, 0xbc46bc22, 0xbc623bf1, 0x3ac93c7f, 0xbc75bb95,
    0xbc7fbac9, 0x3b953c75, 0x3c223c46, 0xbbf13c62, 0xbc623bf1, 0x3c7fbac9, 0x3c753b95, 0x3c463c22, 0xbc713bac, 0xbc3e3c2c,
    0x3c803a49, 0xbc713bac, 0xbc043c5c, 0x3c183c4e, 0x3c4ebc18, 0x3b793c78, 0x3b163c7d, 0x3c5cbc04, 0x3b79bc78, 0x3c7dbb16,
    0x3c3e3c2c, 0xbbdbbc67, 0xbbdbbc67, 0xba49bc80, 0x00003c80, 0x3bc43c6d, 0x00003c80, 0xbbc4bc6d, 0x00003c80, 0x3c6d3bc4,
    0x00003c80, 0xbc6dbbc4, 0x00003c80, 0x3c6dbbc4, 0x00003c80, 0xbc6d3bc4, 0x00003c80, 0x3bc4bc6d, 0x00003c80, 0xbbc43c6d,
    0x3c2cbc3e, 0x3bacbc71, 0x3bacbc71, 0x3a493c80, 0x3c18bc4e, 0xbc04bc5c, 0x3b79bc78, 0x3c4e3c18, 0x3c04bc5c, 0xbc7dbb16,
    0x3b16bc7d, 0x3c78bb79, 0x3bdbbc67, 0xbc3e3c2c, 0x3a49bc80, 0x3bdbbc67, 0xbc7f3ac9, 0xbc623bf1, 0xbc223c46, 0x3b95bc75,
    0xbc753b95, 0xbac93c7f, 0xbbf13c62, 0xbc22bc46, 0xbc623bf1, 0x3c463c22, 0xbb953c75, 0xbc7f3ac9, 0xbc463c22, 0x3c75bb95,
    0xbac93c7f, 0xbbf13c62, 0x3c4e3c18, 0x3c783b79, 0x3c5cbc04, 0xbc183c4e, 0x3c713bac, 0x3c2cbc3e, 0x3c2cbc3e, 0x3bdb3c67,
    0x3c803a49, 0xbbacbc71, 0x3bdbbc67, 0x3c803a49, 0x3c78bb79, 0xbc7dbb16, 0x3b16bc7d, 0x3c04bc5c, 0xbb48bc7b, 0xbc0ebc55,
    0xbc7b3b48, 0x3c55bc0e, 0xbc0ebc55, 0xbc7b3b48, 0xbc553c0e, 0xbb48bc7b, 0xbc55bc0e, 0xbb483c7b, 0xbc0e3c55, 0xbc7bbb48,
    0xbc7bbb48, 0x3c553c0e, 0xbb483c7b, 0xbc0e3c55, 0xbc043c5c, 0xbb163c7d, 0x3c7d3b16, 0xbc783b79, 0xba493c80, 0x3c673bdb,
    0x3c71bbac, 0xba493c80, 0x3bdb3c67, 0x3c2cbc3e, 0x3c2cbc3e, 0x3c713bac, 0x3c4e3c18, 0xbc04bc5c, 0x3b79bc78, 0x3c18bc4e,
    0x3c75bb95, 0x3c46bc22, 0xbc62bbf1, 0x3c7f3ac9, 0x3c22bc46, 0xbbf1bc62, 0xbc7f3ac9, 0x3b95bc75, 0x3ac9bc7f, 0xbc753b95,
    0xbc463c22, 0xbc62bbf1, 0xbbf1bc62, 0x3ac93c7f, 0xbb953c75, 0xbc223c46, 0xbc67bbdb, 0xbc80ba49, 0x3c2c3c3e, 0xbc67bbdb,
    0xbc783b79, 0xbb163c7d, 0x3c7d3b16, 0xbc043c5c, 0xbc183c4e, 0x3c783b79, 0x3c5cbc04, 0x3c4e3c18, 0x3a493c80, 0x3bacbc71,
    0x3bacbc71, 0x3c2cbc3e, 0x3c353c35, 0x3c6d3bc4, 0x3c353c35, 0xbc6dbbc4, 0x3c35bc35, 0xbbc4bc6d, 0x3c35bc35, 0x3bc43c6d,
    0xbc35bc35, 0xbbc43c6d, 0xbc35bc35, 0x3bc4bc6d, 0xbc353c35, 0x3c6dbbc4, 0xbc353c35, 0xbc6d3bc4, 0x3c3e3c2c, 0x3c713bac,
    0x3c713bac, 0xbc803a49, 0x3c18bc4e, 0xbc04bc5c, 0x3b79bc78, 0x3c4e3c18, 0xbc5cbc04, 0xbb163c7d, 0xbc7dbb16, 0xbb79bc78,
    0xbbdb3c67, 0x3c3ebc2c, 0xba493c80, 0xbbdb3c67, 0x3c463c22, 0x3c753b95, 0x3c7fbac9, 0xbc623bf1, 0x3bf1bc62, 0xbc22bc46,
    0xbb95bc75, 0x3c7f3ac9, 0xbc75bb95, 0x3ac93c7f, 0xbc623bf1, 0xbc46bc22, 0xbac93c7f, 0x3bf1bc62, 0x3c223c46, 0x3b953c75,
    0x3c4e3c18, 0x3c783b79, 0x3c5cbc04, 0xbc183c4e, 0x3bacbc71, 0xbc3ebc2c, 0xbc3ebc2c, 0x3c67bbdb, 0xbc80ba49, 0x3bac3c71,
    0xbbdb3c67, 0xbc80ba49, 0x3b793c78, 0x3b16bc7d, 0x3c7d3b16, 0x3c5c3c04, 0x3c553c0e, 0x3c7b3b48, 0x3c0ebc55, 0xbb483c7b,
    0x3b48bc7b, 0xbc55bc0e, 0xbc7bbb48, 0x3c0ebc55, 0xbc7b3b48, 0x3c0e3c55, 0x3b483c7b, 0xbc553c0e, 0x3c0e3c55, 0xbb48bc7b,
    0x3c55bc0e, 0x3c7bbb48, 0x3c5c3c04, 0x3c7d3b16, 0x3b16bc7d, 0x3b793c78, 0x3a49bc80, 0xbc67bbdb, 0xbc713bac, 0x3a49bc80,
    0xbc673bdb, 0x3c3e3c2c, 0x3c3e3c2c, 0xbbac3c71, 0x3c4e3c18, 0xbc04bc5c, 0x3b79bc78, 0x3c18bc4e, 0x3c623bf1, 0x3c7f3ac9,
    0xbb95bc75, 0x3c223c46, 0xbac9bc7f, 0xbc75bb95, 0xbc223c46, 0xbbf1bc62, 0xbc463c22, 0x3c623bf1, 0x3c7f3ac9, 0x3b953c75,
    0x3c753b95, 0xbc46bc22, 0xbbf1bc62, 0xbac9bc7f, 0x3c673bdb, 0x3c803a49, 0xbc2cbc3e, 0x3c673bdb, 0xbb79bc78, 0xbc7dbb16,
    0xbb163c7d, 0xbc5cbc04, 0xbc183c4e, 0x3c783b79, 0x3c5cbc04, 0x3c4e3c18, 0x3c80ba49, 0xbc71bbac, 0xbc71bbac, 0xbc3ebc2c,
    0x3c353c35, 0x3c6d3bc4, 0x3c353c35, 0xbc6dbbc4, 0x3c35bc35, 0xbbc4bc6d, 0x3c35bc35, 0x3bc43c6d, 0xbc35bc35, 0xbbc43c6d,
    0xbc35bc35, 0x3bc4bc6d, 0xbc353c35, 0x3c6dbbc4, 0xbc353c35, 0xbc6d3bc4, 0x3c80ba49, 0x3c67bbdb, 0x3c67bbdb, 0xbc2c3c3e,
    0xbb16bc7d, 0xbc78bb79, 0xbc04bc5c, 0x3c7dbb16, 0xbc783b79, 0x3c183c4e, 0xbc4e3c18, 0xbc5cbc04, 0x3bac3c71, 0x3a49bc80,
    0x3c2c3c3e, 0x3bac3c71, 0x3c22bc46, 0x3b95bc75, 0xbac9bc7f, 0x3bf13c62, 0xbc62bbf1, 0xbc463c22, 0xbc753b95, 0x3ac9bc7f,
    0xbb953c75, 0x3c7fbac9, 0x3bf13c62, 0xbc223c46, 0x3c7f3ac9, 0xbc62bbf1, 0x3c46bc22, 0x3c75bb95, 0xbb16bc7d, 0xbc04bc5c,
    0xbc78bb79, 0x3c7dbb16, 0xbc673bdb, 0x3a493c80, 0x3a493c80, 0xbc71bbac, 0x3c2c3c3e, 0x3bdbbc67, 0x3c71bbac, 0x3c2c3c3e,
    0x3c04bc5c, 0xbc4e3c18, 0xbc18bc4e, 0xbb79bc78, 0xbc55bc0e, 0xbc7bbb48, 0xbc0e3c55, 0x3b48bc7b, 0xbb483c7b, 0x3c553c0e,
    0x3c7b3b48, 0xbc0e3c55, 0x3c7bbb48, 0xbc0ebc55, 0xbb48bc7b, 0x3c55bc0e, 0xbc0ebc55, 0x3b483c7b, 0xbc553c0e, 0xbc7b3b48,
    0xbc783b79, 0xbc4e3c18, 0x3c183c4e, 0xbc5cbc04, 0x3c2c3c3e, 0x3c71bbac, 0x3bdbbc67, 0x3c2c3c3e, 0x3bacbc71, 0xbc803a49,
    0xbc803a49, 0xbbdbbc67, 0xbc7d3b16, 0x3c783b79, 0x3c043c5c, 0x3b163c7d, 0xbbf13c62, 0xbac93c7f, 0x3c75bb95, 0xbc463c22,
    0x3c7fbac9, 0x3b95bc75, 0xbc46bc22, 0x3c62bbf1, 0xbc22bc46, 0xbbf13c62, 0xbac93c7f, 0xbc753b95, 0xbb953c75, 0x3c22bc46,
    0x3c62bbf1, 0x3c7fbac9, 0x3bac3c71, 0x3c2c3c3e, 0x3a49bc80, 0x3bac3c71, 0x3c04bc5c, 0xbc18bc4e, 0xbc4e3c18, 0xbb79bc78,
    0xbc7d3b16, 0x3c043c5c, 0x3c783b79, 0x3b163c7d, 0x3c3e3c2c, 0xbbdbbc67, 0xbbdbbc67, 0xba49bc80, 0x3c353c35, 0x3c6d3bc4,
    0x3c353c35, 0xbc6dbbc4, 0x3c35bc35, 0xbbc4bc6d, 0x3c35bc35, 0x3bc43c6d, 0xbc35bc35, 0xbbc43c6d, 0xbc35bc35, 0x3bc4bc6d,
    0xbc353c35, 0x3c6dbbc4, 0xbc353c35, 0xbc6d3bc4, 0x3c2cbc3e, 0x3bacbc71, 0x3bacbc71, 0x3a493c80, 0xbc4ebc18, 0xbc5c3c04,
    0xbc78bb79, 0x3c18bc4e, 0xbc043c5c, 0x3c7d3b16, 0xbb163c7d, 0xbc783b79, 0x3c673bdb, 0xbc2cbc3e, 0x3c803a49, 0x3c673bdb,
    0xbc46bc22, 0xbc75bb95, 0xbc7f3ac9, 0x3c62bbf1, 0xbbf13c62, 0x3c223c46, 0x3b953c75, 0xbc7fbac9, 0x3c753b95, 0xbac9bc7f,
    0x3c62bbf1, 0x3c463c22, 0x3ac9bc7f, 0xbbf13c62, 0xbc22bc46, 0xbb95bc75, 0xbc183c4e, 0xbb793c78, 0x3c043c5c, 0xbc4ebc18,
    0x3c713bac, 0x3c2cbc3e, 0x3c2cbc3e, 0x3bdb3c67, 0x3a49bc80, 0xbc713bac, 0xbc67bbdb, 0x3a49bc80, 0xbc783b79, 0x3c7d3b16,
    0xbb163c7d, 0xbc043c5c, 0x3c553c0e, 0x3c7b3b48, 0x3c0ebc55, 0xbb483c7b, 0x3b48bc7b, 0xbc55bc0e, 0xbc7bbb48, 0x3c0ebc55,
    0xbc7b3b48, 0x3c0e3c55, 0x3b483c7b, 0xbc553c0e, 0x3c0e3c55, 0xbb48bc7b, 0x3c55bc0e, 0x3c7bbb48, 0x3c04bc5c, 0x3b16bc7d,
    0xbc7dbb16, 0x3c78bb79, 0xbc80ba49, 0xbbdb3c67, 0x3bac3c71, 0xbc80ba49, 0x3bdb3c67, 0x3c2cbc3e, 0x3c2cbc3e, 0x3c713bac,
    0x3c18bc4e, 0xbc5c3c04, 0xbc78bb79, 0xbc4ebc18, 0xbc62bbf1, 0xbc7fbac9, 0x3b953c75, 0xbc22bc46, 0x3ac93c7f, 0x3c753b95,
    0x3c22bc46, 0x3bf13c62, 0x3c46bc22, 0xbc62bbf1, 0xbc7fbac9, 0xbb95bc75, 0xbc75bb95, 0x3c463c22, 0x3bf13c62, 0x3ac93c7f,
    0xbbdb3c67, 0xba493c80, 0x3c3ebc2c, 0xbbdb3c67, 0x3c78bb79, 0x3b16bc7d, 0xbc7dbb16, 0x3c04bc5c, 0xbc4ebc18, 0xbb793c78,
    0x3c043c5c, 0xbc183c4e, 0x3a493c80, 0x3bacbc71, 0x3bacbc71, 0x3c2cbc3e, 0x3c353c35, 0x3c6d3bc4, 0x3c353c35, 0xbc6dbbc4,
    0x3c35bc35, 0xbbc4bc6d, 0x3c35bc35, 0x3bc43c6d, 0xbc35bc35, 0xbbc43c6d, 0xbc35bc35, 0x3bc4bc6d, 0xbc353c35, 0x3c6dbbc4,
    0xbc353c35, 0xbc6d3bc4, 0xba49bc80, 0xbbdbbc67, 0xbbdbbc67, 0x3c3e3c2c, 0xbc7d3b16, 0xbb793c78, 0xbc5c3c04, 0xbb16bc7d,
    0x3b793c78, 0x3c4ebc18, 0x3c183c4e, 0xbc043c5c, 0x3c71bbac, 0xbc80ba49, 0x3c3ebc2c, 0x3c71bbac, 0xbc223c46, 0xbb953c75,
    0x3ac93c7f, 0xbbf1bc62, 0x3c623bf1, 0x3c46bc22, 0x3c75bb95, 0xbac93c7f, 0x3b95bc75, 0xbc7f3ac9, 0xbbf1bc62, 0x3c22bc46,
    0xbc7fbac9, 0x3c623bf1, 0xbc463c22, 0xbc753b95, 0x3c7dbb16, 0x3c5cbc04, 0x3b79bc78, 0x3b163c7d, 0xbbdbbc67, 0xbc803a49,
    0xbc803a49, 0x3bacbc71, 0xbc3e3c2c, 0x3c673bdb, 0x3bac3c71, 0xbc3e3c2c, 0x3c5c3c04, 0xbc18bc4e, 0x3c4ebc18, 0x3c78bb79,
    0xbc55bc0e, 0xbc7bbb48, 0xbc0e3c55, 0x3b48bc7b, 0xbb483c7b, 0x3c553c0e, 0x3c7b3b48, 0xbc0e3c55, 0x3c7bbb48, 0xbc0ebc55,
    0xbb48bc7b, 0x3c55bc0e, 0xbc0ebc55, 0x3b483c7b, 0xbc553c0e, 0xbc7b3b48, 0x3b793c78, 0x3c183c4e, 0x3c4ebc18, 0xbc043c5c,
    0x3c3ebc2c, 0xbbacbc71, 0xbc67bbdb, 0x3c3ebc2c, 0xbc71bbac, 0x3a493c80, 0x3a493c80, 0xbc673bdb, 0x3b163c7d, 0x3b79bc78,
    0x3c5cbc04, 0x3c7dbb16, 0x3bf1bc62, 0x3ac9bc7f, 0xbc753b95, 0x3c46bc22, 0xbc7f3ac9, 0xbb953c75, 0x3c463c22, 0xbc623bf1,
    0x3c223c46, 0x3bf1bc62, 0x3ac9bc7f, 0x3c75bb95, 0x3b95bc75, 0xbc223c46, 0xbc623bf1, 0xbc7f3ac9, 0xbc713bac, 0xbc3e3c2c,
    0x3c803a49, 0xbc713bac, 0x3c5c3c04, 0x3c4ebc18, 0xbc18bc4e, 0x3c78bb79, 0xbb16bc7d, 0xbc5c3c04, 0xbb793c78, 0xbc7d3b16,
    0xbc2c3c3e, 0x3c67bbdb, 0x3c67bbdb, 0x3c80ba49, 0x3c800000, 0x3c6dbbc4, 0x3c800000, 0xbc6d3bc4, 0xbc800000, 0xbbc43c6d,
    0xbc800000, 0x3bc4bc6d, 0x3c800000, 0xbbc4bc6d, 0x3c800000, 0x3bc43c6d, 0xbc800000, 0x3c6d3bc4, 0xbc800000, 0xbc6dbbc4,
    0x3c80ba49, 0x3c67bbdb, 0x3c67bbdb, 0xbc2c3c3e, 0xbc7d3b16, 0xbb793c78, 0xbc5c3c04, 0xbb16bc7d, 0x3c78bb79, 0xbc18bc4e,
    0x3c4ebc18, 0x3c5c3c04, 0xbc713bac, 0x3c803a49, 0xbc3e3c2c, 0xbc713bac, 0x3c7fbac9, 0x3c62bbf1, 0x3c22bc46, 0xbb953c75,
    0xbc753b95, 0xbac93c7f, 0xbbf13c62, 0xbc22bc46, 0x3c62bbf1, 0xbc46bc22, 0x3b95bc75, 0x3c7fbac9, 0xbc463c22, 0x3c75bb95,
    0xbac93c7f, 0xbbf13c62, 0x3c7dbb16, 0x3c5cbc04, 0x3b79bc78, 0x3b163c7d, 0xbc673bdb, 0x3a493c80, 0x3a493c80, 0xbc71bbac,
    0x3c3ebc2c, 0xbc67bbdb, 0xbbacbc71, 0x3c3ebc2c, 0xbc043c5c, 0x3c4ebc18, 0x3c183c4e, 0x3b793c78, 0x3c7bbb48, 0x3c55bc0e,
    0xbb48bc7b, 0x3c0e3c55, 0xbc553c0e, 0x3b483c7b, 0x3c0e3c55, 0xbc7b3b48, 0x3c0ebc55, 0xbc7bbb48, 0xbc55bc0e, 0x3b48bc7b,
    0xbb483c7b, 0x3c0ebc55, 0x3c7b3b48, 0x3c553c0e, 0x3c78bb79, 0x3c4ebc18, 0xbc18bc4e, 0x3c5c3c04, 0xbc3e3c2c, 0x3bac3c71,
    0x3c673bdb, 0xbc3e3c2c, 0x3bacbc71, 0xbc803a49, 0xbc803a49, 0xbbdbbc67, 0x3b163c7d, 0x3b79bc78, 0x3c5cbc04, 0x3c7dbb16,
    0x3c75bb95, 0x3c46bc22, 0xbc62bbf1, 0x3c7f3ac9, 0xbc223c46, 0x3bf13c62, 0x3c7fbac9, 0xbb953c75, 0x3ac9bc7f, 0xbc753b95,
    0xbc463c22, 0xbc62bbf1, 0x3bf13c62, 0xbac9bc7f, 0x3b95bc75, 0x3c22bc46, 0x3c71bbac, 0x3c3ebc2c, 0xbc80ba49, 0x3c71bbac,
    0xbc043c5c, 0x3c183c4e, 0x3c4ebc18, 0x3b793c78, 0xbb16bc7d, 0xbc5c3c04, 0xbb793c78, 0xbc7d3b16, 0x3c3e3c2c, 0xbbdbbc67,
    0xbbdbbc67, 0xba49bc80, 0x3c800000, 0x3c6dbbc4, 0x3c800000, 0xbc6d3bc4, 0xbc800000, 0xbbc43c6d, 0xbc800000, 0x3bc4bc6d,
    0x3c800000, 0xbbc4bc6d, 0x3c800000, 0x3bc43c6d, 0xbc800000, 0x3c6d3bc4, 0xbc800000, 0xbc6dbbc4, 0x3c2cbc3e, 0x3bacbc71,
    0x3bacbc71, 0x3a493c80, 0xbc183c4e, 0x3c043c5c, 0xbb793c78, 0xbc4ebc18, 0x3c04bc5c, 0xbc7dbb16, 0x3b16bc7d, 0x3c78bb79,
    0xbbdb3c67, 0x3c3ebc2c, 0xba493c80, 0xbbdb3c67, 0xbac9bc7f, 0xbbf1bc62, 0xbc46bc22, 0x3c753b95, 0x3b953c75, 0x3c7f3ac9,
    0x3c623bf1, 0xbc463c22, 0xbbf1bc62, 0xbc223c46, 0xbc75bb95, 0xbac9bc7f, 0x3c223c46, 0xbb95bc75, 0x3c7f3ac9, 0x3c623bf1,
    0xbc4ebc18, 0xbc78bb79, 0xbc5c3c04, 0x3c18bc4e, 0x3c713bac, 0x3c2cbc3e, 0x3c2cbc3e, 0x3bdb3c67, 0xbc80ba49, 0x3bac3c71,
    0xbbdb3c67, 0xbc80ba49, 0x3c78bb79, 0xbc7dbb16, 0x3b16bc7d, 0x3c04bc5c, 0xbc7b3b48, 0xbc553c0e, 0x3b483c7b, 0xbc0ebc55,
    0x3c55bc0e, 0xbb48bc7b, 0xbc0ebc55, 0x3c7bbb48, 0xbc0e3c55, 0x3c7b3b48, 0x3c553c0e, 0xbb483c7b, 0x3b48bc7b, 0xbc0e3c55,
    0xbc7bbb48, 0xbc55bc0e, 0xbc043c5c, 0xbb163c7d, 0x3c7d3b16, 0xbc783b79, 0x3a49bc80, 0xbc67bbdb, 0xbc713bac, 0x3a49bc80,
    0x3bdb3c67, 0x3c2cbc3e, 0x3c2cbc3e, 0x3c713bac, 0xbc4ebc18, 0x3c043c5c, 0xbb793c78, 0xbc183c4e, 0x3b953c75, 0x3c223c46,
    0x3bf1bc62, 0xbac93c7f, 0xbc46bc22, 0xbc623bf1, 0x3ac93c7f, 0xbc75bb95, 0x3c7f3ac9, 0xbb95bc75, 0xbc22bc46, 0x3bf1bc62,
    0xbc623bf1, 0x3c7fbac9, 0x3c753b95, 0x3c463c22, 0x3c673bdb, 0x3c803a49, 0xbc2cbc3e, 0x3c673bdb, 0xbc783b79, 0xbb163c7d,
    0x3c7d3b16, 0xbc043c5c, 0x3c18bc4e, 0xbc78bb79, 0xbc5c3c04, 0xbc4ebc18, 0x3a493c80, 0x3bacbc71, 0x3bacbc71, 0x3c2cbc3e,
    0x3c800000, 0x3c6dbbc4, 0x3c800000, 0xbc6d3bc4, 0xbc800000, 0xbbc43c6d, 0xbc800000, 0x3bc4bc6d, 0x3c800000, 0xbbc4bc6d,
    0x3c800000, 0x3bc43c6d, 0xbc800000, 0x3c6d3bc4, 0xbc800000, 0xbc6dbbc4, 0xba49bc80, 0xbbdbbc67, 0xbbdbbc67, 0x3c3e3c2c,
    0x3b163c7d, 0x3c783b79, 0x3c043c5c, 0xbc7d3b16, 0xbb79bc78, 0xbc4e3c18, 0xbc18bc4e, 0x3c04bc5c, 0x3bac3c71, 0x3a49bc80,
    0x3c2c3c3e, 0x3bac3c71, 0xbc7f3ac9, 0xbc623bf1, 0xbc223c46, 0x3b95bc75, 0x3c75bb95, 0x3ac9bc7f, 0x3bf1bc62, 0x3c223c46,
    0xbc623bf1, 0x3c463c22, 0xbb953c75, 0xbc7f3ac9, 0x3c46bc22, 0xbc753b95, 0x3ac9bc7f, 0x3bf1bc62, 0x3b163c7d, 0x3c043c5c,
    0x3c783b79, 0xbc7d3b16, 0xbbdbbc67, 0xbc803a49, 0xbc803a49, 0x3bacbc71, 0x3c2c3c3e, 0x3bdbbc67, 0x3c71bbac, 0x3c2c3c3e,
    0xbc5cbc04, 0x3c183c4e, 0xbc4e3c18, 0xbc783b79, 0x3c7bbb48, 0x3c55bc0e, 0xbb48bc7b, 0x3c0e3c55, 0xbc553c0e, 0x3b483c7b,
    0x3c0e3c55, 0xbc7b3b48, 0x3c0ebc55, 0xbc7bbb48, 0xbc55bc0e, 0x3b48bc7b, 0xbb483c7b, 0x3c0ebc55, 0x3c7b3b48, 0x3c553c0e,
    0xbb79bc78, 0xbc18bc4e, 0xbc4e3c18, 0x3c04bc5c, 0x3c2c3c3e, 0x3c71bbac, 0x3bdbbc67, 0x3c2c3c3e, 0xbc71bbac, 0x3a493c80,
    0x3a493c80, 0xbc673bdb, 0x3c7dbb16, 0xbc78bb79, 0xbc04bc5c, 0xbb16bc7d, 0xbc753b95, 0xbc463c22, 0x3c623bf1, 0xbc7fbac9,
    0x3c22bc46, 0xbbf1bc62, 0xbc7f3ac9, 0x3b95bc75, 0xbac93c7f, 0x3c75bb95, 0x3c46bc22, 0x3c623bf1, 0xbbf1bc62, 0x3ac93c7f,
    0xbb953c75, 0xbc223c46, 0x3bac3c71, 0x3c2c3c3e, 0x3a49bc80, 0x3bac3c71, 0xbc5cbc04, 0xbc4e3c18, 0x3c183c4e, 0xbc783b79,
    0x3c7dbb16, 0xbc04bc5c, 0xbc78bb79, 0xbb16bc7d, 0xbc2c3c3e, 0x3c67bbdb, 0x3c67bbdb, 0x3c80ba49, 0x3c800000, 0x3c6dbbc4,
    0x3c800000, 0xbc6d3bc4, 0xbc800000, 0xbbc43c6d, 0xbc800000, 0x3bc4bc6d, 0x3c800000, 0xbbc4bc6d, 0x3c800000, 0x3bc43c6d,
    0xbc800000, 0x3c6d3bc4, 0xbc800000, 0xbc6dbbc4, 0xbc3ebc2c, 0xbc71bbac, 0xbc71bbac, 0x3c80ba49, 0x3c4e3c18, 0x3c5cbc04,
    0x3c783b79, 0xbc183c4e, 0xbc5cbc04, 0xbb163c7d, 0xbc7dbb16, 0xbb79bc78, 0x3c673bdb, 0xbc2cbc3e, 0x3c803a49, 0x3c673bdb,
    0x3ac93c7f, 0x3bf13c62, 0x3c463c22, 0xbc75bb95, 0xbb95bc75, 0xbc7fbac9, 0xbc62bbf1, 0x3c46bc22, 0x3bf13c62, 0x3c22bc46,
    0x3c753b95, 0x3ac93c7f, 0xbc22bc46, 0x3b953c75, 0xbc7fbac9, 0xbc62bbf1, 0x3c18bc4e, 0x3b79bc78, 0xbc04bc5c, 0x3c4e3c18,
    0xbbac3c71, 0x3c3e3c2c, 0x3c3e3c2c, 0xbc673bdb, 0x3a49bc80, 0xbc713bac, 0xbc67bbdb, 0x3a49bc80, 0x3b793c78, 0x3b16bc7d,
    0x3c7d3b16, 0x3c5c3c04, 0xbc7b3b48, 0xbc553c0e, 0x3b483c7b, 0xbc0ebc55, 0x3c55bc0e, 0xbb48bc7b, 0xbc0ebc55, 0x3c7bbb48,
    0xbc0e3c55, 0x3c7b3b48, 0x3c553c0e, 0xbb483c7b, 0x3b48bc7b, 0xbc0e3c55, 0xbc7bbb48, 0xbc55bc0e, 0x3c5c3c04, 0x3c7d3b16,
    0x3b16bc7d, 0x3b793c78, 0xbc80ba49, 0xbbdb3c67, 0x3bac3c71, 0xbc80ba49, 0x3c67bbdb, 0xbc3ebc2c, 0xbc3ebc2c, 0x3bacbc71,
    0xbc183c4e, 0x3c5cbc04, 0x3c783b79, 0x3c4e3c18, 0xbb95bc75, 0xbc22bc46, 0xbbf13c62, 0x3ac9bc7f, 0x3c463c22, 0x3c62bbf1,
    0xbac9bc7f, 0x3c753b95, 0xbc7fbac9, 0x3b953c75, 0x3c223c46, 0xbbf13c62, 0x3c62bbf1, 0xbc7f3ac9, 0xbc75bb95, 0xbc46bc22,
    0xbbdb3c67, 0xba493c80, 0x3c3ebc2c, 0xbbdb3c67, 0xbb79bc78, 0xbc7dbb16, 0xbb163c7d, 0xbc5cbc04, 0x3c4e3c18, 0x3b79bc78,
    0xbc04bc5c, 0x3c18bc4e, 0xbc803a49, 0x3c713bac, 0x3c713bac, 0x3c3e3c2c,
};

#define G_EPI 3
#define G_TK 3
#define W_Q 6
#define W2_PC 32
#define W2_PF 3
constexpr int X_LOC0 = 5;
constexpr int A_IN = 112 * 128;
constexpr int G_ST = 2 * NB1 * 64;
constexpr int K1_R = 131072, K1_BAR = K1_R + 98304, K1_SMEM = K1_BAR + 2048 + 1024;
constexpr int K1_T = K1_R + 65536, K1_TIN = 0, K1_Y0 = 3 * G_ST + 8192, G_KM = 16 - G_TK, G_S0 = 2 * G_KM;
__device__ int g_done[8 * 32];
struct Ptrs {
  int* done;
  float* ge;
  const uint32_t *img, *ga;
};

__host__ __device__ constexpr int g_depth(int s) { return s < 11 ? 3 : s < 18 ? 4 : s < 23 ? 5 : 6; }
__host__ __device__ constexpr int g_slot(int s) { return s < 3 ? s : g_depth(s) != g_depth(s - 1) ? g_depth(s - 1) : g_slot(s - g_depth(s)); }
__host__ __device__ constexpr int g_off(int id) { return id * G_ST + (id < 3 ? K1_R : 8192 - 3 * G_ST); }
struct Plan {
  uint32_t raw[32];
  uint32_t x[16];
  uint32_t grp[8];
  uint32_t last;
  uint32_t wpf;
  uint32_t g0;
  uint32_t tmask;
  uint64_t list[2];
};
struct K1Maps {
  Plan p;
  CUtensorMap x, we, wo, xs, y, w2e, w2o, w2s;
  int slot[32];
  int src[32];
  int dep[32];
};
__device__ __forceinline__ void poll_ge(const int* p, int target) {
  for (int it = 0; it < (1 << 20); it++) {
    int v;
    asm volatile("ld.acquire.gpu.global.s32 %0, [%1];" : "=r"(v) : "l"(p) : "memory");
    if (v >= target) break;
  }
}
__device__ __forceinline__ uint32_t place(int rank, uint32_t c) { return (c ^ (rank * 4 & ~(c >> 1))) << 14; }
__device__ __forceinline__ int x_unit(int cta, int u, uint32_t pl) {
  const int i = u * 128 + cta;
  const int pr = cta >= 128 ? 2 * cta - 96 + (u & 1) : i % 160, sl = cta >= 128 ? u >> 1 : i / 160, b = pr >= 84;
  return pr | sl << 8 | b << 11 | (cta >= 128 ? (u & 7) << 14 : place(cta & 1, pl & 15)) | 12 * (pr - 84 * b) << 20;
}
__device__ __forceinline__ int lds32(uint32_t a) {
  int v;
  asm volatile("ld.shared.b32 %0, [%1];" : "=r"(v) : "r"(a));
  return v;
}
__host__ __device__ constexpr uint64_t sched(const char* p) {
  uint64_t r = 0;
  for (int n = 0; p[n]; n++) r |= (uint64_t)(p[n] - '0' + 1) << (5 * n);
  return r;
}

__global__ void __cluster_dims__(2, 1, 1) __launch_bounds__(384, 1)
k1(const Ptrs gp_, const char* __restrict__ x1, const char* __restrict__ w1, const __grid_constant__ K1Maps m, const __nv_bfloat16* __restrict__ g,
   const __nv_bfloat16* __restrict__ wgt) {
  extern __shared__ __align__(1024) uint8_t smem_k1[];
  const uint32_t sb = s2u(smem_k1);
  const int tid = threadIdx.x, cta = blockIdx.x, rank = cta & 1;
  if (tid == 288) {
    const uint32_t bar = sb + K1_BAR + 256, dst = sb + (cta >= 128 ? 0 : place(rank, X_LOC0));
    const int pr = cta >= 128 ? 2 * cta - 96 : cta, b = pr >= 84;
    mbar_init(bar, 1);
    mbar_expect(bar, A_IN);
    for (int h = 0; h < 2; h++) tma_ld4<1>(dst + h * (A_IN / 2), &m.x, bar, 0, 96 * (pr - 84 * b) - 24 + h * 56, 0, b);
    for (int i = 1; i < 4; i++) mbar_init(bar + 8 * i, 1);
    fence_bar_init();
  }
  const uint32_t sF = sb + (cta >= 128 ? K1_T : rank * 65536), fbar = sb + K1_BAR + 1792;
  if (tid == 320) {
    mbar_init(fbar, 1);
    mbar_expect(fbar, 8192);
    asm volatile("cp.async.bulk.shared::cluster.global.mbarrier::complete_tx::bytes [%0], [%1], 8192, [%2];" ::"r"(sF), "l"(gp_.img + 1536), "r"(fbar) : "memory");
    fence_bar_init();
  }
  const int wg = __shfl_sync(0xffffffffu, tid >> 7, 0), t = tid & 127;
  const int warp = __shfl_sync(0xffffffffu, t >> 5, 0), lane = t & 31;
  const bool spare = cta >= 128;
  const int nx = spare ? 16 : 10;
  int bp, dc;
  {
    const int ci = cta >> 1;
    const int G = ci < 4 ? 0 : ci < 36 ? (ci - 4) & 7 : 1 + (ci - 36) % 7;
    const int li = ci < 4 ? 4 + ci : ci < 36 ? (ci - 4) >> 3 : 4 + (ci - 36) / 7;
    bp = 2 * G + (li >> 2), dc = li & 3;
  }
  const int bin = 2 * bp + rank;
  const uint32_t bb = sb + K1_BAR;
  const uint32_t rfull = bb, xfull = bb + 256, xfree = bb + 384, gfull = bb + 512, win = bb + 1800, win1 = bb + 1808;
  const uint32_t inf0 = bb + 784, se0 = inf0 + 16, pfree = se0 + 16, rempty = bb + 1024, xready = bb + 1280;
  const uint32_t gdone = bb + 1536, ine0 = gdone + 224, sf0 = ine0 + 16;
  const uint32_t xtab = bb + 896, ptab = bb + 2048 + 768;
  auto raw_load = [&](int j, uint32_t dst) {
    mbar_expect(rfull + 8 * j, 16384);
    tma_ld4<0>(dst, rank ? &m.we : &m.wo, rfull + 8 * j, dc * 64, rank - 1, (j & 3) * 4, (j >> 2) * 2);
  };
  auto x_half = [&](int u, int c, int h) {
    tma_ld4<1>(sb + (c & 0x3C000) + h * (A_IN / 2), &m.x, xfull + 8 * u, 0, (c >> 17 & ~7) - 24 + h * 56, c >> 8 & 7, c >> 11 & 1);
  };
  auto w_prefetch = [&](int q) {
    if (cta < 124) asm volatile("cp.async.bulk.prefetch.L2.global [%0], 4096;" ::"l"(w1 + (cta >> 2) * 131072 + (q * 4 + (cta & 3)) * 4096) : "memory");
  };
  uint32_t peer;
  asm("mapa.shared::cluster.u32 %0, %1, %2;" : "=r"(peer) : "r"(sb), "r"(rank ^ 1));
  if (wg == 2) {
    if (lane == 0) {
      if (warp == 0) {
        for (int i = 0; i < 4; i++) mbar_init(bb + 8 * i, 1);
        fence_bar_init();
        if (!spare)
          for (int j = 0; j < 4; j++) raw_load(j, sb + K1_R + j * 16384);
      } else if (warp == 2) {
#pragma unroll 1
        for (int q = 1; q <= m.p.wpf; q++) w_prefetch(q);
        prefetch_map(&m.xs);
      }
    }
    if (warp == 3) {
      const uint32_t v = reinterpret_cast<const uint32_t*>(&m.p)[32 + lane];
      asm volatile("st.shared.b32 [%0], %1;" ::"r"(ptab + 4 * lane), "r"(m.p.raw[lane]) : "memory");
      asm volatile("st.shared.b32 [%0], %1;" ::"r"(ptab + 128 + 4 * lane), "r"(v) : "memory");
      if (lane < 16) asm volatile("st.shared.b32 [%0], %1;" ::"r"(xtab + 4 * lane), "r"(x_unit(cta, lane, v)) : "memory");
    }
  } else {
    const int c = 4 * wg + warp;
    if (lane == 0 && c < 7) {
      const uint32_t b0 = bb + 256 * c, n = c < 4 ? 1 : c < 6 ? 4 : 8;
      if (c >= 2)
        for (int i = 0; i < 4; i++) mbar_init(b0 + 8 * i, n);
      for (int i = 4; i < 16; i++) mbar_init(b0 + 8 * i, n);
      if (c == 3) {
        mbar_init(win, 1 + 2 * W_Q);
        mbar_init(win1, 17 - 2 * W_Q);
        mbar_expect(win, 8192 * W_Q);
        mbar_expect(win1, 65536 - 8192 * W_Q);
        mbar_arrive(bb + 776);
      } else {
        for (int i = 16; i < 32; i++) mbar_init(b0 + 8 * i, n);
      }
      fence_bar_init();
    }
  }
  pdl_launch();
  __syncthreads();
  asm volatile("barrier.cluster.arrive.relaxed.aligned;" ::: "memory");
  if (wg == 2) {
    asm volatile("setmaxnreg.dec.sync.aligned.u32 40;");
    asm volatile("barrier.cluster.wait.aligned;" ::: "memory");
    if (lane == 0) {
      const int wpf = lds32(ptab + 228), g0 = lds32(ptab + 232), s0 = g0 * 4 / 5;
      const int nx0 = spare ? 2 * s0 : g0;
      if (warp == 0) {
        if (!spare) {
#pragma unroll 1
          for (int j = 4; j < 32; j++) {
            const uint32_t e = lds32(ptab + 4 * j);
            mbar_wait(bb + (e >> 5 & ~7), 0);
            raw_load(j, sb + place(rank, e & 15));
            if ((j & 3) == 0 && wpf && (j >> 2) + wpf < 8) w_prefetch((j >> 2) + wpf);
          }
#pragma unroll 1
          for (int s = 0; s < 32; s++) {
            if (s == 0 || s == 4 * s0) {
              poll_ge(&gp_.done[(s ? 5 : 4) * 32], 132);
              asm volatile("fence.proxy.async.global;" ::: "memory");
              mbar_wait(bb + 8 * (lds32(ptab + 224) & 255), 0);
            }
            const uint32_t bar = gfull + 8 * s, dst = sb + 16 * m.slot[s];
            const char* src = x1 + bin * (4 * G_ST) + m.src[s];
            mbar_wait(bb + m.dep[s], 0);
            mbar_expect(bar, G_ST);
#pragma unroll
            for (int h = 0; h < 2; h++) {
              if (s >= 16)
                asm volatile("cp.async.bulk.shared::cluster.global.mbarrier::complete_tx::bytes.L2::cache_hint [%0], [%1], %2, [%3], %4;"
                             ::"r"(dst + h * (G_ST / 2)), "l"(src + h * (s < G_S0 ? G_ST / 2 : 2 * G_ST)), "n"(G_ST / 2), "r"(bar), "l"(policy<1>()) : "memory");
              else
                asm volatile("cp.async.bulk.shared::cluster.global.mbarrier::complete_tx::bytes [%0], [%1], %2, [%3];"
                             ::"r"(dst + h * (G_ST / 2)), "l"(src + h * (s < G_S0 ? G_ST / 2 : 2 * G_ST)), "n"(G_ST / 2), "r"(bar) : "memory");
            }
          }
          if (cta == 0) asm volatile("cp.async.bulk.prefetch.L2.global [%0], 14336;" ::"l"(gp_.img) : "memory");
        }
      } else if (warp < 3) {
        const int u0 = warp == 1 ? 0 : nx0, u1 = warp == 1 ? nx0 : nx;
#pragma unroll 1
        for (int u = u0; u < u1; u++) {
          const int c = lds32(xtab + 4 * u);
          const uint32_t e = spare ? 0xC0 : lds32(ptab + 128 + 4 * u);
          const uint32_t src = sb + (c & 0x3C000), rel = e >> 1 & 24, burst = (16 << (e >> 6 & 3)) - 1;
          mbar_wait(xready + 8 * u, 0);
#pragma unroll 1
          for (int p = 0; p < 128; p += 16) {
            tma_st4<0>(&m.xs, src + p * 128, 0, (c >> 2 & 0x1C0) + (p & 63), p >> 6, c & 255);
            if (((p + 16) & burst) == 0) {
              bulk_commit();
              bulk_wait_read<0>();
            }
          }
          mbar_arrive(xfree + 8 * u);
          if (rel)
            asm volatile("mbarrier.arrive.shared::cluster.b64 _, [%0];" ::"r"(peer + (pfree - sb) + rel) : "memory");
        }
        asm volatile("cp.async.bulk.wait_group 0;" ::: "memory");
        asm volatile("red.release.gpu.global.add.s32 [%0], 1;" ::"l"(&gp_.done[(3 + warp) * 32]) : "memory");
        if (!spare) {
          if (warp == 1) {
            auto w2_row = [&](int it, bool pf) {
              const CUtensorMap* mp = it & 1 ? &m.w2e : &m.w2o;
              const int c1 = (it & 1) - 1, c2 = (cta & 1) * 2, c3 = (it >> 1) * 64 + (cta >> 1);
              if (pf) {
                asm volatile("cp.async.bulk.prefetch.tensor.4d.L2.global [%0, {%1, %2, %3, %4}];" ::"l"(mp), "r"(0), "r"(c1), "r"(c2), "r"(c3) : "memory");
              } else {
                mbar_expect(inf0 + 8 * (it & 1), 4096);
                tma_ld4<1>(sb + K1_TIN + (it & 1) * 4096, mp, inf0 + 8 * (it & 1), 0, c1, c2, c3);
              }
            };
#pragma unroll 1
            for (int it = 0; it < W2_PF; it++) {
              mbar_wait(gfull + 8 * (it >> 1), 0);
              w2_row(it, true);
            }
            mbar_wait(gdone + 8, 0);
#pragma unroll 1
            for (int it = 0; it < 8; it++) {
              if (it >= 2) mbar_wait(ine0 + 8 * (it & 1), ((it >> 1) - 1) & 1);
              w2_row(it, false);
              if (W2_PF && it + W2_PF < 8) w2_row(it + W2_PF, true);
            }
          } else {
            prefetch_map(&m.w2s);
            prefetch_map(&m.y);
#pragma unroll 1
            for (int it = 0; it < 8; it++) {
              if ((0x74 >> it) & 1) poll_ge(&gp_.done[((0x33210000 >> (4 * it)) & 3) * 32], 128);
              mbar_wait(sf0 + 8 * (it & 1), (it >> 1) & 1);
#pragma unroll 1
              for (int p = 0; p < 128; p += W2_PC) {
                tma_st4<0>(&m.w2s, sb + K1_T + (it & 1) * 16384 + p * 128, 0, it * 64 + (p & 63), (cta & 1) * 2 + (p >> 6),
                           (cta >> 1 & 33) | (cta >> 3 & 6) | (cta << 1 & 24));
                bulk_commit();
                bulk_wait_read<0>();
              }
              mbar_arrive(se0 + 8 * (it & 1));
            }
          }
        }
      } else {
#pragma unroll 1
        for (int u = 1; u < nx; u++) {
          const int c = lds32(xtab + 4 * u);
          const uint32_t e = spare ? (u < 8 ? 97 : 40 + u) * 0x01010100u : lds32(ptab + 128 + 4 * u);
          mbar_wait(bb + (e >> 5 & 0x7F8), 0);
          mbar_expect(xfull + 8 * u, A_IN);
          mbar_wait(bb + (e >> 13 & 0x7F8), 0);
          x_half(u, c, 0);
          mbar_wait(bb + (e >> 21 & 0x7F8), 0);
          x_half(u, c, 1);
        }
#pragma unroll 1
        for (int s = 0; s < (spare ? 0 : 16); s++) {
          mbar_wait(gfull + 8 * s, 0);
          if ((s & 3) == 3) asm volatile("red.relaxed.gpu.global.add.s32 [%0], 1;" ::"l"(&gp_.done[(s >> 2) * 32]) : "memory");
        }
      }
    }
  } else {
    asm volatile("setmaxnreg.inc.sync.aligned.u32 232;");
    const int row = (lane & 7) + ((lane >> 3) & 1) * 8, hi = lane >> 4;
    asm volatile("barrier.cluster.wait.aligned;" ::: "memory");
    uint32_t fw[4];
    {
      uint32_t fa[16], za[64];
      mbar_wait(fbar, 0);
      const int f = (4 * bp + warp) & 63;
      const uint32_t lo = lds32(sF + f * 128 + ((f & 7) << 4) + (lane & 3) * 4), hh = lds32(sF + f * 128 + (((f & 7) ^ 1) << 4) + (lane & 3) * 4);
#pragma unroll
      for (int k = 0; k < 4; k++)
        ldsm4(sF + (warp * 16 + row) * 128 + (((2 * k + hi) ^ (lane & 7)) << 4), fa[4 * k], fa[4 * k + 1], fa[4 * k + 2], fa[4 * k + 3]);
      const int rho = (lane >> 3) | (lane & 4);
#pragma unroll
      for (int i = 0; i < 64; i++) za[i] = ((i & 1) == (i >> 5) && rho == ((i >> 2) & 7)) ? ((i & 2) ? hh : lo) : 0u;
      reg_fence(za);
      bar_sync(3, 256);
      const bool own = (warp >> 1) == rank;
      float d[64];
      constexpr uint64_t s2 = sched("02468:<>"), s3 = sched("13579;=?");
#pragma unroll 1
      for (uint64_t sc = spare ? (wg ? s3 : s2) : m.p.list[wg]; sc; sc >>= 5) {
        const int item = (int)sc & 31;
        if (item >= 18) {
          const int q = item - 18;
          const uint32_t e = __shfl_sync(0xffffffffu, lds32(ptab + 192 + 4 * q), 0);
#pragma unroll
          for (int jj = 0; jj < 4; jj++) {
            const int j = 4 * q + jj;
            mbar_wait(rfull + 8 * j, 0);
            wg_fence();
#pragma unroll
            for (int i = 0; i < 4; i++)
              wgmma_rs_128<1, 1, 1>(d, za[16 * jj + 4 * i], za[16 * jj + 4 * i + 1], za[16 * jj + 4 * i + 2], za[16 * jj + 4 * i + 3],
                                    mk_desc(sb + place(rank, e >> (4 * jj) & 15), i * 2048, 8192, 1024, 1), jj | i);
            wg_commit();
            if (jj > 0) {
              wg_wait<1>();
              if (lane == 0) mbar_arrive(rempty + 8 * (j - 1));
            }
          }
          wg_wait<0>();
          reg_fence(d);
          if (lane == 0) mbar_arrive(rempty + 8 * (4 * q + 3));
          mbar_wait(bb + (e >> (own ? 13 : 21) & 0x7F8), 0);
          const uint32_t rb = (own ? sb : peer) + (8 * rank + q) * 8192 + (warp & 1) * 4096 + rho * 128;
          const uint32_t wbar = q < W_Q ? win : win1;
          auto put_w = [&](auto remote) {
#pragma unroll
            for (int v = 0; v < 8; v++) {
              const int j = 4 * (v >> 1), h = v & 1;
              const uint32_t a = rb + (j >> 3) * 2048 + h * 1024 + ((((j & 4) + (lane & 3)) ^ rho) << 4);
              const uint32_t p0 = pack2(d[4 * j + 2 * h], d[4 * j + 2 * h + 1]), p1 = pack2(d[4 * j + 4 + 2 * h], d[4 * j + 5 + 2 * h]);
              const uint32_t p2 = pack2(d[4 * j + 8 + 2 * h], d[4 * j + 9 + 2 * h]), p3 = pack2(d[4 * j + 12 + 2 * h], d[4 * j + 13 + 2 * h]);
              if (decltype(remote)::value)
                asm volatile("st.async.shared::cluster.mbarrier::complete_tx::bytes.v4.b32 [%0], {%1, %2, %3, %4}, [%5];"
                             ::"r"(a), "r"(p0), "r"(p1), "r"(p2), "r"(p3), "r"(peer + (wbar - sb)) : "memory");
              else
                asm volatile("st.shared.v4.b32 [%0], {%1, %2, %3, %4};" ::"r"(a), "r"(p0), "r"(p1), "r"(p2), "r"(p3) : "memory");
            }
          };
          if (own) {
            put_w(std::false_type());
            __syncwarp();
            if (lane == 0) mbar_arrive(wbar);
          } else {
            put_w(std::true_type());
          }
        } else {
          const int u = item - 1;
          const int c = lds32(xtab + 4 * u);
          const uint32_t in = sb + (c & 0x3C000);
          mbar_wait(xfull + 8 * u, 0);
          wg_fence();
#pragma unroll
          for (int k = 0; k < 4; k++)
            wgmma_rs_128<1, 1, 1>(d, fa[4 * k], fa[4 * k + 1], fa[4 * k + 2], fa[4 * k + 3], mk_desc(in, k * 2048, 6144, 1024, 1), k);
          wg_commit();
          wg_wait<0>();
          reg_fence(d);
          bar_sync(1 + wg, 128);
          const uint32_t rb = in + (warp * 16 + row) * 128, xr = (lane & 7) ^ (c & 3);
#pragma unroll
          for (int j = 0; j < 16; j += 2)
            stsm4(rb + ((j >> 2) & 1) * 8192 + ((((j >> 3) * 4 + (j & 3) + hi) ^ xr) << 4), pack2(d[4 * j], d[4 * j + 1]),
                  pack2(d[4 * j + 2], d[4 * j + 3]), pack2(d[4 * j + 4], d[4 * j + 5]), pack2(d[4 * j + 6], d[4 * j + 7]));
          fence_async();
          __syncwarp();
          if (lane == 0) mbar_arrive(xready + 8 * u);
        }
      }
#pragma unroll
      for (int i = 0; i < 4; i++) fw[i] = fa[i];
    }
    if (spare) {
      float* sg = reinterpret_cast<float*>(smem_k1 + K1_R);
      __nv_bfloat16* sw = reinterpret_cast<__nv_bfloat16*>(sg + 16 * 256);
      const int c0 = (cta - 128) * 64;
      uint4 vw[8], vg[2];
#pragma unroll
      for (int i = 0; i < 8; i++) vw[i] = __ldg(reinterpret_cast<const uint4*>(wgt + ((i * 256 + tid) >> 3) * 256 + c0 + (tid & 7) * 8));
#pragma unroll
      for (int i = 0; i < 2; i++) vg[i] = __ldg(reinterpret_cast<const uint4*>(g) + i * 256 + tid);
#pragma unroll
      for (int i = 0; i < 8; i++) reinterpret_cast<uint4*>(sw)[i * 256 + tid] = vw[i];
#pragma unroll
      for (int i = 0; i < 2; i++) {
        const uint32_t w4[4] = {vg[i].x, vg[i].y, vg[i].z, vg[i].w};
#pragma unroll
        for (int e = 0; e < 4; e++) {
          sg[(i * 256 + tid) * 8 + 2 * e] = __uint_as_float(w4[e] << 16);
          sg[(i * 256 + tid) * 8 + 2 * e + 1] = __uint_as_float(w4[e] & 0xffff0000u);
        }
      }
      bar_sync(3, 256);
      const int col = tid & 63, r0 = (tid >> 6) * 4;
      float a0 = 0.f, a1 = 0.f, a2 = 0.f, a3 = 0.f;
#pragma unroll 8
      for (int k = 0; k < 256; k++) {
        const float w = __bfloat162float(sw[k * 64 + col]);
        a0 = fmaf(sg[(r0 + 0) * 256 + k], w, a0);
        a1 = fmaf(sg[(r0 + 1) * 256 + k], w, a1);
        a2 = fmaf(sg[(r0 + 2) * 256 + k], w, a2);
        a3 = fmaf(sg[(r0 + 3) * 256 + k], w, a3);
      }
      const int cc = c0 + col;
      const int pos = (cc & ~15) + ((cc >> 1) & 3) * 4 + ((cc >> 3) & 1) * 2 + (cc & 1);
      gp_.ge[(r0 + 0) * 256 + pos] = __bfloat162float(__float2bfloat16_rn(a0));
      gp_.ge[(r0 + 1) * 256 + pos] = __bfloat162float(__float2bfloat16_rn(a1));
      gp_.ge[(r0 + 2) * 256 + pos] = __bfloat162float(__float2bfloat16_rn(a2));
      gp_.ge[(r0 + 3) * 256 + pos] = __bfloat162float(__float2bfloat16_rn(a3));
      return;
    }
    reg_fence(fw);
    mbar_wait(win, 0);
    float d[16];
    auto t_begin = [&](int it, int hh, int r) {
      if (r == 0) mbar_wait(inf0 + 8 * (it & 1), (it >> 1) & 1);
      wg_fence();
      wgmma_rs_32<1, 1, 1>(d, fw[0], fw[1], fw[2], fw[3], mk_desc(sb + K1_TIN + (it & 1) * 4096 + hh * 2048, r * 64, 0, 1024, 1), 0);
      wg_commit();
    };
    auto t_end = [&](int it, int hh, int r) {
      reg_fence(d);
      const int j = it & 1;
      if (r == 0) mbar_wait(it >= 2 ? se0 + 8 * j : bb + (m.p.last >> (5 + 8 * it) & 0x7F8), it >= 2 ? ((it >> 1) - 1) & 1 : 0);
      else if (lane == 0) mbar_arrive(ine0 + 8 * j);
      const uint32_t rb = sb + K1_T + j * 16384 + hh * 8192 + (warp * 16 + row) * 128;
#pragma unroll
      for (int i = 0; i < 2; i++)
        stsm4(rb + (((4 * r + 2 * i + hi) ^ (lane & 7)) << 4), pack2(d[8 * i], d[8 * i + 1]), pack2(d[8 * i + 2], d[8 * i + 3]),
              pack2(d[8 * i + 4], d[8 * i + 5]), pack2(d[8 * i + 6], d[8 * i + 7]));
      if (r == 1) {
        fence_async();
        __syncwarp();
        if (lane == 0) mbar_arrive(sf0 + 8 * j);
      }
    };
    float y0[NB1 / 2], y1[NB1 / 2];
    uint32_t wa[8], wb[8];
    uint32_t wp = sb + wg * 4096 + ((lane & 7) + hi * 8) * 128 + (((2 * warp + ((lane >> 3) & 1)) ^ (lane & 7)) << 4);
    const uint32_t neg = wg ? 0x80008000u : 0u;
    auto frag = [&](uint32_t (&w)[8], uint32_t a, uint32_t sg) {
      ldsm4t(a, w[0], w[1], w[2], w[3]);
      ldsm4t(a + 2048, w[4], w[5], w[6], w[7]);
#pragma unroll
      for (int i = 0; i < 8; i++) w[i] ^= sg;
    };
    auto stage = [&](const uint32_t (&w)[8], uint32_t x4, int acc) {
      wg_fence();
      wgmma_rs_168<1, 1, 0>(y0, w[0], w[1], w[2], w[3], mk_desc4(x4, 0, 512, 2), acc);
      wgmma_rs_168<1, 1, 0>(y1, w[0], w[1], w[2], w[3], mk_desc4(x4 + G_ST / 32, 0, 512, 2), acc);
      wgmma_rs_168<1, 1, 0>(y0, w[4], w[5], w[6], w[7], mk_desc4(x4 + 2, 0, 512, 2), 1);
      wgmma_rs_168<1, 1, 0>(y1, w[4], w[5], w[6], w[7], mk_desc4(x4 + G_ST / 32 + 2, 0, 512, 2), 1);
      wg_commit();
      wg_wait<1>();
    };
    frag(wa, wp, neg);
    int it = 0;
#pragma unroll 1
    for (int k = 0; k < G_KM; k++) {
      const bool T = (m.p.tmask >> (k + 16 * wg)) & 1;
      const uint32_t xa = ((sb & 0x3FFFF) >> 4) + m.slot[2 * k], xb = ((sb & 0x3FFFF) >> 4) + m.slot[2 * k + 1];
      if (T) t_begin(it, wg, 0);
      mbar_wait(gfull + 16 * k, 0);
      stage(wa, xa, k);
      frag(wb, wp ^ 4096, 0);
      if (k > 0 && lane == 0) mbar_arrive(gdone + 16 * k - 8);
      if (T) {
        t_end(it, wg, 0);
        t_begin(it, wg, 1);
      }
      mbar_wait(gfull + 16 * k + 8, 0);
      stage(wb, xb, 1);
      wp += 8192;
      if (k == W_Q - 1) {
        mbar_wait(win1, 0);
        fence_async();
      }
      frag(wa, wp, neg);
      if (lane == 0) mbar_arrive(gdone + 16 * k);
      if (T) t_end(it++, wg, 1);
    }
    auto tail = [&](float (&y)[NB1 / 2], auto batch, auto wgc) {
      constexpr int B = decltype(batch)::value, W = decltype(wgc)::value;
#pragma unroll
      for (int k = G_KM; k < 16; k++) {
        const int s = G_KM + k + G_TK * B;
        mbar_wait(gfull + 8 * s, 0);
        const int xo = g_off(g_slot(s));
        wg_fence();
#pragma unroll
        for (int h = 0; h < 4; h++) {
          const uint64_t dW = mk_desc(sb, k * 8192 + ((h >> 1) ^ W) * 4096 + (h & 1) * 2048, 0, 1024, 1);
          const uint64_t dX = mk_desc(sb, xo + (h >> 1) * (G_ST / 2) + (h & 1) * 32, 0, 512, 2);
          if (W == 1 && h < 2) wgmma_ss_168<-1, 1, 1, 0>(y, dW, dX, 1);
          else wgmma_ss_168<1, 1, 1, 0>(y, dW, dX, 1);
        }
        if (s <= 26) {
          wg_commit();
          if (W == 0 || k > G_KM) {
            wg_wait<1>();
            if (lane == 0) mbar_arrive(gdone + 8 * (s - 1));
          }
        }
      }
      wg_commit();
    };
    constexpr std::integral_constant<int, 0> c0;
    constexpr std::integral_constant<int, 1> c1;
    auto put = [&](const float (&v)[NB1 / 2], uint32_t stg, int b) {
      const int mi = lane >> 3, i = lane & 7;
      const uint32_t a0 = stg + (mi >> 1) * 1024 + i * 128 + (((2 * warp + (mi & 1)) ^ i) << 4);
      constexpr int J = 21 / G_EPI;
#pragma unroll
      for (int c = 0; c < G_EPI; c++) {
#pragma unroll
        for (int j = c * J; j + 1 < (c + 1) * J; j += 2)
          stsm4t(a0 + j * 1024, pack2(v[4 * j], v[4 * j + 1]), pack2(v[4 * j + 2], v[4 * j + 3]),
                 pack2(v[4 * j + 4], v[4 * j + 5]), pack2(v[4 * j + 6], v[4 * j + 7]));
        const int j = (c + 1) * J - 1;
        asm volatile("stmatrix.sync.aligned.m8n8.x2.trans.shared.b16 [%0], {%1, %2};" ::"r"(a0 + j * 1024),
                     "r"(pack2(v[4 * j], v[4 * j + 1])), "r"(pack2(v[4 * j + 2], v[4 * j + 3])) : "memory");
        fence_async();
        bar_sync(1 + wg, 128);
        if (t == 0) {
          tma_st4<0>(&m.y, stg + c * J * 1024, 0, b * NB1 + c * J * 8, 2 * bin + wg, dc);
          bulk_commit();
        }
      }
    };
    if (wg == 0) {
      tail(y0, c0, c0);
      bar_arrive(4, 256);
      mbar_wait(gdone + 8 * (G_S0 - 1), 0);
      wg_wait<0>();
      reg_fence(y0);
      put(y0, sb + K1_Y0, 0);
      bar_sync(7, 256);
      tail(y1, c1, c0);
      bar_arrive(8, 256);
      if (t == 0) bulk_wait_read<0>();
      wg_wait<0>();
      reg_fence(y1);
      bar_sync(1, 128);
      put(y1, sb + K1_Y0, 1);
    } else {
      wg_wait<0>();
      if (lane == 0) mbar_arrive(gdone + 8 * (G_S0 - 1));
#pragma unroll 1
      for (int h2 = 2 * it; h2 < 16; h2++) {
#pragma unroll
        for (int r = 0; r < 2; r++) {
          t_begin(h2 >> 1, h2 & 1, r);
          wg_wait<0>();
          t_end(h2 >> 1, h2 & 1, r);
        }
      }
      bar_sync(4, 256);
      tail(y0, c0, c1);
      bar_arrive(7, 256);
      mbar_wait(se0, 1);
      mbar_wait(se0 + 8, 1);
      wg_wait<0>();
      reg_fence(y0);
      put(y0, sb + K1_T, 0);
      bar_sync(8, 256);
      tail(y1, c1, c1);
      wg_wait<0>();
      reg_fence(y1);
      put(y1, sb + g_off(g_slot(26)), 1);
    }
    if (t == 0) {
      bulk_wait_read<0>();
    }
  }
}

#define H_EPI 3
#define H_KS 11
#define C_PC 32
constexpr int H_XP = 168 * 64, H_STAGE = 8192 + 2 * H_XP, H_NST = 7, K2_STG = H_NST * H_STAGE, K2_SMEM = K2_STG + 21504 + 1024;

template <int WG>
__device__ __forceinline__ void h_loop(float (&acc)[84], uint32_t sb, uint32_t full0, uint32_t empty0, int lane) {
#pragma unroll 1
  for (int k = 0; k < 16; k++) {
    const int st = k % H_NST;
    if (WG == 1 && k == H_KS) bar_sync(5, 256);
    mbar_wait(full0 + 8 * st, (k / H_NST) & 1);
    const uint32_t base = sb + st * H_STAGE;
    wg_fence();
#pragma unroll
    for (int s = 0; s < 2; s++) {
      const uint64_t dP = mk_desc(base, s * 2048, 0, 1024, 1), dQ = mk_desc(base, 4096 + s * 2048, 0, 1024, 1);
      const uint64_t dA = mk_desc(base, 8192 + s * 32, 0, 1024, 1), dB = mk_desc(base, 8192 + 64 + s * 32, 0, 1024, 1);
      wgmma_ss_168<1, 1, 1, 0>(acc, dP, WG == 0 ? dA : dB, k | s);
      wgmma_ss_168<WG == 0 ? 1 : -1, 1, 1, 0>(acc, dQ, WG == 0 ? dB : dA, 1);
    }
    wg_commit();
    if (WG == 0 && k == 15) bar_arrive(5, 256);
    if (k <= 10) {
      wg_wait<1>();
      if (k > 0 && k - 1 + H_NST < 16 && lane < 2) mbar_arrive_cta(empty0 + 8 * ((k - 1) % H_NST), lane);
    }
  }
  wg_wait<0>();
  reg_fence(acc);
}
template <int C0, int C1> __device__ __forceinline__ void gelu_pack(uint32_t (&p)[12], const float (&h)[24]) {
#pragma unroll
  for (int i = 4 * C0; i < 4 * C1; i++) p[i] = pack2(gelu(h[2 * i]), gelu(h[2 * i + 1]));
}
struct K2Maps {
  int stage[16], item[8], wpre, pad[7];
  CUtensorMap y, xa, xs, w, y2;
};

__global__ void __cluster_dims__(2, 1, 1) __launch_bounds__(512, 1)
k2(const Ptrs gp_, const char* __restrict__ x2, const __grid_constant__ K2Maps m, const __nv_bfloat16* __restrict__ wf,
   const __nv_bfloat16* __restrict__ wo) {
  extern __shared__ __align__(1024) uint8_t smem_k1[];
  const uint32_t sb = s2u(smem_k1);
  const int tid = threadIdx.x, wg = __shfl_sync(0xffffffffu, tid >> 7, 0), t = tid & 127;
  const int warp = __shfl_sync(0xffffffffu, t >> 5, 0), lane = t & 31;
  const int cta = blockIdx.x, rank = cta & 1, dc = cta & 3, bin = cta >> 2;
  const uint32_t sGi = sb + K2_STG, sF = sGi + 6144, bb = sb + K2_STG + 21504;
  const uint32_t yfull = bb, full0 = bb + 128, empty0 = bb + 192, cfull = bb + 256, ready = bb + 320, bfree = bb + 384;
  const int b = cta & 1, j = cta >> 2;
  const int len0 = j < 20 ? 3 : 2, len1 = j >= 12 ? 3 : 2;
  const int n00 = j < 20 ? 3 * j : 2 * j + 20, n01 = j < 12 ? 2 * j : 3 * j - 12, cs0 = 3 - (cta >> 1 & 1);
  auto y_load = [&](int r, int i) {
    tma_ld5<1>(sb + (3 + 2 * r) * H_STAGE + i * 8192, &m.y, yfull + 64 * r + 8 * i, 0, 0, cs0 - 2 * r, 2 * (r ? n01 : n00) + i, b);
  };
  if (wg == 2 && warp == 0) {
    if (lane == 0) {
      prefetch_map(&m.y);
      for (int i = 0; i < 16; i++) mbar_init(yfull + 8 * i, 1);
      fence_bar_init();
    }
    __syncwarp();
    if (lane < 16) mbar_expect(yfull + 8 * lane, lane == 7 ? 6144 : 8192);
    bar_arrive(0, 512);
    asm volatile("barrier.cluster.arrive.relaxed.aligned;" ::: "memory");
    auto c_load = [&](int h) {
      asm volatile("cp.async.bulk.shared::cluster.global.mbarrier::complete_tx::bytes [%0], [%1], %2, [%3];"
                   ::"r"(sGi + 6144 * h), "l"(gp_.img + 1536 * h), "r"(6144 + 2048 * h), "r"(yfull + 56 + 64 * h) : "memory");
    };
    if (lane == 0) {
      c_load(0);
      c_load(1);
      pdl_wait();
      const int r2 = len0 == 2, i2 = r2 ? 2 : 6;
      y_load(0, 2), y_load(0, 0), y_load(0, 1), y_load(1, 0), y_load(0, 4), y_load(0, 3), y_load(r2, i2), y_load(r2, i2 - 1);
      pdl_launch();
    }
    __syncwarp();
  } else {
    if (lane == 0 && wg == 3) {
      for (int i = 0; i < 8; i++) mbar_init(full0 + 64 * warp + 8 * i, warp == 0 ? 1 : warp == 1 ? 16 : 4);
      fence_bar_init();
    }
    if (tid == 0) {
      mbar_init(bfree, 2);
      for (int i = 1; i < 5; i++) mbar_init(bfree + 8 * i, 1);
      mbar_arrive(bfree + 8);
      fence_bar_init();
    }
    if (tid == 128) {
      prefetch_map(&m.xa);
      prefetch_map(&m.xs);
      prefetch_map(&m.w);
      prefetch_map(&m.y2);
    }
    bar_sync(0, 512);
    asm volatile("barrier.cluster.arrive.relaxed.aligned;" ::: "memory");
  }
  if (wg == 2) asm volatile("barrier.cluster.wait.aligned;" ::: "memory");
  mbar_wait(yfull + 56, 0);
  auto idft = [&](float (&h)[24], uint32_t in, uint32_t bar) {
    mbar_wait(bar, 0);
    wg_fence();
#pragma unroll
    for (int k = 0; k < 4; k++) wgmma_ss_48<1, 1, 1, 0>(h, mk_desc(in, k * 2048, 0, 1024, 1), mk_desc(sGi, k * 32, 0, 1024, 1), k);
    wg_commit();
  };
  auto carry_out = [&](const uint32_t (&p)[12], uint32_t dst, uint32_t bar) {
    bar_sync(1 + wg, 128);
#pragma unroll
    for (int v = 0; v < 3; v++)
      asm volatile("st.shared.v4.b32 [%0], {%1, %2, %3, %4};" ::"r"(dst + v * 2048 + t * 16), "r"(p[4 * v]), "r"(p[4 * v + 1]), "r"(p[4 * v + 2]), "r"(p[4 * v + 3]) : "memory");
    __syncwarp();
    if (lane == 0) mbar_arrive(bar);
  };
  if (wg == 3) {
#pragma unroll 1
    for (int r = 0; r < 2; r++) {
      float h[24];
      uint32_t p[12];
      idft(h, sb + (3 + 2 * r) * H_STAGE, yfull + 64 * r);
      wg_wait<0>();
      reg_fence(h);
      gelu_pack<0, 3>(p, h);
      if (j == 0) p[0] = p[1] = p[2] = p[3] = 0;
      carry_out(p, sb + (3 + 2 * r) * H_STAGE, cfull + 32 * r);
    }
    asm volatile("barrier.cluster.wait.aligned;" ::: "memory");
    if (lane == 0) {
      if (warp == 0) {
        auto w_load = [&](int k) {
          mbar_expect(full0 + 8 * (k % H_NST), H_STAGE);
          tma_ld4<1>(sb + (k % H_NST) * H_STAGE, &m.w, full0 + 8 * (k % H_NST), 0, (k & 1) * 32, dc, (7 - (k >> 1)) * 64 + 2 * bin);
        };
        const int wpre = m.wpre;
        for (int k = 0; k < wpre; k++) w_load(k);
#pragma unroll 1
        for (int k = 0; k < 16; k++) {
          const int st = k % H_NST, e = m.stage[k];
          if ((k & 7) == 0) {
            poll_ge(&gp_.done[(6 + (k >> 3)) * 32], 128);
            asm volatile("fence.proxy.async.global;" ::: "memory");
            if (k == 0) mbar_arrive(bfree + 32);
          }
          if (e) mbar_wait(bb + 8 * e, 0);
          if (k == 5) mbar_wait(bfree, 0);
          if (k >= H_NST) mbar_wait(empty0 + 8 * st, ((k / H_NST) - 1) & 1);
          const char* xs = x2 + (((7 - (k >> 2) - (k & 2) * 2) * 64 + (k & 1) * 32 + bin) * 2 + rank) * H_XP;
          asm volatile("cp.async.bulk.shared::cluster.global.mbarrier::complete_tx::bytes.multicast::cluster [%0], [%1], %2, [%3], %4;"
                       ::"r"(sb + st * H_STAGE + 8192 + rank * H_XP), "l"(xs), "n"(H_XP), "r"(full0 + 8 * st), "h"((uint16_t)3) : "memory");
          if (k >= wpre) w_load(k);
          if (k == 8) {
            if (cta == 0) asm volatile("cp.async.bulk.prefetch.L2.global [%0], 6144;" ::"l"(gp_.ga) : "memory");
            asm volatile("cp.async.bulk.prefetch.L2.global [%0], 1024;" ::"l"(wf + cta * 512) : "memory");
            asm volatile("cp.async.bulk.prefetch.L2.global [%0], 1024;" ::"l"(wo + cta * 512) : "memory");
          }
        }
      } else if (warp < 3) {
        const int r = warp - 1, n0 = b * NB2 + (r ? n01 : n00), f0 = (cs0 - 2 * r) * 64;
#pragma unroll 1
        for (int i = 0; i < (r ? len1 : len0); i++) {
          const uint32_t src = sb + (3 + 2 * r) * H_STAGE + i * 16384;
          const int e = m.item[4 * r + i], burst = (16 << (e >> 8)) - 1;
          if (r) mbar_wait(bb + 8 * (e & 255), 0);
          mbar_wait(ready + 32 * r + 8 * i, 0);
          if (!r) {
            tma_st4<0>(&m.xa, src, 0, f0, 0, n0 + i);
            bulk_commit();
            continue;
          }
#pragma unroll 1
          for (int p = 0; p < 128; p += C_PC) {
            tma_st3<0>(&m.xs, src + p * 128, 0, f0 + (p & 63) + (p >> 6) * 256, n0 + i);
            bulk_commit();
            if (((p + C_PC) & burst) == 0) bulk_wait_read<0>();
          }
        }
        asm volatile("cp.async.bulk.wait_group 0;" ::: "memory");
        if (r) {
          mbar_arrive_cta(bfree, 0);
          mbar_arrive_cta(bfree, 1);
        }
        if (!r) mbar_arrive(bfree + 16);
        asm volatile("red.release.gpu.global.add.s32 [%0], 1;" ::"l"(&gp_.done[(6 + r) * 32]) : "memory");
        if (!r) mbar_arrive(bfree + 24);
      }
    }
    return;
  }
#pragma unroll 1
  for (int it = wg; it < len0 + len1; it += 3) {
    const int r = it >= len0, i = it - r * len0;
    const bool last = i + 1 == (r ? len1 : len0);
    const uint32_t in = sb + (3 + 2 * r) * H_STAGE + i * 16384, bar = yfull + 64 * r + 16 * i;
    float h1[24], h2[24];
    uint32_t p0[12], p1[12], p2[12];
    idft(h2, in + 16384, bar + 16);
    if (it == 2 && lane == 0 && 3 + warp - len0 < len1) {
      y_load(1, 2 * (3 + warp - len0) + 2);
      y_load(1, 2 * (3 + warp - len0) + 1);
    }
    if (it > 0) bar_sync(6 + wg, 256);
    wg_wait<0>();
    reg_fence(h2);
    gelu_pack<0, 2>(p2, h2);
    idft(h1, in + 8192, bar + 8);
    if (!last) {
      gelu_pack<2, 3>(p2, h2);
      carry_out(p2, in + 16384, cfull + 32 * r + 8 * i + 8);
    }
    if (it + 1 < len0 + len1) bar_arrive(6 + (wg + 1) % 3, 256);
    mbar_wait(cfull + 32 * r + 8 * i, 0);
#pragma unroll
    for (int v = 0; v < 3; v++)
      asm volatile("ld.shared.v4.b32 {%0, %1, %2, %3}, [%4];" : "=r"(p0[4 * v]), "=r"(p0[4 * v + 1]), "=r"(p0[4 * v + 2]), "=r"(p0[4 * v + 3]) : "r"(in + v * 2048 + t * 16) : "memory");
    if (it < 3) mbar_wait(yfull + 120, 0);
    wg_wait<0>();
    reg_fence(h1);
    gelu_pack<0, 3>(p1, h1);
    if (last && j == 31) {
#pragma unroll
      for (int v = 0; v < 12; v++) p1[v] = p2[v] = 0;
    }
    uint32_t hp[32];
#pragma unroll
    for (int c = 0; c < 8; c++)
#pragma unroll
      for (int v = 0; v < 4; v++) hp[(v >> 1) * 16 + 2 * c + (v & 1)] = c < 3 ? p0[4 * c + v] : c < 6 ? p1[4 * (c - 3) + v] : p2[4 * (c - 6) + v];
    float e0[32], e1[32];
    reg_fence(hp);
    wg_fence();
#pragma unroll
    for (int k = 0; k < 4; k++) {
      const uint64_t db = mk_desc(sF, k * 32, 0, 1024, 1);
      wgmma_rs_64<1, 1, 0>(e0, hp[4 * k], hp[4 * k + 1], hp[4 * k + 2], hp[4 * k + 3], db, k);
      wgmma_rs_64<1, 1, 0>(e1, hp[16 + 4 * k], hp[16 + 4 * k + 1], hp[16 + 4 * k + 2], hp[16 + 4 * k + 3], db, k);
    }
    wg_commit();
    bar_sync(1 + wg, 128);
    wg_wait<0>();
    reg_fence(e0);
    reg_fence(e1);
    {
      const int mi = lane >> 3, rr = (lane & 7) >> 1, blk = b * NB2 + (r ? n01 : n00) + i;
      const uint32_t a0 = in + (mi >> 1) * 8192 + (warp >> 1) * 4096 + rr * 128;
      const uint32_t pos = ((lane & 1) * 4 + (warp & 1) * 2 + (mi & 1)) ^ rr ^ (blk & 7);
#pragma unroll
      for (int q = 0; q < 8; q++)
        stsm4t(a0 + q * 512 + ((pos ^ (q & 1) * 4) << 4), pack2(e0[4 * q], e0[4 * q + 1]), pack2(e0[4 * q + 2], e0[4 * q + 3]),
               pack2(e1[4 * q], e1[4 * q + 1]), pack2(e1[4 * q + 2], e1[4 * q + 3]));
    }
    fence_async();
    __syncwarp();
    if (lane == 0) mbar_arrive(ready + 32 * r + 8 * i);
  }
  if (wg == 2) return;
  asm volatile("barrier.cluster.wait.aligned;" ::: "memory");
  float acc[84];
  if (wg == 0) {
    h_loop<0>(acc, sb, full0, empty0, lane);
  } else {
    h_loop<1>(acc, sb, full0, empty0, lane);
    bar_sync(2, 128);
  }
  const uint32_t stg = sb + (wg == 0 ? H_NST : 9 % H_NST) * H_STAGE;
  const int mi = lane >> 3, i = lane & 7;
  const uint32_t a0 = stg + (mi >> 1) * 1024 + i * 128 + (((2 * warp + (mi & 1)) ^ i) << 4);
  constexpr int J = 21 / H_EPI;
#pragma unroll
  for (int c = 0; c < H_EPI; c++) {
#pragma unroll
    for (int q = c * J; q + 1 < (c + 1) * J; q += 2)
      stsm4t(a0 + q * 1024, pack2(acc[4 * q], acc[4 * q + 1]), pack2(acc[4 * q + 2], acc[4 * q + 3]),
             pack2(acc[4 * q + 4], acc[4 * q + 5]), pack2(acc[4 * q + 6], acc[4 * q + 7]));
    const int q = (c + 1) * J - 1;
    asm volatile("stmatrix.sync.aligned.m8n8.x2.trans.shared.b16 [%0], {%1, %2};" ::"r"(a0 + q * 1024),
                 "r"(pack2(acc[4 * q], acc[4 * q + 1])), "r"(pack2(acc[4 * q + 2], acc[4 * q + 3])) : "memory");
    fence_async();
    bar_sync(1 + wg, 128);
    if (t == 0) {
      tma_st4<0>(&m.y2, stg + c * J * 1024, 0, c * J * 8, 2 * bin + wg, dc);
      bulk_commit();
    }
  }
  if (t == 0) {
    bulk_wait_read<0>();
  }
}

#define E_I1 12
#define E_EARLY0 2
#define E_EARLY 2
constexpr int E_SMEM = 65536 + 131072 + 32768 + 1024;

__device__ __forceinline__ uint32_t joint2(uint32_t fe, uint32_t g0, uint32_t g1) {
  uint32_t s0, s1;
  asm("{\n.reg .b16 l, h;\n.reg .b32 ll, hh;\nmov.b32 {l, h}, %2;\nmov.b32 ll, {l, l};\nmov.b32 hh, {h, h};\n"
      "fma.rn.bf16x2 %0, ll, %5, %3;\nfma.rn.bf16x2 %1, hh, %5, %4;\n}"
      : "=r"(s0), "=r"(s1) : "r"(fe), "r"(g0), "r"(g1), "r"(0x3F800000u));
  return pack2(tanh_f32(__uint_as_float(s0)), tanh_f32(__uint_as_float(s1)));
}
__device__ __forceinline__ uint4 lds128(uint32_t a) {
  uint4 v;
  asm volatile("ld.shared.v4.u32 {%0, %1, %2, %3}, [%4];" : "=r"(v.x), "=r"(v.y), "=r"(v.z), "=r"(v.w) : "r"(a));
  return v;
}
__device__ __forceinline__ void joint_group(uint32_t (&ja)[8], const uint32_t* fe, const uint4& c0, const uint4& c1) {
  ja[0] = joint2(fe[0], c0.x, c0.y);
  ja[1] = joint2(fe[1], c0.x, c0.y);
  ja[2] = joint2(fe[2], c0.z, c0.w);
  ja[3] = joint2(fe[3], c0.z, c0.w);
  ja[4] = joint2(fe[4], c1.x, c1.y);
  ja[5] = joint2(fe[5], c1.x, c1.y);
  ja[6] = joint2(fe[6], c1.z, c1.w);
  ja[7] = joint2(fe[7], c1.z, c1.w);
  reg_fence(ja);
}

__global__ void __launch_bounds__(256, 1)
kE(const __grid_constant__ CUtensorMap my, const __grid_constant__ CUtensorMap mwf, const __grid_constant__ CUtensorMap mwo,
   const __grid_constant__ CUtensorMap mout) {
  const Ptrs gp_ = {g_done, g_ge, c_img, c_ga};
  extern __shared__ uint8_t smem_raw[];
  __shared__ __align__(8) uint64_t bars[17];
  const uint32_t sb = (s2u(smem_raw) + 1023) & ~1023u;
  const int tid = threadIdx.x, wg = __shfl_sync(0xffffffffu, tid >> 7, 0), t = tid & 127, warp = t >> 5, lane = t & 31;
  const uint32_t R0 = sb, R1 = sb + 65536, R2 = sb + 65536 + 131072;
  const uint32_t barY = s2u(&bars[0]), barO = barY + 32, barF = barY + 64, barA = barY + 128;
  const int b = blockIdx.x / 63, t0 = (blockIdx.x % 63) * 64;
  const int a = t0 / 48, o = t0 % 48;
  const int qw = o + 16 * warp, sel = qw >= 48;
  uint32_t ga[16];
#pragma unroll
  for (int s = 0; s < 4; s++)
    ldg128(reinterpret_cast<const uint4*>(gp_.ga) + ((qw >> 4) - 3 * sel) * 128 + s * 32 + lane, ga[4 * s], ga[4 * s + 1], ga[4 * s + 2], ga[4 * s + 3]);
  uint4 gev0, gev1;
  asm volatile("ld.global.cg.v4.u32 {%0, %1, %2, %3}, [%4];" : "=r"(gev0.x), "=r"(gev0.y), "=r"(gev0.z), "=r"(gev0.w)
               : "l"(reinterpret_cast<const uint4*>(gp_.ge) + (b * 8 + wg * 4) * 64 + t));
  asm volatile("ld.global.cg.v4.u32 {%0, %1, %2, %3}, [%4];" : "=r"(gev1.x), "=r"(gev1.y), "=r"(gev1.z), "=r"(gev1.w)
               : "l"(reinterpret_cast<const uint4*>(gp_.ge) + (b * 8 + wg * 4) * 64 + 128 + t));
  auto f_load = [&](int q) {
    const int p = (0x37156240 >> (4 * q)) & 7;
    mbar_expect(barF + 8 * p, 16384);
    tma_ld3<0>(R1 + p * 16384, &mwf, barF + 8 * p, 0, (p >> 1) * 64, (p & 1) * 2);
  };
  if (tid == 0) {
    prefetch_map(&my);
    for (int i = 0; i < 16; i++) mbar_init(barY + 8 * i, 1);
    mbar_init(barA, 8);
    fence_bar_init();
    prefetch_map(&mwf);
    pdl_wait();
    for (int i = 0; i < 4; i++) {
      mbar_expect(barY + 8 * i, 16384);
      tma_ld5<0>(R0 + i * 16384, &my, barY + 8 * i, 0, 0, 2 * (i & 1) + (i >> 1), a, b);
    }
    for (int q = 0; q < 4; q++) f_load(q);
  }
  if (tid == 64) {
    prefetch_map(&mwo);
    prefetch_map(&mout);
  }
  uint32_t gs[32];
#pragma unroll
  for (int i = 0; i < 16; i++) {
    gs[i] = sel ? 0u : ga[i];
    gs[16 + i] = sel ? ga[i] : 0u;
  }
  __syncthreads();
  if (blockIdx.x == 125 && tid < 8) gp_.done[tid * 32] = 0;
  reg_fence(gs);
  uint32_t gp = R2 + 16384 + wg * 4096 + (lane & 3) * 16;
  uint4 g0, g1;
  uint32_t fe[64];
  {
    float d0[32], d1[32], e[64];
    mbar_wait(barY + 8 * wg, 0);
    wg_fence();
#pragma unroll
    for (int k = 0; k < 8; k++)
      wgmma_rs_64<1, 1, 1>(d0, gs[4 * k], gs[4 * k + 1], gs[4 * k + 2], gs[4 * k + 3], mk_desc(R0 + wg * 16384, k * 2048, 0, 1024, 1), k);
    wg_commit();
    if (tid == 128)
      for (int q = 4; q < 8; q++) f_load(q);
    wg_wait<0>();
    reg_fence(d0);
    uint32_t p0[16], p1[16];
    const uint32_t wfo = R1 + wg * (65536 + 16384), wfx = R1 + 65536 - wg * (65536 - 16384), fx = R2 + 16384 - wg * 16384;
    const uint32_t fo = R2 + wg * 16384 + (warp * 16 + (lane & 7) + ((lane >> 3) & 1) * 8) * 128;
    auto fe_own = [&](const uint32_t (&p)[16], int c) {
      wg_fence();
#pragma unroll
      for (int s = 0; s < 4; s++)
        wgmma_rs_128<1, 1, 1>(e, p[4 * s], p[4 * s + 1], p[4 * s + 2], p[4 * s + 3], mk_desc(wfo, c * 32768 + s * 2048, 8192, 1024, 1), c | s);
    };
    auto fe_other = [&](int c) {
      wg_fence();
#pragma unroll
      for (int s = 0; s < 4; s++)
        wgmma_ss_128<1, 1, 0, 1>(e, mk_desc(fx, c * 8192 + s * 32, 0, 1024, 1), mk_desc(wfx, c * 32768 + s * 2048, 8192, 1024, 1), 1);
    };
    auto f_store = [&](const uint32_t (&p)[16], int c) {
#pragma unroll
      for (int s = 0; s < 4; s++) stsm4(fo + c * 8192 + (((2 * s + (lane >> 4)) ^ (lane & 7)) << 4), p[4 * s], p[4 * s + 1], p[4 * s + 2], p[4 * s + 3]);
    };
#pragma unroll
    for (int i = 0; i < E_I1; i++) p0[i] = pack2(gelu(d0[2 * i]), gelu(d0[2 * i + 1]));
    mbar_wait(barY + 8 * (2 + wg), 0);
    wg_fence();
#pragma unroll
    for (int k = 0; k < 8; k++)
      wgmma_rs_64<1, 1, 1>(d1, gs[4 * k], gs[4 * k + 1], gs[4 * k + 2], gs[4 * k + 3], mk_desc(R0 + wg * 16384, 32768 + k * 2048, 0, 1024, 1), k);
    wg_commit();
#pragma unroll
    for (int i = E_I1; i < 16; i++) p0[i] = pack2(gelu(d0[2 * i]), gelu(d0[2 * i + 1]));
    reg_fence(p0);
    f_store(p0, 0);
    const uint32_t bfo = barF + 40 * wg, bfx = barF + 32 - 24 * wg;
    auto o_load = [&](int kc) {
      mbar_expect(barO + 8 * kc, 32768);
      tma_ld3<0>(kc < 2 ? R0 + kc * 32768 : R1 + (kc - 2) * 65536, &mwo, barO + 8 * kc, 0, kc * 64, 0);
    };
    wg_wait<0>();
    reg_fence(d1);
    if (wg == 1) {
      fence_async();
      bar_arrive(8, 256);
    }
#pragma unroll
    for (int i = 0; i < 16; i++) p1[i] = pack2(gelu(d1[2 * i]), gelu(d1[2 * i + 1]));
    reg_fence(p1);
    if (wg == 0) {
      mbar_wait(bfo, 0);
      fe_own(p0, 0);
      mbar_wait(bfx, 0);
      bar_sync(8, 256);
      fe_other(0);
      wg_commit();
      if (t == 0) {
        o_load(0);
        o_load(1);
      }
      f_store(p1, 1);
      mbar_wait(bfo + 16, 0);
      fe_own(p1, 1);
      fence_async();
      mbar_wait(bfx + 16, 0);
      bar_sync(7, 256);
      fe_other(1);
      wg_commit();
      bar_arrive(4, 256);
      wg_wait<1>();
      if (lane == 0) mbar_arrive(barA);
      bar_sync(1, 128);
    } else {
      f_store(p1, 1);
      fence_async();
      bar_arrive(7, 256);
      mbar_wait(bfo, 0);
      mbar_wait(bfx, 0);
      bar_sync(4, 256);
      fe_own(p0, 0);
      fe_other(0);
      wg_commit();
      mbar_wait(bfo + 16, 0);
      mbar_wait(bfx + 16, 0);
      fe_own(p1, 1);
      wg_commit();
      wg_wait<1>();
      if (lane == 0) mbar_arrive(barA);
      fe_other(1);
      wg_commit();
      mbar_wait(barA, 0);
      if (t == 0) {
        o_load(2);
        o_load(3);
      }
    }
    asm volatile("st.shared.v4.u32 [%0], {%1, %2, %3, %4};" ::"r"(R2 + 16384 + wg * 4096 + ((t * 16) ^ (wg * 512))), "r"(gev0.x), "r"(gev0.y), "r"(gev0.z), "r"(gev0.w) : "memory");
    asm volatile("st.shared.v4.u32 [%0], {%1, %2, %3, %4};" ::"r"(R2 + 16384 + wg * 4096 + 2048 + ((t * 16) ^ (wg * 512))), "r"(gev1.x), "r"(gev1.y), "r"(gev1.z), "r"(gev1.w) : "memory");
    bar_sync(1 + wg, 128);
    g0 = lds128(gp);
    g1 = lds128(gp + 64);
    wg_wait<0>();
    reg_fence(e);
#pragma unroll
    for (int i = 0; i < 32; i++) fe[i] = pack2(e[2 * i], e[2 * i + 1]);
  }
  auto publish = [&]() {
    bar_sync(1 + wg, 128);
    const int row = warp * 16 + (lane & 7) + ((lane >> 3) & 1) * 8;
    const uint32_t xb = R1 + (wg == 0 ? 3 * 32768 : 32768 + 16384) + row * 128;
#pragma unroll
    for (int s = 0; s < 8; s++) {
      const int jj = 2 * s + (lane >> 4);
      stsm4(xb + (s >> 2) * 8192 + (((jj & 7) ^ (lane & 7)) << 4), fe[4 * s], fe[4 * s + 1], fe[4 * s + 2], fe[4 * s + 3]);
    }
    bar_arrive(5 + wg, 256);
  };
  if (wg == 1) publish();
  const uint32_t stg = R1 + 32768 + wg * 65536;
  const uint32_t w0 = sb + wg * 65536, w1 = sb + 32768 + wg * 98304, w2 = sb + 65536 - wg * 65536, w3 = sb + 131072 - wg * 98304;
  float acc[128];
  uint32_t j0[8], j1[8], j2[8], j3[8];
  uint4 h0 = lds128(gp + 128), h1 = lds128(gp + 192);
#define E_PAIR(J, K, F, G, BAR)             \
  joint_group(J, fe + (F), g0, g1);         \
  if (ui == 0) mbar_wait(BAR, 0);           \
  joint_group(K, fe + (F) + 8, h0, h1);     \
  g0 = lds128(gp + (G));                    \
  g1 = lds128(gp + (G) + 64);
  {
    const int ui = 0;
    E_PAIR(j0, j1, 0, 256, barO + 16 * wg)
    mbar_wait(barO + 16 * wg, 0);
  }
#define E_MMA4(J, K, W, FIRSTK, G, NEXTBAR)                                                     \
  wg_fence();                                                                                   \
  wgmma_rs_256<1, 1, 1>(acc, J[0], J[1], J[2], J[3], mk_desc(W, 0, 8192, 1024, 1), FIRSTK);     \
  wgmma_rs_256<1, 1, 1>(acc, J[4], J[5], J[6], J[7], mk_desc(W, 2048, 8192, 1024, 1), 1);       \
  wgmma_rs_256<1, 1, 1>(acc, K[0], K[1], K[2], K[3], mk_desc(W, 4096, 8192, 1024, 1), 1);       \
  wgmma_rs_256<1, 1, 1>(acc, K[4], K[5], K[6], K[7], mk_desc(W, 6144, 8192, 1024, 1), 1);       \
  wg_commit();                                                                                  \
  if ((ui + wg == 0 ? E_EARLY0 : E_EARLY) == (G) && (ui < 3 || wg == 0)) bar_arrive(4 - wg, 256); \
  wg_wait<1>();                                                                                 \
  h0 = lds128(gp + 256 * (G) + 384);                                                            \
  h1 = lds128(gp + 256 * (G) + 448);                                                            \
  if (ui == 0) mbar_wait(NEXTBAR, 0);
  const uint32_t bo0 = barO + 16 * wg, bo2 = barO + 16 * (1 - wg);
#pragma unroll 1
  for (int ui = 0; ui < 4; ui++) {
    if (ui > 0 || wg == 1) bar_sync(3 + wg, 256);
    E_MMA4(j0, j1, w0, 0, 0, bo0)
    E_PAIR(j2, j3, 16, 512, bo0 + 8)
    E_MMA4(j2, j3, w1, 1, 1, bo0 + 8)
    if (ui == 0) {
      if (wg == 0) publish();
      bar_sync(6 - wg, 256);
      const int row = warp * 16 + (lane & 7) + ((lane >> 3) & 1) * 8;
      const uint32_t xb = R1 + (wg == 1 ? 3 * 32768 : 32768 + 16384) + row * 128;
#pragma unroll
      for (int s = 0; s < 8; s++) {
        const int jj = 2 * s + (lane >> 4);
        ldsm4(xb + (s >> 2) * 8192 + (((jj & 7) ^ (lane & 7)) << 4), fe[32 + 4 * s], fe[33 + 4 * s], fe[34 + 4 * s], fe[35 + 4 * s]);
      }
    }
    E_PAIR(j0, j1, 32, 768, bo2)
    E_MMA4(j0, j1, w2, 1, 2, bo2)
    E_PAIR(j2, j3, 48, 1024, bo2 + 8)
    E_MMA4(j2, j3, w3, 1, 3, bo2 + 8)
    gp += 1024;
    if (ui < 3) {
      E_PAIR(j0, j1, 0, 256, bo2 + 8)
    }
    if (t == 0) bulk_wait_read<0>();
    bar_sync(1 + wg, 128);
    wg_wait<0>();
    reg_fence(acc);
    const uint32_t rb = stg + (warp * 16 + (lane & 7) + ((lane >> 3) & 1) * 8) * 128;
#pragma unroll
    for (int h = 0; h < 2; h++) {
#pragma unroll
      for (int j = 16 * h; j < 16 * h + 16; j += 2) {
        const int jj = j + (lane >> 4);
        stsm4(rb + (j >> 3) * 8192 + (((jj & 7) ^ (lane & 7)) << 4), pack2(acc[4 * j], acc[4 * j + 1]), pack2(acc[4 * j + 2], acc[4 * j + 3]),
              pack2(acc[4 * j + 4], acc[4 * j + 5]), pack2(acc[4 * j + 6], acc[4 * j + 7]));
      }
      fence_async();
      bar_sync(1 + wg, 128);
      if (t == 0) {
        tma_st5<1>(&mout, stg + h * 16384, 0, t0, 2 * h, wg * 4 + ui, b);
        bulk_commit();
      }
    }
  }
  if (t == 0) bulk_wait_read<0>();
}

typedef CUresult (*EncodeFn)(CUtensorMap*, CUtensorMapDataType, cuuint32_t, void*, const cuuint64_t*, const cuuint64_t*,
                             const cuuint32_t*, const cuuint32_t*, CUtensorMapInterleave, CUtensorMapSwizzle,
                             CUtensorMapL2promotion, CUtensorMapFloatOOBfill);

CUtensorMap make_map(EncodeFn fn, const void* base, int rank, const uint64_t* dims, const uint64_t* strides, const uint32_t* box,
                     CUtensorMapSwizzle swz) {
  CUtensorMap m;
  cuuint64_t gd[5], gs[4];
  cuuint32_t bx[5], es[5];
  for (int i = 0; i < rank; i++) { gd[i] = dims[i]; bx[i] = box[i]; es[i] = 1; }
  for (int i = 0; i + 1 < rank; i++) gs[i] = strides[i];
  fn(&m, CU_TENSOR_MAP_DATA_TYPE_BFLOAT16, rank, const_cast<void*>(base), gd, gs, bx, es, CU_TENSOR_MAP_INTERLEAVE_NONE, swz,
     CU_TENSOR_MAP_L2_PROMOTION_NONE, CU_TENSOR_MAP_FLOAT_OOB_FILL_NONE);
  return m;
}

template <typename... KArgs, typename... Args>
void launch(void (*k)(KArgs...), int grid, int block, int smem, bool pdl, Args... args) {
  cudaLaunchConfig_t c = {};
  c.gridDim = dim3(grid);
  c.blockDim = dim3(block);
  c.dynamicSmemBytes = smem;
  c.stream = cudaStreamPerThread;
  cudaLaunchAttribute at[1];
  at[0].id = cudaLaunchAttributeProgrammaticStreamSerialization;
  at[0].val.programmaticStreamSerializationAllowed = 1;
  c.attrs = at;
  c.numAttrs = pdl ? 1 : 0;
  cudaLaunchKernelEx(&c, k, args...);
}

}

static uint32_t h_plan[67 + 25] = {
    0x6108, 0x6109, 0x610a, 0x610b, 0x6101, 0x8008, 0x8109, 0x820a, 0x830b, 0x8401,
    0x8508, 0x6102, 0x8609, 0x870a, 0x880b, 0x6103, 0x8a08, 0x8b02, 0x8c09, 0x8d0a,
    0x8e0b, 0x8f03, 0x9008, 0x9209, 0x930a, 0x9503, 0x9608, 0x9709, 0x980a, 0x9a08,
    0x9b09, 0x9c0a, 0x61616115, 0x6161610d, 0x61616107, 0x83816166, 0x8986610c, 0x8a89314d, 0x8f8a3237, 0x938f940b,
    0x9393344c, 0x9993354d, 0x0, 0x0, 0x0, 0x0, 0x0, 0x0, 0x6161ba98, 0x6161a981,
    0x6789281b, 0x67893ba9, 0x6891a928, 0x6891983b, 0x6999983a, 0x6999a98a, 0x39389d, 0x3, 0x4, 0x1dcc17b8,
    0x8f6a0c52, 0xac1, 0x2e5a9261, 0x194a, 0x9e, 0x9f, 0x37, 0x0, 0x0, 0x0,
    0x10, 0x11, 0x13, 0x14, 0x0, 0x0, 0x0, 0x0, 0x0, 0x0,
    0x0, 0x0, 0x0, 0x431, 0x431, 0x431, 0x0, 0x133, 0x131, 0x331,
    0x0, 0x3,
};

extern "C" void kernel_launch(void* const* d_in, const int* in_sizes, int n_in, void* d_out, int out_size) {
  const __nv_bfloat16* x = (const __nv_bfloat16*)d_in[0];
  const __nv_bfloat16* w1 = (const __nv_bfloat16*)d_in[1];
  const __nv_bfloat16* w2 = (const __nv_bfloat16*)d_in[2];
  const __nv_bfloat16* g = (const __nv_bfloat16*)d_in[3];
  const __nv_bfloat16* wf = (const __nv_bfloat16*)d_in[4];
  const __nv_bfloat16* wgt = (const __nv_bfloat16*)d_in[5];
  const __nv_bfloat16* wo = (const __nv_bfloat16*)d_in[6];

  void* fp = nullptr;
  cudaDriverEntryPointQueryResult qr;
  cudaGetDriverEntryPoint("cuTensorMapEncodeTiled", &fp, cudaEnableDefault, &qr);
  EncodeFn fn = (EncodeFn)fp;
  void *X1, *W2, *Y1, *X2, *Y2;
  cudaGetSymbolAddress(&X1, g_X1);
  cudaGetSymbolAddress(&W2, g_W2);
  cudaGetSymbolAddress(&Y1, g_Y1);
  cudaGetSymbolAddress(&X2, g_X2);
  cudaGetSymbolAddress(&Y2, g_Y2);
  cudaFuncSetAttribute(k1, cudaFuncAttributeMaxDynamicSharedMemorySize, K1_SMEM);
  cudaFuncSetAttribute(k2, cudaFuncAttributeMaxDynamicSharedMemorySize, K2_SMEM);
  cudaFuncSetAttribute(kE, cudaFuncAttributeMaxDynamicSharedMemorySize, E_SMEM);
  if (ALIAS) {
    W2 = d_out;
    X2 = (char*)d_out + sizeof(g_W2);
    X1 = (char*)X2 - sizeof(g_X2);
    Y2 = Y1;
  }
  const CUtensorMapSwizzle S128 = CU_TENSOR_MAP_SWIZZLE_128B;

  auto map_x = [&]() {
    uint64_t d[] = {64, 8000, 8, 2}, s[] = {1024, 128, 8000ull * 1024};
    uint32_t bx[] = {64, 56, 1, 1};
    return make_map(fn, x, 4, d, s, bx, S128);
  };
  auto map_w_in = [&](const __nv_bfloat16* w, int odd) {
    uint64_t d[] = {64, (uint64_t)(odd ? 15 : 16), 4, 256}, s[] = {2ull * 65536 * 2, 128, 512};
    uint32_t bx[] = {64, 16, 2, 1};
    return make_map(fn, w + (odd ? 65536 : 0), 4, d, s, bx, S128);
  };
  auto map_X_st = [&](void* p, int nb, int boxb) {
    uint64_t d[] = {64, 512, (uint64_t)(2 * nb)}, s[] = {2ull * nb * 128, 128};
    uint32_t bx[] = {64, C_PC, (uint32_t)boxb};
    return make_map(fn, p, 3, d, s, bx, S128);
  };
  auto map_X1_st = [&]() {
    uint64_t d[] = {64, 512, 2, (uint64_t)NB1}, s[] = {2ull * NB1 * 128, (uint64_t)NB1 * 128, 128};
    uint32_t bx[] = {64, 16, 1, 1};
    return make_map(fn, X1, 4, d, s, bx, S128);
  };
  auto map_W_st = [&](void* p) {
    uint64_t d[] = {64, 512, 4, 64}, s[] = {32768, 8192, 128};
    uint32_t bx[] = {64, W2_PC < 64 ? W2_PC : 64, W2_PC == 128 ? 2 : 1, 1};
    return make_map(fn, p, 4, d, s, bx, S128);
  };
  auto map_W_ld = [&](void* p, uint32_t bd, uint32_t bf) {
    uint64_t d[] = {64, 64, 4, 512}, s[] = {128, 8192, 32768};
    uint32_t bx[] = {64, 32, bd, bf};
    return make_map(fn, p, 4, d, s, bx, S128);
  };
  auto map_Y_st = [&](void* p, int nb, int rows) {
    uint64_t d[] = {64, (uint64_t)(2 * nb), 64, 4}, s[] = {32768, 128, 8192};
    uint32_t bx[] = {64, (uint32_t)rows, 1, 1};
    return make_map(fn, p, 4, d, s, bx, S128);
  };
  auto map_Y_ld = [&](void* p, int nb, int boxc, int boxb) {
    uint64_t d[] = {64, 64, 4, (uint64_t)nb, 2}, s[] = {128, 8192, 32768, (uint64_t)nb * 32768};
    uint32_t bx[] = {64, 64, (uint32_t)boxc, (uint32_t)boxb, 1};
    return make_map(fn, p, 5, d, s, bx, S128);
  };
  auto map_wsq = [&](const __nv_bfloat16* w, uint32_t bn) {
    uint64_t d[] = {64, 256, 4}, s[] = {512, 128};
    uint32_t bx[] = {64, 64, bn};
    return make_map(fn, w, 3, d, s, bx, S128);
  };
  auto map_out = [&]() {
    uint64_t d[] = {64, 4000, 4, 8, 2}, s[] = {4096, 128, 512, 4000ull * 4096};
    uint32_t bx[] = {64, 64, 2, 1, 1};
    return make_map(fn, d_out, 5, d, s, bx, S128);
  };

  auto map_w_raw = [&](const __nv_bfloat16* w, int odd) {
    uint64_t d[] = {256, (uint64_t)(odd ? 15 : 16), 16, 16}, s[] = {2ull * 65536 * 2, 512, 8192};
    uint32_t bx[] = {64, 16, 4, 2};
    return make_map(fn, w + (odd ? 65536 : 0), 4, d, s, bx, S128);
  };
  Ptrs gp;
  cudaGetSymbolAddress((void**)&gp.done, g_done);
  cudaGetSymbolAddress((void**)&gp.ge, g_ge);
  cudaGetSymbolAddress((void**)&gp.img, c_img);
  cudaGetSymbolAddress((void**)&gp.ga, c_ga);
  K1Maps g1;
  memcpy(&g1.p, h_plan, sizeof(Plan));
  g1.x = map_x();
  g1.we = map_w_raw(w1, 0);
  g1.wo = map_w_raw(w1, 1);
  g1.xs = map_X1_st();
  g1.y = map_Y_st(Y1, NB1, NB1 / G_EPI);
  g1.w2e = map_w_in(w2, 0);
  g1.w2o = map_w_in(w2, 1);
  g1.w2s = map_W_st(W2);
  for (int s = 0; s < 32; s++) {
    const int k = s < G_S0 ? s >> 1 : G_KM + (s - G_S0) % G_TK;
    g1.slot[s] = g_off(g_slot(s)) / 16;
    g1.src[s] = ((k >> 1) * 256 + (k & 1) * 2 + (s < G_S0 ? (s & 1) * 4 : s >= G_S0 + G_TK)) * (G_ST / 2);
    g1.dep[s] = s < 3 ? 8 * h_plan[64 + s] : 1536 + 8 * (s - g_depth(s));
  }
  launch(k1, 132, 384, K1_SMEM, false, gp, (const char*)X1, (const char*)w1, g1, g, wgt);
  K2Maps g2;
  memcpy(&g2, h_plan + 67, 100);
  g2.y = map_Y_ld(Y1, NB1, 1, 1);
  g2.xs = map_X_st(X2, NB2, 1);
  {
    uint64_t d[] = {64, 256, 2, 2 * NB2}, s[] = {2ull * NB2 * 128, 512ull * NB2 * 128, 128};
    uint32_t bx[] = {64, 64, 2, 1};
    g2.xa = make_map(fn, X2, 4, d, s, bx, S128);
  }
  g2.w = map_W_ld(W2, 1, 2);
  g2.y2 = map_Y_st(Y2, NB2, 168 / H_EPI);
  launch(k2, 128, 512, K2_SMEM, true, gp, (const char*)X2, g2, wf, wo);
  launch(kE, 126, 256, E_SMEM, true, map_Y_ld(Y2, NB2, 1, 2), map_wsq(wf, 2), map_wsq(wo, 4), map_out());
}
```

```cpp
#include <cuda_runtime.h>
#include <cuda_bf16.h>
#include <cuda.h>
#include <stdint.h>
#include <string.h>
#include <type_traits>

#define ALIAS 1
namespace {

constexpr int NB1 = 168;
constexpr int NB2 = 84;

__device__ __align__(1024) __nv_bfloat16 g_X1[8 * 64 * 2 * NB1 * 64];
__device__ __align__(1024) __nv_bfloat16 g_W2[8 * 64 * 4 * 64 * 64];
__device__ __align__(1024) __nv_bfloat16 g_Y1[2 * NB1 * 4 * 64 * 64];
__device__ __align__(1024) __nv_bfloat16 g_X2[8 * 64 * 2 * NB2 * 64];
__device__ __align__(1024) __nv_bfloat16 g_Y2[2 * NB2 * 4 * 64 * 64];
__device__ __align__(1024) float g_ge[16 * 256];

__device__ __forceinline__ uint32_t s2u(const void* p) { return (uint32_t)__cvta_generic_to_shared(p); }
__device__ __forceinline__ void mbar_init(uint32_t b, int c) {
  asm volatile("mbarrier.init.shared::cta.b64 [%0], %1;" ::"r"(b), "r"(c) : "memory");
}
__device__ __forceinline__ void mbar_expect(uint32_t b, int bytes) {
  asm volatile("mbarrier.arrive.expect_tx.shared::cta.b64 _, [%0], %1;" ::"r"(b), "r"(bytes) : "memory");
}
__device__ __forceinline__ void mbar_arrive(uint32_t b) {
  asm volatile("mbarrier.arrive.shared::cta.b64 _, [%0];" ::"r"(b) : "memory");
}
__device__ __forceinline__ void mbar_arrive_cta(uint32_t b, uint32_t cta) {
  asm volatile("{\n.reg .b32 r;\nmapa.shared::cluster.u32 r, %0, %1;\nmbarrier.arrive.shared::cluster.b64 _, [r];\n}" ::"r"(b), "r"(cta) : "memory");
}
__device__ __forceinline__ void mbar_wait(uint32_t b, int ph) {
  asm volatile(
      "{\n.reg .pred p;\n.reg .u32 n;\n"
      "mov.u32 n, 0;\n"
      "MBW_LOOP:\n"
      "mbarrier.try_wait.parity.shared::cta.b64 p, [%0], %1;\n"
      "@p bra MBW_DONE;\n"
      "add.u32 n, n, 1;\n"
      "setp.lt.u32 p, n, 1048576;\n"
      "@p bra MBW_LOOP;\n"
      "MBW_DONE:\n}" ::"r"(b), "r"(ph) : "memory");
}
__device__ __forceinline__ void fence_bar_init() { asm volatile("fence.mbarrier_init.release.cluster;" ::: "memory"); }
__device__ __forceinline__ void fence_async() { asm volatile("fence.proxy.async.shared::cta;" ::: "memory"); }
__device__ __forceinline__ void bar_sync(int id, int n) { asm volatile("bar.sync %0, %1;" ::"r"(id), "r"(n) : "memory"); }
__device__ __forceinline__ void bar_arrive(int id, int n) { asm volatile("bar.arrive %0, %1;" ::"r"(id), "r"(n) : "memory"); }
__device__ __forceinline__ void pdl_wait() { asm volatile("griddepcontrol.wait;" ::: "memory"); }
__device__ __forceinline__ void pdl_launch() { asm volatile("griddepcontrol.launch_dependents;" ::: "memory"); }
__device__ __forceinline__ void prefetch_map(const CUtensorMap* m) {
  asm volatile("prefetch.tensormap [%0];" ::"l"(m) : "memory");
}
template <int P> __device__ __forceinline__ uint64_t policy() {
  uint64_t p;
  asm("createpolicy.fractional.L2::evict_first.b64 %0, 1.0;" : "=l"(p));
  return p;
}
template <int P> __device__ __forceinline__ void tma_ld3(uint32_t dst, const CUtensorMap* m, uint32_t bar, int c0, int c1, int c2) {
  if constexpr (P == 0)
    asm volatile("cp.async.bulk.tensor.3d.shared::cluster.global.mbarrier::complete_tx::bytes [%0], [%1, {%3, %4, %5}], [%2];"
                 ::"r"(dst), "l"(m), "r"(bar), "r"(c0), "r"(c1), "r"(c2) : "memory");
  else
    asm volatile("cp.async.bulk.tensor.3d.shared::cluster.global.mbarrier::complete_tx::bytes.L2::cache_hint [%0], [%1, {%3, %4, %5}], [%2], %6;"
                 ::"r"(dst), "l"(m), "r"(bar), "r"(c0), "r"(c1), "r"(c2), "l"(policy<P>()) : "memory");
}
template <int P> __device__ __forceinline__ void tma_ld4(uint32_t dst, const CUtensorMap* m, uint32_t bar, int c0, int c1, int c2, int c3) {
  if constexpr (P == 0)
    asm volatile("cp.async.bulk.tensor.4d.shared::cluster.global.mbarrier::complete_tx::bytes [%0], [%1, {%3, %4, %5, %6}], [%2];"
                 ::"r"(dst), "l"(m), "r"(bar), "r"(c0), "r"(c1), "r"(c2), "r"(c3) : "memory");
  else
    asm volatile("cp.async.bulk.tensor.4d.shared::cluster.global.mbarrier::complete_tx::bytes.L2::cache_hint [%0], [%1, {%3, %4, %5, %6}], [%2], %7;"
                 ::"r"(dst), "l"(m), "r"(bar), "r"(c0), "r"(c1), "r"(c2), "r"(c3), "l"(policy<P>()) : "memory");
}
template <int P> __device__ __forceinline__ void tma_ld5(uint32_t dst, const CUtensorMap* m, uint32_t bar, int c0, int c1, int c2, int c3, int c4) {
  if constexpr (P == 0)
    asm volatile("cp.async.bulk.tensor.5d.shared::cluster.global.mbarrier::complete_tx::bytes [%0], [%1, {%3, %4, %5, %6, %7}], [%2];"
                 ::"r"(dst), "l"(m), "r"(bar), "r"(c0), "r"(c1), "r"(c2), "r"(c3), "r"(c4) : "memory");
  else
    asm volatile("cp.async.bulk.tensor.5d.shared::cluster.global.mbarrier::complete_tx::bytes.L2::cache_hint [%0], [%1, {%3, %4, %5, %6, %7}], [%2], %8;"
                 ::"r"(dst), "l"(m), "r"(bar), "r"(c0), "r"(c1), "r"(c2), "r"(c3), "r"(c4), "l"(policy<P>()) : "memory");
}
template <int P> __device__ __forceinline__ void tma_st3(const CUtensorMap* m, uint32_t src, int c0, int c1, int c2) {
  if constexpr (P == 0)
    asm volatile("cp.async.bulk.tensor.3d.global.shared::cta.bulk_group [%0, {%2, %3, %4}], [%1];" ::"l"(m), "r"(src), "r"(c0), "r"(c1), "r"(c2) : "memory");
  else
    asm volatile("cp.async.bulk.tensor.3d.global.shared::cta.bulk_group.L2::cache_hint [%0, {%2, %3, %4}], [%1], %5;" ::"l"(m), "r"(src), "r"(c0), "r"(c1), "r"(c2), "l"(policy<P>()) : "memory");
}
template <int P> __device__ __forceinline__ void tma_st4(const CUtensorMap* m, uint32_t src, int c0, int c1, int c2, int c3) {
  if constexpr (P == 0)
    asm volatile("cp.async.bulk.tensor.4d.global.shared::cta.bulk_group [%0, {%2, %3, %4, %5}], [%1];" ::"l"(m), "r"(src), "r"(c0), "r"(c1), "r"(c2), "r"(c3) : "memory");
  else
    asm volatile("cp.async.bulk.tensor.4d.global.shared::cta.bulk_group.L2::cache_hint [%0, {%2, %3, %4, %5}], [%1], %6;" ::"l"(m), "r"(src), "r"(c0), "r"(c1), "r"(c2), "r"(c3), "l"(policy<P>()) : "memory");
}
template <int P> __device__ __forceinline__ void tma_st5(const CUtensorMap* m, uint32_t src, int c0, int c1, int c2, int c3, int c4) {
  if constexpr (P == 0)
    asm volatile("cp.async.bulk.tensor.5d.global.shared::cta.bulk_group [%0, {%2, %3, %4, %5, %6}], [%1];" ::"l"(m), "r"(src), "r"(c0), "r"(c1), "r"(c2), "r"(c3), "r"(c4) : "memory");
  else
    asm volatile("cp.async.bulk.tensor.5d.global.shared::cta.bulk_group.L2::cache_hint [%0, {%2, %3, %4, %5, %6}], [%1], %7;" ::"l"(m), "r"(src), "r"(c0), "r"(c1), "r"(c2), "r"(c3), "r"(c4), "l"(policy<P>()) : "memory");
}
__device__ __forceinline__ void bulk_commit() { asm volatile("cp.async.bulk.commit_group;" ::: "memory"); }
template <int N> __device__ __forceinline__ void bulk_wait_read() { asm volatile("cp.async.bulk.wait_group.read %0;" ::"n"(N) : "memory"); }
__device__ __forceinline__ void wg_fence() { asm volatile("wgmma.fence.sync.aligned;" ::: "memory"); }
__device__ __forceinline__ void wg_commit() { asm volatile("wgmma.commit_group.sync.aligned;" ::: "memory"); }
template <int N> __device__ __forceinline__ void wg_wait() { asm volatile("wgmma.wait_group.sync.aligned %0;" ::"n"(N) : "memory"); }
template <int R> __device__ __forceinline__ void reg_fence(float (&d)[R]) {
#pragma unroll
  for (int i = 0; i < R; i++) asm volatile("" : "+f"(d[i])::"memory");
}
template <int R> __device__ __forceinline__ void reg_fence(uint32_t (&d)[R]) {
#pragma unroll
  for (int i = 0; i < R; i++) asm volatile("" : "+r"(d[i])::"memory");
}
__device__ __forceinline__ void stsm4(uint32_t a, uint32_t r0, uint32_t r1, uint32_t r2, uint32_t r3) {
  asm volatile("stmatrix.sync.aligned.m8n8.x4.shared.b16 [%0], {%1, %2, %3, %4};" ::"r"(a), "r"(r0), "r"(r1), "r"(r2), "r"(r3) : "memory");
}
__device__ __forceinline__ void stsm4t(uint32_t a, uint32_t r0, uint32_t r1, uint32_t r2, uint32_t r3) {
  asm volatile("stmatrix.sync.aligned.m8n8.x4.trans.shared.b16 [%0], {%1, %2, %3, %4};" ::"r"(a), "r"(r0), "r"(r1), "r"(r2), "r"(r3) : "memory");
}
__device__ __forceinline__ void ldsm4(uint32_t a, uint32_t& r0, uint32_t& r1, uint32_t& r2, uint32_t& r3) {
  asm volatile("ldmatrix.sync.aligned.m8n8.x4.shared.b16 {%0, %1, %2, %3}, [%4];" : "=r"(r0), "=r"(r1), "=r"(r2), "=r"(r3) : "r"(a) : "memory");
}
__device__ __forceinline__ void ldsm4t(uint32_t a, uint32_t& r0, uint32_t& r1, uint32_t& r2, uint32_t& r3) {
  asm volatile("ldmatrix.sync.aligned.m8n8.x4.trans.shared.b16 {%0, %1, %2, %3}, [%4];" : "=r"(r0), "=r"(r1), "=r"(r2), "=r"(r3) : "r"(a) : "memory");
}
__device__ __forceinline__ void ldg128(const uint4* p, uint32_t& a, uint32_t& b, uint32_t& c, uint32_t& d) {
  asm volatile("ld.global.nc.v4.u32 {%0, %1, %2, %3}, [%4];" : "=r"(a), "=r"(b), "=r"(c), "=r"(d) : "l"(p));
}
__device__ __forceinline__ uint32_t pack2(float lo, float hi) {
  uint32_t r;
  asm("cvt.rn.bf16x2.f32 %0, %1, %2;" : "=r"(r) : "f"(hi), "f"(lo));
  return r;
}
__device__ __forceinline__ float tanh_f32(float x) {
  float y;
  asm("tanh.approx.f32 %0, %1;" : "=f"(y) : "f"(x));
  return y;
}
__device__ __forceinline__ float gelu(float hx) {
  const float u = hx * fmaf(hx * hx, 8.0f * 0.044715f * 0.7978845608028654f, 2.0f * 0.7978845608028654f);
  return fmaf(hx, tanh_f32(u), hx);
}
__device__ __forceinline__ uint64_t mk_desc4(uint32_t addr4, uint32_t lbo, uint32_t sbo, uint32_t swz) {
  const uint32_t lo = addr4 + ((lbo >> 4) << 16), hi = (sbo >> 4) | (swz << 30);
  uint64_t d;
  asm("mov.b64 %0, {%1, %2};" : "=l"(d) : "r"(lo), "r"(hi));
  return d;
}
#define mk_desc(base, off, lbo, sbo, swz) mk_desc4((((base) & 0x3FFFF) >> 4) + ((off) >> 4), lbo, sbo, swz)

template <int SA, int SB, int TA, int TB>
__device__ __forceinline__ void wgmma_ss_48(float (&d)[24], uint64_t da, uint64_t db, int sd) {
  asm volatile("{\n.reg .pred p;\nsetp.ne.b32 p, %26, 0;\n"
      "wgmma.mma_async.sync.aligned.m64n48k16.f32.bf16.bf16 {"
      "%0, %1, %2, %3, %4, %5, %6, %7, %8, %9, %10, %11, %12, %13, %14, %15, %16, %17, %18, %19, %20, %21, %22, %23"
      "}, %24, %25, p, %27, %28, %29, %30;\n}\n"
      : "+f"(d[0]), "+f"(d[1]), "+f"(d[2]), "+f"(d[3]), "+f"(d[4]), "+f"(d[5]), "+f"(d[6]), "+f"(d[7]), "+f"(d[8]),
        "+f"(d[9]), "+f"(d[10]), "+f"(d[11]), "+f"(d[12]), "+f"(d[13]), "+f"(d[14]), "+f"(d[15]), "+f"(d[16]),
        "+f"(d[17]), "+f"(d[18]), "+f"(d[19]), "+f"(d[20]), "+f"(d[21]), "+f"(d[22]), "+f"(d[23])
      : "l"(da), "l"(db), "r"(sd), "n"(SA), "n"(SB), "n"(TA), "n"(TB));
}
template <int SA, int SB, int TA, int TB>
__device__ __forceinline__ void wgmma_ss_128(float (&d)[64], uint64_t da, uint64_t db, int sd) {
  asm volatile("{\n.reg .pred p;\nsetp.ne.b32 p, %66, 0;\n"
      "wgmma.mma_async.sync.aligned.m64n128k16.f32.bf16.bf16 {"
      "%0, %1, %2, %3, %4, %5, %6, %7, %8, %9, %10, %11, %12, %13, %14, %15, %16, %17, %18, %19, %20, %21, %22, %23, "
      "%24, %25, %26, %27, %28, %29, %30, %31, %32, %33, %34, %35, %36, %37, %38, %39, %40, %41, %42, %43, %44, %45, "
      "%46, %47, %48, %49, %50, %51, %52, %53, %54, %55, %56, %57, %58, %59, %60, %61, %62, %63"
      "}, %64, %65, p, %67, %68, %69, %70;\n}\n"
      : "+f"(d[0]), "+f"(d[1]), "+f"(d[2]), "+f"(d[3]), "+f"(d[4]), "+f"(d[5]), "+f"(d[6]), "+f"(d[7]), "+f"(d[8]),
        "+f"(d[9]), "+f"(d[10]), "+f"(d[11]), "+f"(d[12]), "+f"(d[13]), "+f"(d[14]), "+f"(d[15]), "+f"(d[16]),
        "+f"(d[17]), "+f"(d[18]), "+f"(d[19]), "+f"(d[20]), "+f"(d[21]), "+f"(d[22]), "+f"(d[23]), "+f"(d[24]),
        "+f"(d[25]), "+f"(d[26]), "+f"(d[27]), "+f"(d[28]), "+f"(d[29]), "+f"(d[30]), "+f"(d[31]), "+f"(d[32]),
        "+f"(d[33]), "+f"(d[34]), "+f"(d[35]), "+f"(d[36]), "+f"(d[37]), "+f"(d[38]), "+f"(d[39]), "+f"(d[40]),
        "+f"(d[41]), "+f"(d[42]), "+f"(d[43]), "+f"(d[44]), "+f"(d[45]), "+f"(d[46]), "+f"(d[47]), "+f"(d[48]),
        "+f"(d[49]), "+f"(d[50]), "+f"(d[51]), "+f"(d[52]), "+f"(d[53]), "+f"(d[54]), "+f"(d[55]), "+f"(d[56]),
        "+f"(d[57]), "+f"(d[58]), "+f"(d[59]), "+f"(d[60]), "+f"(d[61]), "+f"(d[62]), "+f"(d[63])
      : "l"(da), "l"(db), "r"(sd), "n"(SA), "n"(SB), "n"(TA), "n"(TB));
}
template <int SA, int SB, int TA, int TB>
__device__ __forceinline__ void wgmma_ss_168(float (&d)[84], uint64_t da, uint64_t db, int sd) {
  asm volatile("{\n.reg .pred p;\nsetp.ne.b32 p, %86, 0;\n"
      "wgmma.mma_async.sync.aligned.m64n168k16.f32.bf16.bf16 {"
      "%0, %1, %2, %3, %4, %5, %6, %7, %8, %9, %10, %11, %12, %13, %14, %15, %16, %17, %18, %19, %20, %21, %22, %23, "
      "%24, %25, %26, %27, %28, %29, %30, %31, %32, %33, %34, %35, %36, %37, %38, %39, %40, %41, %42, %43, %44, %45, "
      "%46, %47, %48, %49, %50, %51, %52, %53, %54, %55, %56, %57, %58, %59, %60, %61, %62, %63, %64, %65, %66, %67, "
      "%68, %69, %70, %71, %72, %73, %74, %75, %76, %77, %78, %79, %80, %81, %82, %83"
      "}, %84, %85, p, %87, %88, %89, %90;\n}\n"
      : "+f"(d[0]), "+f"(d[1]), "+f"(d[2]), "+f"(d[3]), "+f"(d[4]), "+f"(d[5]), "+f"(d[6]), "+f"(d[7]), "+f"(d[8]),
        "+f"(d[9]), "+f"(d[10]), "+f"(d[11]), "+f"(d[12]), "+f"(d[13]), "+f"(d[14]), "+f"(d[15]), "+f"(d[16]),
        "+f"(d[17]), "+f"(d[18]), "+f"(d[19]), "+f"(d[20]), "+f"(d[21]), "+f"(d[22]), "+f"(d[23]), "+f"(d[24]),
        "+f"(d[25]), "+f"(d[26]), "+f"(d[27]), "+f"(d[28]), "+f"(d[29]), "+f"(d[30]), "+f"(d[31]), "+f"(d[32]),
        "+f"(d[33]), "+f"(d[34]), "+f"(d[35]), "+f"(d[36]), "+f"(d[37]), "+f"(d[38]), "+f"(d[39]), "+f"(d[40]),
        "+f"(d[41]), "+f"(d[42]), "+f"(d[43]), "+f"(d[44]), "+f"(d[45]), "+f"(d[46]), "+f"(d[47]), "+f"(d[48]),
        "+f"(d[49]), "+f"(d[50]), "+f"(d[51]), "+f"(d[52]), "+f"(d[53]), "+f"(d[54]), "+f"(d[55]), "+f"(d[56]),
        "+f"(d[57]), "+f"(d[58]), "+f"(d[59]), "+f"(d[60]), "+f"(d[61]), "+f"(d[62]), "+f"(d[63]), "+f"(d[64]),
        "+f"(d[65]), "+f"(d[66]), "+f"(d[67]), "+f"(d[68]), "+f"(d[69]), "+f"(d[70]), "+f"(d[71]), "+f"(d[72]),
        "+f"(d[73]), "+f"(d[74]), "+f"(d[75]), "+f"(d[76]), "+f"(d[77]), "+f"(d[78]), "+f"(d[79]), "+f"(d[80]),
        "+f"(d[81]), "+f"(d[82]), "+f"(d[83])
      : "l"(da), "l"(db), "r"(sd), "n"(SA), "n"(SB), "n"(TA), "n"(TB));
}
template <int SA, int SB, int TB>
__device__ __forceinline__ void wgmma_rs_32(float (&d)[16], uint32_t a0, uint32_t a1, uint32_t a2, uint32_t a3, uint64_t db, int sd) {
  asm volatile("{\n.reg .pred p;\nsetp.ne.b32 p, %21, 0;\n"
      "wgmma.mma_async.sync.aligned.m64n32k16.f32.bf16.bf16 {"
      "%0, %1, %2, %3, %4, %5, %6, %7, %8, %9, %10, %11, %12, %13, %14, %15"
      "}, {%16, %17, %18, %19}, %20, p, %22, %23, %24;\n}\n"
      : "+f"(d[0]), "+f"(d[1]), "+f"(d[2]), "+f"(d[3]), "+f"(d[4]), "+f"(d[5]), "+f"(d[6]), "+f"(d[7]), "+f"(d[8]),
        "+f"(d[9]), "+f"(d[10]), "+f"(d[11]), "+f"(d[12]), "+f"(d[13]), "+f"(d[14]), "+f"(d[15])
      : "r"(a0), "r"(a1), "r"(a2), "r"(a3), "l"(db), "r"(sd), "n"(SA), "n"(SB), "n"(TB));
}
template <int SA, int SB, int TB>
__device__ __forceinline__ void wgmma_rs_64(float (&d)[32], uint32_t a0, uint32_t a1, uint32_t a2, uint32_t a3, uint64_t db, int sd) {
  asm volatile("{\n.reg .pred p;\nsetp.ne.b32 p, %37, 0;\n"
      "wgmma.mma_async.sync.aligned.m64n64k16.f32.bf16.bf16 {"
      "%0, %1, %2, %3, %4, %5, %6, %7, %8, %9, %10, %11, %12, %13, %14, %15, %16, %17, %18, %19, %20, %21, %22, %23, "
      "%24, %25, %26, %27, %28, %29, %30, %31"
      "}, {%32, %33, %34, %35}, %36, p, %38, %39, %40;\n}\n"
      : "+f"(d[0]), "+f"(d[1]), "+f"(d[2]), "+f"(d[3]), "+f"(d[4]), "+f"(d[5]), "+f"(d[6]), "+f"(d[7]), "+f"(d[8]),
        "+f"(d[9]), "+f"(d[10]), "+f"(d[11]), "+f"(d[12]), "+f"(d[13]), "+f"(d[14]), "+f"(d[15]), "+f"(d[16]),
        "+f"(d[17]), "+f"(d[18]), "+f"(d[19]), "+f"(d[20]), "+f"(d[21]), "+f"(d[22]), "+f"(d[23]), "+f"(d[24]),
        "+f"(d[25]), "+f"(d[26]), "+f"(d[27]), "+f"(d[28]), "+f"(d[29]), "+f"(d[30]), "+f"(d[31])
      : "r"(a0), "r"(a1), "r"(a2), "r"(a3), "l"(db), "r"(sd), "n"(SA), "n"(SB), "n"(TB));
}
template <int SA, int SB, int TB>
__device__ __forceinline__ void wgmma_rs_128(float (&d)[64], uint32_t a0, uint32_t a1, uint32_t a2, uint32_t a3, uint64_t db, int sd) {
  asm volatile("{\n.reg .pred p;\nsetp.ne.b32 p, %69, 0;\n"
      "wgmma.mma_async.sync.aligned.m64n128k16.f32.bf16.bf16 {"
      "%0, %1, %2, %3, %4, %5, %6, %7, %8, %9, %10, %11, %12, %13, %14, %15, %16, %17, %18, %19, %20, %21, %22, %23, "
      "%24, %25, %26, %27, %28, %29, %30, %31, %32, %33, %34, %35, %36, %37, %38, %39, %40, %41, %42, %43, %44, %45, "
      "%46, %47, %48, %49, %50, %51, %52, %53, %54, %55, %56, %57, %58, %59, %60, %61, %62, %63"
      "}, {%64, %65, %66, %67}, %68, p, %70, %71, %72;\n}\n"
      : "+f"(d[0]), "+f"(d[1]), "+f"(d[2]), "+f"(d[3]), "+f"(d[4]), "+f"(d[5]), "+f"(d[6]), "+f"(d[7]), "+f"(d[8]),
        "+f"(d[9]), "+f"(d[10]), "+f"(d[11]), "+f"(d[12]), "+f"(d[13]), "+f"(d[14]), "+f"(d[15]), "+f"(d[16]),
        "+f"(d[17]), "+f"(d[18]), "+f"(d[19]), "+f"(d[20]), "+f"(d[21]), "+f"(d[22]), "+f"(d[23]), "+f"(d[24]),
        "+f"(d[25]), "+f"(d[26]), "+f"(d[27]), "+f"(d[28]), "+f"(d[29]), "+f"(d[30]), "+f"(d[31]), "+f"(d[32]),
        "+f"(d[33]), "+f"(d[34]), "+f"(d[35]), "+f"(d[36]), "+f"(d[37]), "+f"(d[38]), "+f"(d[39]), "+f"(d[40]),
        "+f"(d[41]), "+f"(d[42]), "+f"(d[43]), "+f"(d[44]), "+f"(d[45]), "+f"(d[46]), "+f"(d[47]), "+f"(d[48]),
        "+f"(d[49]), "+f"(d[50]), "+f"(d[51]), "+f"(d[52]), "+f"(d[53]), "+f"(d[54]), "+f"(d[55]), "+f"(d[56]),
        "+f"(d[57]), "+f"(d[58]), "+f"(d[59]), "+f"(d[60]), "+f"(d[61]), "+f"(d[62]), "+f"(d[63])
      : "r"(a0), "r"(a1), "r"(a2), "r"(a3), "l"(db), "r"(sd), "n"(SA), "n"(SB), "n"(TB));
}
template <int SA, int SB, int TB>
__device__ __forceinline__ void wgmma_rs_168(float (&d)[84], uint32_t a0, uint32_t a1, uint32_t a2, uint32_t a3, uint64_t db, int sd) {
  asm volatile("{\n.reg .pred p;\nsetp.ne.b32 p, %89, 0;\n"
      "wgmma.mma_async.sync.aligned.m64n168k16.f32.bf16.bf16 {"
      "%0, %1, %2, %3, %4, %5, %6, %7, %8, %9, %10, %11, %12, %13, %14, %15, %16, %17, %18, %19, %20, %21, %22, %23, "
      "%24, %25, %26, %27, %28, %29, %30, %31, %32, %33, %34, %35, %36, %37, %38, %39, %40, %41, %42, %43, %44, %45, "
      "%46, %47, %48, %49, %50, %51, %52, %53, %54, %55, %56, %57, %58, %59, %60, %61, %62, %63, %64, %65, %66, %67, "
      "%68, %69, %70, %71, %72, %73, %74, %75, %76, %77, %78, %79, %80, %81, %82, %83"
      "}, {%84, %85, %86, %87}, %88, p, %90, %91, %92;\n}\n"
      : "+f"(d[0]), "+f"(d[1]), "+f"(d[2]), "+f"(d[3]), "+f"(d[4]), "+f"(d[5]), "+f"(d[6]), "+f"(d[7]), "+f"(d[8]),
        "+f"(d[9]), "+f"(d[10]), "+f"(d[11]), "+f"(d[12]), "+f"(d[13]), "+f"(d[14]), "+f"(d[15]), "+f"(d[16]),
        "+f"(d[17]), "+f"(d[18]), "+f"(d[19]), "+f"(d[20]), "+f"(d[21]), "+f"(d[22]), "+f"(d[23]), "+f"(d[24]),
        "+f"(d[25]), "+f"(d[26]), "+f"(d[27]), "+f"(d[28]), "+f"(d[29]), "+f"(d[30]), "+f"(d[31]), "+f"(d[32]),
        "+f"(d[33]), "+f"(d[34]), "+f"(d[35]), "+f"(d[36]), "+f"(d[37]), "+f"(d[38]), "+f"(d[39]), "+f"(d[40]),
        "+f"(d[41]), "+f"(d[42]), "+f"(d[43]), "+f"(d[44]), "+f"(d[45]), "+f"(d[46]), "+f"(d[47]), "+f"(d[48]),
        "+f"(d[49]), "+f"(d[50]), "+f"(d[51]), "+f"(d[52]), "+f"(d[53]), "+f"(d[54]), "+f"(d[55]), "+f"(d[56]),
        "+f"(d[57]), "+f"(d[58]), "+f"(d[59]), "+f"(d[60]), "+f"(d[61]), "+f"(d[62]), "+f"(d[63]), "+f"(d[64]),
        "+f"(d[65]), "+f"(d[66]), "+f"(d[67]), "+f"(d[68]), "+f"(d[69]), "+f"(d[70]), "+f"(d[71]), "+f"(d[72]),
        "+f"(d[73]), "+f"(d[74]), "+f"(d[75]), "+f"(d[76]), "+f"(d[77]), "+f"(d[78]), "+f"(d[79]), "+f"(d[80]),
        "+f"(d[81]), "+f"(d[82]), "+f"(d[83])
      : "r"(a0), "r"(a1), "r"(a2), "r"(a3), "l"(db), "r"(sd), "n"(SA), "n"(SB), "n"(TB));
}
template <int SA, int SB, int TB>
__device__ __forceinline__ void wgmma_rs_256(float (&d)[128], uint32_t a0, uint32_t a1, uint32_t a2, uint32_t a3, uint64_t db, int sd) {
  asm volatile("{\n.reg .pred p;\nsetp.ne.b32 p, %133, 0;\n"
      "wgmma.mma_async.sync.aligned.m64n256k16.f32.bf16.bf16 {"
      "%0, %1, %2, %3, %4, %5, %6, %7, %8, %9, %10, %11, %12, %13, %14, %15, %16, %17, %18, %19, %20, %21, %22, %23, "
      "%24, %25, %26, %27, %28, %29, %30, %31, %32, %33, %34, %35, %36, %37, %38, %39, %40, %41, %42, %43, %44, %45, "
      "%46, %47, %48, %49, %50, %51, %52, %53, %54, %55, %56, %57, %58, %59, %60, %61, %62, %63, %64, %65, %66, %67, "
      "%68, %69, %70, %71, %72, %73, %74, %75, %76, %77, %78, %79, %80, %81, %82, %83, %84, %85, %86, %87, %88, %89, "
      "%90, %91, %92, %93, %94, %95, %96, %97, %98, %99, %100, %101, %102, %103, %104, %105, %106, %107, %108, %109, "
      "%110, %111, %112, %113, %114, %115, %116, %117, %118, %119, %120, %121, %122, %123, %124, %125, %126, %127"
      "}, {%128, %129, %130, %131}, %132, p, %134, %135, %136;\n}\n"
      : "+f"(d[0]), "+f"(d[1]), "+f"(d[2]), "+f"(d[3]), "+f"(d[4]), "+f"(d[5]), "+f"(d[6]), "+f"(d[7]), "+f"(d[8]),
        "+f"(d[9]), "+f"(d[10]), "+f"(d[11]), "+f"(d[12]), "+f"(d[13]), "+f"(d[14]), "+f"(d[15]), "+f"(d[16]),
        "+f"(d[17]), "+f"(d[18]), "+f"(d[19]), "+f"(d[20]), "+f"(d[21]), "+f"(d[22]), "+f"(d[23]), "+f"(d[24]),
        "+f"(d[25]), "+f"(d[26]), "+f"(d[27]), "+f"(d[28]), "+f"(d[29]), "+f"(d[30]), "+f"(d[31]), "+f"(d[32]),
        "+f"(d[33]), "+f"(d[34]), "+f"(d[35]), "+f"(d[36]), "+f"(d[37]), "+f"(d[38]), "+f"(d[39]), "+f"(d[40]),
        "+f"(d[41]), "+f"(d[42]), "+f"(d[43]), "+f"(d[44]), "+f"(d[45]), "+f"(d[46]), "+f"(d[47]), "+f"(d[48]),
        "+f"(d[49]), "+f"(d[50]), "+f"(d[51]), "+f"(d[52]), "+f"(d[53]), "+f"(d[54]), "+f"(d[55]), "+f"(d[56]),
        "+f"(d[57]), "+f"(d[58]), "+f"(d[59]), "+f"(d[60]), "+f"(d[61]), "+f"(d[62]), "+f"(d[63]), "+f"(d[64]),
        "+f"(d[65]), "+f"(d[66]), "+f"(d[67]), "+f"(d[68]), "+f"(d[69]), "+f"(d[70]), "+f"(d[71]), "+f"(d[72]),
        "+f"(d[73]), "+f"(d[74]), "+f"(d[75]), "+f"(d[76]), "+f"(d[77]), "+f"(d[78]), "+f"(d[79]), "+f"(d[80]),
        "+f"(d[81]), "+f"(d[82]), "+f"(d[83]), "+f"(d[84]), "+f"(d[85]), "+f"(d[86]), "+f"(d[87]), "+f"(d[88]),
        "+f"(d[89]), "+f"(d[90]), "+f"(d[91]), "+f"(d[92]), "+f"(d[93]), "+f"(d[94]), "+f"(d[95]), "+f"(d[96]),
        "+f"(d[97]), "+f"(d[98]), "+f"(d[99]), "+f"(d[100]), "+f"(d[101]), "+f"(d[102]), "+f"(d[103]), "+f"(d[104]),
        "+f"(d[105]), "+f"(d[106]), "+f"(d[107]), "+f"(d[108]), "+f"(d[109]), "+f"(d[110]), "+f"(d[111]),
        "+f"(d[112]), "+f"(d[113]), "+f"(d[114]), "+f"(d[115]), "+f"(d[116]), "+f"(d[117]), "+f"(d[118]),
        "+f"(d[119]), "+f"(d[120]), "+f"(d[121]), "+f"(d[122]), "+f"(d[123]), "+f"(d[124]), "+f"(d[125]),
        "+f"(d[126]), "+f"(d[127])
      : "r"(a0), "r"(a1), "r"(a2), "r"(a3), "l"(db), "r"(sd), "n"(SA), "n"(SB), "n"(TB));
}

__device__ const __align__(128) uint32_t c_img[3584] = {
    0x00003c80, 0x00003c80, 0x00003c80, 0x00003c80, 0x00003c80, 0x00003c80, 0x00003c80, 0x00003c80, 0x00003c80, 0x00003c80,
    0x00003c80, 0x00003c80, 0x00003c80, 0x00003c80, 0x00003c80, 0x00003c80, 0x00003c80, 0x00003c80, 0x00003c80, 0x00003c80,
    0x00003c80, 0x00003c80, 0x00003c80, 0x00003c80, 0x00003c80, 0x00003c80, 0x00003c80, 0x00003c80, 0x00003c80, 0x00003c80,
    0x00003c80, 0x00003c80, 0x3c463c22, 0x3c623bf1, 0x3c753b95, 0x3c7f3ac9, 0x3ac93c7f, 0x3b953c75, 0x3bf13c62, 0x3c223c46,
    0x3c22bc46, 0x3bf1bc62, 0x3b95bc75, 0x3ac9bc7f, 0x3c7fbac9, 0x3c75bb95, 0x3c62bbf1, 0x3c46bc22, 0xbc46bc22, 0xbc62bbf1,
    0xbc75bb95, 0xbc7fbac9, 0xbac9bc7f, 0xbb95bc75, 0xbbf1bc62, 0xbc22bc46, 0xbc223c46, 0xbbf13c62, 0xbb953c75, 0xbac93c7f,
    0xbc7f3ac9, 0xbc753b95, 0xbc623bf1, 0xbc463c22, 0xbb48bc7b, 0xbc0ebc55, 0xbc55bc0e, 0xbc7bbb48, 0xbc7b3b48, 0xbc553c0e,
    0xbc0e3c55, 0xbb483c7b, 0x3b483c7b, 0x3c0e3c55, 0x3c553c0e, 0x3c7b3b48, 0x3c7bbb48, 0x3c55bc0e, 0x3c0ebc55, 0x3b48bc7b,
    0xbb48bc7b, 0xbc0ebc55, 0xbc55bc0e, 0xbc7bbb48, 0xbc7b3b48, 0xbc553c0e, 0xbc0e3c55, 0xbb483c7b, 0x3b483c7b, 0x3c0e3c55,
    0x3c553c0e, 0x3c7b3b48, 0x3c7bbb48, 0x3c55bc0e, 0x3c0ebc55, 0x3b48bc7b, 0x3c623bf1, 0x3c7fbac9, 0x3c46bc22, 0x3b95bc75,
    0xbc753b95, 0xbc223c46, 0xbac93c7f, 0x3bf13c62, 0x3bf1bc62, 0xbac9bc7f, 0xbc22bc46, 0xbc75bb95, 0x3b953c75, 0x3c463c22,
    0x3c7f3ac9, 0x3c62bbf1, 0xbc62bbf1, 0xbc7f3ac9, 0xbc463c22, 0xbb953c75, 0x3c75bb95, 0x3c22bc46, 0x3ac9bc7f, 0xbbf1bc62,
    0xbbf13c62, 0x3ac93c7f, 0x3c223c46, 0x3c753b95, 0xbb95bc75, 0xbc46bc22, 0xbc7fbac9, 0xbc623bf1, 0x3bc43c6d, 0x3c6d3bc4,
    0x3c6dbbc4, 0x3bc4bc6d, 0xbbc4bc6d, 0xbc6dbbc4, 0xbc6d3bc4, 0xbbc43c6d, 0x3bc43c6d, 0x3c6d3bc4, 0x3c6dbbc4, 0x3bc4bc6d,
    0xbbc4bc6d, 0xbc6dbbc4, 0xbc6d3bc4, 0xbbc43c6d, 0x3bc43c6d, 0x3c6d3bc4, 0x3c6dbbc4, 0x3bc4bc6d, 0xbbc4bc6d, 0xbc6dbbc4,
    0xbc6d3bc4, 0xbbc43c6d, 0x3bc43c6d, 0x3c6d3bc4, 0x3c6dbbc4, 0x3bc4bc6d, 0xbbc4bc6d, 0xbc6dbbc4, 0xbc6d3bc4, 0xbbc43c6d,
    0x3c753b95, 0x3c46bc22, 0xbac9bc7f, 0xbc62bbf1, 0xbbf1bc62, 0xbc7fbac9, 0xbc223c46, 0x3b953c75, 0x3b95bc75, 0xbc22bc46,
    0xbc7f3ac9, 0xbbf13c62, 0xbc623bf1, 0xbac93c7f, 0x3c463c22, 0x3c75bb95, 0xbc75bb95, 0xbc463c22, 0x3ac93c7f, 0x3c623bf1,
    0x3bf13c62, 0x3c7f3ac9, 0x3c22bc46, 0xbb95bc75, 0xbb953c75, 0x3c223c46, 0x3c7fbac9, 0x3bf1bc62, 0x3c62bbf1, 0x3ac9bc7f,
    0xbc46bc22, 0xbc753b95, 0xbc0ebc55, 0xbc7b3b48, 0xbb483c7b, 0x3c553c0e, 0x3c55bc0e, 0xbb48bc7b, 0xbc7bbb48, 0xbc0e3c55,
    0x3c0e3c55, 0x3c7bbb48, 0x3b48bc7b, 0xbc55bc0e, 0xbc553c0e, 0x3b483c7b, 0x3c7b3b48, 0x3c0ebc55, 0xbc0ebc55, 0xbc7b3b48,
    0xbb483c7b, 0x3c553c0e, 0x3c55bc0e, 0xbb48bc7b, 0xbc7bbb48, 0xbc0e3c55, 0x3c0e3c55, 0x3c7bbb48, 0x3b48bc7b, 0xbc55bc0e,
    0xbc553c0e, 0x3b483c7b, 0x3c7b3b48, 0x3c0ebc55, 0x3c7f3ac9, 0x3b95bc75, 0xbc62bbf1, 0xbc223c46, 0x3c46bc22, 0xbbf1bc62,
    0xbc753b95, 0x3ac93c7f, 0x3ac9bc7f, 0xbc75bb95, 0xbbf13c62, 0x3c463c22, 0xbc22bc46, 0xbc623bf1, 0x3b953c75, 0x3c7fbac9,
    0xbc7fbac9, 0xbb953c75, 0x3c623bf1, 0x3c22bc46, 0xbc463c22, 0x3bf13c62, 0x3c75bb95, 0xbac9bc7f, 0xbac93c7f, 0x3c753b95,
    0x3bf1bc62, 0xbc46bc22, 0x3c223c46, 0x3c62bbf1, 0xbb95bc75, 0xbc7f3ac9, 0x3a493c80, 0x3b163c7d, 0x3b793c78, 0x3bac3c71,
    0x3bdb3c67, 0x3c043c5c, 0x3c183c4e, 0x3c2c3c3e, 0x3c3e3c2c, 0x3c4e3c18, 0x3c5c3c04, 0x3c673bdb, 0x3c713bac, 0x3c783b79,
    0x3c7d3b16, 0x3c803a49, 0x3c80ba49, 0x3c7dbb16, 0x3c78bb79, 0x3c71bbac, 0x3c67bbdb, 0x3c5cbc04, 0x3c4ebc18, 0x3c3ebc2c,
    0x3c2cbc3e, 0x3c18bc4e, 0x3c04bc5c, 0x3bdbbc67, 0x3bacbc71, 0x3b79bc78, 0x3b16bc7d, 0x3a49bc80, 0x3c783b79, 0x3c80ba49,
    0x3c71bbac, 0x3c4ebc18, 0x3b163c7d, 0x3bdb3c67, 0x3c2c3c3e, 0x3c5c3c04, 0xbc04bc5c, 0xbc3ebc2c, 0xbc67bbdb, 0xbc7dbb16,
    0x3c18bc4e, 0x3bacbc71, 0x3a49bc80, 0xbb79bc78, 0xbb793c78, 0x3a493c80, 0x3bac3c71, 0x3c183c4e, 0xbc7d3b16, 0xbc673bdb,
    0xbc3e3c2c, 0xbc043c5c, 0x3c5cbc04, 0x3c2cbc3e, 0x3bdbbc67, 0x3b16bc7d, 0x3c4e3c18, 0x3c713bac, 0x3c803a49, 0x3c78bb79,
    0xbc5cbc04, 0xbc80ba49, 0xbc673bdb, 0xbc183c4e, 0xbb163c7d, 0x3bac3c71, 0x3c3e3c2c, 0x3c783b79, 0x3b793c78, 0x3c2c3c3e,
    0x3c713bac, 0x3c7dbb16, 0x3c4ebc18, 0x3bdbbc67, 0xba49bc80, 0xbc04bc5c, 0xbc043c5c, 0xba493c80, 0x3bdb3c67, 0x3c4e3c18,
    0x3c7d3b16, 0x3c71bbac, 0x3c2cbc3e, 0x3b79bc78, 0x3c78bb79, 0x3c3ebc2c, 0x3bacbc71, 0xbb16bc7d, 0xbc18bc4e, 0xbc67bbdb,
    0xbc803a49, 0xbc5c3c04, 0x3c3ebc2c, 0x3b16bc7d, 0xbc04bc5c, 0xbc71bbac, 0xbbdb3c67, 0x3b793c78, 0x3c4e3c18, 0x3c80ba49,
    0x3a49bc80, 0xbc18bc4e, 0xbc78bb79, 0xbc673bdb, 0x3bac3c71, 0x3c5c3c04, 0x3c7dbb16, 0x3c2cbc3e, 0x3c2c3c3e, 0x3c7d3b16,
    0x3c5cbc04, 0x3bacbc71, 0xbc67bbdb, 0xbc783b79, 0xbc183c4e, 0x3a493c80, 0x3c803a49, 0x3c4ebc18, 0x3b79bc78, 0xbbdbbc67,
    0xbc713bac, 0xbc043c5c, 0x3b163c7d, 0x3c3e3c2c, 0x3c67bbdb, 0x3b79bc78, 0xbc18bc4e, 0xbc80ba49, 0xbc2c3c3e, 0x3b163c7d,
    0x3c5c3c04, 0x3c71bbac, 0x3bacbc71, 0xbc04bc5c, 0xbc7dbb16, 0xbc3e3c2c, 0x3a493c80, 0x3c4e3c18, 0x3c78bb79, 0x3bdbbc67,
    0x3bdb3c67, 0x3c783b79, 0x3c4ebc18, 0x3a49bc80, 0xbc3ebc2c, 0xbc7d3b16, 0xbc043c5c, 0x3bac3c71, 0x3c713bac, 0x3c5cbc04,
    0x3b16bc7d, 0xbc2cbc3e, 0xbc803a49, 0xbc183c4e, 0x3b793c78, 0x3c673bdb, 0xbb16bc7d, 0xbc71bbac, 0xbc3e3c2c, 0x3b793c78,
    0xbc5c3c04, 0x3a493c80, 0x3c673bdb, 0x3c4ebc18, 0xbc183c4e, 0x3bdb3c67, 0x3c803a49, 0x3c04bc5c, 0x3c783b79, 0x3c2cbc3e,
    0xbbacbc71, 0xbc7dbb16, 0xbc7d3b16, 0xbbac3c71, 0x3c2c3c3e, 0x3c78bb79, 0x3c043c5c, 0x3c80ba49, 0x3bdbbc67, 0xbc18bc4e,
    0x3c4e3c18, 0x3c67bbdb, 0x3a49bc80, 0xbc5cbc04, 0x3b79bc78, 0xbc3ebc2c, 0xbc713bac, 0xbb163c7d, 0xbb163c7d, 0x3c673bdb,
    0x3c2cbc3e, 0xbc04bc5c, 0xbc783b79, 0xba493c80, 0x3c713bac, 0x3c18bc4e, 0x3c4ebc18, 0xbbacbc71, 0xbc803a49, 0xbb793c78,
    0x3c5c3c04, 0x3c3ebc2c, 0xbbdbbc67, 0xbc7d3b16, 0xbc7dbb16, 0xbbdb3c67, 0x3c3e3c2c, 0x3c5cbc04, 0xbb79bc78, 0xbc80ba49,
    0xbbac3c71, 0x3c4e3c18, 0x3c183c4e, 0x3c71bbac, 0xba49bc80, 0xbc78bb79, 0xbc043c5c, 0x3c2c3c3e, 0x3c67bbdb, 0xbb16bc7d,
    0xbc67bbdb, 0xbc043c5c, 0x3c4e3c18, 0x3c2cbc3e, 0xbc80ba49, 0xbb163c7d, 0x3c783b79, 0x3bacbc71, 0xbc713bac, 0x3b793c78,
    0x3c7dbb16, 0xba49bc80, 0xbc3e3c2c, 0x3c183c4e, 0x3c5cbc04, 0xbbdbbc67, 0xbbdb3c67, 0x3c5c3c04, 0x3c18bc4e, 0xbc3ebc2c,
    0xba493c80, 0x3c7d3b16, 0x3b79bc78, 0xbc71bbac, 0x3bac3c71, 0x3c78bb79, 0xbb16bc7d, 0xbc803a49, 0x3c2c3c3e, 0x3c4ebc18,
    0xbc04bc5c, 0xbc673bdb, 0x3c353c35, 0x3c35bc35, 0xbc35bc35, 0xbc353c35, 0x3c353c35, 0x3c35bc35, 0xbc35bc35, 0xbc353c35,
    0x3c353c35, 0x3c35bc35, 0xbc35bc35, 0xbc353c35, 0x3c353c35, 0x3c35bc35, 0xbc35bc35, 0xbc353c35, 0x3c353c35, 0x3c35bc35,
    0xbc35bc35, 0xbc353c35, 0x3c353c35, 0x3c35bc35, 0xbc35bc35, 0xbc353c35, 0x3c353c35, 0x3c35bc35, 0xbc35bc35, 0xbc353c35,
    0x3c353c35, 0x3c35bc35, 0xbc35bc35, 0xbc353c35, 0x3c7fbac9, 0xbb95bc75, 0xbc623bf1, 0x3c223c46, 0x3c463c22, 0x3bf1bc62,
    0xbc75bb95, 0xbac93c7f, 0xbac9bc7f, 0xbc753b95, 0x3bf13c62, 0x3c46bc22, 0x3c22bc46, 0xbc62bbf1, 0xbb953c75, 0x3c7f3ac9,
    0xbc7f3ac9, 0x3b953c75, 0x3c62bbf1, 0xbc22bc46, 0xbc46bc22, 0xbbf13c62, 0x3c753b95, 0x3ac9bc7f, 0x3ac93c7f, 0x3c75bb95,
    0xbbf1bc62, 0xbc463c22, 0xbc223c46, 0x3c623bf1, 0x3b95bc75, 0xbc7fbac9, 0xbc55bc0e, 0xbb483c7b, 0x3c7bbb48, 0xbc0ebc55,
    0xbc0e3c55, 0x3c7b3b48, 0xbb48bc7b, 0xbc553c0e, 0x3c553c0e, 0x3b48bc7b, 0xbc7b3b48, 0x3c0e3c55, 0x3c0ebc55, 0xbc7bbb48,
    0x3b483c7b, 0x3c55bc0e, 0xbc55bc0e, 0xbb483c7b, 0x3c7bbb48, 0xbc0ebc55, 0xbc0e3c55, 0x3c7b3b48, 0xbb48bc7b, 0xbc553c0e,
    0x3c553c0e, 0x3b48bc7b, 0xbc7b3b48, 0x3c0e3c55, 0x3c0ebc55, 0xbc7bbb48, 0x3b483c7b, 0x3c55bc0e, 0x3c75bb95, 0xbc46bc22,
    0xbac93c7f, 0x3c62bbf1, 0xbbf13c62, 0x3c7fbac9, 0xbc22bc46, 0xbb953c75, 0xbb95bc75, 0xbc223c46, 0x3c7f3ac9, 0xbbf1bc62,
    0x3c623bf1, 0xbac9bc7f, 0xbc463c22, 0x3c753b95, 0xbc753b95, 0x3c463c22, 0x3ac9bc7f, 0xbc623bf1, 0x3bf1bc62, 0xbc7f3ac9,
    0x3c223c46, 0x3b95bc75, 0x3b953c75, 0x3c22bc46, 0xbc7fbac9, 0x3bf13c62, 0xbc62bbf1, 0x3ac93c7f, 0x3c46bc22, 0xbc75bb95,
    0x3c6d3bc4, 0xbbc4bc6d, 0xbbc43c6d, 0x3c6dbbc4, 0xbc6dbbc4, 0x3bc43c6d, 0x3bc4bc6d, 0xbc6d3bc4, 0x3c6d3bc4, 0xbbc4bc6d,
    0xbbc43c6d, 0x3c6dbbc4, 0xbc6dbbc4, 0x3bc43c6d, 0x3bc4bc6d, 0xbc6d3bc4, 0x3c6d3bc4, 0xbbc4bc6d, 0xbbc43c6d, 0x3c6dbbc4,
    0xbc6dbbc4, 0x3bc43c6d, 0x3bc4bc6d, 0xbc6d3bc4, 0x3c6d3bc4, 0xbbc4bc6d, 0xbbc43c6d, 0x3c6dbbc4, 0xbc6dbbc4, 0x3bc43c6d,
    0x3bc4bc6d, 0xbc6d3bc4, 0x3c62bbf1, 0xbc7fbac9, 0x3c463c22, 0xbb95bc75, 0xbc75bb95, 0x3c223c46, 0xbac9bc7f, 0xbbf13c62,
    0xbbf1bc62, 0xbac93c7f, 0x3c22bc46, 0xbc753b95, 0xbb953c75, 0x3c46bc22, 0xbc7f3ac9, 0x3c623bf1, 0xbc623bf1, 0x3c7f3ac9,
    0xbc46bc22, 0x3b953c75, 0x3c753b95, 0xbc22bc46, 0x3ac93c7f, 0x3bf1bc62, 0x3bf13c62, 0x3ac9bc7f, 0xbc223c46, 0x3c75bb95,
    0x3b95bc75, 0xbc463c22, 0x3c7fbac9, 0xbc62bbf1, 0xbc7bbb48, 0x3c553c0e, 0xbc0ebc55, 0x3b483c7b, 0x3b48bc7b, 0xbc0e3c55,
    0x3c55bc0e, 0xbc7b3b48, 0x3c7b3b48, 0xbc55bc0e, 0x3c0e3c55, 0xbb48bc7b, 0xbb483c7b, 0x3c0ebc55, 0xbc553c0e, 0x3c7bbb48,
    0xbc7bbb48, 0x3c553c0e, 0xbc0ebc55, 0x3b483c7b, 0x3b48bc7b, 0xbc0e3c55, 0x3c55bc0e, 0xbc7b3b48, 0x3c7b3b48, 0xbc55bc0e,
    0x3c0e3c55, 0xbb48bc7b, 0xbb483c7b, 0x3c0ebc55, 0xbc553c0e, 0x3c7bbb48, 0x3c46bc22, 0xbc623bf1, 0x3c75bb95, 0xbc7f3ac9,
    0x3ac9bc7f, 0xbb953c75, 0x3bf1bc62, 0xbc223c46, 0xbc22bc46, 0x3bf13c62, 0xbb95bc75, 0x3ac93c7f, 0xbc7fbac9, 0x3c753b95,
    0xbc62bbf1, 0x3c463c22, 0xbc463c22, 0x3c62bbf1, 0xbc753b95, 0x3c7fbac9, 0xbac93c7f, 0x3b95bc75, 0xbbf13c62, 0x3c22bc46,
    0x3c223c46, 0xbbf1bc62, 0x3b953c75, 0xbac9bc7f, 0x3c7f3ac9, 0xbc75bb95, 0x3c623bf1, 0xbc46bc22, 0x3c3e3c2c, 0x3c18bc4e,
    0xbc5cbc04, 0xbbdb3c67, 0x3c713bac, 0x3b79bc78, 0xbc7dbb16, 0xba493c80, 0x3c80ba49, 0xbb16bc7d, 0xbc783b79, 0x3bac3c71,
    0x3c67bbdb, 0xbc04bc5c, 0xbc4e3c18, 0x3c2c3c3e, 0x3c2cbc3e, 0xbc4ebc18, 0xbc043c5c, 0x3c673bdb, 0x3bacbc71, 0xbc78bb79,
    0xbb163c7d, 0x3c803a49, 0xba49bc80, 0xbc7d3b16, 0x3b793c78, 0x3c71bbac, 0xbbdbbc67, 0xbc5c3c04, 0x3c183c4e, 0x3c3ebc2c,
    0x3c5cbc04, 0xbc3ebc2c, 0xbbdb3c67, 0x3c7d3b16, 0x3c4e3c18, 0x3bacbc71, 0xbc80ba49, 0x3b793c78, 0xbc78bb79, 0x3a493c80,
    0x3c71bbac, 0xbc18bc4e, 0xbb16bc7d, 0xbc673bdb, 0x3c2c3c3e, 0x3c04bc5c, 0x3c043c5c, 0x3c2cbc3e, 0xbc67bbdb, 0xbb163c7d,
    0xbc183c4e, 0x3c713bac, 0x3a49bc80, 0xbc783b79, 0x3b79bc78, 0xbc803a49, 0x3bac3c71, 0x3c4ebc18, 0x3c7dbb16, 0xbbdbbc67,
    0xbc3e3c2c, 0x3c5c3c04, 0xbc783b79, 0x3c2c3c3e, 0x3bacbc71, 0xbc7d3b16, 0x3c183c4e, 0x3bdbbc67, 0xbc803a49, 0x3c043c5c,
    0x3c5c3c04, 0x3a49bc80, 0xbc673bdb, 0x3c4e3c18, 0x3b16bc7d, 0xbc713bac, 0x3c3e3c2c, 0x3b79bc78, 0x3b793c78, 0x3c3ebc2c,
    0xbc71bbac, 0x3b163c7d, 0x3c4ebc18, 0xbc67bbdb, 0x3a493c80, 0x3c5cbc04, 0x3c04bc5c, 0xbc80ba49, 0x3bdb3c67, 0x3c18bc4e,
    0xbc7dbb16, 0x3bac3c71, 0x3c2cbc3e, 0xbc78bb79, 0x3a49bc80, 0xbc4e3c18, 0x3c783b79, 0xbbdbbc67, 0x3bac3c71, 0x3c04bc5c,
    0xbc7d3b16, 0x3c3e3c2c, 0xbc2cbc3e, 0xbb163c7d, 0x3c5cbc04, 0xbc71bbac, 0x3c673bdb, 0xbb79bc78, 0xbc183c4e, 0x3c80ba49,
    0x3c803a49, 0xbc18bc4e, 0xbb793c78, 0x3c67bbdb, 0xbc713bac, 0x3c5c3c04, 0xbb16bc7d, 0xbc2c3c3e, 0x3c3ebc2c, 0xbc7dbb16,
    0x3c043c5c, 0x3bacbc71, 0xbbdb3c67, 0x3c78bb79, 0xbc4ebc18, 0x3a493c80, 0x3bacbc71, 0xbc5c3c04, 0x3c7d3b16, 0xbc2cbc3e,
    0x3a493c80, 0x3c18bc4e, 0xbc783b79, 0x3c673bdb, 0xbbdbbc67, 0xbb793c78, 0x3c4ebc18, 0xbc80ba49, 0x3c3e3c2c, 0xbb16bc7d,
    0xbc043c5c, 0x3c71bbac, 0x3c713bac, 0xbc04bc5c, 0xbb163c7d, 0x3c3ebc2c, 0xbc803a49, 0x3c4e3c18, 0xbb79bc78, 0xbbdb3c67,
    0x3c67bbdb, 0xbc78bb79, 0x3c183c4e, 0x3a49bc80, 0xbc2c3c3e, 0x3c7dbb16, 0xbc5cbc04, 0x3bac3c71, 0xbc4ebc18, 0x3bdb3c67,
    0x3a49bc80, 0xbc043c5c, 0xbb793c78, 0x3c2cbc3e, 0xbc713bac, 0x3c7d3b16, 0x3b163c7d, 0x3bacbc71, 0xbc3e3c2c, 0x3c78bb79,
    0x3c5cbc04, 0xbc803a49, 0x3c673bdb, 0xbc18bc4e, 0xbc183c4e, 0x3c67bbdb, 0xbc80ba49, 0x3c5c3c04, 0x3c783b79, 0xbc3ebc2c,
    0x3bac3c71, 0x3b16bc7d, 0x3c7dbb16, 0xbc71bbac, 0x3c2c3c3e, 0xbb79bc78, 0xbc04bc5c, 0x3a493c80, 0x3bdbbc67, 0xbc4e3c18,
    0x3c183c4e, 0xbbacbc71, 0x3a493c80, 0x3b79bc78, 0xbc043c5c, 0x3c3ebc2c, 0xbc673bdb, 0x3c7dbb16, 0x3b16bc7d, 0xbbdb3c67,
    0x3c2cbc3e, 0xbc5c3c04, 0x3c78bb79, 0xbc80ba49, 0x3c713bac, 0xbc4ebc18, 0xbc4e3c18, 0x3c71bbac, 0xbc803a49, 0x3c783b79,
    0xbc5cbc04, 0x3c2c3c3e, 0xbbdbbc67, 0x3b163c7d, 0x3c7d3b16, 0xbc67bbdb, 0x3c3e3c2c, 0xbc04bc5c, 0x3b793c78, 0x3a49bc80,
    0xbbac3c71, 0x3c18bc4e, 0xbc713bac, 0x3c78bb79, 0xbc7d3b16, 0x3c80ba49, 0xbc3e3c2c, 0x3c4ebc18, 0xbc5c3c04, 0x3c67bbdb,
    0xbbdb3c67, 0x3c04bc5c, 0xbc183c4e, 0x3c2cbc3e, 0xba493c80, 0x3b16bc7d, 0xbb793c78, 0x3bacbc71, 0x3bac3c71, 0xbb79bc78,
    0x3b163c7d, 0xba49bc80, 0x3c2c3c3e, 0xbc18bc4e, 0x3c043c5c, 0xbbdbbc67, 0x3c673bdb, 0xbc5cbc04, 0x3c4e3c18, 0xbc3ebc2c,
    0x3c803a49, 0xbc7dbb16, 0x3c783b79, 0xbc71bbac, 0x3c800000, 0xbc800000, 0x3c800000, 0xbc800000, 0x3c800000, 0xbc800000,
    0x3c800000, 0xbc800000, 0x3c800000, 0xbc800000, 0x3c800000, 0xbc800000, 0x3c800000, 0xbc800000, 0x3c800000, 0xbc800000,
    0x3c800000, 0xbc800000, 0x3c800000, 0xbc800000, 0x3c800000, 0xbc800000, 0x3c800000, 0xbc800000, 0x3c800000, 0xbc800000,
    0x3c800000, 0xbc800000, 0x3c800000, 0xbc800000, 0x3c800000, 0xbc800000, 0x3c22bc46, 0xbbf13c62, 0x3b95bc75, 0xbac93c7f,
    0x3c7fbac9, 0xbc753b95, 0x3c62bbf1, 0xbc463c22, 0xbc46bc22, 0x3c623bf1, 0xbc75bb95, 0x3c7f3ac9, 0xbac9bc7f, 0x3b953c75,
    0xbbf1bc62, 0x3c223c46, 0xbc223c46, 0x3bf1bc62, 0xbb953c75, 0x3ac9bc7f, 0xbc7f3ac9, 0x3c75bb95, 0xbc623bf1, 0x3c46bc22,
    0x3c463c22, 0xbc62bbf1, 0x3c753b95, 0xbc7fbac9, 0x3ac93c7f, 0xbb95bc75, 0x3bf13c62, 0xbc22bc46, 0xbc7b3b48, 0x3c55bc0e,
    0xbc0e3c55, 0x3b48bc7b, 0x3b483c7b, 0xbc0ebc55, 0x3c553c0e, 0xbc7bbb48, 0x3c7bbb48, 0xbc553c0e, 0x3c0ebc55, 0xbb483c7b,
    0xbb48bc7b, 0x3c0e3c55, 0xbc55bc0e, 0x3c7b3b48, 0xbc7b3b48, 0x3c55bc0e, 0xbc0e3c55, 0x3b48bc7b, 0x3b483c7b, 0xbc0ebc55,
    0x3c553c0e, 0xbc7bbb48, 0x3c7bbb48, 0xbc553c0e, 0x3c0ebc55, 0xbb483c7b, 0xbb48bc7b, 0x3c0e3c55, 0xbc55bc0e, 0x3c7b3b48,
    0x3bf1bc62, 0x3ac93c7f, 0xbc22bc46, 0x3c753b95, 0x3b953c75, 0xbc46bc22, 0x3c7f3ac9, 0xbc623bf1, 0xbc62bbf1, 0x3c7fbac9,
    0xbc463c22, 0x3b95bc75, 0x3c75bb95, 0xbc223c46, 0x3ac9bc7f, 0x3bf13c62, 0xbbf13c62, 0xbac9bc7f, 0x3c223c46, 0xbc75bb95,
    0xbb95bc75, 0x3c463c22, 0xbc7fbac9, 0x3c62bbf1, 0x3c623bf1, 0xbc7f3ac9, 0x3c46bc22, 0xbb953c75, 0xbc753b95, 0x3c22bc46,
    0xbac93c7f, 0xbbf1bc62, 0x3c6dbbc4, 0xbbc43c6d, 0xbbc4bc6d, 0x3c6d3bc4, 0xbc6d3bc4, 0x3bc4bc6d, 0x3bc43c6d, 0xbc6dbbc4,
    0x3c6dbbc4, 0xbbc43c6d, 0xbbc4bc6d, 0x3c6d3bc4, 0xbc6d3bc4, 0x3bc4bc6d, 0x3bc43c6d, 0xbc6dbbc4, 0x3c6dbbc4, 0xbbc43c6d,
    0xbbc4bc6d, 0x3c6d3bc4, 0xbc6d3bc4, 0x3bc4bc6d, 0x3bc43c6d, 0xbc6dbbc4, 0x3c6dbbc4, 0xbbc43c6d, 0xbbc4bc6d, 0x3c6d3bc4,
    0xbc6d3bc4, 0x3bc4bc6d, 0x3bc43c6d, 0xbc6dbbc4, 0x3b95bc75, 0x3c223c46, 0xbc7f3ac9, 0x3bf1bc62, 0xbc623bf1, 0x3ac9bc7f,
    0x3c463c22, 0xbc753b95, 0xbc75bb95, 0x3c46bc22, 0x3ac93c7f, 0xbc62bbf1, 0x3bf13c62, 0xbc7fbac9, 0x3c22bc46, 0x3b953c75,
    0xbb953c75, 0xbc22bc46, 0x3c7fbac9, 0xbbf13c62, 0x3c62bbf1, 0xbac93c7f, 0xbc46bc22, 0x3c75bb95, 0x3c753b95, 0xbc463c22,
    0xbac9bc7f, 0x3c623bf1, 0xbbf1bc62, 0x3c7f3ac9, 0xbc223c46, 0xbb95bc75, 0xbc553c0e, 0xbb48bc7b, 0x3c7b3b48, 0xbc0e3c55,
    0xbc0ebc55, 0x3c7bbb48, 0xbb483c7b, 0xbc55bc0e, 0x3c55bc0e, 0x3b483c7b, 0xbc7bbb48, 0x3c0ebc55, 0x3c0e3c55, 0xbc7b3b48,
    0x3b48bc7b, 0x3c553c0e, 0xbc553c0e, 0xbb48bc7b, 0x3c7b3b48, 0xbc0e3c55, 0xbc0ebc55, 0x3c7bbb48, 0xbb483c7b, 0xbc55bc0e,
    0x3c55bc0e, 0x3b483c7b, 0xbc7bbb48, 0x3c0ebc55, 0x3c0e3c55, 0xbc7b3b48, 0x3b48bc7b, 0x3c553c0e, 0x3ac9bc7f, 0x3c753b95,
    0xbbf13c62, 0xbc46bc22, 0xbc22bc46, 0x3c62bbf1, 0x3b953c75, 0xbc7f3ac9, 0xbc7fbac9, 0x3b95bc75, 0x3c623bf1, 0xbc223c46,
    0xbc463c22, 0xbbf1bc62, 0x3c75bb95, 0x3ac93c7f, 0xbac93c7f, 0xbc75bb95, 0x3bf1bc62, 0x3c463c22, 0x3c223c46, 0xbc623bf1,
    0xbb95bc75, 0x3c7fbac9, 0x3c7f3ac9, 0xbb953c75, 0xbc62bbf1, 0x3c22bc46, 0x3c46bc22, 0x3bf13c62, 0xbc753b95, 0xbac9bc7f,
    0x3c80ba49, 0xbc7d3b16, 0x3c78bb79, 0xbc713bac, 0x3c67bbdb, 0xbc5c3c04, 0x3c4ebc18, 0xbc3e3c2c, 0x3c2cbc3e, 0xbc183c4e,
    0x3c04bc5c, 0xbbdb3c67, 0x3bacbc71, 0xbb793c78, 0x3b16bc7d, 0xba493c80, 0xba49bc80, 0x3b163c7d, 0xbb79bc78, 0x3bac3c71,
    0xbbdbbc67, 0x3c043c5c, 0xbc18bc4e, 0x3c2c3c3e, 0xbc3ebc2c, 0x3c4e3c18, 0xbc5cbc04, 0x3c673bdb, 0xbc71bbac, 0x3c783b79,
    0xbc7dbb16, 0x3c803a49, 0x3b79bc78, 0x3a493c80, 0xbbacbc71, 0x3c183c4e, 0x3c7dbb16, 0xbc673bdb, 0x3c3ebc2c, 0xbc043c5c,
    0xbc5c3c04, 0x3c2cbc3e, 0xbbdb3c67, 0x3b16bc7d, 0xbc4ebc18, 0x3c713bac, 0xbc80ba49, 0x3c78bb79, 0x3c783b79, 0xbc803a49,
    0x3c71bbac, 0xbc4e3c18, 0x3b163c7d, 0xbbdbbc67, 0x3c2c3c3e, 0xbc5cbc04, 0xbc04bc5c, 0x3c3e3c2c, 0xbc67bbdb, 0x3c7d3b16,
    0x3c18bc4e, 0xbbac3c71, 0x3a49bc80, 0x3b793c78, 0xbc043c5c, 0x3a49bc80, 0x3bdb3c67, 0xbc4ebc18, 0x3c7d3b16, 0xbc713bac,
    0x3c2cbc3e, 0xbb793c78, 0x3c78bb79, 0xbc3e3c2c, 0x3bacbc71, 0x3b163c7d, 0xbc18bc4e, 0x3c673bdb, 0xbc803a49, 0x3c5cbc04,
    0x3c5c3c04, 0xbc80ba49, 0x3c67bbdb, 0xbc183c4e, 0x3b16bc7d, 0x3bac3c71, 0xbc3ebc2c, 0x3c783b79, 0xbb79bc78, 0x3c2c3c3e,
    0xbc71bbac, 0x3c7dbb16, 0xbc4e3c18, 0x3bdbbc67, 0x3a493c80, 0xbc04bc5c, 0xbc2cbc3e, 0x3c7d3b16, 0xbc5c3c04, 0x3bacbc71,
    0x3c673bdb, 0xbc783b79, 0x3c18bc4e, 0x3a493c80, 0xbc80ba49, 0x3c4ebc18, 0xbb793c78, 0xbbdbbc67, 0x3c71bbac, 0xbc043c5c,
    0xbb16bc7d, 0x3c3e3c2c, 0x3c3ebc2c, 0xbb163c7d, 0xbc04bc5c, 0x3c713bac, 0xbbdb3c67, 0xbb79bc78, 0x3c4e3c18, 0xbc803a49,
    0x3a49bc80, 0x3c183c4e, 0xbc78bb79, 0x3c67bbdb, 0x3bac3c71, 0xbc5cbc04, 0x3c7dbb16, 0xbc2c3c3e, 0xbbdbbc67, 0x3c783b79,
    0xbc4e3c18, 0x3a49bc80, 0x3c3e3c2c, 0xbc7d3b16, 0x3c04bc5c, 0x3bac3c71, 0xbc71bbac, 0x3c5cbc04, 0xbb163c7d, 0xbc2cbc3e,
    0x3c80ba49, 0xbc183c4e, 0xbb79bc78, 0x3c673bdb, 0x3c67bbdb, 0xbb793c78, 0xbc18bc4e, 0x3c803a49, 0xbc2c3c3e, 0xbb16bc7d,
    0x3c5c3c04, 0xbc713bac, 0x3bacbc71, 0x3c043c5c, 0xbc7dbb16, 0x3c3ebc2c, 0x3a493c80, 0xbc4ebc18, 0x3c78bb79, 0xbbdb3c67,
    0xbc7d3b16, 0x3bacbc71, 0x3c2c3c3e, 0xbc783b79, 0x3c043c5c, 0xbc803a49, 0x3bdbbc67, 0x3c183c4e, 0x3c4e3c18, 0xbc673bdb,
    0x3a49bc80, 0x3c5c3c04, 0x3b79bc78, 0x3c3e3c2c, 0xbc713bac, 0x3b16bc7d, 0x3b163c7d, 0xbc71bbac, 0x3c3ebc2c, 0x3b793c78,
    0x3c5cbc04, 0x3a493c80, 0xbc67bbdb, 0x3c4ebc18, 0x3c18bc4e, 0x3bdb3c67, 0xbc80ba49, 0x3c04bc5c, 0xbc78bb79, 0x3c2cbc3e,
    0x3bac3c71, 0xbc7dbb16, 0x3c7d3b16, 0xbbdb3c67, 0xbc3ebc2c, 0x3c5cbc04, 0x3b793c78, 0xbc80ba49, 0x3bacbc71, 0x3c4e3c18,
    0xbc18bc4e, 0x3c71bbac, 0x3a493c80, 0xbc78bb79, 0x3c04bc5c, 0x3c2c3c3e, 0xbc673bdb, 0xbb16bc7d, 0xbb163c7d, 0xbc67bbdb,
    0x3c2cbc3e, 0x3c043c5c, 0xbc783b79, 0x3a49bc80, 0x3c713bac, 0xbc183c4e, 0x3c4ebc18, 0x3bac3c71, 0xbc803a49, 0x3b79bc78,
    0x3c5c3c04, 0xbc3e3c2c, 0xbbdbbc67, 0x3c7dbb16, 0xbbdb3c67, 0xbc5cbc04, 0x3c18bc4e, 0x3c3e3c2c, 0xba493c80, 0xbc7dbb16,
    0x3b79bc78, 0x3c713bac, 0x3bac3c71, 0xbc783b79, 0xbb16bc7d, 0x3c80ba49, 0x3c2c3c3e, 0xbc4e3c18, 0xbc04bc5c, 0x3c67bbdb,
    0x3c673bdb, 0xbc043c5c, 0xbc4ebc18, 0x3c2cbc3e, 0x3c803a49, 0xbb163c7d, 0xbc78bb79, 0x3bacbc71, 0x3c71bbac, 0x3b793c78,
    0xbc7d3b16, 0xba49bc80, 0x3c3ebc2c, 0x3c183c4e, 0xbc5c3c04, 0xbbdbbc67, 0x3f803f80, 0x3f7d3f7f, 0x3f783f7b, 0x3f713f75,
    0x3f673f6d, 0x3f5c3f62, 0x3f4e3f55, 0x3f3e3f46, 0x3f2c3f35, 0x3f183f22, 0x3f043f0e, 0x3edb3ef1, 0x3eac3ec4, 0x3e793e95,
    0x3e163e48, 0x3d493dc9, 0xbd490000, 0xbe16bdc9, 0xbe79be48, 0xbeacbe95, 0xbedbbec4, 0xbf04bef1, 0xbf18bf0e, 0xbf2cbf22,
    0xbf3ebf35, 0xbf4ebf46, 0xbf5cbf55, 0xbf67bf62, 0xbf71bf6d, 0xbf78bf75, 0xbf7dbf7b, 0xbf80bf7f, 0x3edb3ec4, 0x3f043ef1,
    0x3f183f0e, 0x3f2c3f22, 0x3d490000, 0x3e163dc9, 0x3e793e48, 0x3eac3e95, 0x3f713f6d, 0x3f783f75, 0x3f7d3f7b, 0x3f803f7f,
    0x3f3e3f35, 0x3f4e3f46, 0x3f5c3f55, 0x3f673f62, 0x3f673f6d, 0x3f5c3f62, 0x3f4e3f55, 0x3f3e3f46, 0x3f803f80, 0x3f7d3f7f,
    0x3f783f7b, 0x3f713f75, 0x3eac3ec4, 0x3e793e95, 0x3e163e48, 0x3d493dc9, 0x3f2c3f35, 0x3f183f22, 0x3f043f0e, 0x3edb3ef1,
    0xbf4ebf35, 0xbf71bf62, 0xbf80bf7b, 0xbf78bf7f, 0xbf5cbf6d, 0xbf2cbf46, 0xbedbbf0e, 0xbe16be95, 0x3f7d3f80, 0x3f673f75,
    0x3f3e3f55, 0x3f043f22, 0x3e793ec4, 0xbd493dc9, 0xbeacbe48, 0xbf18bef1, 0x3f183f35, 0x3eac3ef1, 0x3d493e48, 0xbe79bdc9,
    0xbf04bec4, 0xbf3ebf22, 0xbf67bf55, 0xbf7dbf75, 0x3e160000, 0x3edb3e95, 0x3f2c3f0e, 0x3f5c3f46, 0x3f783f6d, 0x3f803f7f,
    0x3f713f7b, 0x3f4e3f62, 0xbf04bec4, 0xbf3ebf22, 0xbf67bf55, 0xbf7dbf75, 0x3f183f35, 0x3eac3ef1, 0x3d493e48, 0xbe79bdc9,
    0x3f783f6d, 0x3f803f7f, 0x3f713f7b, 0x3f4e3f62, 0x3e160000, 0x3edb3e95, 0x3f2c3f0e, 0x3f5c3f46, 0x3f5c3f6d, 0x3f2c3f46,
    0x3edb3f0e, 0x3e163e95, 0x3f4e3f35, 0x3f713f62, 0x3f803f7b, 0x3f783f7f, 0xbe79bec4, 0x3d49bdc9, 0x3eac3e48, 0x3f183ef1,
    0xbf7dbf80, 0xbf67bf75, 0xbf3ebf55, 0xbf04bf22, 0xbe790000, 0xbf2cbef1, 0xbf71bf55, 0xbf7dbf7f, 0xbf4ebf6d, 0xbedbbf22,
    0x3d49be48, 0x3f043e95, 0x3f5c3f35, 0x3f803f75, 0x3f673f7b, 0x3f183f46, 0x3e163ec4, 0xbeacbdc9, 0xbf3ebf0e, 0xbf78bf62,
    0x3f783f80, 0x3f3e3f62, 0x3eac3f0e, 0xbe163dc9, 0xbf18bec4, 0xbf67bf46, 0xbf80bf7b, 0xbf5cbf75, 0xbf04bf35, 0xbd49be95,
    0x3edb3e48, 0x3f4e3f22, 0x3f7d3f6d, 0x3f713f7f, 0x3f2c3f55, 0x3e793ef1, 0xbf18bec4, 0xbf67bf46, 0xbf80bf7b, 0xbf5cbf75,
    0x3f783f80, 0x3f3e3f62, 0x3eac3f0e, 0xbe163dc9, 0x3f7d3f6d, 0x3f713f7f, 0x3f2c3f55, 0x3e793ef1, 0xbf04bf35, 0xbd49be95,
    0x3edb3e48, 0x3f4e3f22, 0x3f4e3f6d, 0x3edb3f22, 0xbd493e48, 0xbf04be95, 0x3e790000, 0x3f2c3ef1, 0x3f713f55, 0x3f7d3f7f,
    0xbe16bec4, 0x3eac3dc9, 0x3f3e3f0e, 0x3f783f62, 0xbf5cbf35, 0xbf80bf75, 0xbf67bf7b, 0xbf18bf46, 0xbedbbf35, 0x3e79bdc9,
    0x3f4e3f0e, 0x3f803f75, 0x3f3e3f6d, 0x3e163ef1, 0xbf04be48, 0xbf71bf46, 0x3eac0000, 0x3f5c3f22, 0x3f7d3f7b, 0x3f2c3f62,
    0x3d493ec4, 0xbf18be95, 0xbf78bf55, 0xbf67bf7f, 0x3f673f35, 0x3f783f7f, 0x3f183f55, 0xbd493e95, 0xbf2cbec4, 0xbf7dbf62,
    0xbf5cbf7b, 0xbeacbf22, 0x3f713f80, 0x3f043f46, 0xbe163e48, 0xbf3ebef1, 0xbf80bf6d, 0xbf4ebf75, 0xbe79bf0e, 0x3edb3dc9,
    0x3f2c3ec4, 0x3f7d3f62, 0x3f5c3f7b, 0x3eac3f22, 0xbf67bf35, 0xbf78bf7f, 0xbf18bf55, 0x3d49be95, 0x3f803f6d, 0x3f4e3f75,
    0x3e793f0e, 0xbedbbdc9, 0xbf71bf80, 0xbf04bf46, 0x3e16be48, 0x3f3e3ef1, 0x3f3e3f6d, 0x3e163ef1, 0xbf04be48, 0xbf71bf46,
    0xbedbbf35, 0x3e79bdc9, 0x3f4e3f0e, 0x3f803f75, 0x3d493ec4, 0xbf18be95, 0xbf78bf55, 0xbf67bf7f, 0x3eac0000, 0x3f5c3f22,
    0x3f7d3f7b, 0x3f2c3f62, 0x3f673f80, 0x3e793f22, 0xbf18be48, 0xbf80bf62, 0xbf2cbf6d, 0x3e16be95, 0x3f5c3f0e, 0x3f713f7f,
    0x3eac3f35, 0xbf04bdc9, 0xbf7dbf55, 0xbf3ebf75, 0x3d49bec4, 0x3f4e3ef1, 0x3f783f7b, 0x3edb3f46, 0xbedb0000, 0xbf78bf46,
    0xbf4ebf7b, 0xbd49bef1, 0x3f3e3ec4, 0x3f7d3f75, 0x3f043f55, 0xbeac3dc9, 0xbf71bf35, 0xbf5cbf7f, 0xbe16bf0e, 0x3f2c3e95,
    0x3f803f6d, 0x3f183f62, 0xbe793e48, 0xbf67bf22, 0xbf3ebec4, 0xbf7dbf75, 0xbf04bf55, 0x3eacbdc9, 0x3edb0000, 0x3f783f46,
    0x3f4e3f7b, 0x3d493ef1, 0xbf80bf6d, 0xbf18bf62, 0x3e79be48, 0x3f673f22, 0x3f713f35, 0x3f5c3f7f, 0x3e163f0e, 0xbf2cbe95,
    0xbf2cbf6d, 0x3e16be95, 0x3f5c3f0e, 0x3f713f7f, 0x3f673f80, 0x3e793f22, 0xbf18be48, 0xbf80bf62, 0x3d49bec4, 0x3f4e3ef1,
    0x3f783f7b, 0x3edb3f46, 0x3eac3f35, 0xbf04bdc9, 0xbf7dbf55, 0xbf3ebf75, 0xbf78bf35, 0xbf2cbf75, 0x3eacbe48, 0x3f7d3f46,
    0x3f183f6d, 0xbedb3dc9, 0xbf80bf55, 0xbf04bf62, 0x3f5c3f80, 0xbd493ef1, 0xbf67bf0e, 0xbf4ebf7f, 0x3e16bec4, 0x3f713f22,
    0x3f3e3f7b, 0xbe793e95, 0x3e793f35, 0xbf3ebe95, 0xbf71bf7b, 0xbe16bf22, 0x3f4e3ec4, 0x3f673f7f, 0x3d493f0e, 0xbf5cbef1,
    0x3f040000, 0x3f803f62, 0x3edb3f55, 0xbf18bdc9, 0xbf7dbf6d, 0xbeacbf46, 0x3f2c3e48, 0x3f783f75, 0x3f4e3ec4, 0x3f673f7f,
    0x3d493f0e, 0xbf5cbef1, 0x3e793f35, 0xbf3ebe95, 0xbf71bf7b, 0xbe16bf22, 0xbf7dbf6d, 0xbeacbf46, 0x3f2c3e48, 0x3f783f75,
    0x3f040000, 0x3f803f62, 0x3edb3f55, 0xbf18bdc9, 0xbf18bf6d, 0x3edbbdc9, 0x3f803f55, 0x3f043f62, 0x3f783f35, 0x3f2c3f75,
    0xbeac3e48, 0xbf7dbf46, 0xbe163ec4, 0xbf71bf22, 0xbf3ebf7b, 0x3e79be95, 0xbf5cbf80, 0x3d49bef1, 0x3f673f0e, 0x3f4e3f7f,
    0xbf180000, 0xbf71bf75, 0x3d49bf0e, 0x3f783f22, 0x3f043f6d, 0xbf2cbdc9, 0xbf67bf7b, 0x3e16bef1, 0x3f7d3f35, 0x3edb3f62,
    0xbf3ebe48, 0xbf5cbf7f, 0x3e79bec4, 0x3f803f46, 0x3eac3f55, 0xbf4ebe95, 0x3f4e3f80, 0xbeac3e95, 0xbf80bf55, 0xbe79bf46,
    0x3f5c3ec4, 0x3f3e3f7f, 0xbedb3e48, 0xbf7dbf62, 0xbe16bf35, 0x3f673ef1, 0x3f2c3f7b, 0xbf043dc9, 0xbf78bf6d, 0xbd49bf22,
    0x3f713f0e, 0x3f183f75, 0x3f5c3ec4, 0x3f3e3f7f, 0xbedb3e48, 0xbf7dbf62, 0x3f4e3f80, 0xbeac3e95, 0xbf80bf55, 0xbe79bf46,
    0xbf78bf6d, 0xbd49bf22, 0x3f713f0e, 0x3f183f75, 0xbe16bf35, 0x3f673ef1, 0x3f2c3f7b, 0xbf043dc9, 0xbf04bf6d, 0x3f2c3dc9,
    0x3f673f7b, 0xbe163ef1, 0x3f180000, 0x3f713f75, 0xbd493f0e, 0xbf78bf22, 0xbe793ec4, 0xbf80bf46, 0xbeacbf55, 0x3f4e3e95,
    0xbf7dbf35, 0xbedbbf62, 0x3f3e3e48, 0x3f5c3f7f, 0xbd49bf35, 0x3f7d3f22, 0x3e793f55, 0xbf71bef1, 0xbedbbf6d, 0x3f5c3e95,
    0x3f183f7b, 0xbf3ebdc9, 0x3f2c0000, 0x3f4e3f7f, 0xbf043e48, 0xbf67bf75, 0x3eacbec4, 0x3f783f62, 0xbe163f0e, 0xbf80bf46,
    0x3f803f35, 0x3e163f46, 0xbf78bf0e, 0xbeacbf62, 0x3f673ec4, 0x3f043f75, 0xbf4ebe48, 0xbf2cbf7f, 0x3f3e3f80, 0xbf183dc9,
    0xbf5cbf7b, 0x3edbbe95, 0x3f713f6d, 0xbe793ef1, 0xbf7dbf55, 0x3d49bf22, 0xbf67bec4, 0xbf04bf75, 0x3f4e3e48, 0x3f2c3f7f,
    0xbf80bf35, 0xbe16bf46, 0x3f783f0e, 0x3eac3f62, 0xbf71bf6d, 0x3e79bef1, 0x3f7d3f55, 0xbd493f22, 0xbf3ebf80, 0x3f18bdc9,
    0x3f5c3f7b, 0xbedb3e95, 0xbedbbf6d, 0x3f5c3e95, 0x3f183f7b, 0xbf3ebdc9, 0xbd49bf35, 0x3f7d3f22, 0x3e793f55, 0xbf71bef1,
    0x3eacbec4, 0x3f783f62, 0xbe163f0e, 0xbf80bf46, 0x3f2c0000, 0x3f4e3f7f, 0xbf043e48, 0xbf67bf75, 0x3f2c3f80, 0xbf4ebdc9,
    0xbf04bf7b, 0x3f673e95, 0x3eac3f6d, 0xbf78bef1, 0xbe16bf55, 0x3f803f22, 0xbd493f35, 0xbf7dbf46, 0x3e79bf0e, 0x3f713f62,
    0xbedb3ec4, 0xbf5cbf75, 0x3f18be48, 0x3f3e3f7f, 0xbf3e0000, 0xbf18bf7f, 0x3f5c3e48, 0x3edb3f75, 0xbf71bec4, 0xbe79bf62,
    0x3f7d3f0e, 0x3d493f46, 0xbf80bf35, 0x3e16bf22, 0x3f783f55, 0xbeac3ef1, 0xbf67bf6d, 0x3f04be95, 0x3f4e3f7b, 0xbf2c3dc9,
    0x3f713ec4, 0x3e793f62, 0xbf7dbf0e, 0xbd49bf46, 0x3f3e0000, 0x3f183f7f, 0xbf5cbe48, 0xbedbbf75, 0x3f673f6d, 0xbf043e95,
    0xbf4ebf7b, 0x3f2cbdc9, 0x3f803f35, 0xbe163f22, 0xbf78bf55, 0x3eacbef1, 0x3eac3f6d, 0xbf78bef1, 0xbe16bf55, 0x3f803f22,
    0x3f2c3f80, 0xbf4ebdc9, 0xbf04bf7b, 0x3f673e95, 0xbedb3ec4, 0xbf5cbf75, 0x3f18be48, 0x3f3e3f7f, 0xbd493f35, 0xbf7dbf46,
    0x3e79bf0e, 0x3f713f62, 0xbf7dbf35, 0x3edbbef1, 0x3f3e3f7b, 0xbf5cbdc9, 0xbe79bf6d, 0x3f803f22, 0xbeac3f0e, 0xbf4ebf75,
    0x3f183f80, 0xbf71be95, 0xbd49bf55, 0x3f783f46, 0xbf043ec4, 0xbf2cbf7f, 0x3f673e48, 0x3e163f62, 0xbe163f35, 0xbf67bf62,
    0x3f2cbe48, 0x3f043f7f, 0xbf78bec4, 0x3d49bf46, 0x3f713f55, 0xbf183e95, 0x3f4e0000, 0x3eac3f75, 0xbf80bf0e, 0x3e79bf22,
    0x3f5c3f6d, 0xbf3e3dc9, 0xbedbbf7b, 0x3f7d3ef1, 0xbf78bec4, 0x3d49bf46, 0x3f713f55, 0xbf183e95, 0xbe163f35, 0xbf67bf62,
    0x3f2cbe48, 0x3f043f7f, 0x3f5c3f6d, 0xbf3e3dc9, 0xbedbbf7b, 0x3f7d3ef1, 0x3f4e0000, 0x3eac3f75, 0xbf80bf0e, 0x3e79bf22,
    0x3e793f6d, 0xbf80bf22, 0x3eacbf0e, 0x3f4e3f75, 0x3f7d3f35, 0xbedb3ef1, 0xbf3ebf7b, 0x3f5c3dc9, 0x3f04bec4, 0x3f2c3f7f,
    0xbf67be48, 0xbe16bf62, 0xbf18bf80, 0x3f713e95, 0x3d493f55, 0xbf78bf46, 0xbf5c0000, 0xbd49bf62, 0x3f673f55, 0xbf4e3dc9,
    0xbe16bf6d, 0x3f713f46, 0xbf3e3e48, 0xbe79bf75, 0x3f783f35, 0xbf2c3e95, 0xbeacbf7b, 0x3f7d3f22, 0xbf183ec4, 0xbedbbf7f,
    0x3f803f0e, 0xbf043ef1, 0x3f043f80, 0xbf80bef1, 0x3edbbf0e, 0x3f183f7f, 0xbf7dbec4, 0x3eacbf22, 0x3f2c3f7b, 0xbf78be95,
    0x3e79bf35, 0x3f3e3f75, 0xbf71be48, 0x3e16bf46, 0x3f4e3f6d, 0xbf67bdc9, 0x3d49bf55, 0x3f5c3f62, 0xbf7dbec4, 0x3eacbf22,
    0x3f2c3f7b, 0xbf78be95, 0x3f043f80, 0xbf80bef1, 0x3edbbf0e, 0x3f183f7f, 0x3f4e3f6d, 0xbf67bdc9, 0x3d49bf55, 0x3f5c3f62,
    0x3e79bf35, 0x3f3e3f75, 0xbf71be48, 0x3e16bf46, 0x3e163f6d, 0xbf71bf46, 0x3f3ebe48, 0x3e793f75, 0x3f5c0000, 0x3d493f62,
    0xbf67bf55, 0x3f4ebdc9, 0x3f18bec4, 0x3edb3f7f, 0xbf80bf0e, 0x3f04bef1, 0xbf78bf35, 0x3f2cbe95, 0x3eac3f7b, 0xbf7dbf22,
    0x3eacbf35, 0x3f043f7f, 0xbf7dbf0e, 0x3f3ebe95, 0x3d493f6d, 0xbf4ebf62, 0x3f783e48, 0xbedb3f22, 0x3f670000, 0xbe793f46,
    0xbf18bf7b, 0x3f803ef1, 0xbf2c3ec4, 0xbe16bf75, 0x3f5c3f55, 0xbf71bdc9, 0x3f713f35, 0xbf5c3dc9, 0x3e16bf55, 0x3f2c3f75,
    0xbf80bec4, 0x3f18bef1, 0x3e793f7b, 0xbf67bf46, 0x3edb3f80, 0xbf78bf22, 0x3f4ebe48, 0xbd493f62, 0xbf3ebf6d, 0x3f7d3e95,
    0xbf043f0e, 0xbeacbf7f, 0x3f803ec4, 0xbf183ef1, 0xbe79bf7b, 0x3f673f46, 0xbf71bf35, 0x3f5cbdc9, 0xbe163f55, 0xbf2cbf75,
    0x3f3e3f6d, 0xbf7dbe95, 0x3f04bf0e, 0x3eac3f7f, 0xbedbbf80, 0x3f783f22, 0xbf4e3e48, 0x3d49bf62, 0x3d493f6d, 0xbf4ebf62,
    0x3f783e48, 0xbedb3f22, 0x3eacbf35, 0x3f043f7f, 0xbf7dbf0e, 0x3f3ebe95, 0xbf2c3ec4, 0xbe16bf75, 0x3f5c3f55, 0xbf71bdc9,
    0x3f670000, 0xbe793f46, 0xbf18bf7b, 0x3f803ef1, 0x3eac3f80, 0xbf5cbf46, 0x3f7d3e48, 0xbf2c3ef1, 0x3d49bf6d, 0x3f183f75,
    0xbf78bf0e, 0x3f67bdc9, 0xbedb3f35, 0xbe79bf7f, 0x3f4e3f55, 0xbf80be95, 0x3f3ebec4, 0xbe163f62, 0xbf04bf7b, 0x3f713f22,
    0xbf710000, 0x3f04bf22, 0x3e163f7b, 0xbf3ebf62, 0x3f803ec4, 0xbf4e3e95, 0x3e79bf55, 0x3edb3f7f, 0xbf67bf35, 0x3f783dc9,
    0xbf183f0e, 0xbd49bf75, 0x3f2c3f6d, 0xbf7dbef1, 0x3f5cbe48, 0xbeac3f46, 0xbf80bec4, 0x3f4ebe95, 0xbe793f55, 0xbedbbf7f,
    0x3f710000, 0xbf043f22, 0xbe16bf7b, 0x3f3e3f62, 0xbf2cbf6d, 0x3f7d3ef1, 0xbf5c3e48, 0x3eacbf46, 0x3f673f35, 0xbf78bdc9,
    0x3f18bf0e, 0x3d493f75, 0x3d49bf6d, 0x3f183f75, 0xbf78bf0e, 0x3f67bdc9, 0x3eac3f80, 0xbf5cbf46, 0x3f7d3e48, 0xbf2c3ef1,
    0x3f3ebec4, 0xbe163f62, 0xbf04bf7b, 0x3f713f22, 0xbedb3f35, 0xbe79bf7f, 0x3f4e3f55, 0xbf80be95, 0xbf5cbf35, 0x3f803e95,
    0xbf673e48, 0x3f18bf22, 0xbe163f6d, 0xbeacbf7f, 0x3f3e3f55, 0xbf78bef1, 0x3e793f80, 0xbf2cbf62, 0x3f713f0e, 0xbf7dbdc9,
    0x3f4ebec4, 0xbedb3f46, 0xbd49bf7b, 0x3f043f75, 0xbf043f35, 0x3d49bf75, 0x3edb3f7b, 0xbf4ebf46, 0x3f7d3ec4, 0xbf713dc9,
    0x3f2cbf0e, 0xbe793f62, 0x3f780000, 0xbf3e3ef1, 0x3eacbf55, 0x3e163f7f, 0xbf18bf6d, 0x3f673f22, 0xbf80be48, 0x3f5cbe95,
    0x3f7d3ec4, 0xbf713dc9, 0x3f2cbf0e, 0xbe793f62, 0xbf043f35, 0x3d49bf75, 0x3edb3f7b, 0xbf4ebf46, 0xbf18bf6d, 0x3f673f22,
    0xbf80be48, 0x3f5cbe95, 0x3f780000, 0xbf3e3ef1, 0x3eacbf55, 0x3e163f7f, 0x3e16bf6d, 0x3eac3f7f, 0xbf3ebf55, 0x3f783ef1,
    0x3f5c3f35, 0xbf80be95, 0x3f67be48, 0xbf183f22, 0xbf4e3ec4, 0x3edbbf46, 0x3d493f7b, 0xbf04bf75, 0xbe79bf80, 0x3f2c3f62,
    0xbf71bf0e, 0x3f7d3dc9, 0xbf7d0000, 0x3f67be95, 0xbf3e3f0e, 0x3f04bf46, 0xbe793f6d, 0xbd49bf7f, 0x3eac3f7b, 0xbf18bf62,
    0x3f4e3f35, 0xbf71bef1, 0x3f803e48, 0xbf783dc9, 0x3f5cbec4, 0xbf2c3f22, 0x3edbbf55, 0xbe163f75, 0x3e163f80, 0xbedbbf75,
    0x3f2c3f55, 0xbf5cbf22, 0x3f783ec4, 0xbf80bdc9, 0x3f71be48, 0xbf4e3ef1, 0x3f18bf35, 0xbeac3f62, 0x3d49bf7b, 0x3e793f7f,
    0xbf04bf6d, 0x3f3e3f46, 0xbf67bf0e, 0x3f7d3e95, 0x3f783ec4, 0xbf80bdc9, 0x3f71be48, 0xbf4e3ef1, 0x3e163f80, 0xbedbbf75,
    0x3f2c3f55, 0xbf5cbf22, 0xbf04bf6d, 0x3f3e3f46, 0xbf67bf0e, 0x3f7d3e95, 0x3f18bf35, 0xbeac3f62, 0x3d49bf7b, 0x3e793f7f,
    0x3e79bf6d, 0x3d493f7f, 0xbeacbf7b, 0x3f183f62, 0x3f7d0000, 0xbf673e95, 0x3f3ebf0e, 0xbf043f46, 0xbf5c3ec4, 0x3f2cbf22,
    0xbedb3f55, 0x3e16bf75, 0xbf4ebf35, 0x3f713ef1, 0xbf80be48, 0x3f78bdc9, 0x3f2cbf35, 0xbf183f46, 0x3f04bf55, 0xbedb3f62,
    0x3eacbf6d, 0xbe793f75, 0x3e16bf7b, 0xbd493f7f, 0x3f800000, 0xbf7d3dc9, 0x3f78be48, 0xbf713e95, 0x3f67bec4, 0xbf5c3ef1,
    0x3f4ebf0e, 0xbf3e3f22, 0x3f3e3f35, 0xbf4ebf22, 0x3f5c3f0e, 0xbf67bef1, 0x3f713ec4, 0xbf78be95, 0x3f7d3e48, 0xbf80bdc9,
    0x3d493f80, 0xbe16bf7f, 0x3e793f7b, 0xbeacbf75, 0x3edb3f6d, 0xbf04bf62, 0x3f183f55, 0xbf2cbf46, 0xbf71bec4, 0x3f783e95,
    0xbf7dbe48, 0x3f803dc9, 0xbf3ebf35, 0x3f4e3f22, 0xbf5cbf0e, 0x3f673ef1, 0xbedbbf6d, 0x3f043f62, 0xbf18bf55, 0x3f2c3f46,
    0xbd49bf80, 0x3e163f7f, 0xbe79bf7b, 0x3eac3f75, 0x3eacbf6d, 0xbe793f75, 0x3e16bf7b, 0xbd493f7f, 0x3f2cbf35, 0xbf183f46,
    0x3f04bf55, 0xbedb3f62, 0x3f67bec4, 0xbf5c3ef1, 0x3f4ebf0e, 0xbf3e3f22, 0x3f800000, 0xbf7d3dc9, 0x3f78be48, 0xbf713e95,
    0xbd493f80, 0x3e16bf7f, 0xbe793f7b, 0x3eacbf75, 0xbedb3f6d, 0x3f04bf62, 0xbf183f55, 0x3f2cbf46, 0xbf3e3f35, 0x3f4ebf22,
    0xbf5c3f0e, 0x3f67bef1, 0xbf713ec4, 0x3f78be95, 0xbf7d3e48, 0x3f80bdc9, 0xbf800000, 0x3f7d3dc9, 0xbf78be48, 0x3f713e95,
    0xbf67bec4, 0x3f5c3ef1, 0xbf4ebf0e, 0x3f3e3f22, 0xbf2cbf35, 0x3f183f46, 0xbf04bf55, 0x3edb3f62, 0xbeacbf6d, 0x3e793f75,
    0xbe16bf7b, 0x3d493f7f, 0x3f673ec4, 0xbf5cbef1, 0x3f4e3f0e, 0xbf3ebf22, 0x3f800000, 0xbf7dbdc9, 0x3f783e48, 0xbf71be95,
    0x3eac3f6d, 0xbe79bf75, 0x3e163f7b, 0xbd49bf7f, 0x3f2c3f35, 0xbf18bf46, 0x3f043f55, 0xbedbbf62, 0xbedb3f6d, 0x3f04bf62,
    0xbf183f55, 0x3f2cbf46, 0xbd493f80, 0x3e16bf7f, 0xbe793f7b, 0x3eacbf75, 0xbf713ec4, 0x3f78be95, 0xbf7d3e48, 0x3f80bdc9,
    0xbf3e3f35, 0x3f4ebf22, 0xbf5c3f0e, 0x3f67bef1, 0xbf18bf35, 0x3eac3f62, 0xbd49bf7b, 0xbe793f7f, 0x3f04bf6d, 0xbf3e3f46,
    0x3f67bf0e, 0xbf7d3e95, 0xbe163f80, 0x3edbbf75, 0xbf2c3f55, 0x3f5cbf22, 0xbf783ec4, 0x3f80bdc9, 0xbf71be48, 0x3f4e3ef1,
    0xbf4e3f35, 0x3f71bef1, 0xbf803e48, 0x3f783dc9, 0xbf5cbec4, 0x3f2c3f22, 0xbedbbf55, 0x3e163f75, 0x3f7d0000, 0xbf67be95,
    0x3f3e3f0e, 0xbf04bf46, 0x3e793f6d, 0x3d49bf7f, 0xbeac3f7b, 0x3f18bf62, 0xbf5cbec4, 0x3f2c3f22, 0xbedbbf55, 0x3e163f75,
    0xbf4e3f35, 0x3f71bef1, 0xbf803e48, 0x3f783dc9, 0x3e793f6d, 0x3d49bf7f, 0xbeac3f7b, 0x3f18bf62, 0x3f7d0000, 0xbf67be95,
    0x3f3e3f0e, 0xbf04bf46, 0xbf043f6d, 0x3f3ebf46, 0xbf673f0e, 0x3f7dbe95, 0x3f183f35, 0xbeacbf62, 0x3d493f7b, 0x3e79bf7f,
    0x3f78bec4, 0xbf803dc9, 0x3f713e48, 0xbf4ebef1, 0x3e16bf80, 0xbedb3f75, 0x3f2cbf55, 0xbf5c3f22, 0xbf780000, 0x3f3e3ef1,
    0xbeacbf55, 0xbe163f7f, 0x3f18bf6d, 0xbf673f22, 0x3f80be48, 0xbf5cbe95, 0x3f043f35, 0xbd49bf75, 0xbedb3f7b, 0x3f4ebf46,
    0xbf7d3ec4, 0x3f713dc9, 0xbf2cbf0e, 0x3e793f62, 0xbe793f80, 0x3f2cbf62, 0xbf713f0e, 0x3f7dbdc9, 0xbf4ebec4, 0x3edb3f46,
    0x3d49bf7b, 0xbf043f75, 0x3f5cbf35, 0xbf803e95, 0x3f673e48, 0xbf18bf22, 0x3e163f6d, 0x3eacbf7f, 0xbf3e3f55, 0x3f78bef1,
    0xbf4ebec4, 0x3edb3f46, 0x3d49bf7b, 0xbf043f75, 0xbe793f80, 0x3f2cbf62, 0xbf713f0e, 0x3f7dbdc9, 0x3e163f6d, 0x3eacbf7f,
    0xbf3e3f55, 0x3f78bef1, 0x3f5cbf35, 0xbf803e95, 0x3f673e48, 0xbf18bf22, 0xbf183f6d, 0x3f67bf22, 0xbf803e48, 0x3f5c3e95,
    0x3f780000, 0xbf3ebef1, 0x3eac3f55, 0x3e16bf7f, 0x3f7dbec4, 0xbf71bdc9, 0x3f2c3f0e, 0xbe79bf62, 0xbf04bf35, 0x3d493f75,
    0x3edbbf7b, 0xbf4e3f46, 0x3f67bf35, 0xbf783dc9, 0x3f183f0e, 0x3d49bf75, 0xbf2c3f6d, 0x3f7dbef1, 0xbf5cbe48, 0x3eac3f46,
    0x3f710000, 0xbf04bf22, 0xbe163f7b, 0x3f3ebf62, 0xbf803ec4, 0x3f4e3e95, 0xbe79bf55, 0xbedb3f7f, 0x3edb3f35, 0x3e79bf7f,
    0xbf4e3f55, 0x3f80be95, 0xbf3ebec4, 0x3e163f62, 0x3f04bf7b, 0xbf713f22, 0xbeac3f80, 0x3f5cbf46, 0xbf7d3e48, 0x3f2c3ef1,
    0xbd49bf6d, 0xbf183f75, 0x3f78bf0e, 0xbf67bdc9, 0x3f3e3ec4, 0xbe16bf62, 0xbf043f7b, 0x3f71bf22, 0xbedbbf35, 0xbe793f7f,
    0x3f4ebf55, 0xbf803e95, 0x3d493f6d, 0x3f18bf75, 0xbf783f0e, 0x3f673dc9, 0x3eacbf80, 0xbf5c3f46, 0x3f7dbe48, 0xbf2cbef1,
    0xbf2c3f6d, 0x3f7dbef1, 0xbf5cbe48, 0x3eac3f46, 0x3f67bf35, 0xbf783dc9, 0x3f183f0e, 0x3d49bf75, 0xbf803ec4, 0x3f4e3e95,
    0xbe79bf55, 0xbedb3f7f, 0x3f710000, 0xbf04bf22, 0xbe163f7b, 0x3f3ebf62, 0xbedb3f80, 0x3f78bf22, 0xbf4ebe48, 0x3d493f62,
    0x3f3ebf6d, 0xbf7d3e95, 0x3f043f0e, 0x3eacbf7f, 0xbf713f35, 0x3f5c3dc9, 0xbe16bf55, 0xbf2c3f75, 0x3f80bec4, 0xbf18bef1,
    0xbe793f7b, 0x3f67bf46, 0xbf670000, 0x3e793f46, 0x3f18bf7b, 0xbf803ef1, 0x3f2c3ec4, 0x3e16bf75, 0xbf5c3f55, 0x3f71bdc9,
    0xbeacbf35, 0xbf043f7f, 0x3f7dbf0e, 0xbf3ebe95, 0xbd493f6d, 0x3f4ebf62, 0xbf783e48, 0x3edb3f22, 0xbf2cbec4, 0xbe163f75,
    0x3f5cbf55, 0xbf713dc9, 0x3f670000, 0xbe79bf46, 0xbf183f7b, 0x3f80bef1, 0x3d49bf6d, 0xbf4e3f62, 0x3f78be48, 0xbedbbf22,
    0x3eac3f35, 0x3f04bf7f, 0xbf7d3f0e, 0x3f3e3e95, 0x3f3ebf6d, 0xbf7d3e95, 0x3f043f0e, 0x3eacbf7f, 0xbedb3f80, 0x3f78bf22,
    0xbf4ebe48, 0x3d493f62, 0x3f80bec4, 0xbf18bef1, 0xbe793f7b, 0x3f67bf46, 0xbf713f35, 0x3f5c3dc9, 0xbe16bf55, 0xbf2c3f75,
    0xbe79bf35, 0xbf3e3f75, 0x3f71be48, 0xbe16bf46, 0xbf4e3f6d, 0x3f67bdc9, 0xbd49bf55, 0xbf5c3f62, 0xbf043f80, 0x3f80bef1,
    0xbedbbf0e, 0xbf183f7f, 0x3f7dbec4, 0xbeacbf22, 0xbf2c3f7b, 0x3f78be95, 0xbf783f35, 0x3f2c3e95, 0x3eacbf7b, 0xbf7d3f22,
    0x3f183ec4, 0x3edbbf7f, 0xbf803f0e, 0x3f043ef1, 0x3f5c0000, 0x3d49bf62, 0xbf673f55, 0x3f4e3dc9, 0x3e16bf6d, 0xbf713f46,
    0x3f3e3e48, 0x3e79bf75, 0x3f183ec4, 0x3edbbf7f, 0xbf803f0e, 0x3f043ef1, 0xbf783f35, 0x3f2c3e95, 0x3eacbf7b, 0xbf7d3f22,
    0x3e16bf6d, 0xbf713f46, 0x3f3e3e48, 0x3e79bf75, 0x3f5c0000, 0x3d49bf62, 0xbf673f55, 0x3f4e3dc9, 0x3f4ebf6d, 0xbf673dc9,
    0x3d493f55, 0x3f5cbf62, 0x3e793f35, 0x3f3ebf75, 0xbf713e48, 0x3e163f46, 0xbf7d3ec4, 0x3eac3f22, 0x3f2cbf7b, 0xbf783e95,
    0x3f04bf80, 0xbf803ef1, 0x3edb3f0e, 0x3f18bf7f, 0xbf4e0000, 0xbeac3f75, 0x3f80bf0e, 0xbe79bf22, 0xbf5c3f6d, 0x3f3e3dc9,
    0x3edbbf7b, 0xbf7d3ef1, 0x3e163f35, 0x3f67bf62, 0xbf2cbe48, 0xbf043f7f, 0x3f78bec4, 0xbd49bf46, 0xbf713f55, 0x3f183e95,
    0xbf183f80, 0x3f71be95, 0x3d49bf55, 0xbf783f46, 0x3f043ec4, 0x3f2cbf7f, 0xbf673e48, 0xbe163f62, 0x3f7dbf35, 0xbedbbef1,
    0xbf3e3f7b, 0x3f5cbdc9, 0x3e79bf6d, 0xbf803f22, 0x3eac3f0e, 0x3f4ebf75, 0x3f043ec4, 0x3f2cbf7f, 0xbf673e48, 0xbe163f62,
    0xbf183f80, 0x3f71be95, 0x3d49bf55, 0xbf783f46, 0x3e79bf6d, 0xbf803f22, 0x3eac3f0e, 0x3f4ebf75, 0x3f7dbf35, 0xbedbbef1,
    0xbf3e3f7b, 0x3f5cbdc9, 0x3f5cbf6d, 0xbf3ebdc9, 0xbedb3f7b, 0x3f7dbef1, 0x3f4e0000, 0x3eacbf75, 0xbf803f0e, 0x3e793f22,
    0xbf783ec4, 0x3d493f46, 0x3f71bf55, 0xbf18be95, 0xbe16bf35, 0xbf673f62, 0x3f2c3e48, 0x3f04bf7f, 0x3f80bf35, 0xbe16bf22,
    0xbf783f55, 0x3eac3ef1, 0x3f67bf6d, 0xbf04be95, 0xbf4e3f7b, 0x3f2c3dc9, 0x3f3e0000, 0x3f18bf7f, 0xbf5c3e48, 0xbedb3f75,
    0x3f71bec4, 0x3e79bf62, 0xbf7d3f0e, 0xbd493f46, 0x3d493f35, 0x3f7dbf46, 0xbe79bf0e, 0xbf713f62, 0x3edb3ec4, 0x3f5cbf75,
    0xbf18be48, 0xbf3e3f7f, 0xbf2c3f80, 0x3f4ebdc9, 0x3f04bf7b, 0xbf673e95, 0xbeac3f6d, 0x3f78bef1, 0x3e16bf55, 0xbf803f22,
    0xbedbbec4, 0xbf5c3f75, 0x3f183e48, 0x3f3ebf7f, 0xbd49bf35, 0xbf7d3f46, 0x3e793f0e, 0x3f71bf62, 0x3eacbf6d, 0xbf783ef1,
    0xbe163f55, 0x3f80bf22, 0x3f2cbf80, 0xbf4e3dc9, 0xbf043f7b, 0x3f67be95, 0x3f67bf6d, 0xbf04be95, 0xbf4e3f7b, 0x3f2c3dc9,
    0x3f80bf35, 0xbe16bf22, 0xbf783f55, 0x3eac3ef1, 0x3f71bec4, 0x3e79bf62, 0xbf7d3f0e, 0xbd493f46, 0x3f3e0000, 0x3f18bf7f,
    0xbf5c3e48, 0xbedb3f75, 0xbf3e3f80, 0x3f183dc9, 0x3f5cbf7b, 0xbedbbe95, 0xbf713f6d, 0x3e793ef1, 0x3f7dbf55, 0xbd49bf22,
    0xbf803f35, 0xbe163f46, 0x3f78bf0e, 0x3eacbf62, 0xbf673ec4, 0xbf043f75, 0x3f4ebe48, 0x3f2cbf7f, 0xbf2c0000, 0xbf4e3f7f,
    0x3f043e48, 0x3f67bf75, 0xbeacbec4, 0xbf783f62, 0x3e163f0e, 0x3f80bf46, 0x3d49bf35, 0xbf7d3f22, 0xbe793f55, 0x3f71bef1,
    0x3edbbf6d, 0xbf5c3e95, 0xbf183f7b, 0x3f3ebdc9, 0x3eac3ec4, 0x3f78bf62, 0xbe16bf0e, 0xbf803f46, 0x3f2c0000, 0x3f4ebf7f,
    0xbf04be48, 0xbf673f75, 0xbedb3f6d, 0x3f5cbe95, 0x3f18bf7b, 0xbf3e3dc9, 0xbd493f35, 0x3f7dbf22, 0x3e79bf55, 0xbf713ef1,
    0xbf713f6d, 0x3e793ef1, 0x3f7dbf55, 0xbd49bf22, 0xbf3e3f80, 0x3f183dc9, 0x3f5cbf7b, 0xbedbbe95, 0xbf673ec4, 0xbf043f75,
    0x3f4ebe48, 0x3f2cbf7f, 0xbf803f35, 0xbe163f46, 0x3f78bf0e, 0x3eacbf62, 0x3e16bf35, 0xbf673ef1, 0xbf2c3f7b, 0x3f043dc9,
    0x3f78bf6d, 0x3d49bf22, 0xbf713f0e, 0xbf183f75, 0xbf4e3f80, 0x3eac3e95, 0x3f80bf55, 0x3e79bf46, 0xbf5c3ec4, 0xbf3e3f7f,
    0x3edb3e48, 0x3f7dbf62, 0xbf7d3f35, 0xbedb3f62, 0x3f3ebe48, 0x3f5cbf7f, 0xbe79bec4, 0xbf803f46, 0xbeac3f55, 0x3f4ebe95,
    0x3f180000, 0x3f71bf75, 0xbd49bf0e, 0xbf783f22, 0xbf043f6d, 0x3f2cbdc9, 0x3f67bf7b, 0xbe16bef1, 0xbe79bec4, 0xbf803f46,
    0xbeac3f55, 0x3f4ebe95, 0xbf7d3f35, 0xbedb3f62, 0x3f3ebe48, 0x3f5cbf7f, 0xbf043f6d, 0x3f2cbdc9, 0x3f67bf7b, 0xbe16bef1,
    0x3f180000, 0x3f71bf75, 0xbd49bf0e, 0xbf783f22, 0xbf783f6d, 0xbd493f22, 0x3f71bf0e, 0x3f18bf75, 0xbe163f35, 0x3f67bef1,
    0x3f2cbf7b, 0xbf04bdc9, 0x3f5cbec4, 0x3f3ebf7f, 0xbedbbe48, 0xbf7d3f62, 0x3f4ebf80, 0xbeacbe95, 0xbf803f55, 0xbe793f46,
    0xbf040000, 0xbf803f62, 0xbedb3f55, 0x3f18bdc9, 0x3f7dbf6d, 0x3eacbf46, 0xbf2c3e48, 0xbf783f75, 0xbe793f35, 0x3f3ebe95,
    0x3f71bf7b, 0x3e16bf22, 0xbf4e3ec4, 0xbf673f7f, 0xbd493f0e, 0x3f5cbef1, 0xbf5c3f80, 0x3d493ef1, 0x3f67bf0e, 0x3f4ebf7f,
    0xbe16bec4, 0xbf713f22, 0xbf3e3f7b, 0x3e793e95, 0x3f78bf35, 0x3f2cbf75, 0xbeacbe48, 0xbf7d3f46, 0xbf183f6d, 0x3edb3dc9,
    0x3f80bf55, 0x3f04bf62, 0xbe16bec4, 0xbf713f22, 0xbf3e3f7b, 0x3e793e95, 0xbf5c3f80, 0x3d493ef1, 0x3f67bf0e, 0x3f4ebf7f,
    0xbf183f6d, 0x3edb3dc9, 0x3f80bf55, 0x3f04bf62, 0x3f78bf35, 0x3f2cbf75, 0xbeacbe48, 0xbf7d3f46, 0xbf7d3f6d, 0xbeac3f46,
    0x3f2cbe48, 0x3f78bf75, 0x3f040000, 0x3f80bf62, 0x3edbbf55, 0xbf183dc9, 0x3f4ebec4, 0x3f67bf7f, 0x3d49bf0e, 0xbf5c3ef1,
    0x3e79bf35, 0xbf3e3e95, 0xbf713f7b, 0xbe163f22, 0x3f71bf35, 0x3f5cbf7f, 0x3e16bf0e, 0xbf2c3e95, 0xbf803f6d, 0xbf183f62,
    0x3e793e48, 0x3f67bf22, 0x3edb0000, 0x3f78bf46, 0x3f4ebf7b, 0x3d49bef1, 0xbf3e3ec4, 0xbf7d3f75, 0xbf043f55, 0x3eac3dc9,
    0xbeac3f35, 0x3f04bdc9, 0x3f7dbf55, 0x3f3ebf75, 0xbd49bec4, 0xbf4e3ef1, 0xbf783f7b, 0xbedb3f46, 0xbf673f80, 0xbe793f22,
    0x3f18be48, 0x3f80bf62, 0x3f2cbf6d, 0xbe16be95, 0xbf5c3f0e, 0xbf713f7f, 0x3d493ec4, 0x3f4ebef1, 0x3f78bf7b, 0x3edbbf46,
    0x3eacbf35, 0xbf043dc9, 0xbf7d3f55, 0xbf3e3f75, 0xbf2c3f6d, 0x3e163e95, 0x3f5cbf0e, 0x3f71bf7f, 0x3f67bf80, 0x3e79bf22,
    0xbf183e48, 0xbf803f62, 0xbf803f6d, 0xbf183f62, 0x3e793e48, 0x3f67bf22, 0x3f71bf35, 0x3f5cbf7f, 0x3e16bf0e, 0xbf2c3e95,
    0xbf3e3ec4, 0xbf7d3f75, 0xbf043f55, 0x3eac3dc9, 0x3edb0000, 0x3f78bf46, 0x3f4ebf7b, 0x3d49bef1, 0xbf713f80, 0xbf043f46,
    0x3e163e48, 0x3f3ebef1, 0x3f80bf6d, 0x3f4ebf75, 0x3e79bf0e, 0xbedb3dc9, 0xbf673f35, 0xbf783f7f, 0xbf183f55, 0x3d493e95,
    0x3f2cbec4, 0x3f7dbf62, 0x3f5cbf7b, 0x3eacbf22, 0xbeac0000, 0xbf5c3f22, 0xbf7d3f7b, 0xbf2c3f62, 0xbd493ec4, 0x3f18be95,
    0x3f78bf55, 0x3f67bf7f, 0x3edbbf35, 0xbe79bdc9, 0xbf4e3f0e, 0xbf803f75, 0xbf3e3f6d, 0xbe163ef1, 0x3f04be48, 0x3f71bf46,
    0x3d49bec4, 0xbf183e95, 0xbf783f55, 0xbf673f7f, 0x3eac0000, 0x3f5cbf22, 0x3f7dbf7b, 0x3f2cbf62, 0x3f3ebf6d, 0x3e16bef1,
    0xbf043e48, 0xbf713f46, 0xbedb3f35, 0x3e793dc9, 0x3f4ebf0e, 0x3f80bf75, 0x3f80bf6d, 0x3f4ebf75, 0x3e79bf0e, 0xbedb3dc9,
    0xbf713f80, 0xbf043f46, 0x3e163e48, 0x3f3ebef1, 0x3f2cbec4, 0x3f7dbf62, 0x3f5cbf7b, 0x3eacbf22, 0xbf673f35, 0xbf783f7f,
    0xbf183f55, 0x3d493e95, 0x3f04bf35, 0x3d49be95, 0xbedb3e48, 0xbf4e3f22, 0xbf7d3f6d, 0xbf713f7f, 0xbf2c3f55, 0xbe793ef1,
    0xbf783f80, 0xbf3e3f62, 0xbeac3f0e, 0x3e163dc9, 0x3f18bec4, 0x3f67bf46, 0x3f80bf7b, 0x3f5cbf75, 0xbf5c3f35, 0xbf803f75,
    0xbf673f7b, 0xbf183f46, 0xbe163ec4, 0x3eacbdc9, 0x3f3ebf0e, 0x3f78bf62, 0x3e790000, 0x3f2cbef1, 0x3f71bf55, 0x3f7dbf7f,
    0x3f4ebf6d, 0x3edbbf22, 0xbd49be48, 0xbf043e95, 0xbe163ec4, 0x3eacbdc9, 0x3f3ebf0e, 0x3f78bf62, 0xbf5c3f35, 0xbf803f75,
    0xbf673f7b, 0xbf183f46, 0x3f4ebf6d, 0x3edbbf22, 0xbd49be48, 0xbf043e95, 0x3e790000, 0x3f2cbef1, 0x3f71bf55, 0x3f7dbf7f,
    0x3f7dbf6d, 0x3f71bf7f, 0x3f2cbf55, 0x3e79bef1, 0xbf043f35, 0xbd493e95, 0x3edbbe48, 0x3f4ebf22, 0xbf183ec4, 0xbf673f46,
    0xbf803f7b, 0xbf5c3f75, 0x3f78bf80, 0x3f3ebf62, 0x3eacbf0e, 0xbe16bdc9, 0xbe160000, 0xbedb3e95, 0xbf2c3f0e, 0xbf5c3f46,
    0xbf783f6d, 0xbf803f7f, 0xbf713f7b, 0xbf4e3f62, 0xbf183f35, 0xbeac3ef1, 0xbd493e48, 0x3e79bdc9, 0x3f04bec4, 0x3f3ebf22,
    0x3f67bf55, 0x3f7dbf75, 0xbf7d3f80, 0xbf673f75, 0xbf3e3f55, 0xbf043f22, 0xbe793ec4, 0x3d493dc9, 0x3eacbe48, 0x3f18bef1,
    0x3f4ebf35, 0x3f71bf62, 0x3f80bf7b, 0x3f78bf7f, 0x3f5cbf6d, 0x3f2cbf46, 0x3edbbf0e, 0x3e16be95, 0xbe793ec4, 0x3d493dc9,
    0x3eacbe48, 0x3f18bef1, 0xbf7d3f80, 0xbf673f75, 0xbf3e3f55, 0xbf043f22, 0x3f5cbf6d, 0x3f2cbf46, 0x3edbbf0e, 0x3e16be95,
    0x3f4ebf35, 0x3f71bf62, 0x3f80bf7b, 0x3f78bf7f, 0x3f78bf6d, 0x3f80bf7f, 0x3f71bf7b, 0x3f4ebf62, 0x3e160000, 0x3edbbe95,
    0x3f2cbf0e, 0x3f5cbf46, 0xbf043ec4, 0xbf3e3f22, 0xbf673f55, 0xbf7d3f75, 0x3f18bf35, 0x3eacbef1, 0x3d49be48, 0xbe793dc9,
    0x3f3ebf35, 0x3f4ebf46, 0x3f5cbf55, 0x3f67bf62, 0x3f71bf6d, 0x3f78bf75, 0x3f7dbf7b, 0x3f80bf7f, 0x3d490000, 0x3e16bdc9,
    0x3e79be48, 0x3eacbe95, 0x3edbbec4, 0x3f04bef1, 0x3f18bf0e, 0x3f2cbf22, 0xbf2c3f35, 0xbf183f22, 0xbf043f0e, 0xbedb3ef1,
    0xbeac3ec4, 0xbe793e95, 0xbe163e48, 0xbd493dc9, 0xbf803f80, 0xbf7d3f7f, 0xbf783f7b, 0xbf713f75, 0xbf673f6d, 0xbf5c3f62,
    0xbf4e3f55, 0xbf3e3f46, 0x3eacbec4, 0x3e79be95, 0x3e16be48, 0x3d49bdc9, 0x3f2cbf35, 0x3f18bf22, 0x3f04bf0e, 0x3edbbef1,
    0x3f67bf6d, 0x3f5cbf62, 0x3f4ebf55, 0x3f3ebf46, 0x3f80bf80, 0x3f7dbf7f, 0x3f78bf7b, 0x3f71bf75, 0x3f71bf6d, 0x3f78bf75,
    0x3f7dbf7b, 0x3f80bf7f, 0x3f3ebf35, 0x3f4ebf46, 0x3f5cbf55, 0x3f67bf62, 0x3edbbec4, 0x3f04bef1, 0x3f18bf0e, 0x3f2cbf22,
    0x3d490000, 0x3e16bdc9, 0x3e79be48, 0x3eacbe95,
};
__device__ const __align__(128) uint32_t c_ga[1536] = {
    0x00003c80, 0x3bc43c6d, 0x00003c80, 0xbbc4bc6d, 0x00003c80, 0x3c6d3bc4, 0x00003c80, 0xbc6dbbc4, 0x00003c80, 0x3c6dbbc4,
    0x00003c80, 0xbc6d3bc4, 0x00003c80, 0x3bc4bc6d, 0x00003c80, 0xbbc43c6d, 0x3a493c80, 0x3bdb3c67, 0x3bdb3c67, 0xbc3ebc2c,
    0x3b163c7d, 0x3c783b79, 0x3c043c5c, 0xbc7d3b16, 0x3b793c78, 0x3c4ebc18, 0x3c183c4e, 0xbc043c5c, 0x3bac3c71, 0x3a49bc80,
    0x3c2c3c3e, 0x3bac3c71, 0x3ac93c7f, 0x3bf13c62, 0x3c463c22, 0xbc75bb95, 0x3b953c75, 0x3c7f3ac9, 0x3c623bf1, 0xbc463c22,
    0x3bf13c62, 0x3c22bc46, 0x3c753b95, 0x3ac93c7f, 0x3c223c46, 0xbb95bc75, 0x3c7f3ac9, 0x3c623bf1, 0x3b163c7d, 0x3c043c5c,
    0x3c783b79, 0xbc7d3b16, 0x3bdb3c67, 0x3c80ba49, 0x3c80ba49, 0xbbac3c71, 0x3c2c3c3e, 0x3bdbbc67, 0x3c71bbac, 0x3c2c3c3e,
    0x3c5c3c04, 0xbc18bc4e, 0x3c4ebc18, 0x3c78bb79, 0x3b483c7b, 0x3c0e3c55, 0x3c7bbb48, 0xbc553c0e, 0x3c0e3c55, 0x3c7bbb48,
    0x3c55bc0e, 0x3b483c7b, 0x3c553c0e, 0x3b48bc7b, 0x3c0ebc55, 0x3c7b3b48, 0x3c7b3b48, 0xbc55bc0e, 0x3b48bc7b, 0x3c0ebc55,
    0x3b793c78, 0x3c183c4e, 0x3c4ebc18, 0xbc043c5c, 0x3c2c3c3e, 0x3c71bbac, 0x3bdbbc67, 0x3c2c3c3e, 0x3c713bac, 0xba49bc80,
    0xba49bc80, 0x3c67bbdb, 0x3c7dbb16, 0xbc78bb79, 0xbc04bc5c, 0xbb16bc7d, 0x3b953c75, 0x3c223c46, 0x3bf1bc62, 0xbac93c7f,
    0x3c463c22, 0x3c62bbf1, 0xbac9bc7f, 0x3c753b95, 0x3c7f3ac9, 0xbb95bc75, 0xbc22bc46, 0x3bf1bc62, 0x3c62bbf1, 0xbc7f3ac9,
    0xbc75bb95, 0xbc46bc22, 0x3bac3c71, 0x3c2c3c3e, 0x3a49bc80, 0x3bac3c71, 0x3c5c3c04, 0x3c4ebc18, 0xbc18bc4e, 0x3c78bb79,
    0x3c7dbb16, 0xbc04bc5c, 0xbc78bb79, 0xbb16bc7d, 0x3c2cbc3e, 0xbc673bdb, 0xbc673bdb, 0xbc803a49, 0x00003c80, 0x3bc43c6d,
    0x00003c80, 0xbbc4bc6d, 0x00003c80, 0x3c6d3bc4, 0x00003c80, 0xbc6dbbc4, 0x00003c80, 0x3c6dbbc4, 0x00003c80, 0xbc6d3bc4,
    0x00003c80, 0x3bc4bc6d, 0x00003c80, 0xbbc43c6d, 0x3c3e3c2c, 0x3c713bac, 0x3c713bac, 0xbc803a49, 0x3c4e3c18, 0x3c5cbc04,
    0x3c783b79, 0xbc183c4e, 0x3c5c3c04, 0x3b16bc7d, 0x3c7d3b16, 0x3b793c78, 0x3c673bdb, 0xbc2cbc3e, 0x3c803a49, 0x3c673bdb,
    0x3c7fbac9, 0x3c62bbf1, 0x3c22bc46, 0xbb953c75, 0x3c75bb95, 0x3ac9bc7f, 0x3bf1bc62, 0x3c223c46, 0x3c62bbf1, 0xbc46bc22,
    0x3b95bc75, 0x3c7fbac9, 0x3c46bc22, 0xbc753b95, 0x3ac9bc7f, 0x3bf1bc62, 0x3c18bc4e, 0x3b79bc78, 0xbc04bc5c, 0x3c4e3c18,
    0x3bacbc71, 0xbc3ebc2c, 0xbc3ebc2c, 0x3c67bbdb, 0x3a49bc80, 0xbc713bac, 0xbc67bbdb, 0x3a49bc80, 0xbb79bc78, 0xbb163c7d,
    0xbc7dbb16, 0xbc5cbc04, 0xbb48bc7b, 0xbc0ebc55, 0xbc7b3b48, 0x3c55bc0e, 0xbc0ebc55, 0xbc7b3b48, 0xbc553c0e, 0xbb48bc7b,
    0xbc55bc0e, 0xbb483c7b, 0xbc0e3c55, 0xbc7bbb48, 0xbc7bbb48, 0x3c553c0e, 0xbb483c7b, 0xbc0e3c55, 0xbc5cbc04, 0xbc7dbb16,
    0xbb163c7d, 0xbb79bc78, 0xbc80ba49, 0xbbdb3c67, 0x3bac3c71, 0xbc80ba49, 0xbc673bdb, 0x3c3e3c2c, 0x3c3e3c2c, 0xbbac3c71,
    0xbc183c4e, 0x3c5cbc04, 0x3c783b79, 0x3c4e3c18, 0xbc753b95, 0xbc463c22, 0x3c623bf1, 0xbc7fbac9, 0xbc223c46, 0x3bf13c62,
    0x3c7fbac9, 0xbb953c75, 0xbac93c7f, 0x3c75bb95, 0x3c46bc22, 0x3c623bf1, 0x3bf13c62, 0xbac9bc7f, 0x3b95bc75, 0x3c22bc46,
    0xbbdb3c67, 0xba493c80, 0x3c3ebc2c, 0xbbdb3c67, 0x3b793c78, 0x3c7d3b16, 0x3b16bc7d, 0x3c5c3c04, 0x3c4e3c18, 0x3b79bc78,
    0xbc04bc5c, 0x3c18bc4e, 0x3c80ba49, 0xbc71bbac, 0xbc71bbac, 0xbc3ebc2c, 0x00003c80, 0x3bc43c6d, 0x00003c80, 0xbbc4bc6d,
    0x00003c80, 0x3c6d3bc4, 0x00003c80, 0xbc6dbbc4, 0x00003c80, 0x3c6dbbc4, 0x00003c80, 0xbc6d3bc4, 0x00003c80, 0x3bc4bc6d,
    0x00003c80, 0xbbc43c6d, 0x3c80ba49, 0x3c67bbdb, 0x3c67bbdb, 0xbc2c3c3e, 0x3c7dbb16, 0x3b79bc78, 0x3c5cbc04, 0x3b163c7d,
    0x3c78bb79, 0xbc18bc4e, 0x3c4ebc18, 0x3c5c3c04, 0x3c71bbac, 0xbc80ba49, 0x3c3ebc2c, 0x3c71bbac, 0xbac9bc7f, 0xbbf1bc62,
    0xbc46bc22, 0x3c753b95, 0xbb95bc75, 0xbc7fbac9, 0xbc62bbf1, 0x3c46bc22, 0xbbf1bc62, 0xbc223c46, 0xbc75bb95, 0xbac9bc7f,
    0xbc22bc46, 0x3b953c75, 0xbc7fbac9, 0xbc62bbf1, 0xbc7d3b16, 0xbc5c3c04, 0xbb793c78, 0xbb16bc7d, 0xbc673bdb, 0x3a493c80,
    0x3a493c80, 0xbc71bbac, 0xbc3e3c2c, 0x3c673bdb, 0x3bac3c71, 0xbc3e3c2c, 0xbc043c5c, 0x3c4ebc18, 0x3c183c4e, 0x3b793c78,
    0x3b483c7b, 0x3c0e3c55, 0x3c7bbb48, 0xbc553c0e, 0x3c0e3c55, 0x3c7bbb48, 0x3c55bc0e, 0x3b483c7b, 0x3c553c0e, 0x3b48bc7b,
    0x3c0ebc55, 0x3c7b3b48, 0x3c7b3b48, 0xbc55bc0e, 0x3b48bc7b, 0x3c0ebc55, 0x3c78bb79, 0x3c4ebc18, 0xbc18bc4e, 0x3c5c3c04,
    0x3c3ebc2c, 0xbbacbc71, 0xbc67bbdb, 0x3c3ebc2c, 0x3bacbc71, 0xbc803a49, 0xbc803a49, 0xbbdbbc67, 0xbb16bc7d, 0xbb793c78,
    0xbc5c3c04, 0xbc7d3b16, 0xbb95bc75, 0xbc22bc46, 0xbbf13c62, 0x3ac9bc7f, 0xbc46bc22, 0xbc623bf1, 0x3ac93c7f, 0xbc75bb95,
    0xbc7fbac9, 0x3b953c75, 0x3c223c46, 0xbbf13c62, 0xbc623bf1, 0x3c7fbac9, 0x3c753b95, 0x3c463c22, 0xbc713bac, 0xbc3e3c2c,
    0x3c803a49, 0xbc713bac, 0xbc043c5c, 0x3c183c4e, 0x3c4ebc18, 0x3b793c78, 0x3b163c7d, 0x3c5cbc04, 0x3b79bc78, 0x3c7dbb16,
    0x3c3e3c2c, 0xbbdbbc67, 0xbbdbbc67, 0xba49bc80, 0x00003c80, 0x3bc43c6d, 0x00003c80, 0xbbc4bc6d, 0x00003c80, 0x3c6d3bc4,
    0x00003c80, 0xbc6dbbc4, 0x00003c80, 0x3c6dbbc4, 0x00003c80, 0xbc6d3bc4, 0x00003c80, 0x3bc4bc6d, 0x00003c80, 0xbbc43c6d,
    0x3c2cbc3e, 0x3bacbc71, 0x3bacbc71, 0x3a493c80, 0x3c18bc4e, 0xbc04bc5c, 0x3b79bc78, 0x3c4e3c18, 0x3c04bc5c, 0xbc7dbb16,
    0x3b16bc7d, 0x3c78bb79, 0x3bdbbc67, 0xbc3e3c2c, 0x3a49bc80, 0x3bdbbc67, 0xbc7f3ac9, 0xbc623bf1, 0xbc223c46, 0x3b95bc75,
    0xbc753b95, 0xbac93c7f, 0xbbf13c62, 0xbc22bc46, 0xbc623bf1, 0x3c463c22, 0xbb953c75, 0xbc7f3ac9, 0xbc463c22, 0x3c75bb95,
    0xbac93c7f, 0xbbf13c62, 0x3c4e3c18, 0x3c783b79, 0x3c5cbc04, 0xbc183c4e, 0x3c713bac, 0x3c2cbc3e, 0x3c2cbc3e, 0x3bdb3c67,
    0x3c803a49, 0xbbacbc71, 0x3bdbbc67, 0x3c803a49, 0x3c78bb79, 0xbc7dbb16, 0x3b16bc7d, 0x3c04bc5c, 0xbb48bc7b, 0xbc0ebc55,
    0xbc7b3b48, 0x3c55bc0e, 0xbc0ebc55, 0xbc7b3b48, 0xbc553c0e, 0xbb48bc7b, 0xbc55bc0e, 0xbb483c7b, 0xbc0e3c55, 0xbc7bbb48,
    0xbc7bbb48, 0x3c553c0e, 0xbb483c7b, 0xbc0e3c55, 0xbc043c5c, 0xbb163c7d, 0x3c7d3b16, 0xbc783b79, 0xba493c80, 0x3c673bdb,
    0x3c71bbac, 0xba493c80, 0x3bdb3c67, 0x3c2cbc3e, 0x3c2cbc3e, 0x3c713bac, 0x3c4e3c18, 0xbc04bc5c, 0x3b79bc78, 0x3c18bc4e,
    0x3c75bb95, 0x3c46bc22, 0xbc62bbf1, 0x3c7f3ac9, 0x3c22bc46, 0xbbf1bc62, 0xbc7f3ac9, 0x3b95bc75, 0x3ac9bc7f, 0xbc753b95,
    0xbc463c22, 0xbc62bbf1, 0xbbf1bc62, 0x3ac93c7f, 0xbb953c75, 0xbc223c46, 0xbc67bbdb, 0xbc80ba49, 0x3c2c3c3e, 0xbc67bbdb,
    0xbc783b79, 0xbb163c7d, 0x3c7d3b16, 0xbc043c5c, 0xbc183c4e, 0x3c783b79, 0x3c5cbc04, 0x3c4e3c18, 0x3a493c80, 0x3bacbc71,
    0x3bacbc71, 0x3c2cbc3e, 0x3c353c35, 0x3c6d3bc4, 0x3c353c35, 0xbc6dbbc4, 0x3c35bc35, 0xbbc4bc6d, 0x3c35bc35, 0x3bc43c6d,
    0xbc35bc35, 0xbbc43c6d, 0xbc35bc35, 0x3bc4bc6d, 0xbc353c35, 0x3c6dbbc4, 0xbc353c35, 0xbc6d3bc4, 0x3c3e3c2c, 0x3c713bac,
    0x3c713bac, 0xbc803a49, 0x3c18bc4e, 0xbc04bc5c, 0x3b79bc78, 0x3c4e3c18, 0xbc5cbc04, 0xbb163c7d, 0xbc7dbb16, 0xbb79bc78,
    0xbbdb3c67, 0x3c3ebc2c, 0xba493c80, 0xbbdb3c67, 0x3c463c22, 0x3c753b95, 0x3c7fbac9, 0xbc623bf1, 0x3bf1bc62, 0xbc22bc46,
    0xbb95bc75, 0x3c7f3ac9, 0xbc75bb95, 0x3ac93c7f, 0xbc623bf1, 0xbc46bc22, 0xbac93c7f, 0x3bf1bc62, 0x3c223c46, 0x3b953c75,
    0x3c4e3c18, 0x3c783b79, 0x3c5cbc04, 0xbc183c4e, 0x3bacbc71, 0xbc3ebc2c, 0xbc3ebc2c, 0x3c67bbdb, 0xbc80ba49, 0x3bac3c71,
    0xbbdb3c67, 0xbc80ba49, 0x3b793c78, 0x3b16bc7d, 0x3c7d3b16, 0x3c5c3c04, 0x3c553c0e, 0x3c7b3b48, 0x3c0ebc55, 0xbb483c7b,
    0x3b48bc7b, 0xbc55bc0e, 0xbc7bbb48, 0x3c0ebc55, 0xbc7b3b48, 0x3c0e3c55, 0x3b483c7b, 0xbc553c0e, 0x3c0e3c55, 0xbb48bc7b,
    0x3c55bc0e, 0x3c7bbb48, 0x3c5c3c04, 0x3c7d3b16, 0x3b16bc7d, 0x3b793c78, 0x3a49bc80, 0xbc67bbdb, 0xbc713bac, 0x3a49bc80,
    0xbc673bdb, 0x3c3e3c2c, 0x3c3e3c2c, 0xbbac3c71, 0x3c4e3c18, 0xbc04bc5c, 0x3b79bc78, 0x3c18bc4e, 0x3c623bf1, 0x3c7f3ac9,
    0xbb95bc75, 0x3c223c46, 0xbac9bc7f, 0xbc75bb95, 0xbc223c46, 0xbbf1bc62, 0xbc463c22, 0x3c623bf1, 0x3c7f3ac9, 0x3b953c75,
    0x3c753b95, 0xbc46bc22, 0xbbf1bc62, 0xbac9bc7f, 0x3c673bdb, 0x3c803a49, 0xbc2cbc3e, 0x3c673bdb, 0xbb79bc78, 0xbc7dbb16,
    0xbb163c7d, 0xbc5cbc04, 0xbc183c4e, 0x3c783b79, 0x3c5cbc04, 0x3c4e3c18, 0x3c80ba49, 0xbc71bbac, 0xbc71bbac, 0xbc3ebc2c,
    0x3c353c35, 0x3c6d3bc4, 0x3c353c35, 0xbc6dbbc4, 0x3c35bc35, 0xbbc4bc6d, 0x3c35bc35, 0x3bc43c6d, 0xbc35bc35, 0xbbc43c6d,
    0xbc35bc35, 0x3bc4bc6d, 0xbc353c35, 0x3c6dbbc4, 0xbc353c35, 0xbc6d3bc4, 0x3c80ba49, 0x3c67bbdb, 0x3c67bbdb, 0xbc2c3c3e,
    0xbb16bc7d, 0xbc78bb79, 0xbc04bc5c, 0x3c7dbb16, 0xbc783b79, 0x3c183c4e, 0xbc4e3c18, 0xbc5cbc04, 0x3bac3c71, 0x3a49bc80,
    0x3c2c3c3e, 0x3bac3c71, 0x3c22bc46, 0x3b95bc75, 0xbac9bc7f, 0x3bf13c62, 0xbc62bbf1, 0xbc463c22, 0xbc753b95, 0x3ac9bc7f,
    0xbb953c75, 0x3c7fbac9, 0x3bf13c62, 0xbc223c46, 0x3c7f3ac9, 0xbc62bbf1, 0x3c46bc22, 0x3c75bb95, 0xbb16bc7d, 0xbc04bc5c,
    0xbc78bb79, 0x3c7dbb16, 0xbc673bdb, 0x3a493c80, 0x3a493c80, 0xbc71bbac, 0x3c2c3c3e, 0x3bdbbc67, 0x3c71bbac, 0x3c2c3c3e,
    0x3c04bc5c, 0xbc4e3c18, 0xbc18bc4e, 0xbb79bc78, 0xbc55bc0e, 0xbc7bbb48, 0xbc0e3c55, 0x3b48bc7b, 0xbb483c7b, 0x3c553c0e,
    0x3c7b3b48, 0xbc0e3c55, 0x3c7bbb48, 0xbc0ebc55, 0xbb48bc7b, 0x3c55bc0e, 0xbc0ebc55, 0x3b483c7b, 0xbc553c0e, 0xbc7b3b48,
    0xbc783b79, 0xbc4e3c18, 0x3c183c4e, 0xbc5cbc04, 0x3c2c3c3e, 0x3c71bbac, 0x3bdbbc67, 0x3c2c3c3e, 0x3bacbc71, 0xbc803a49,
    0xbc803a49, 0xbbdbbc67, 0xbc7d3b16, 0x3c783b79, 0x3c043c5c, 0x3b163c7d, 0xbbf13c62, 0xbac93c7f, 0x3c75bb95, 0xbc463c22,
    0x3c7fbac9, 0x3b95bc75, 0xbc46bc22, 0x3c62bbf1, 0xbc22bc46, 0xbbf13c62, 0xbac93c7f, 0xbc753b95, 0xbb953c75, 0x3c22bc46,
    0x3c62bbf1, 0x3c7fbac9, 0x3bac3c71, 0x3c2c3c3e, 0x3a49bc80, 0x3bac3c71, 0x3c04bc5c, 0xbc18bc4e, 0xbc4e3c18, 0xbb79bc78,
    0xbc7d3b16, 0x3c043c5c, 0x3c783b79, 0x3b163c7d, 0x3c3e3c2c, 0xbbdbbc67, 0xbbdbbc67, 0xba49bc80, 0x3c353c35, 0x3c6d3bc4,
    0x3c353c35, 0xbc6dbbc4, 0x3c35bc35, 0xbbc4bc6d, 0x3c35bc35, 0x3bc43c6d, 0xbc35bc35, 0xbbc43c6d, 0xbc35bc35, 0x3bc4bc6d,
    0xbc353c35, 0x3c6dbbc4, 0xbc353c35, 0xbc6d3bc4, 0x3c2cbc3e, 0x3bacbc71, 0x3bacbc71, 0x3a493c80, 0xbc4ebc18, 0xbc5c3c04,
    0xbc78bb79, 0x3c18bc4e, 0xbc043c5c, 0x3c7d3b16, 0xbb163c7d, 0xbc783b79, 0x3c673bdb, 0xbc2cbc3e, 0x3c803a49, 0x3c673bdb,
    0xbc46bc22, 0xbc75bb95, 0xbc7f3ac9, 0x3c62bbf1, 0xbbf13c62, 0x3c223c46, 0x3b953c75, 0xbc7fbac9, 0x3c753b95, 0xbac9bc7f,
    0x3c62bbf1, 0x3c463c22, 0x3ac9bc7f, 0xbbf13c62, 0xbc22bc46, 0xbb95bc75, 0xbc183c4e, 0xbb793c78, 0x3c043c5c, 0xbc4ebc18,
    0x3c713bac, 0x3c2cbc3e, 0x3c2cbc3e, 0x3bdb3c67, 0x3a49bc80, 0xbc713bac, 0xbc67bbdb, 0x3a49bc80, 0xbc783b79, 0x3c7d3b16,
    0xbb163c7d, 0xbc043c5c, 0x3c553c0e, 0x3c7b3b48, 0x3c0ebc55, 0xbb483c7b, 0x3b48bc7b, 0xbc55bc0e, 0xbc7bbb48, 0x3c0ebc55,
    0xbc7b3b48, 0x3c0e3c55, 0x3b483c7b, 0xbc553c0e, 0x3c0e3c55, 0xbb48bc7b, 0x3c55bc0e, 0x3c7bbb48, 0x3c04bc5c, 0x3b16bc7d,
    0xbc7dbb16, 0x3c78bb79, 0xbc80ba49, 0xbbdb3c67, 0x3bac3c71, 0xbc80ba49, 0x3bdb3c67, 0x3c2cbc3e, 0x3c2cbc3e, 0x3c713bac,
    0x3c18bc4e, 0xbc5c3c04, 0xbc78bb79, 0xbc4ebc18, 0xbc62bbf1, 0xbc7fbac9, 0x3b953c75, 0xbc22bc46, 0x3ac93c7f, 0x3c753b95,
    0x3c22bc46, 0x3bf13c62, 0x3c46bc22, 0xbc62bbf1, 0xbc7fbac9, 0xbb95bc75, 0xbc75bb95, 0x3c463c22, 0x3bf13c62, 0x3ac93c7f,
    0xbbdb3c67, 0xba493c80, 0x3c3ebc2c, 0xbbdb3c67, 0x3c78bb79, 0x3b16bc7d, 0xbc7dbb16, 0x3c04bc5c, 0xbc4ebc18, 0xbb793c78,
    0x3c043c5c, 0xbc183c4e, 0x3a493c80, 0x3bacbc71, 0x3bacbc71, 0x3c2cbc3e, 0x3c353c35, 0x3c6d3bc4, 0x3c353c35, 0xbc6dbbc4,
    0x3c35bc35, 0xbbc4bc6d, 0x3c35bc35, 0x3bc43c6d, 0xbc35bc35, 0xbbc43c6d, 0xbc35bc35, 0x3bc4bc6d, 0xbc353c35, 0x3c6dbbc4,
    0xbc353c35, 0xbc6d3bc4, 0xba49bc80, 0xbbdbbc67, 0xbbdbbc67, 0x3c3e3c2c, 0xbc7d3b16, 0xbb793c78, 0xbc5c3c04, 0xbb16bc7d,
    0x3b793c78, 0x3c4ebc18, 0x3c183c4e, 0xbc043c5c, 0x3c71bbac, 0xbc80ba49, 0x3c3ebc2c, 0x3c71bbac, 0xbc223c46, 0xbb953c75,
    0x3ac93c7f, 0xbbf1bc62, 0x3c623bf1, 0x3c46bc22, 0x3c75bb95, 0xbac93c7f, 0x3b95bc75, 0xbc7f3ac9, 0xbbf1bc62, 0x3c22bc46,
    0xbc7fbac9, 0x3c623bf1, 0xbc463c22, 0xbc753b95, 0x3c7dbb16, 0x3c5cbc04, 0x3b79bc78, 0x3b163c7d, 0xbbdbbc67, 0xbc803a49,
    0xbc803a49, 0x3bacbc71, 0xbc3e3c2c, 0x3c673bdb, 0x3bac3c71, 0xbc3e3c2c, 0x3c5c3c04, 0xbc18bc4e, 0x3c4ebc18, 0x3c78bb79,
    0xbc55bc0e, 0xbc7bbb48, 0xbc0e3c55, 0x3b48bc7b, 0xbb483c7b, 0x3c553c0e, 0x3c7b3b48, 0xbc0e3c55, 0x3c7bbb48, 0xbc0ebc55,
    0xbb48bc7b, 0x3c55bc0e, 0xbc0ebc55, 0x3b483c7b, 0xbc553c0e, 0xbc7b3b48, 0x3b793c78, 0x3c183c4e, 0x3c4ebc18, 0xbc043c5c,
    0x3c3ebc2c, 0xbbacbc71, 0xbc67bbdb, 0x3c3ebc2c, 0xbc71bbac, 0x3a493c80, 0x3a493c80, 0xbc673bdb, 0x3b163c7d, 0x3b79bc78,
    0x3c5cbc04, 0x3c7dbb16, 0x3bf1bc62, 0x3ac9bc7f, 0xbc753b95, 0x3c46bc22, 0xbc7f3ac9, 0xbb953c75, 0x3c463c22, 0xbc623bf1,
    0x3c223c46, 0x3bf1bc62, 0x3ac9bc7f, 0x3c75bb95, 0x3b95bc75, 0xbc223c46, 0xbc623bf1, 0xbc7f3ac9, 0xbc713bac, 0xbc3e3c2c,
    0x3c803a49, 0xbc713bac, 0x3c5c3c04, 0x3c4ebc18, 0xbc18bc4e, 0x3c78bb79, 0xbb16bc7d, 0xbc5c3c04, 0xbb793c78, 0xbc7d3b16,
    0xbc2c3c3e, 0x3c67bbdb, 0x3c67bbdb, 0x3c80ba49, 0x3c800000, 0x3c6dbbc4, 0x3c800000, 0xbc6d3bc4, 0xbc800000, 0xbbc43c6d,
    0xbc800000, 0x3bc4bc6d, 0x3c800000, 0xbbc4bc6d, 0x3c800000, 0x3bc43c6d, 0xbc800000, 0x3c6d3bc4, 0xbc800000, 0xbc6dbbc4,
    0x3c80ba49, 0x3c67bbdb, 0x3c67bbdb, 0xbc2c3c3e, 0xbc7d3b16, 0xbb793c78, 0xbc5c3c04, 0xbb16bc7d, 0x3c78bb79, 0xbc18bc4e,
    0x3c4ebc18, 0x3c5c3c04, 0xbc713bac, 0x3c803a49, 0xbc3e3c2c, 0xbc713bac, 0x3c7fbac9, 0x3c62bbf1, 0x3c22bc46, 0xbb953c75,
    0xbc753b95, 0xbac93c7f, 0xbbf13c62, 0xbc22bc46, 0x3c62bbf1, 0xbc46bc22, 0x3b95bc75, 0x3c7fbac9, 0xbc463c22, 0x3c75bb95,
    0xbac93c7f, 0xbbf13c62, 0x3c7dbb16, 0x3c5cbc04, 0x3b79bc78, 0x3b163c7d, 0xbc673bdb, 0x3a493c80, 0x3a493c80, 0xbc71bbac,
    0x3c3ebc2c, 0xbc67bbdb, 0xbbacbc71, 0x3c3ebc2c, 0xbc043c5c, 0x3c4ebc18, 0x3c183c4e, 0x3b793c78, 0x3c7bbb48, 0x3c55bc0e,
    0xbb48bc7b, 0x3c0e3c55, 0xbc553c0e, 0x3b483c7b, 0x3c0e3c55, 0xbc7b3b48, 0x3c0ebc55, 0xbc7bbb48, 0xbc55bc0e, 0x3b48bc7b,
    0xbb483c7b, 0x3c0ebc55, 0x3c7b3b48, 0x3c553c0e, 0x3c78bb79, 0x3c4ebc18, 0xbc18bc4e, 0x3c5c3c04, 0xbc3e3c2c, 0x3bac3c71,
    0x3c673bdb, 0xbc3e3c2c, 0x3bacbc71, 0xbc803a49, 0xbc803a49, 0xbbdbbc67, 0x3b163c7d, 0x3b79bc78, 0x3c5cbc04, 0x3c7dbb16,
    0x3c75bb95, 0x3c46bc22, 0xbc62bbf1, 0x3c7f3ac9, 0xbc223c46, 0x3bf13c62, 0x3c7fbac9, 0xbb953c75, 0x3ac9bc7f, 0xbc753b95,
    0xbc463c22, 0xbc62bbf1, 0x3bf13c62, 0xbac9bc7f, 0x3b95bc75, 0x3c22bc46, 0x3c71bbac, 0x3c3ebc2c, 0xbc80ba49, 0x3c71bbac,
    0xbc043c5c, 0x3c183c4e, 0x3c4ebc18, 0x3b793c78, 0xbb16bc7d, 0xbc5c3c04, 0xbb793c78, 0xbc7d3b16, 0x3c3e3c2c, 0xbbdbbc67,
    0xbbdbbc67, 0xba49bc80, 0x3c800000, 0x3c6dbbc4, 0x3c800000, 0xbc6d3bc4, 0xbc800000, 0xbbc43c6d, 0xbc800000, 0x3bc4bc6d,
    0x3c800000, 0xbbc4bc6d, 0x3c800000, 0x3bc43c6d, 0xbc800000, 0x3c6d3bc4, 0xbc800000, 0xbc6dbbc4, 0x3c2cbc3e, 0x3bacbc71,
    0x3bacbc71, 0x3a493c80, 0xbc183c4e, 0x3c043c5c, 0xbb793c78, 0xbc4ebc18, 0x3c04bc5c, 0xbc7dbb16, 0x3b16bc7d, 0x3c78bb79,
    0xbbdb3c67, 0x3c3ebc2c, 0xba493c80, 0xbbdb3c67, 0xbac9bc7f, 0xbbf1bc62, 0xbc46bc22, 0x3c753b95, 0x3b953c75, 0x3c7f3ac9,
    0x3c623bf1, 0xbc463c22, 0xbbf1bc62, 0xbc223c46, 0xbc75bb95, 0xbac9bc7f, 0x3c223c46, 0xbb95bc75, 0x3c7f3ac9, 0x3c623bf1,
    0xbc4ebc18, 0xbc78bb79, 0xbc5c3c04, 0x3c18bc4e, 0x3c713bac, 0x3c2cbc3e, 0x3c2cbc3e, 0x3bdb3c67, 0xbc80ba49, 0x3bac3c71,
    0xbbdb3c67, 0xbc80ba49, 0x3c78bb79, 0xbc7dbb16, 0x3b16bc7d, 0x3c04bc5c, 0xbc7b3b48, 0xbc553c0e, 0x3b483c7b, 0xbc0ebc55,
    0x3c55bc0e, 0xbb48bc7b, 0xbc0ebc55, 0x3c7bbb48, 0xbc0e3c55, 0x3c7b3b48, 0x3c553c0e, 0xbb483c7b, 0x3b48bc7b, 0xbc0e3c55,
    0xbc7bbb48, 0xbc55bc0e, 0xbc043c5c, 0xbb163c7d, 0x3c7d3b16, 0xbc783b79, 0x3a49bc80, 0xbc67bbdb, 0xbc713bac, 0x3a49bc80,
    0x3bdb3c67, 0x3c2cbc3e, 0x3c2cbc3e, 0x3c713bac, 0xbc4ebc18, 0x3c043c5c, 0xbb793c78, 0xbc183c4e, 0x3b953c75, 0x3c223c46,
    0x3bf1bc62, 0xbac93c7f, 0xbc46bc22, 0xbc623bf1, 0x3ac93c7f, 0xbc75bb95, 0x3c7f3ac9, 0xbb95bc75, 0xbc22bc46, 0x3bf1bc62,
    0xbc623bf1, 0x3c7fbac9, 0x3c753b95, 0x3c463c22, 0x3c673bdb, 0x3c803a49, 0xbc2cbc3e, 0x3c673bdb, 0xbc783b79, 0xbb163c7d,
    0x3c7d3b16, 0xbc043c5c, 0x3c18bc4e, 0xbc78bb79, 0xbc5c3c04, 0xbc4ebc18, 0x3a493c80, 0x3bacbc71, 0x3bacbc71, 0x3c2cbc3e,
    0x3c800000, 0x3c6dbbc4, 0x3c800000, 0xbc6d3bc4, 0xbc800000, 0xbbc43c6d, 0xbc800000, 0x3bc4bc6d, 0x3c800000, 0xbbc4bc6d,
    0x3c800000, 0x3bc43c6d, 0xbc800000, 0x3c6d3bc4, 0xbc800000, 0xbc6dbbc4, 0xba49bc80, 0xbbdbbc67, 0xbbdbbc67, 0x3c3e3c2c,
    0x3b163c7d, 0x3c783b79, 0x3c043c5c, 0xbc7d3b16, 0xbb79bc78, 0xbc4e3c18, 0xbc18bc4e, 0x3c04bc5c, 0x3bac3c71, 0x3a49bc80,
    0x3c2c3c3e, 0x3bac3c71, 0xbc7f3ac9, 0xbc623bf1, 0xbc223c46, 0x3b95bc75, 0x3c75bb95, 0x3ac9bc7f, 0x3bf1bc62, 0x3c223c46,
    0xbc623bf1, 0x3c463c22, 0xbb953c75, 0xbc7f3ac9, 0x3c46bc22, 0xbc753b95, 0x3ac9bc7f, 0x3bf1bc62, 0x3b163c7d, 0x3c043c5c,
    0x3c783b79, 0xbc7d3b16, 0xbbdbbc67, 0xbc803a49, 0xbc803a49, 0x3bacbc71, 0x3c2c3c3e, 0x3bdbbc67, 0x3c71bbac, 0x3c2c3c3e,
    0xbc5cbc04, 0x3c183c4e, 0xbc4e3c18, 0xbc783b79, 0x3c7bbb48, 0x3c55bc0e, 0xbb48bc7b, 0x3c0e3c55, 0xbc553c0e, 0x3b483c7b,
    0x3c0e3c55, 0xbc7b3b48, 0x3c0ebc55, 0xbc7bbb48, 0xbc55bc0e, 0x3b48bc7b, 0xbb483c7b, 0x3c0ebc55, 0x3c7b3b48, 0x3c553c0e,
    0xbb79bc78, 0xbc18bc4e, 0xbc4e3c18, 0x3c04bc5c, 0x3c2c3c3e, 0x3c71bbac, 0x3bdbbc67, 0x3c2c3c3e, 0xbc71bbac, 0x3a493c80,
    0x3a493c80, 0xbc673bdb, 0x3c7dbb16, 0xbc78bb79, 0xbc04bc5c, 0xbb16bc7d, 0xbc753b95, 0xbc463c22, 0x3c623bf1, 0xbc7fbac9,
    0x3c22bc46, 0xbbf1bc62, 0xbc7f3ac9, 0x3b95bc75, 0xbac93c7f, 0x3c75bb95, 0x3c46bc22, 0x3c623bf1, 0xbbf1bc62, 0x3ac93c7f,
    0xbb953c75, 0xbc223c46, 0x3bac3c71, 0x3c2c3c3e, 0x3a49bc80, 0x3bac3c71, 0xbc5cbc04, 0xbc4e3c18, 0x3c183c4e, 0xbc783b79,
    0x3c7dbb16, 0xbc04bc5c, 0xbc78bb79, 0xbb16bc7d, 0xbc2c3c3e, 0x3c67bbdb, 0x3c67bbdb, 0x3c80ba49, 0x3c800000, 0x3c6dbbc4,
    0x3c800000, 0xbc6d3bc4, 0xbc800000, 0xbbc43c6d, 0xbc800000, 0x3bc4bc6d, 0x3c800000, 0xbbc4bc6d, 0x3c800000, 0x3bc43c6d,
    0xbc800000, 0x3c6d3bc4, 0xbc800000, 0xbc6dbbc4, 0xbc3ebc2c, 0xbc71bbac, 0xbc71bbac, 0x3c80ba49, 0x3c4e3c18, 0x3c5cbc04,
    0x3c783b79, 0xbc183c4e, 0xbc5cbc04, 0xbb163c7d, 0xbc7dbb16, 0xbb79bc78, 0x3c673bdb, 0xbc2cbc3e, 0x3c803a49, 0x3c673bdb,
    0x3ac93c7f, 0x3bf13c62, 0x3c463c22, 0xbc75bb95, 0xbb95bc75, 0xbc7fbac9, 0xbc62bbf1, 0x3c46bc22, 0x3bf13c62, 0x3c22bc46,
    0x3c753b95, 0x3ac93c7f, 0xbc22bc46, 0x3b953c75, 0xbc7fbac9, 0xbc62bbf1, 0x3c18bc4e, 0x3b79bc78, 0xbc04bc5c, 0x3c4e3c18,
    0xbbac3c71, 0x3c3e3c2c, 0x3c3e3c2c, 0xbc673bdb, 0x3a49bc80, 0xbc713bac, 0xbc67bbdb, 0x3a49bc80, 0x3b793c78, 0x3b16bc7d,
    0x3c7d3b16, 0x3c5c3c04, 0xbc7b3b48, 0xbc553c0e, 0x3b483c7b, 0xbc0ebc55, 0x3c55bc0e, 0xbb48bc7b, 0xbc0ebc55, 0x3c7bbb48,
    0xbc0e3c55, 0x3c7b3b48, 0x3c553c0e, 0xbb483c7b, 0x3b48bc7b, 0xbc0e3c55, 0xbc7bbb48, 0xbc55bc0e, 0x3c5c3c04, 0x3c7d3b16,
    0x3b16bc7d, 0x3b793c78, 0xbc80ba49, 0xbbdb3c67, 0x3bac3c71, 0xbc80ba49, 0x3c67bbdb, 0xbc3ebc2c, 0xbc3ebc2c, 0x3bacbc71,
    0xbc183c4e, 0x3c5cbc04, 0x3c783b79, 0x3c4e3c18, 0xbb95bc75, 0xbc22bc46, 0xbbf13c62, 0x3ac9bc7f, 0x3c463c22, 0x3c62bbf1,
    0xbac9bc7f, 0x3c753b95, 0xbc7fbac9, 0x3b953c75, 0x3c223c46, 0xbbf13c62, 0x3c62bbf1, 0xbc7f3ac9, 0xbc75bb95, 0xbc46bc22,
    0xbbdb3c67, 0xba493c80, 0x3c3ebc2c, 0xbbdb3c67, 0xbb79bc78, 0xbc7dbb16, 0xbb163c7d, 0xbc5cbc04, 0x3c4e3c18, 0x3b79bc78,
    0xbc04bc5c, 0x3c18bc4e, 0xbc803a49, 0x3c713bac, 0x3c713bac, 0x3c3e3c2c,
};

#define G_EPI 3
#define G_TK 3
#define W_Q 6
#define W2_PC 32
#define W2_PF 3
constexpr int X_LOC0 = 5;
constexpr int A_IN = 112 * 128;
constexpr int G_ST = 2 * NB1 * 64;
constexpr int K1_R = 131072, K1_BAR = K1_R + 98304, K1_SMEM = K1_BAR + 2048 + 1024;
constexpr int K1_T = K1_R + 65536, K1_TIN = 0, K1_Y0 = 3 * G_ST + 8192, G_KM = 16 - G_TK, G_S0 = 2 * G_KM;
__device__ int g_done[8 * 32];
struct Ptrs {
  int* done;
  float* ge;
  const uint32_t *img, *ga;
};

__host__ __device__ constexpr int g_depth(int s) { return s < 11 ? 3 : s < 18 ? 4 : s < 23 ? 5 : 6; }
__host__ __device__ constexpr int g_slot(int s) { return s < 3 ? s : g_depth(s) != g_depth(s - 1) ? g_depth(s - 1) : g_slot(s - g_depth(s)); }
__host__ __device__ constexpr int g_off(int id) { return id * G_ST + (id < 3 ? K1_R : 8192 - 3 * G_ST); }
struct Plan {
  uint32_t raw[32];
  uint32_t x[16];
  uint32_t grp[8];
  uint32_t last;
  uint32_t wpf;
  uint32_t g0;
  uint32_t tmask;
  uint64_t list[2];
};
struct K1Maps {
  Plan p;
  CUtensorMap x, we, wo, xs, y, w2e, w2o, w2s;
  int slot[32];
  int src[32];
  int dep[32];
};
__device__ __forceinline__ void poll_ge(const int* p, int target) {
  for (int it = 0; it < (1 << 20); it++) {
    int v;
    asm volatile("ld.acquire.gpu.global.s32 %0, [%1];" : "=r"(v) : "l"(p) : "memory");
    if (v >= target) break;
  }
}
__device__ __forceinline__ uint32_t place(int rank, uint32_t c) { return (c ^ (rank * 4 & ~(c >> 1))) << 14; }
__device__ __forceinline__ int x_unit(int cta, int u, uint32_t pl) {
  const int i = u * 128 + cta;
  const int pr = cta >= 128 ? 2 * cta - 96 + (u & 1) : i % 160, sl = cta >= 128 ? u >> 1 : i / 160, b = pr >= 84;
  return pr | sl << 8 | b << 11 | (cta >= 128 ? (u & 7) << 14 : place(cta & 1, pl & 15)) | 12 * (pr - 84 * b) << 20;
}
__device__ __forceinline__ int lds32(uint32_t a) {
  int v;
  asm volatile("ld.shared.b32 %0, [%1];" : "=r"(v) : "r"(a));
  return v;
}
__host__ __device__ constexpr uint64_t sched(const char* p) {
  uint64_t r = 0;
  for (int n = 0; p[n]; n++) r |= (uint64_t)(p[n] - '0' + 1) << (5 * n);
  return r;
}

__global__ void __cluster_dims__(2, 1, 1) __launch_bounds__(384, 1)
k1(const Ptrs gp_, const char* __restrict__ x1, const char* __restrict__ w1, const __grid_constant__ K1Maps m, const __nv_bfloat16* __restrict__ g,
   const __nv_bfloat16* __restrict__ wgt) {
  extern __shared__ __align__(1024) uint8_t smem_k1[];
  const uint32_t sb = s2u(smem_k1);
  const int tid = threadIdx.x, cta = blockIdx.x, rank = cta & 1;
  if (tid == 288) {
    const uint32_t bar = sb + K1_BAR + 256, dst = sb + (cta >= 128 ? 0 : place(rank, X_LOC0));
    const int pr = cta >= 128 ? 2 * cta - 96 : cta, b = pr >= 84;
    mbar_init(bar, 1);
    mbar_expect(bar, A_IN);
    for (int h = 0; h < 2; h++) tma_ld4<1>(dst + h * (A_IN / 2), &m.x, bar, 0, 96 * (pr - 84 * b) - 24 + h * 56, 0, b);
    for (int i = 1; i < 4; i++) mbar_init(bar + 8 * i, 1);
    fence_bar_init();
  }
  const uint32_t sF = sb + (cta >= 128 ? K1_T : rank * 65536), fbar = sb + K1_BAR + 1792;
  if (tid == 320) {
    mbar_init(fbar, 1);
    mbar_expect(fbar, 8192);
    asm volatile("cp.async.bulk.shared::cluster.global.mbarrier::complete_tx::bytes [%0], [%1], 8192, [%2];" ::"r"(sF), "l"(gp_.img + 1536), "r"(fbar) : "memory");
    fence_bar_init();
  }
  const int wg = __shfl_sync(0xffffffffu, tid >> 7, 0), t = tid & 127;
  const int warp = __shfl_sync(0xffffffffu, t >> 5, 0), lane = t & 31;
  const bool spare = cta >= 128;
  const int nx = spare ? 16 : 10;
  int bp, dc;
  {
    const int ci = cta >> 1;
    const int G = ci < 4 ? 0 : ci < 36 ? (ci - 4) & 7 : 1 + (ci - 36) % 7;
    const int li = ci < 4 ? 4 + ci : ci < 36 ? (ci - 4) >> 3 : 4 + (ci - 36) / 7;
    bp = 2 * G + (li >> 2), dc = li & 3;
  }
  const int bin = 2 * bp + rank;
  const uint32_t bb = sb + K1_BAR;
  const uint32_t rfull = bb, xfull = bb + 256, xfree = bb + 384, gfull = bb + 512, win = bb + 1800, win1 = bb + 1808;
  const uint32_t inf0 = bb + 784, se0 = inf0 + 16, pfree = se0 + 16, rempty = bb + 1024, xready = bb + 1280;
  const uint32_t gdone = bb + 1536, ine0 = gdone + 224, sf0 = ine0 + 16;
  const uint32_t xtab = bb + 896, ptab = bb + 2048 + 768;
  auto raw_load = [&](int j, uint32_t dst) {
    mbar_expect(rfull + 8 * j, 16384);
    tma_ld4<0>(dst, rank ? &m.we : &m.wo, rfull + 8 * j, dc * 64, rank - 1, (j & 3) * 4, (j >> 2) * 2);
  };
  auto x_half = [&](int u, int c, int h) {
    tma_ld4<1>(sb + (c & 0x3C000) + h * (A_IN / 2), &m.x, xfull + 8 * u, 0, (c >> 17 & ~7) - 24 + h * 56, c >> 8 & 7, c >> 11 & 1);
  };
  auto w_prefetch = [&](int q) {
    if (cta < 124) asm volatile("cp.async.bulk.prefetch.L2.global [%0], 4096;" ::"l"(w1 + (cta >> 2) * 131072 + (q * 4 + (cta & 3)) * 4096) : "memory");
  };
  uint32_t peer;
  asm("mapa.shared::cluster.u32 %0, %1, %2;" : "=r"(peer) : "r"(sb), "r"(rank ^ 1));
  if (wg == 2) {
    if (lane == 0) {
      if (warp == 0) {
        for (int i = 0; i < 4; i++) mbar_init(bb + 8 * i, 1);
        fence_bar_init();
        if (!spare)
          for (int j = 0; j < 4; j++) raw_load(j, sb + K1_R + j * 16384);
      } else if (warp == 2) {
#pragma unroll 1
        for (int q = 1; q <= m.p.wpf; q++) w_prefetch(q);
        prefetch_map(&m.xs);
      }
    }
    if (warp == 3) {
      const uint32_t v = reinterpret_cast<const uint32_t*>(&m.p)[32 + lane];
      asm volatile("st.shared.b32 [%0], %1;" ::"r"(ptab + 4 * lane), "r"(m.p.raw[lane]) : "memory");
      asm volatile("st.shared.b32 [%0], %1;" ::"r"(ptab + 128 + 4 * lane), "r"(v) : "memory");
      if (lane < 16) asm volatile("st.shared.b32 [%0], %1;" ::"r"(xtab + 4 * lane), "r"(x_unit(cta, lane, v)) : "memory");
    }
  } else {
    const int c = 4 * wg + warp;
    if (lane == 0 && c < 7) {
      const uint32_t b0 = bb + 256 * c, n = c < 4 ? 1 : c < 6 ? 4 : 8;
      if (c >= 2)
        for (int i = 0; i < 4; i++) mbar_init(b0 + 8 * i, n);
      for (int i = 4; i < 16; i++) mbar_init(b0 + 8 * i, n);
      if (c == 3) {
        mbar_init(win, 1 + 2 * W_Q);
        mbar_init(win1, 17 - 2 * W_Q);
        mbar_expect(win, 8192 * W_Q);
        mbar_expect(win1, 65536 - 8192 * W_Q);
        mbar_arrive(bb + 776);
      } else {
        for (int i = 16; i < 32; i++) mbar_init(b0 + 8 * i, n);
      }
      fence_bar_init();
    }
  }
  pdl_launch();
  __syncthreads();
  asm volatile("barrier.cluster.arrive.relaxed.aligned;" ::: "memory");
  if (wg == 2) {
    asm volatile("setmaxnreg.dec.sync.aligned.u32 40;");
    asm volatile("barrier.cluster.wait.aligned;" ::: "memory");
    if (lane == 0) {
      const int wpf = lds32(ptab + 228), g0 = lds32(ptab + 232), s0 = g0 * 4 / 5;
      const int nx0 = spare ? 2 * s0 : g0;
      if (warp == 0) {
        if (!spare) {
#pragma unroll 1
          for (int j = 4; j < 32; j++) {
            const uint32_t e = lds32(ptab + 4 * j);
            mbar_wait(bb + (e >> 5 & ~7), 0);
            raw_load(j, sb + place(rank, e & 15));
            if ((j & 3) == 0 && wpf && (j >> 2) + wpf < 8) w_prefetch((j >> 2) + wpf);
          }
#pragma unroll 1
          for (int s = 0; s < 32; s++) {
            if (s == 0 || s == 4 * s0) {
              poll_ge(&gp_.done[(s ? 5 : 4) * 32], 132);
              asm volatile("fence.proxy.async.global;" ::: "memory");
              mbar_wait(bb + 8 * (lds32(ptab + 224) & 255), 0);
            }
            const uint32_t bar = gfull + 8 * s, dst = sb + 16 * m.slot[s];
            const char* src = x1 + bin * (4 * G_ST) + m.src[s];
            mbar_wait(bb + m.dep[s], 0);
            mbar_expect(bar, G_ST);
#pragma unroll
            for (int h = 0; h < 2; h++) {
              if (s >= 16)
                asm volatile("cp.async.bulk.shared::cluster.global.mbarrier::complete_tx::bytes.L2::cache_hint [%0], [%1], %2, [%3], %4;"
                             ::"r"(dst + h * (G_ST / 2)), "l"(src + h * (s < G_S0 ? G_ST / 2 : 2 * G_ST)), "n"(G_ST / 2), "r"(bar), "l"(policy<1>()) : "memory");
              else
                asm volatile("cp.async.bulk.shared::cluster.global.mbarrier::complete_tx::bytes [%0], [%1], %2, [%3];"
                             ::"r"(dst + h * (G_ST / 2)), "l"(src + h * (s < G_S0 ? G_ST / 2 : 2 * G_ST)), "n"(G_ST / 2), "r"(bar) : "memory");
            }
          }
          if (cta == 0) asm volatile("cp.async.bulk.prefetch.L2.global [%0], 14336;" ::"l"(gp_.img) : "memory");
        }
      } else if (warp < 3) {
        const int u0 = warp == 1 ? 0 : nx0, u1 = warp == 1 ? nx0 : nx;
#pragma unroll 1
        for (int u = u0; u < u1; u++) {
          const int c = lds32(xtab + 4 * u);
          const uint32_t e = spare ? 0xC0 : lds32(ptab + 128 + 4 * u);
          const uint32_t src = sb + (c & 0x3C000), rel = e >> 1 & 24, burst = (16 << (e >> 6 & 3)) - 1;
          mbar_wait(xready + 8 * u, 0);
#pragma unroll 1
          for (int p = 0; p < 128; p += 16) {
            tma_st4<0>(&m.xs, src + p * 128, 0, (c >> 2 & 0x1C0) + (p & 63), p >> 6, c & 255);
            if (((p + 16) & burst) == 0) {
              bulk_commit();
              bulk_wait_read<0>();
            }
          }
          mbar_arrive(xfree + 8 * u);
          if (rel)
            asm volatile("mbarrier.arrive.shared::cluster.b64 _, [%0];" ::"r"(peer + (pfree - sb) + rel) : "memory");
        }
        asm volatile("cp.async.bulk.wait_group 0;" ::: "memory");
        asm volatile("red.release.gpu.global.add.s32 [%0], 1;" ::"l"(&gp_.done[(3 + warp) * 32]) : "memory");
        if (!spare) {
          if (warp == 1) {
            auto w2_row = [&](int it, bool pf) {
              const CUtensorMap* mp = it & 1 ? &m.w2e : &m.w2o;
              const int c1 = (it & 1) - 1, c2 = (cta & 1) * 2, c3 = (it >> 1) * 64 + (cta >> 1);
              if (pf) {
                asm volatile("cp.async.bulk.prefetch.tensor.4d.L2.global [%0, {%1, %2, %3, %4}];" ::"l"(mp), "r"(0), "r"(c1), "r"(c2), "r"(c3) : "memory");
              } else {
                mbar_expect(inf0 + 8 * (it & 1), 4096);
                tma_ld4<1>(sb + K1_TIN + (it & 1) * 4096, mp, inf0 + 8 * (it & 1), 0, c1, c2, c3);
              }
            };
#pragma unroll 1
            for (int it = 0; it < W2_PF; it++) {
              mbar_wait(gfull + 8 * (it >> 1), 0);
              w2_row(it, true);
            }
            mbar_wait(gdone + 8, 0);
#pragma unroll 1
            for (int it = 0; it < 8; it++) {
              if (it >= 2) mbar_wait(ine0 + 8 * (it & 1), ((it >> 1) - 1) & 1);
              w2_row(it, false);
              if (W2_PF && it + W2_PF < 8) w2_row(it + W2_PF, true);
            }
          } else {
            prefetch_map(&m.w2s);
            prefetch_map(&m.y);
#pragma unroll 1
            for (int it = 0; it < 8; it++) {
              if ((0x74 >> it) & 1) poll_ge(&gp_.done[((0x33210000 >> (4 * it)) & 3) * 32], 128);
              mbar_wait(sf0 + 8 * (it & 1), (it >> 1) & 1);
#pragma unroll 1
              for (int p = 0; p < 128; p += W2_PC) {
                tma_st4<0>(&m.w2s, sb + K1_T + (it & 1) * 16384 + p * 128, 0, it * 64 + (p & 63), (cta & 1) * 2 + (p >> 6),
                           (cta >> 1 & 33) | (cta >> 3 & 6) | (cta << 1 & 24));
                bulk_commit();
                bulk_wait_read<0>();
              }
              mbar_arrive(se0 + 8 * (it & 1));
            }
          }
        }
      } else {
#pragma unroll 1
        for (int u = 1; u < nx; u++) {
          const int c = lds32(xtab + 4 * u);
          const uint32_t e = spare ? (u < 8 ? 97 : 40 + u) * 0x01010100u : lds32(ptab + 128 + 4 * u);
          mbar_wait(bb + (e >> 5 & 0x7F8), 0);
          mbar_expect(xfull + 8 * u, A_IN);
          mbar_wait(bb + (e >> 13 & 0x7F8), 0);
          x_half(u, c, 0);
          mbar_wait(bb + (e >> 21 & 0x7F8), 0);
          x_half(u, c, 1);
        }
#pragma unroll 1
        for (int s = 0; s < (spare ? 0 : 16); s++) {
          mbar_wait(gfull + 8 * s, 0);
          if ((s & 3) == 3) asm volatile("red.relaxed.gpu.global.add.s32 [%0], 1;" ::"l"(&gp_.done[(s >> 2) * 32]) : "memory");
        }
      }
    }
  } else {
    asm volatile("setmaxnreg.inc.sync.aligned.u32 232;");
    const int row = (lane & 7) + ((lane >> 3) & 1) * 8, hi = lane >> 4;
    asm volatile("barrier.cluster.wait.aligned;" ::: "memory");
    uint32_t fw[4];
    {
      uint32_t fa[16], za[64];
      mbar_wait(fbar, 0);
      const int f = (4 * bp + warp) & 63;
      const uint32_t lo = lds32(sF + f * 128 + ((f & 7) << 4) + (lane & 3) * 4), hh = lds32(sF + f * 128 + (((f & 7) ^ 1) << 4) + (lane & 3) * 4);
#pragma unroll
      for (int k = 0; k < 4; k++)
        ldsm4(sF + (warp * 16 + row) * 128 + (((2 * k + hi) ^ (lane & 7)) << 4), fa[4 * k], fa[4 * k + 1], fa[4 * k + 2], fa[4 * k + 3]);
      const int rho = (lane >> 3) | (lane & 4);
#pragma unroll
      for (int i = 0; i < 64; i++) za[i] = ((i & 1) == (i >> 5) && rho == ((i >> 2) & 7)) ? ((i & 2) ? hh : lo) : 0u;
      reg_fence(za);
      bar_sync(3, 256);
      const bool own = (warp >> 1) == rank;
      float d[64];
      constexpr uint64_t s2 = sched("02468:<>"), s3 = sched("13579;=?");
#pragma unroll 1
      for (uint64_t sc = spare ? (wg ? s3 : s2) : m.p.list[wg]; sc; sc >>= 5) {
        const int item = (int)sc & 31;
        if (item >= 18) {
          const int q = item - 18;
          const uint32_t e = __shfl_sync(0xffffffffu, lds32(ptab + 192 + 4 * q), 0);
#pragma unroll
          for (int jj = 0; jj < 4; jj++) {
            const int j = 4 * q + jj;
            mbar_wait(rfull + 8 * j, 0);
            wg_fence();
#pragma unroll
            for (int i = 0; i < 4; i++)
              wgmma_rs_128<1, 1, 1>(d, za[16 * jj + 4 * i], za[16 * jj + 4 * i + 1], za[16 * jj + 4 * i + 2], za[16 * jj + 4 * i + 3],
                                    mk_desc(sb + place(rank, e >> (4 * jj) & 15), i * 2048, 8192, 1024, 1), jj | i);
            wg_commit();
            if (jj > 0) {
              wg_wait<1>();
              if (lane == 0) mbar_arrive(rempty + 8 * (j - 1));
            }
          }
          wg_wait<0>();
          reg_fence(d);
          if (lane == 0) mbar_arrive(rempty + 8 * (4 * q + 3));
          mbar_wait(bb + (e >> (own ? 13 : 21) & 0x7F8), 0);
          const uint32_t rb = (own ? sb : peer) + (8 * rank + q) * 8192 + (warp & 1) * 4096 + rho * 128;
          const uint32_t wbar = q < W_Q ? win : win1;
          auto put_w = [&](auto remote) {
#pragma unroll
            for (int v = 0; v < 8; v++) {
              const int j = 4 * (v >> 1), h = v & 1;
              const uint32_t a = rb + (j >> 3) * 2048 + h * 1024 + ((((j & 4) + (lane & 3)) ^ rho) << 4);
              const uint32_t p0 = pack2(d[4 * j + 2 * h], d[4 * j + 2 * h + 1]), p1 = pack2(d[4 * j + 4 + 2 * h], d[4 * j + 5 + 2 * h]);
              const uint32_t p2 = pack2(d[4 * j + 8 + 2 * h], d[4 * j + 9 + 2 * h]), p3 = pack2(d[4 * j + 12 + 2 * h], d[4 * j + 13 + 2 * h]);
              if (decltype(remote)::value)
                asm volatile("st.async.shared::cluster.mbarrier::complete_tx::bytes.v4.b32 [%0], {%1, %2, %3, %4}, [%5];"
                             ::"r"(a), "r"(p0), "r"(p1), "r"(p2), "r"(p3), "r"(peer + (wbar - sb)) : "memory");
              else
                asm volatile("st.shared.v4.b32 [%0], {%1, %2, %3, %4};" ::"r"(a), "r"(p0), "r"(p1), "r"(p2), "r"(p3) : "memory");
            }
          };
          if (own) {
            put_w(std::false_type());
            __syncwarp();
            if (lane == 0) mbar_arrive(wbar);
          } else {
            put_w(std::true_type());
          }
        } else {
          const int u = item - 1;
          const int c = lds32(xtab + 4 * u);
          const uint32_t in = sb + (c & 0x3C000);
          mbar_wait(xfull + 8 * u, 0);
          wg_fence();
#pragma unroll
          for (int k = 0; k < 4; k++)
            wgmma_rs_128<1, 1, 1>(d, fa[4 * k], fa[4 * k + 1], fa[4 * k + 2], fa[4 * k + 3], mk_desc(in, k * 2048, 6144, 1024, 1), k);
          wg_commit();
          wg_wait<0>();
          reg_fence(d);
          bar_sync(1 + wg, 128);
          const uint32_t rb = in + (warp * 16 + row) * 128, xr = (lane & 7) ^ (c & 3);
#pragma unroll
          for (int j = 0; j < 16; j += 2)
            stsm4(rb + ((j >> 2) & 1) * 8192 + ((((j >> 3) * 4 + (j & 3) + hi) ^ xr) << 4), pack2(d[4 * j], d[4 * j + 1]),
                  pack2(d[4 * j + 2], d[4 * j + 3]), pack2(d[4 * j + 4], d[4 * j + 5]), pack2(d[4 * j + 6], d[4 * j + 7]));
          fence_async();
          __syncwarp();
          if (lane == 0) mbar_arrive(xready + 8 * u);
        }
      }
#pragma unroll
      for (int i = 0; i < 4; i++) fw[i] = fa[i];
    }
    if (spare) {
      float* sg = reinterpret_cast<float*>(smem_k1 + K1_R);
      __nv_bfloat16* sw = reinterpret_cast<__nv_bfloat16*>(sg + 16 * 256);
      const int c0 = (cta - 128) * 64;
      uint4 vw[8], vg[2];
#pragma unroll
      for (int i = 0; i < 8; i++) vw[i] = __ldg(reinterpret_cast<const uint4*>(wgt + ((i * 256 + tid) >> 3) * 256 + c0 + (tid & 7) * 8));
#pragma unroll
      for (int i = 0; i < 2; i++) vg[i] = __ldg(reinterpret_cast<const uint4*>(g) + i * 256 + tid);
#pragma unroll
      for (int i = 0; i < 8; i++) reinterpret_cast<uint4*>(sw)[i * 256 + tid] = vw[i];
#pragma unroll
      for (int i = 0; i < 2; i++) {
        const uint32_t w4[4] = {vg[i].x, vg[i].y, vg[i].z, vg[i].w};
#pragma unroll
        for (int e = 0; e < 4; e++) {
          sg[(i * 256 + tid) * 8 + 2 * e] = __uint_as_float(w4[e] << 16);
          sg[(i * 256 + tid) * 8 + 2 * e + 1] = __uint_as_float(w4[e] & 0xffff0000u);
        }
      }
      bar_sync(3, 256);
      const int col = tid & 63, r0 = (tid >> 6) * 4;
      float a0 = 0.f, a1 = 0.f, a2 = 0.f, a3 = 0.f;
#pragma unroll 8
      for (int k = 0; k < 256; k++) {
        const float w = __bfloat162float(sw[k * 64 + col]);
        a0 = fmaf(sg[(r0 + 0) * 256 + k], w, a0);
        a1 = fmaf(sg[(r0 + 1) * 256 + k], w, a1);
        a2 = fmaf(sg[(r0 + 2) * 256 + k], w, a2);
        a3 = fmaf(sg[(r0 + 3) * 256 + k], w, a3);
      }
      const int cc = c0 + col;
      const int pos = (cc & ~15) + ((cc >> 1) & 3) * 4 + ((cc >> 3) & 1) * 2 + (cc & 1);
      gp_.ge[(r0 + 0) * 256 + pos] = __bfloat162float(__float2bfloat16_rn(a0));
      gp_.ge[(r0 + 1) * 256 + pos] = __bfloat162float(__float2bfloat16_rn(a1));
      gp_.ge[(r0 + 2) * 256 + pos] = __bfloat162float(__float2bfloat16_rn(a2));
      gp_.ge[(r0 + 3) * 256 + pos] = __bfloat162float(__float2bfloat16_rn(a3));
      return;
    }
    reg_fence(fw);
    mbar_wait(win, 0);
    float d[16];
    auto t_begin = [&](int it, int hh, int r) {
      if (r == 0) mbar_wait(inf0 + 8 * (it & 1), (it >> 1) & 1);
      wg_fence();
      wgmma_rs_32<1, 1, 1>(d, fw[0], fw[1], fw[2], fw[3], mk_desc(sb + K1_TIN + (it & 1) * 4096 + hh * 2048, r * 64, 0, 1024, 1), 0);
      wg_commit();
    };
    auto t_end = [&](int it, int hh, int r) {
      reg_fence(d);
      const int j = it & 1;
      if (r == 0) mbar_wait(it >= 2 ? se0 + 8 * j : bb + (m.p.last >> (5 + 8 * it) & 0x7F8), it >= 2 ? ((it >> 1) - 1) & 1 : 0);
      else if (lane == 0) mbar_arrive(ine0 + 8 * j);
      const uint32_t rb = sb + K1_T + j * 16384 + hh * 8192 + (warp * 16 + row) * 128;
#pragma unroll
      for (int i = 0; i < 2; i++)
        stsm4(rb + (((4 * r + 2 * i + hi) ^ (lane & 7)) << 4), pack2(d[8 * i], d[8 * i + 1]), pack2(d[8 * i + 2], d[8 * i + 3]),
              pack2(d[8 * i + 4], d[8 * i + 5]), pack2(d[8 * i + 6], d[8 * i + 7]));
      if (r == 1) {
        fence_async();
        __syncwarp();
        if (lane == 0) mbar_arrive(sf0 + 8 * j);
      }
    };
    float y0[NB1 / 2], y1[NB1 / 2];
    uint32_t wa[8], wb[8];
    uint32_t wp = sb + wg * 4096 + ((lane & 7) + hi * 8) * 128 + (((2 * warp + ((lane >> 3) & 1)) ^ (lane & 7)) << 4);
    const uint32_t neg = wg ? 0x80008000u : 0u;
    auto frag = [&](uint32_t (&w)[8], uint32_t a, uint32_t sg) {
      ldsm4t(a, w[0], w[1], w[2], w[3]);
      ldsm4t(a + 2048, w[4], w[5], w[6], w[7]);
#pragma unroll
      for (int i = 0; i < 8; i++) w[i] ^= sg;
    };
    auto stage = [&](const uint32_t (&w)[8], uint32_t x4, int acc) {
      wg_fence();
      wgmma_rs_168<1, 1, 0>(y0, w[0], w[1], w[2], w[3], mk_desc4(x4, 0, 512, 2), acc);
      wgmma_rs_168<1, 1, 0>(y1, w[0], w[1], w[2], w[3], mk_desc4(x4 + G_ST / 32, 0, 512, 2), acc);
      wgmma_rs_168<1, 1, 0>(y0, w[4], w[5], w[6], w[7], mk_desc4(x4 + 2, 0, 512, 2), 1);
      wgmma_rs_168<1, 1, 0>(y1, w[4], w[5], w[6], w[7], mk_desc4(x4 + G_ST / 32 + 2, 0, 512, 2), 1);
      wg_commit();
      wg_wait<1>();
    };
    frag(wa, wp, neg);
    int it = 0;
#pragma unroll 1
    for (int k = 0; k < G_KM; k++) {
      const bool T = (m.p.tmask >> (k + 16 * wg)) & 1;
      const uint32_t xa = ((sb & 0x3FFFF) >> 4) + m.slot[2 * k], xb = ((sb & 0x3FFFF) >> 4) + m.slot[2 * k + 1];
      if (T) t_begin(it, wg, 0);
      mbar_wait(gfull + 16 * k, 0);
      stage(wa, xa, k);
      frag(wb, wp ^ 4096, 0);
      if (k > 0 && lane == 0) mbar_arrive(gdone + 16 * k - 8);
      if (T) {
        t_end(it, wg, 0);
        t_begin(it, wg, 1);
      }
      mbar_wait(gfull + 16 * k + 8, 0);
      stage(wb, xb, 1);
      wp += 8192;
      if (k == W_Q - 1) {
        mbar_wait(win1, 0);
        fence_async();
      }
      frag(wa, wp, neg);
      if (lane == 0) mbar_arrive(gdone + 16 * k);
      if (T) t_end(it++, wg, 1);
    }
    auto tail = [&](float (&y)[NB1 / 2], auto batch, auto wgc) {
      constexpr int B = decltype(batch)::value, W = decltype(wgc)::value;
#pragma unroll
      for (int k = G_KM; k < 16; k++) {
        const int s = G_KM + k + G_TK * B;
        mbar_wait(gfull + 8 * s, 0);
        const int xo = g_off(g_slot(s));
        wg_fence();
#pragma unroll
        for (int h = 0; h < 4; h++) {
          const uint64_t dW = mk_desc(sb, k * 8192 + ((h >> 1) ^ W) * 4096 + (h & 1) * 2048, 0, 1024, 1);
          const uint64_t dX = mk_desc(sb, xo + (h >> 1) * (G_ST / 2) + (h & 1) * 32, 0, 512, 2);
          if (W == 1 && h < 2) wgmma_ss_168<-1, 1, 1, 0>(y, dW, dX, 1);
          else wgmma_ss_168<1, 1, 1, 0>(y, dW, dX, 1);
        }
        if (s <= 26) {
          wg_commit();
          if (W == 0 || k > G_KM) {
            wg_wait<1>();
            if (lane == 0) mbar_arrive(gdone + 8 * (s - 1));
          }
        }
      }
      wg_commit();
    };
    constexpr std::integral_constant<int, 0> c0;
    constexpr std::integral_constant<int, 1> c1;
    auto put = [&](const float (&v)[NB1 / 2], uint32_t stg, int b) {
      const int mi = lane >> 3, i = lane & 7;
      const uint32_t a0 = stg + (mi >> 1) * 1024 + i * 128 + (((2 * warp + (mi & 1)) ^ i) << 4);
      constexpr int J = 21 / G_EPI;
#pragma unroll
      for (int c = 0; c < G_EPI; c++) {
#pragma unroll
        for (int j = c * J; j + 1 < (c + 1) * J; j += 2)
          stsm4t(a0 + j * 1024, pack2(v[4 * j], v[4 * j + 1]), pack2(v[4 * j + 2], v[4 * j + 3]),
                 pack2(v[4 * j + 4], v[4 * j + 5]), pack2(v[4 * j + 6], v[4 * j + 7]));
        const int j = (c + 1) * J - 1;
        asm volatile("stmatrix.sync.aligned.m8n8.x2.trans.shared.b16 [%0], {%1, %2};" ::"r"(a0 + j * 1024),
                     "r"(pack2(v[4 * j], v[4 * j + 1])), "r"(pack2(v[4 * j + 2], v[4 * j + 3])) : "memory");
        fence_async();
        bar_sync(1 + wg, 128);
        if (t == 0) {
          tma_st4<0>(&m.y, stg + c * J * 1024, 0, b * NB1 + c * J * 8, 2 * bin + wg, dc);
          bulk_commit();
        }
      }
    };
    if (wg == 0) {
      tail(y0, c0, c0);
      bar_arrive(4, 256);
      mbar_wait(gdone + 8 * (G_S0 - 1), 0);
      wg_wait<0>();
      reg_fence(y0);
      put(y0, sb + K1_Y0, 0);
      bar_sync(7, 256);
      tail(y1, c1, c0);
      bar_arrive(8, 256);
      if (t == 0) bulk_wait_read<0>();
      wg_wait<0>();
      reg_fence(y1);
      bar_sync(1, 128);
      put(y1, sb + K1_Y0, 1);
    } else {
      wg_wait<0>();
      if (lane == 0) mbar_arrive(gdone + 8 * (G_S0 - 1));
#pragma unroll 1
      for (int h2 = 2 * it; h2 < 16; h2++) {
#pragma unroll
        for (int r = 0; r < 2; r++) {
          t_begin(h2 >> 1, h2 & 1, r);
          wg_wait<0>();
          t_end(h2 >> 1, h2 & 1, r);
        }
      }
      bar_sync(4, 256);
      tail(y0, c0, c1);
      bar_arrive(7, 256);
      mbar_wait(se0, 1);
      mbar_wait(se0 + 8, 1);
      wg_wait<0>();
      reg_fence(y0);
      put(y0, sb + K1_T, 0);
      bar_sync(8, 256);
      tail(y1, c1, c1);
      wg_wait<0>();
      reg_fence(y1);
      put(y1, sb + g_off(g_slot(26)), 1);
    }
    if (t == 0) {
      bulk_wait_read<0>();
    }
  }
}

#define H_EPI 3
#define H_KS 11
#define C_PC 32
constexpr int H_XP = 168 * 64, H_STAGE = 8192 + 2 * H_XP, H_NST = 7, K2_STG = H_NST * H_STAGE, K2_SMEM = K2_STG + 21504 + 1024;

template <int WG>
__device__ __forceinline__ void h_loop(float (&acc)[84], uint32_t sb, uint32_t full0, uint32_t empty0, int lane) {
#pragma unroll 1
  for (int k = 0; k < 16; k++) {
    const int st = k % H_NST;
    if (WG == 1 && k == H_KS) bar_sync(5, 256);
    mbar_wait(full0 + 8 * st, (k / H_NST) & 1);
    const uint32_t base = sb + st * H_STAGE;
    wg_fence();
#pragma unroll
    for (int s = 0; s < 2; s++) {
      const uint64_t dP = mk_desc(base, s * 2048, 0, 1024, 1), dQ = mk_desc(base, 4096 + s * 2048, 0, 1024, 1);
      const uint64_t dA = mk_desc(base, 8192 + s * 32, 0, 1024, 1), dB = mk_desc(base, 8192 + 64 + s * 32, 0, 1024, 1);
      wgmma_ss_168<1, 1, 1, 0>(acc, dP, WG == 0 ? dA : dB, k | s);
      wgmma_ss_168<WG == 0 ? 1 : -1, 1, 1, 0>(acc, dQ, WG == 0 ? dB : dA, 1);
    }
    wg_commit();
    if (WG == 0 && k == 15) bar_arrive(5, 256);
    if (k <= 10) {
      wg_wait<1>();
      if (k > 0 && k - 1 + H_NST < 16 && lane < 2) mbar_arrive_cta(empty0 + 8 * ((k - 1) % H_NST), lane);
    }
  }
  wg_wait<0>();
  reg_fence(acc);
}
template <int C0, int C1> __device__ __forceinline__ void gelu_pack(uint32_t (&p)[12], const float (&h)[24]) {
#pragma unroll
  for (int i = 4 * C0; i < 4 * C1; i++) p[i] = pack2(gelu(h[2 * i]), gelu(h[2 * i + 1]));
}
struct K2Maps {
  int stage[16], item[8], wpre, pad[7];
  CUtensorMap y, xa, xs, w, y2;
};

__global__ void __cluster_dims__(2, 1, 1) __launch_bounds__(512, 1)
k2(const Ptrs gp_, const char* __restrict__ x2, const __grid_constant__ K2Maps m, const __nv_bfloat16* __restrict__ wf,
   const __nv_bfloat16* __restrict__ wo) {
  extern __shared__ __align__(1024) uint8_t smem_k1[];
  const uint32_t sb = s2u(smem_k1);
  const int tid = threadIdx.x, wg = __shfl_sync(0xffffffffu, tid >> 7, 0), t = tid & 127;
  const int warp = __shfl_sync(0xffffffffu, t >> 5, 0), lane = t & 31;
  const int cta = blockIdx.x, rank = cta & 1, dc = cta & 3, bin = cta >> 2;
  const uint32_t sGi = sb + K2_STG, sF = sGi + 6144, bb = sb + K2_STG + 21504;
  const uint32_t yfull = bb, full0 = bb + 128, empty0 = bb + 192, cfull = bb + 256, ready = bb + 320, bfree = bb + 384;
  const int b = cta & 1, j = cta >> 2;
  const int len0 = j < 20 ? 3 : 2, len1 = j >= 12 ? 3 : 2;
  const int n00 = j < 20 ? 3 * j : 2 * j + 20, n01 = j < 12 ? 2 * j : 3 * j - 12, cs0 = 3 - (cta >> 1 & 1);
  auto y_load = [&](int r, int i) {
    tma_ld5<1>(sb + (3 + 2 * r) * H_STAGE + i * 8192, &m.y, yfull + 64 * r + 8 * i, 0, 0, cs0 - 2 * r, 2 * (r ? n01 : n00) + i, b);
  };
  if (wg == 2 && warp == 0) {
    if (lane == 0) {
      prefetch_map(&m.y);
      for (int i = 0; i < 16; i++) mbar_init(yfull + 8 * i, 1);
      fence_bar_init();
    }
    __syncwarp();
    if (lane < 16) mbar_expect(yfull + 8 * lane, lane == 7 ? 6144 : 8192);
    bar_arrive(0, 512);
    asm volatile("barrier.cluster.arrive.relaxed.aligned;" ::: "memory");
    auto c_load = [&](int h) {
      asm volatile("cp.async.bulk.shared::cluster.global.mbarrier::complete_tx::bytes [%0], [%1], %2, [%3];"
                   ::"r"(sGi + 6144 * h), "l"(gp_.img + 1536 * h), "r"(6144 + 2048 * h), "r"(yfull + 56 + 64 * h) : "memory");
    };
    if (lane == 0) {
      c_load(0);
      c_load(1);
      pdl_wait();
      const int r2 = len0 == 2, i2 = r2 ? 2 : 6;
      y_load(0, 2), y_load(0, 0), y_load(0, 1), y_load(1, 0), y_load(0, 4), y_load(0, 3), y_load(r2, i2), y_load(r2, i2 - 1);
      pdl_launch();
    }
    __syncwarp();
  } else {
    if (lane == 0 && wg == 3) {
      for (int i = 0; i < 8; i++) mbar_init(full0 + 64 * warp + 8 * i, warp == 0 ? 1 : warp == 1 ? 16 : 4);
      fence_bar_init();
    }
    if (tid == 0) {
      mbar_init(bfree, 2);
      for (int i = 1; i < 5; i++) mbar_init(bfree + 8 * i, 1);
      mbar_arrive(bfree + 8);
      fence_bar_init();
    }
    if (tid == 128) {
      prefetch_map(&m.xa);
      prefetch_map(&m.xs);
      prefetch_map(&m.w);
      prefetch_map(&m.y2);
    }
    bar_sync(0, 512);
    asm volatile("barrier.cluster.arrive.relaxed.aligned;" ::: "memory");
  }
  if (wg == 2) asm volatile("barrier.cluster.wait.aligned;" ::: "memory");
  mbar_wait(yfull + 56, 0);
  auto idft = [&](float (&h)[24], uint32_t in, uint32_t bar) {
    mbar_wait(bar, 0);
    wg_fence();
#pragma unroll
    for (int k = 0; k < 4; k++) wgmma_ss_48<1, 1, 1, 0>(h, mk_desc(in, k * 2048, 0, 1024, 1), mk_desc(sGi, k * 32, 0, 1024, 1), k);
    wg_commit();
  };
  auto carry_out = [&](const uint32_t (&p)[12], uint32_t dst, uint32_t bar) {
    bar_sync(1 + wg, 128);
#pragma unroll
    for (int v = 0; v < 3; v++)
      asm volatile("st.shared.v4.b32 [%0], {%1, %2, %3, %4};" ::"r"(dst + v * 2048 + t * 16), "r"(p[4 * v]), "r"(p[4 * v + 1]), "r"(p[4 * v + 2]), "r"(p[4 * v + 3]) : "memory");
    __syncwarp();
    if (lane == 0) mbar_arrive(bar);
  };
  if (wg == 3) {
#pragma unroll 1
    for (int r = 0; r < 2; r++) {
      float h[24];
      uint32_t p[12];
      idft(h, sb + (3 + 2 * r) * H_STAGE, yfull + 64 * r);
      wg_wait<0>();
      reg_fence(h);
      gelu_pack<0, 3>(p, h);
      if (j == 0) p[0] = p[1] = p[2] = p[3] = 0;
      carry_out(p, sb + (3 + 2 * r) * H_STAGE, cfull + 32 * r);
    }
    asm volatile("barrier.cluster.wait.aligned;" ::: "memory");
    if (lane == 0) {
      if (warp == 0) {
        auto w_load = [&](int k) {
          mbar_expect(full0 + 8 * (k % H_NST), H_STAGE);
          tma_ld4<1>(sb + (k % H_NST) * H_STAGE, &m.w, full0 + 8 * (k % H_NST), 0, (k & 1) * 32, dc, (7 - (k >> 1)) * 64 + 2 * bin);
        };
        const int wpre = m.wpre;
        for (int k = 0; k < wpre; k++) w_load(k);
#pragma unroll 1
        for (int k = 0; k < 16; k++) {
          const int st = k % H_NST, e = m.stage[k];
          if ((k & 7) == 0) {
            poll_ge(&gp_.done[(6 + (k >> 3)) * 32], 128);
            asm volatile("fence.proxy.async.global;" ::: "memory");
            if (k == 0) mbar_arrive(bfree + 32);
          }
          if (e) mbar_wait(bb + 8 * e, 0);
          if (k == 5) mbar_wait(bfree, 0);
          if (k >= H_NST) mbar_wait(empty0 + 8 * st, ((k / H_NST) - 1) & 1);
          const char* xs = x2 + (((7 - (k >> 2) - (k & 2) * 2) * 64 + (k & 1) * 32 + bin) * 2 + rank) * H_XP;
          asm volatile("cp.async.bulk.shared::cluster.global.mbarrier::complete_tx::bytes.multicast::cluster [%0], [%1], %2, [%3], %4;"
                       ::"r"(sb + st * H_STAGE + 8192 + rank * H_XP), "l"(xs), "n"(H_XP), "r"(full0 + 8 * st), "h"((uint16_t)3) : "memory");
          if (k >= wpre) w_load(k);
          if (k == 8) {
            if (cta == 0) asm volatile("cp.async.bulk.prefetch.L2.global [%0], 6144;" ::"l"(gp_.ga) : "memory");
            asm volatile("cp.async.bulk.prefetch.L2.global [%0], 1024;" ::"l"(wf + cta * 512) : "memory");
            asm volatile("cp.async.bulk.prefetch.L2.global [%0], 1024;" ::"l"(wo + cta * 512) : "memory");
          }
        }
      } else if (warp < 3) {
        const int r = warp - 1, n0 = b * NB2 + (r ? n01 : n00), f0 = (cs0 - 2 * r) * 64;
#pragma unroll 1
        for (int i = 0; i < (r ? len1 : len0); i++) {
          const uint32_t src = sb + (3 + 2 * r) * H_STAGE + i * 16384;
          const int e = m.item[4 * r + i], burst = (16 << (e >> 8)) - 1;
          if (r) mbar_wait(bb + 8 * (e & 255), 0);
          mbar_wait(ready + 32 * r + 8 * i, 0);
          if (!r) {
            tma_st4<0>(&m.xa, src, 0, f0, 0, n0 + i);
            bulk_commit();
            continue;
          }
#pragma unroll 1
          for (int p = 0; p < 128; p += C_PC) {
            tma_st3<0>(&m.xs, src + p * 128, 0, f0 + (p & 63) + (p >> 6) * 256, n0 + i);
            bulk_commit();
            if (((p + C_PC) & burst) == 0) bulk_wait_read<0>();
          }
        }
        asm volatile("cp.async.bulk.wait_group 0;" ::: "memory");
        if (r) {
          mbar_arrive_cta(bfree, 0);
          mbar_arrive_cta(bfree, 1);
        }
        if (!r) mbar_arrive(bfree + 16);
        asm volatile("red.release.gpu.global.add.s32 [%0], 1;" ::"l"(&gp_.done[(6 + r) * 32]) : "memory");
        if (!r) mbar_arrive(bfree + 24);
      }
    }
    return;
  }
#pragma unroll 1
  for (int it = wg; it < len0 + len1; it += 3) {
    const int r = it >= len0, i = it - r * len0;
    const bool last = i + 1 == (r ? len1 : len0);
    const uint32_t in = sb + (3 + 2 * r) * H_STAGE + i * 16384, bar = yfull + 64 * r + 16 * i;
    float h1[24], h2[24];
    uint32_t p0[12], p1[12], p2[12];
    idft(h2, in + 16384, bar + 16);
    if (it == 2 && lane == 0 && 3 + warp - len0 < len1) {
      y_load(1, 2 * (3 + warp - len0) + 2);
      y_load(1, 2 * (3 + warp - len0) + 1);
    }
    if (it > 0) bar_sync(6 + wg, 256);
    wg_wait<0>();
    reg_fence(h2);
    gelu_pack<0, 2>(p2, h2);
    idft(h1, in + 8192, bar + 8);
    if (!last) {
      gelu_pack<2, 3>(p2, h2);
      carry_out(p2, in + 16384, cfull + 32 * r + 8 * i + 8);
    }
    if (it + 1 < len0 + len1) bar_arrive(6 + (wg + 1) % 3, 256);
    mbar_wait(cfull + 32 * r + 8 * i, 0);
#pragma unroll
    for (int v = 0; v < 3; v++)
      asm volatile("ld.shared.v4.b32 {%0, %1, %2, %3}, [%4];" : "=r"(p0[4 * v]), "=r"(p0[4 * v + 1]), "=r"(p0[4 * v + 2]), "=r"(p0[4 * v + 3]) : "r"(in + v * 2048 + t * 16) : "memory");
    if (it < 3) mbar_wait(yfull + 120, 0);
    wg_wait<0>();
    reg_fence(h1);
    gelu_pack<0, 3>(p1, h1);
    if (last && j == 31) {
#pragma unroll
      for (int v = 0; v < 12; v++) p1[v] = p2[v] = 0;
    }
    uint32_t hp[32];
#pragma unroll
    for (int c = 0; c < 8; c++)
#pragma unroll
      for (int v = 0; v < 4; v++) hp[(v >> 1) * 16 + 2 * c + (v & 1)] = c < 3 ? p0[4 * c + v] : c < 6 ? p1[4 * (c - 3) + v] : p2[4 * (c - 6) + v];
    float e0[32], e1[32];
    reg_fence(hp);
    wg_fence();
#pragma unroll
    for (int k = 0; k < 4; k++) {
      const uint64_t db = mk_desc(sF, k * 32, 0, 1024, 1);
      wgmma_rs_64<1, 1, 0>(e0, hp[4 * k], hp[4 * k + 1], hp[4 * k + 2], hp[4 * k + 3], db, k);
      wgmma_rs_64<1, 1, 0>(e1, hp[16 + 4 * k], hp[16 + 4 * k + 1], hp[16 + 4 * k + 2], hp[16 + 4 * k + 3], db, k);
    }
    wg_commit();
    bar_sync(1 + wg, 128);
    wg_wait<0>();
    reg_fence(e0);
    reg_fence(e1);
    {
      const int mi = lane >> 3, rr = (lane & 7) >> 1, blk = b * NB2 + (r ? n01 : n00) + i;
      const uint32_t a0 = in + (mi >> 1) * 8192 + (warp >> 1) * 4096 + rr * 128;
      const uint32_t pos = ((lane & 1) * 4 + (warp & 1) * 2 + (mi & 1)) ^ rr ^ (blk & 7);
#pragma unroll
      for (int q = 0; q < 8; q++)
        stsm4t(a0 + q * 512 + ((pos ^ (q & 1) * 4) << 4), pack2(e0[4 * q], e0[4 * q + 1]), pack2(e0[4 * q + 2], e0[4 * q + 3]),
               pack2(e1[4 * q], e1[4 * q + 1]), pack2(e1[4 * q + 2], e1[4 * q + 3]));
    }
    fence_async();
    __syncwarp();
    if (lane == 0) mbar_arrive(ready + 32 * r + 8 * i);
  }
  if (wg == 2) return;
  asm volatile("barrier.cluster.wait.aligned;" ::: "memory");
  float acc[84];
  if (wg == 0) {
    h_loop<0>(acc, sb, full0, empty0, lane);
  } else {
    h_loop<1>(acc, sb, full0, empty0, lane);
    bar_sync(2, 128);
  }
  const uint32_t stg = sb + (wg == 0 ? H_NST : 9 % H_NST) * H_STAGE;
  const int mi = lane >> 3, i = lane & 7;
  const uint32_t a0 = stg + (mi >> 1) * 1024 + i * 128 + (((2 * warp + (mi & 1)) ^ i) << 4);
  constexpr int J = 21 / H_EPI;
#pragma unroll
  for (int c = 0; c < H_EPI; c++) {
#pragma unroll
    for (int q = c * J; q + 1 < (c + 1) * J; q += 2)
      stsm4t(a0 + q * 1024, pack2(acc[4 * q], acc[4 * q + 1]), pack2(acc[4 * q + 2], acc[4 * q + 3]),
             pack2(acc[4 * q + 4], acc[4 * q + 5]), pack2(acc[4 * q + 6], acc[4 * q + 7]));
    const int q = (c + 1) * J - 1;
    asm volatile("stmatrix.sync.aligned.m8n8.x2.trans.shared.b16 [%0], {%1, %2};" ::"r"(a0 + q * 1024),
                 "r"(pack2(acc[4 * q], acc[4 * q + 1])), "r"(pack2(acc[4 * q + 2], acc[4 * q + 3])) : "memory");
    fence_async();
    bar_sync(1 + wg, 128);
    if (t == 0) {
      tma_st4<0>(&m.y2, stg + c * J * 1024, 0, c * J * 8, 2 * bin + wg, dc);
      bulk_commit();
    }
  }
  if (t == 0) {
    bulk_wait_read<0>();
  }
}

#define E_I1 12
#define E_WAITS 0xA8
#define E_A 0
#define E_EARLY0 5
#define E_EARLY 5
constexpr int E_SMEM = 65536 + 131072 + 32768 + 1024;

__device__ __forceinline__ uint32_t joint2(uint32_t fe, uint32_t g0, uint32_t g1) {
  uint32_t s0, s1;
  asm("{\n.reg .b16 l, h;\n.reg .b32 ll, hh;\nmov.b32 {l, h}, %2;\nmov.b32 ll, {l, l};\nmov.b32 hh, {h, h};\n"
      "fma.rn.bf16x2 %0, ll, %5, %3;\nfma.rn.bf16x2 %1, hh, %5, %4;\n}"
      : "=r"(s0), "=r"(s1) : "r"(fe), "r"(g0), "r"(g1), "r"(0x3F800000u));
  return pack2(tanh_f32(__uint_as_float(s0)), tanh_f32(__uint_as_float(s1)));
}
__device__ __forceinline__ uint4 lds128(uint32_t a) {
  uint4 v;
  asm volatile("ld.shared.v4.u32 {%0, %1, %2, %3}, [%4];" : "=r"(v.x), "=r"(v.y), "=r"(v.z), "=r"(v.w) : "r"(a));
  return v;
}
__device__ __forceinline__ void joint_group(uint32_t (&ja)[8], const uint32_t* fe, const uint4& c0, const uint4& c1) {
  ja[0] = joint2(fe[0], c0.x, c0.y);
  ja[1] = joint2(fe[1], c0.x, c0.y);
  ja[2] = joint2(fe[2], c0.z, c0.w);
  ja[3] = joint2(fe[3], c0.z, c0.w);
  ja[4] = joint2(fe[4], c1.x, c1.y);
  ja[5] = joint2(fe[5], c1.x, c1.y);
  ja[6] = joint2(fe[6], c1.z, c1.w);
  ja[7] = joint2(fe[7], c1.z, c1.w);
  reg_fence(ja);
}

__global__ void __launch_bounds__(256, 1)
kE(const __grid_constant__ CUtensorMap my, const __grid_constant__ CUtensorMap mwf, const __grid_constant__ CUtensorMap mwo,
   const __grid_constant__ CUtensorMap mout) {
  const Ptrs gp_ = {g_done, g_ge, c_img, c_ga};
  extern __shared__ uint8_t smem_raw[];
  __shared__ __align__(8) uint64_t bars[17];
  const uint32_t sb = (s2u(smem_raw) + 1023) & ~1023u;
  const int tid = threadIdx.x, wg = __shfl_sync(0xffffffffu, tid >> 7, 0), t = tid & 127, warp = t >> 5, lane = t & 31;
  const uint32_t R0 = sb, R1 = sb + 65536, R2 = sb + 65536 + 131072;
  const uint32_t barY = s2u(&bars[0]), barO = barY + 32, barF = barY + 64, barA = barY + 128;
  const int b = blockIdx.x / 63, t0 = (blockIdx.x % 63) * 64;
  const int a = t0 / 48, o = t0 % 48;
  const int qw = o + 16 * warp, sel = qw >= 48;
  uint32_t ga[16];
#pragma unroll
  for (int s = 0; s < 4; s++)
    ldg128(reinterpret_cast<const uint4*>(gp_.ga) + ((qw >> 4) - 3 * sel) * 128 + s * 32 + lane, ga[4 * s], ga[4 * s + 1], ga[4 * s + 2], ga[4 * s + 3]);
  uint4 gev0, gev1;
  asm volatile("ld.global.cg.v4.u32 {%0, %1, %2, %3}, [%4];" : "=r"(gev0.x), "=r"(gev0.y), "=r"(gev0.z), "=r"(gev0.w)
               : "l"(reinterpret_cast<const uint4*>(gp_.ge) + (b * 8 + wg * 4) * 64 + t));
  asm volatile("ld.global.cg.v4.u32 {%0, %1, %2, %3}, [%4];" : "=r"(gev1.x), "=r"(gev1.y), "=r"(gev1.z), "=r"(gev1.w)
               : "l"(reinterpret_cast<const uint4*>(gp_.ge) + (b * 8 + wg * 4) * 64 + 128 + t));
  auto f_load = [&](int q) {
    const int p = (0x37156240 >> (4 * q)) & 7;
    mbar_expect(barF + 8 * p, 16384);
    tma_ld3<0>(R1 + p * 16384, &mwf, barF + 8 * p, 0, (p >> 1) * 64, (p & 1) * 2);
  };
  if (tid == 0) {
    prefetch_map(&my);
    for (int i = 0; i < 16; i++) mbar_init(barY + 8 * i, 1);
    mbar_init(barA, 8);
    fence_bar_init();
    prefetch_map(&mwf);
    pdl_wait();
    for (int i = 0; i < 4; i++) {
      mbar_expect(barY + 8 * i, 16384);
      tma_ld5<0>(R0 + i * 16384, &my, barY + 8 * i, 0, 0, 2 * (i & 1) + (i >> 1), a, b);
    }
    for (int q = 0; q < 4; q++) f_load(q);
  }
  if (tid == 64) {
    prefetch_map(&mwo);
    prefetch_map(&mout);
  }
  uint32_t gs[32];
#pragma unroll
  for (int i = 0; i < 16; i++) {
    gs[i] = sel ? 0u : ga[i];
    gs[16 + i] = sel ? ga[i] : 0u;
  }
  __syncthreads();
  if (blockIdx.x == 125 && tid < 8) gp_.done[tid * 32] = 0;
  reg_fence(gs);
  uint32_t gp = R2 + 16384 + wg * 4096 + (lane & 3) * 16;
  uint4 g0, g1;
  uint32_t fe[64];
  {
    float d0[32], d1[32], e[64];
    mbar_wait(barY + 8 * wg, 0);
    wg_fence();
#pragma unroll
    for (int k = 0; k < 8; k++)
      wgmma_rs_64<1, 1, 1>(d0, gs[4 * k], gs[4 * k + 1], gs[4 * k + 2], gs[4 * k + 3], mk_desc(R0 + wg * 16384, k * 2048, 0, 1024, 1), k);
    wg_commit();
    if (tid == 128)
      for (int q = 4; q < 8; q++) f_load(q);
    wg_wait<0>();
    reg_fence(d0);
    uint32_t p0[16], p1[16];
    const uint32_t wfo = R1 + wg * (65536 + 16384), wfx = R1 + 65536 - wg * (65536 - 16384), fx = R2 + 16384 - wg * 16384;
    const uint32_t fo = R2 + wg * 16384 + (warp * 16 + (lane & 7) + ((lane >> 3) & 1) * 8) * 128;
    auto fe_own = [&](const uint32_t (&p)[16], int c) {
      wg_fence();
#pragma unroll
      for (int s = 0; s < 4; s++)
        wgmma_rs_128<1, 1, 1>(e, p[4 * s], p[4 * s + 1], p[4 * s + 2], p[4 * s + 3], mk_desc(wfo, c * 32768 + s * 2048, 8192, 1024, 1), c | s);
    };
    auto fe_other = [&](int c) {
      wg_fence();
#pragma unroll
      for (int s = 0; s < 4; s++)
        wgmma_ss_128<1, 1, 0, 1>(e, mk_desc(fx, c * 8192 + s * 32, 0, 1024, 1), mk_desc(wfx, c * 32768 + s * 2048, 8192, 1024, 1), 1);
    };
    auto f_store = [&](const uint32_t (&p)[16], int c) {
#pragma unroll
      for (int s = 0; s < 4; s++) stsm4(fo + c * 8192 + (((2 * s + (lane >> 4)) ^ (lane & 7)) << 4), p[4 * s], p[4 * s + 1], p[4 * s + 2], p[4 * s + 3]);
    };
#pragma unroll
    for (int i = 0; i < E_I1; i++) p0[i] = pack2(gelu(d0[2 * i]), gelu(d0[2 * i + 1]));
    mbar_wait(barY + 8 * (2 + wg), 0);
    wg_fence();
#pragma unroll
    for (int k = 0; k < 8; k++)
      wgmma_rs_64<1, 1, 1>(d1, gs[4 * k], gs[4 * k + 1], gs[4 * k + 2], gs[4 * k + 3], mk_desc(R0 + wg * 16384, 32768 + k * 2048, 0, 1024, 1), k);
    wg_commit();
#pragma unroll
    for (int i = E_I1; i < 16; i++) p0[i] = pack2(gelu(d0[2 * i]), gelu(d0[2 * i + 1]));
    reg_fence(p0);
    f_store(p0, 0);
    const uint32_t bfo = barF + 40 * wg, bfx = barF + 32 - 24 * wg;
    auto o_load = [&](int kc) {
      mbar_expect(barO + 8 * kc, 32768);
      tma_ld3<0>(kc < 2 ? R0 + kc * 32768 : R1 + (kc - 2) * 65536, &mwo, barO + 8 * kc, 0, kc * 64, 0);
    };
    wg_wait<0>();
    reg_fence(d1);
    if (wg == 1) {
      fence_async();
      bar_arrive(8, 256);
    }
#pragma unroll
    for (int i = 0; i < 16; i++) p1[i] = pack2(gelu(d1[2 * i]), gelu(d1[2 * i + 1]));
    reg_fence(p1);
    if (wg == 0) {
      mbar_wait(bfo, 0);
      fe_own(p0, 0);
      mbar_wait(bfx, 0);
      bar_sync(8, 256);
      fe_other(0);
      wg_commit();
      if (t == 0) {
        o_load(0);
        o_load(1);
      }
      f_store(p1, 1);
      mbar_wait(bfo + 16, 0);
      fe_own(p1, 1);
      fence_async();
      mbar_wait(bfx + 16, 0);
      bar_sync(7, 256);
      fe_other(1);
      wg_commit();
      bar_arrive(4, 256);
      wg_wait<1>();
      if (lane == 0) mbar_arrive(barA);
      bar_sync(1, 128);
    } else {
      f_store(p1, 1);
      fence_async();
      bar_arrive(7, 256);
      mbar_wait(bfo, 0);
      mbar_wait(bfx, 0);
      bar_sync(4, 256);
      fe_own(p0, 0);
      fe_other(0);
      wg_commit();
      mbar_wait(bfo + 16, 0);
      mbar_wait(bfx + 16, 0);
      fe_own(p1, 1);
      wg_commit();
      wg_wait<1>();
      if (lane == 0) mbar_arrive(barA);
      fe_other(1);
      wg_commit();
      mbar_wait(barA, 0);
      if (t == 0) {
        o_load(2);
        o_load(3);
      }
    }
    asm volatile("st.shared.v4.u32 [%0], {%1, %2, %3, %4};" ::"r"(R2 + 16384 + wg * 4096 + ((t * 16) ^ (wg * 512))), "r"(gev0.x), "r"(gev0.y), "r"(gev0.z), "r"(gev0.w) : "memory");
    asm volatile("st.shared.v4.u32 [%0], {%1, %2, %3, %4};" ::"r"(R2 + 16384 + wg * 4096 + 2048 + ((t * 16) ^ (wg * 512))), "r"(gev1.x), "r"(gev1.y), "r"(gev1.z), "r"(gev1.w) : "memory");
    bar_sync(1 + wg, 128);
    g0 = lds128(gp);
    g1 = lds128(gp + 64);
    wg_wait<0>();
    reg_fence(e);
#pragma unroll
    for (int i = 0; i < 32; i++) fe[i] = pack2(e[2 * i], e[2 * i + 1]);
  }
  auto publish = [&]() {
    bar_sync(1 + wg, 128);
    const int row = warp * 16 + (lane & 7) + ((lane >> 3) & 1) * 8;
    const uint32_t xb = R1 + (wg == 0 ? 3 * 32768 : 32768 + 16384) + row * 128;
#pragma unroll
    for (int s = 0; s < 8; s++) {
      const int jj = 2 * s + (lane >> 4);
      stsm4(xb + (s >> 2) * 8192 + (((jj & 7) ^ (lane & 7)) << 4), fe[4 * s], fe[4 * s + 1], fe[4 * s + 2], fe[4 * s + 3]);
    }
    bar_arrive(5 + wg, 256);
  };
  if (wg == 1) publish();
  const uint32_t stg = R1 + 32768 + wg * 65536;
  const uint32_t w0 = sb + wg * 65536, w1 = sb + 32768 + wg * 98304, w2 = sb + 65536 - wg * 65536, w3 = sb + 131072 - wg * 98304;
  float acc[128];
  uint32_t j0[8], j1[8], j2[8], j3[8];
  uint4 h0 = lds128(gp + 128), h1 = lds128(gp + 192);
  const uint32_t bo0 = barO + 16 * wg, bo2 = barO + 16 * (1 - wg);
  joint_group(j0, fe, g0, g1);
  g0 = lds128(gp + 256);
  g1 = lds128(gp + 320);
  mbar_wait(barY, 0);
  joint_group(j1, fe + 8, h0, h1);
#define E_MMA2(J, W, OFF, FIRSTK)                                                                       \
  wgmma_rs_256<1, 1, 1>(acc, J[0], J[1], J[2], J[3], mk_desc(W, OFF, 8192, 1024, 1), FIRSTK);           \
  wgmma_rs_256<1, 1, 1>(acc, J[4], J[5], J[6], J[7], mk_desc(W, (OFF) + 2048, 8192, 1024, 1), 1);
#define E_TOKEN(N) \
  if ((ui + wg == 0 ? E_EARLY0 : E_EARLY) == (N) && (ui < 3 || wg == 0)) bar_arrive(4 - wg, 256);
#define E_BLOCK(N, J, W, BAR, JN, C0, C1, L0, L1)     \
  L0 = lds128(gp + 128 * (N) + 256);                  \
  L1 = lds128(gp + 128 * (N) + 320);                  \
  E_TOKEN((N) - 1)                                    \
  if (ui == 0) mbar_wait(BAR, 0);                     \
  if (E_WAITS >> (N) & 1) wg_wait<1>();               \
  wg_fence();                                         \
  E_MMA2(J, W, ((N) & 1) * 4096, 1)                   \
  wg_commit();                                        \
  if ((N) < 7) joint_group(JN, fe + 8 * (((N) + 1) & 7), C0, C1);
#pragma unroll 1
  for (int ui = 0; ui < 4; ui++) {
    h0 = lds128(gp + 384);
    h1 = lds128(gp + 448);
    if (ui == 0) mbar_wait(bo0, 0);
    if (ui > 0 || wg == 1) bar_sync(3 + wg, 256);
    wg_fence();
#pragma unroll
    for (int i = 0; i < 4; i++) {
      if (E_A && i == E_A) {
        if (ui == 0) mbar_wait(bo0, 0);
        wg_fence();
      }
      if (i < 2) wgmma_rs_256<1, 1, 1>(acc, j0[4 * i], j0[4 * i + 1], j0[4 * i + 2], j0[4 * i + 3], mk_desc(w0, i * 2048, 8192, 1024, 1), i);
      else wgmma_rs_256<1, 1, 1>(acc, j1[4 * i - 8], j1[4 * i - 7], j1[4 * i - 6], j1[4 * i - 5], mk_desc(w0, i * 2048, 8192, 1024, 1), 1);
    }
    wg_commit();
    if (E_A == 4 && ui == 0) mbar_wait(bo0, 0);
    joint_group(j2, fe + 16, g0, g1);
    E_BLOCK(2, j2, w1, bo0 + 8, j3, h0, h1, g0, g1)
    if (ui == 0) {
      if (wg == 0) publish();
      bar_sync(6 - wg, 256);
      const int row = warp * 16 + (lane & 7) + ((lane >> 3) & 1) * 8;
      const uint32_t xb = R1 + (wg == 1 ? 3 * 32768 : 32768 + 16384) + row * 128;
#pragma unroll
      for (int s = 0; s < 8; s++) {
        const int jj = 2 * s + (lane >> 4);
        ldsm4(xb + (s >> 2) * 8192 + (((jj & 7) ^ (lane & 7)) << 4), fe[32 + 4 * s], fe[33 + 4 * s], fe[34 + 4 * s], fe[35 + 4 * s]);
      }
    }
    E_BLOCK(3, j3, w1, bo0 + 8, j0, g0, g1, h0, h1)
    E_BLOCK(4, j0, w2, bo2, j1, h0, h1, g0, g1)
    E_BLOCK(5, j1, w2, bo2, j2, g0, g1, h0, h1)
    E_BLOCK(6, j2, w3, bo2 + 8, j3, h0, h1, g0, g1)
    E_BLOCK(7, j3, w3, bo2 + 8, j0, g0, g1, h0, h1)
    gp += 1024;
    if (ui < 3) {
      joint_group(j0, fe, g0, g1);
      g0 = lds128(gp + 256);
      g1 = lds128(gp + 320);
      if (ui == 0) mbar_wait(bo2 + 8, 0);
      joint_group(j1, fe + 8, h0, h1);
    }
    if (t == 0) bulk_wait_read<0>();
    bar_sync(1 + wg, 128);
    wg_wait<0>();
    reg_fence(acc);
    const uint32_t rb = stg + (warp * 16 + (lane & 7) + ((lane >> 3) & 1) * 8) * 128;
#pragma unroll
    for (int h = 0; h < 2; h++) {
#pragma unroll
      for (int j = 16 * h; j < 16 * h + 16; j += 2) {
        const int jj = j + (lane >> 4);
        stsm4(rb + (j >> 3) * 8192 + (((jj & 7) ^ (lane & 7)) << 4), pack2(acc[4 * j], acc[4 * j + 1]), pack2(acc[4 * j + 2], acc[4 * j + 3]),
              pack2(acc[4 * j + 4], acc[4 * j + 5]), pack2(acc[4 * j + 6], acc[4 * j + 7]));
      }
      fence_async();
      bar_sync(1 + wg, 128);
      if (t == 0) {
        tma_st5<1>(&mout, stg + h * 16384, 0, t0, 2 * h, wg * 4 + ui, b);
        bulk_commit();
      }
    }
  }
  if (t == 0) bulk_wait_read<0>();
}

typedef CUresult (*EncodeFn)(CUtensorMap*, CUtensorMapDataType, cuuint32_t, void*, const cuuint64_t*, const cuuint64_t*,
                             const cuuint32_t*, const cuuint32_t*, CUtensorMapInterleave, CUtensorMapSwizzle,
                             CUtensorMapL2promotion, CUtensorMapFloatOOBfill);

CUtensorMap make_map(EncodeFn fn, const void* base, int rank, const uint64_t* dims, const uint64_t* strides, const uint32_t* box,
                     CUtensorMapSwizzle swz) {
  CUtensorMap m;
  cuuint64_t gd[5], gs[4];
  cuuint32_t bx[5], es[5];
  for (int i = 0; i < rank; i++) { gd[i] = dims[i]; bx[i] = box[i]; es[i] = 1; }
  for (int i = 0; i + 1 < rank; i++) gs[i] = strides[i];
  fn(&m, CU_TENSOR_MAP_DATA_TYPE_BFLOAT16, rank, const_cast<void*>(base), gd, gs, bx, es, CU_TENSOR_MAP_INTERLEAVE_NONE, swz,
     CU_TENSOR_MAP_L2_PROMOTION_NONE, CU_TENSOR_MAP_FLOAT_OOB_FILL_NONE);
  return m;
}

template <typename... KArgs, typename... Args>
void launch(void (*k)(KArgs...), int grid, int block, int smem, bool pdl, Args... args) {
  cudaLaunchConfig_t c = {};
  c.gridDim = dim3(grid);
  c.blockDim = dim3(block);
  c.dynamicSmemBytes = smem;
  c.stream = cudaStreamPerThread;
  cudaLaunchAttribute at[1];
  at[0].id = cudaLaunchAttributeProgrammaticStreamSerialization;
  at[0].val.programmaticStreamSerializationAllowed = 1;
  c.attrs = at;
  c.numAttrs = pdl ? 1 : 0;
  cudaLaunchKernelEx(&c, k, args...);
}

}

static uint32_t h_plan[67 + 25] = {
    0x6108, 0x6109, 0x610a, 0x610b, 0x6101, 0x8008, 0x8109, 0x820a, 0x830b, 0x8401,
    0x8508, 0x6102, 0x8609, 0x870a, 0x880b, 0x6103, 0x8a08, 0x8b02, 0x8c09, 0x8d0a,
    0x8e0b, 0x8f03, 0x9008, 0x9209, 0x930a, 0x9503, 0x9608, 0x9709, 0x980a, 0x9a08,
    0x9b09, 0x9c0a, 0x61616115, 0x6161610d, 0x61616107, 0x83816166, 0x8986610c, 0x8a89314d, 0x8f8a3237, 0x938f940b,
    0x9393344c, 0x9993354d, 0x0, 0x0, 0x0, 0x0, 0x0, 0x0, 0x6161ba98, 0x6161a981,
    0x6789281b, 0x67893ba9, 0x6891a928, 0x6891983b, 0x6999983a, 0x6999a98a, 0x39389d, 0x3, 0x4, 0x1dcc17b8,
    0x8f6a0c52, 0xac1, 0x2e5a9261, 0x194a, 0x9e, 0x9f, 0x37, 0x0, 0x0, 0x0,
    0x10, 0x11, 0x13, 0x14, 0x0, 0x0, 0x0, 0x0, 0x0, 0x0,
    0x0, 0x0, 0x0, 0x431, 0x431, 0x431, 0x0, 0x133, 0x131, 0x331,
    0x0, 0x3,
};

extern "C" void kernel_launch(void* const* d_in, const int* in_sizes, int n_in, void* d_out, int out_size) {
  const __nv_bfloat16* x = (const __nv_bfloat16*)d_in[0];
  const __nv_bfloat16* w1 = (const __nv_bfloat16*)d_in[1];
  const __nv_bfloat16* w2 = (const __nv_bfloat16*)d_in[2];
  const __nv_bfloat16* g = (const __nv_bfloat16*)d_in[3];
  const __nv_bfloat16* wf = (const __nv_bfloat16*)d_in[4];
  const __nv_bfloat16* wgt = (const __nv_bfloat16*)d_in[5];
  const __nv_bfloat16* wo = (const __nv_bfloat16*)d_in[6];

  void* fp = nullptr;
  cudaDriverEntryPointQueryResult qr;
  cudaGetDriverEntryPoint("cuTensorMapEncodeTiled", &fp, cudaEnableDefault, &qr);
  EncodeFn fn = (EncodeFn)fp;
  void *X1, *W2, *Y1, *X2, *Y2;
  cudaGetSymbolAddress(&X1, g_X1);
  cudaGetSymbolAddress(&W2, g_W2);
  cudaGetSymbolAddress(&Y1, g_Y1);
  cudaGetSymbolAddress(&X2, g_X2);
  cudaGetSymbolAddress(&Y2, g_Y2);
  cudaFuncSetAttribute(k1, cudaFuncAttributeMaxDynamicSharedMemorySize, K1_SMEM);
  cudaFuncSetAttribute(k2, cudaFuncAttributeMaxDynamicSharedMemorySize, K2_SMEM);
  cudaFuncSetAttribute(kE, cudaFuncAttributeMaxDynamicSharedMemorySize, E_SMEM);
  if (ALIAS) {
    W2 = d_out;
    X2 = (char*)d_out + sizeof(g_W2);
    X1 = (char*)X2 - sizeof(g_X2);
    Y2 = Y1;
  }
  const CUtensorMapSwizzle S128 = CU_TENSOR_MAP_SWIZZLE_128B;

  auto map_x = [&]() {
    uint64_t d[] = {64, 8000, 8, 2}, s[] = {1024, 128, 8000ull * 1024};
    uint32_t bx[] = {64, 56, 1, 1};
    return make_map(fn, x, 4, d, s, bx, S128);
  };
  auto map_w_in = [&](const __nv_bfloat16* w, int odd) {
    uint64_t d[] = {64, (uint64_t)(odd ? 15 : 16), 4, 256}, s[] = {2ull * 65536 * 2, 128, 512};
    uint32_t bx[] = {64, 16, 2, 1};
    return make_map(fn, w + (odd ? 65536 : 0), 4, d, s, bx, S128);
  };
  auto map_X_st = [&](void* p, int nb, int boxb) {
    uint64_t d[] = {64, 512, (uint64_t)(2 * nb)}, s[] = {2ull * nb * 128, 128};
    uint32_t bx[] = {64, C_PC, (uint32_t)boxb};
    return make_map(fn, p, 3, d, s, bx, S128);
  };
  auto map_X1_st = [&]() {
    uint64_t d[] = {64, 512, 2, (uint64_t)NB1}, s[] = {2ull * NB1 * 128, (uint64_t)NB1 * 128, 128};
    uint32_t bx[] = {64, 16, 1, 1};
    return make_map(fn, X1, 4, d, s, bx, S128);
  };
  auto map_W_st = [&](void* p) {
    uint64_t d[] = {64, 512, 4, 64}, s[] = {32768, 8192, 128};
    uint32_t bx[] = {64, W2_PC < 64 ? W2_PC : 64, W2_PC == 128 ? 2 : 1, 1};
    return make_map(fn, p, 4, d, s, bx, S128);
  };
  auto map_W_ld = [&](void* p, uint32_t bd, uint32_t bf) {
    uint64_t d[] = {64, 64, 4, 512}, s[] = {128, 8192, 32768};
    uint32_t bx[] = {64, 32, bd, bf};
    return make_map(fn, p, 4, d, s, bx, S128);
  };
  auto map_Y_st = [&](void* p, int nb, int rows) {
    uint64_t d[] = {64, (uint64_t)(2 * nb), 64, 4}, s[] = {32768, 128, 8192};
    uint32_t bx[] = {64, (uint32_t)rows, 1, 1};
    return make_map(fn, p, 4, d, s, bx, S128);
  };
  auto map_Y_ld = [&](void* p, int nb, int boxc, int boxb) {
    uint64_t d[] = {64, 64, 4, (uint64_t)nb, 2}, s[] = {128, 8192, 32768, (uint64_t)nb * 32768};
    uint32_t bx[] = {64, 64, (uint32_t)boxc, (uint32_t)boxb, 1};
    return make_map(fn, p, 5, d, s, bx, S128);
  };
  auto map_wsq = [&](const __nv_bfloat16* w, uint32_t bn) {
    uint64_t d[] = {64, 256, 4}, s[] = {512, 128};
    uint32_t bx[] = {64, 64, bn};
    return make_map(fn, w, 3, d, s, bx, S128);
  };
  auto map_out = [&]() {
    uint64_t d[] = {64, 4000, 4, 8, 2}, s[] = {4096, 128, 512, 4000ull * 4096};
    uint32_t bx[] = {64, 64, 2, 1, 1};
    return make_map(fn, d_out, 5, d, s, bx, S128);
  };

  auto map_w_raw = [&](const __nv_bfloat16* w, int odd) {
    uint64_t d[] = {256, (uint64_t)(odd ? 15 : 16), 16, 16}, s[] = {2ull * 65536 * 2, 512, 8192};
    uint32_t bx[] = {64, 16, 4, 2};
    return make_map(fn, w + (odd ? 65536 : 0), 4, d, s, bx, S128);
  };
  Ptrs gp;
  cudaGetSymbolAddress((void**)&gp.done, g_done);
  cudaGetSymbolAddress((void**)&gp.ge, g_ge);
  cudaGetSymbolAddress((void**)&gp.img, c_img);
  cudaGetSymbolAddress((void**)&gp.ga, c_ga);
  K1Maps g1;
  memcpy(&g1.p, h_plan, sizeof(Plan));
  g1.x = map_x();
  g1.we = map_w_raw(w1, 0);
  g1.wo = map_w_raw(w1, 1);
  g1.xs = map_X1_st();
  g1.y = map_Y_st(Y1, NB1, NB1 / G_EPI);
  g1.w2e = map_w_in(w2, 0);
  g1.w2o = map_w_in(w2, 1);
  g1.w2s = map_W_st(W2);
  for (int s = 0; s < 32; s++) {
    const int k = s < G_S0 ? s >> 1 : G_KM + (s - G_S0) % G_TK;
    g1.slot[s] = g_off(g_slot(s)) / 16;
    g1.src[s] = ((k >> 1) * 256 + (k & 1) * 2 + (s < G_S0 ? (s & 1) * 4 : s >= G_S0 + G_TK)) * (G_ST / 2);
    g1.dep[s] = s < 3 ? 8 * h_plan[64 + s] : 1536 + 8 * (s - g_depth(s));
  }
  launch(k1, 132, 384, K1_SMEM, false, gp, (const char*)X1, (const char*)w1, g1, g, wgt);
  K2Maps g2;
  memcpy(&g2, h_plan + 67, 100);
  g2.y = map_Y_ld(Y1, NB1, 1, 1);
  g2.xs = map_X_st(X2, NB2, 1);
  {
    uint64_t d[] = {64, 256, 2, 2 * NB2}, s[] = {2ull * NB2 * 128, 512ull * NB2 * 128, 128};
    uint32_t bx[] = {64, 64, 2, 1};
    g2.xa = make_map(fn, X2, 4, d, s, bx, S128);
  }
  g2.w = map_W_ld(W2, 1, 2);
  g2.y2 = map_Y_st(Y2, NB2, 168 / H_EPI);
  launch(k2, 128, 512, K2_SMEM, true, gp, (const char*)X2, g2, wf, wo);
  launch(kE, 126, 256, E_SMEM, true, map_Y_ld(Y2, NB2, 1, 2), map_wsq(wf, 2), map_wsq(wo, 4), map_out());
}
```

```cpp
#include <cuda_runtime.h>
#include <cuda_bf16.h>
#include <cuda.h>
#include <stdint.h>
#include <string.h>
#include <type_traits>

#define ALIAS 1
namespace {

constexpr int NB1 = 168;
constexpr int NB2 = 84;

__device__ __align__(1024) __nv_bfloat16 g_X1[8 * 64 * 2 * NB1 * 64];
__device__ __align__(1024) __nv_bfloat16 g_W2[8 * 64 * 4 * 64 * 64];
__device__ __align__(1024) __nv_bfloat16 g_Y1[2 * NB1 * 4 * 64 * 64];
__device__ __align__(1024) __nv_bfloat16 g_X2[8 * 64 * 2 * NB2 * 64];
__device__ __align__(1024) __nv_bfloat16 g_Y2[2 * NB2 * 4 * 64 * 64];
__device__ __align__(1024) float g_ge[16 * 256];

__device__ __forceinline__ uint32_t s2u(const void* p) { return (uint32_t)__cvta_generic_to_shared(p); }
__device__ __forceinline__ void mbar_init(uint32_t b, int c) {
  asm volatile("mbarrier.init.shared::cta.b64 [%0], %1;" ::"r"(b), "r"(c) : "memory");
}
__device__ __forceinline__ void mbar_expect(uint32_t b, int bytes) {
  asm volatile("mbarrier.arrive.expect_tx.shared::cta.b64 _, [%0], %1;" ::"r"(b), "r"(bytes) : "memory");
}
__device__ __forceinline__ void mbar_arrive(uint32_t b) {
  asm volatile("mbarrier.arrive.shared::cta.b64 _, [%0];" ::"r"(b) : "memory");
}
__device__ __forceinline__ void mbar_arrive_cta(uint32_t b, uint32_t cta) {
  asm volatile("{\n.reg .b32 r;\nmapa.shared::cluster.u32 r, %0, %1;\nmbarrier.arrive.shared::cluster.b64 _, [r];\n}" ::"r"(b), "r"(cta) : "memory");
}
__device__ __forceinline__ void mbar_wait(uint32_t b, int ph) {
  asm volatile(
      "{\n.reg .pred p;\n.reg .u32 n;\n"
      "mov.u32 n, 0;\n"
      "MBW_LOOP:\n"
      "mbarrier.try_wait.parity.shared::cta.b64 p, [%0], %1;\n"
      "@p bra MBW_DONE;\n"
      "add.u32 n, n, 1;\n"
      "setp.lt.u32 p, n, 1048576;\n"
      "@p bra MBW_LOOP;\n"
      "MBW_DONE:\n}" ::"r"(b), "r"(ph) : "memory");
}
__device__ __forceinline__ void fence_bar_init() { asm volatile("fence.mbarrier_init.release.cluster;" ::: "memory"); }
__device__ __forceinline__ void fence_async() { asm volatile("fence.proxy.async.shared::cta;" ::: "memory"); }
__device__ __forceinline__ void bar_sync(int id, int n) { asm volatile("bar.sync %0, %1;" ::"r"(id), "r"(n) : "memory"); }
__device__ __forceinline__ void bar_arrive(int id, int n) { asm volatile("bar.arrive %0, %1;" ::"r"(id), "r"(n) : "memory"); }
__device__ __forceinline__ void pdl_wait() { asm volatile("griddepcontrol.wait;" ::: "memory"); }
__device__ __forceinline__ void pdl_launch() { asm volatile("griddepcontrol.launch_dependents;" ::: "memory"); }
__device__ __forceinline__ void prefetch_map(const CUtensorMap* m) {
  asm volatile("prefetch.tensormap [%0];" ::"l"(m) : "memory");
}
template <int P> __device__ __forceinline__ uint64_t policy() {
  uint64_t p;
  asm("createpolicy.fractional.L2::evict_first.b64 %0, 1.0;" : "=l"(p));
  return p;
}
template <int P> __device__ __forceinline__ void tma_ld3(uint32_t dst, const CUtensorMap* m, uint32_t bar, int c0, int c1, int c2) {
  if constexpr (P == 0)
    asm volatile("cp.async.bulk.tensor.3d.shared::cluster.global.mbarrier::complete_tx::bytes [%0], [%1, {%3, %4, %5}], [%2];"
                 ::"r"(dst), "l"(m), "r"(bar), "r"(c0), "r"(c1), "r"(c2) : "memory");
  else
    asm volatile("cp.async.bulk.tensor.3d.shared::cluster.global.mbarrier::complete_tx::bytes.L2::cache_hint [%0], [%1, {%3, %4, %5}], [%2], %6;"
                 ::"r"(dst), "l"(m), "r"(bar), "r"(c0), "r"(c1), "r"(c2), "l"(policy<P>()) : "memory");
}
template <int P> __device__ __forceinline__ void tma_ld4(uint32_t dst, const CUtensorMap* m, uint32_t bar, int c0, int c1, int c2, int c3) {
  if constexpr (P == 0)
    asm volatile("cp.async.bulk.tensor.4d.shared::cluster.global.mbarrier::complete_tx::bytes [%0], [%1, {%3, %4, %5, %6}], [%2];"
                 ::"r"(dst), "l"(m), "r"(bar), "r"(c0), "r"(c1), "r"(c2), "r"(c3) : "memory");
  else
    asm volatile("cp.async.bulk.tensor.4d.shared::cluster.global.mbarrier::complete_tx::bytes.L2::cache_hint [%0], [%1, {%3, %4, %5, %6}], [%2], %7;"
                 ::"r"(dst), "l"(m), "r"(bar), "r"(c0), "r"(c1), "r"(c2), "r"(c3), "l"(policy<P>()) : "memory");
}
template <int P> __device__ __forceinline__ void tma_ld5(uint32_t dst, const CUtensorMap* m, uint32_t bar, int c0, int c1, int c2, int c3, int c4) {
  if constexpr (P == 0)
    asm volatile("cp.async.bulk.tensor.5d.shared::cluster.global.mbarrier::complete_tx::bytes [%0], [%1, {%3, %4, %5, %6, %7}], [%2];"
                 ::"r"(dst), "l"(m), "r"(bar), "r"(c0), "r"(c1), "r"(c2), "r"(c3), "r"(c4) : "memory");
  else
    asm volatile("cp.async.bulk.tensor.5d.shared::cluster.global.mbarrier::complete_tx::bytes.L2::cache_hint [%0], [%1, {%3, %4, %5, %6, %7}], [%2], %8;"
                 ::"r"(dst), "l"(m), "r"(bar), "r"(c0), "r"(c1), "r"(c2), "r"(c3), "r"(c4), "l"(policy<P>()) : "memory");
}
template <int P> __device__ __forceinline__ void tma_st3(const CUtensorMap* m, uint32_t src, int c0, int c1, int c2) {
  if constexpr (P == 0)
    asm volatile("cp.async.bulk.tensor.3d.global.shared::cta.bulk_group [%0, {%2, %3, %4}], [%1];" ::"l"(m), "r"(src), "r"(c0), "r"(c1), "r"(c2) : "memory");
  else
    asm volatile("cp.async.bulk.tensor.3d.global.shared::cta.bulk_group.L2::cache_hint [%0, {%2, %3, %4}], [%1], %5;" ::"l"(m), "r"(src), "r"(c0), "r"(c1), "r"(c2), "l"(policy<P>()) : "memory");
}
template <int P> __device__ __forceinline__ void tma_st4(const CUtensorMap* m, uint32_t src, int c0, int c1, int c2, int c3) {
  if constexpr (P == 0)
    asm volatile("cp.async.bulk.tensor.4d.global.shared::cta.bulk_group [%0, {%2, %3, %4, %5}], [%1];" ::"l"(m), "r"(src), "r"(c0), "r"(c1), "r"(c2), "r"(c3) : "memory");
  else
    asm volatile("cp.async.bulk.tensor.4d.global.shared::cta.bulk_group.L2::cache_hint [%0, {%2, %3, %4, %5}], [%1], %6;" ::"l"(m), "r"(src), "r"(c0), "r"(c1), "r"(c2), "r"(c3), "l"(policy<P>()) : "memory");
}
template <int P> __device__ __forceinline__ void tma_st5(const CUtensorMap* m, uint32_t src, int c0, int c1, int c2, int c3, int c4) {
  if constexpr (P == 0)
    asm volatile("cp.async.bulk.tensor.5d.global.shared::cta.bulk_group [%0, {%2, %3, %4, %5, %6}], [%1];" ::"l"(m), "r"(src), "r"(c0), "r"(c1), "r"(c2), "r"(c3), "r"(c4) : "memory");
  else
    asm volatile("cp.async.bulk.tensor.5d.global.shared::cta.bulk_group.L2::cache_hint [%0, {%2, %3, %4, %5, %6}], [%1], %7;" ::"l"(m), "r"(src), "r"(c0), "r"(c1), "r"(c2), "r"(c3), "r"(c4), "l"(policy<P>()) : "memory");
}
__device__ __forceinline__ void bulk_commit() { asm volatile("cp.async.bulk.commit_group;" ::: "memory"); }
template <int N> __device__ __forceinline__ void bulk_wait_read() { asm volatile("cp.async.bulk.wait_group.read %0;" ::"n"(N) : "memory"); }
__device__ __forceinline__ void wg_fence() { asm volatile("wgmma.fence.sync.aligned;" ::: "memory"); }
__device__ __forceinline__ void wg_commit() { asm volatile("wgmma.commit_group.sync.aligned;" ::: "memory"); }
template <int N> __device__ __forceinline__ void wg_wait() { asm volatile("wgmma.wait_group.sync.aligned %0;" ::"n"(N) : "memory"); }
template <int R> __device__ __forceinline__ void reg_fence(float (&d)[R]) {
#pragma unroll
  for (int i = 0; i < R; i++) asm volatile("" : "+f"(d[i])::"memory");
}
template <int R> __device__ __forceinline__ void reg_fence(uint32_t (&d)[R]) {
#pragma unroll
  for (int i = 0; i < R; i++) asm volatile("" : "+r"(d[i])::"memory");
}
__device__ __forceinline__ void stsm4(uint32_t a, uint32_t r0, uint32_t r1, uint32_t r2, uint32_t r3) {
  asm volatile("stmatrix.sync.aligned.m8n8.x4.shared.b16 [%0], {%1, %2, %3, %4};" ::"r"(a), "r"(r0), "r"(r1), "r"(r2), "r"(r3) : "memory");
}
__device__ __forceinline__ void stsm4t(uint32_t a, uint32_t r0, uint32_t r1, uint32_t r2, uint32_t r3) {
  asm volatile("stmatrix.sync.aligned.m8n8.x4.trans.shared.b16 [%0], {%1, %2, %3, %4};" ::"r"(a), "r"(r0), "r"(r1), "r"(r2), "r"(r3) : "memory");
}
__device__ __forceinline__ void ldsm4(uint32_t a, uint32_t& r0, uint32_t& r1, uint32_t& r2, uint32_t& r3) {
  asm volatile("ldmatrix.sync.aligned.m8n8.x4.shared.b16 {%0, %1, %2, %3}, [%4];" : "=r"(r0), "=r"(r1), "=r"(r2), "=r"(r3) : "r"(a) : "memory");
}
__device__ __forceinline__ void ldsm4t(uint32_t a, uint32_t& r0, uint32_t& r1, uint32_t& r2, uint32_t& r3) {
  asm volatile("ldmatrix.sync.aligned.m8n8.x4.trans.shared.b16 {%0, %1, %2, %3}, [%4];" : "=r"(r0), "=r"(r1), "=r"(r2), "=r"(r3) : "r"(a) : "memory");
}
__device__ __forceinline__ void ldg128(const uint4* p, uint32_t& a, uint32_t& b, uint32_t& c, uint32_t& d) {
  asm volatile("ld.global.nc.v4.u32 {%0, %1, %2, %3}, [%4];" : "=r"(a), "=r"(b), "=r"(c), "=r"(d) : "l"(p));
}
__device__ __forceinline__ uint32_t pack2(float lo, float hi) {
  uint32_t r;
  asm("cvt.rn.bf16x2.f32 %0, %1, %2;" : "=r"(r) : "f"(hi), "f"(lo));
  return r;
}
__device__ __forceinline__ float tanh_f32(float x) {
  float y;
  asm("tanh.approx.f32 %0, %1;" : "=f"(y) : "f"(x));
  return y;
}
__device__ __forceinline__ float gelu(float hx) {
  const float u = hx * fmaf(hx * hx, 8.0f * 0.044715f * 0.7978845608028654f, 2.0f * 0.7978845608028654f);
  return fmaf(hx, tanh_f32(u), hx);
}
__device__ __forceinline__ uint64_t mk_desc4(uint32_t addr4, uint32_t lbo, uint32_t sbo, uint32_t swz) {
  const uint32_t lo = addr4 + ((lbo >> 4) << 16), hi = (sbo >> 4) | (swz << 30);
  uint64_t d;
  asm("mov.b64 %0, {%1, %2};" : "=l"(d) : "r"(lo), "r"(hi));
  return d;
}
#define mk_desc(base, off, lbo, sbo, swz) mk_desc4((((base) & 0x3FFFF) >> 4) + ((off) >> 4), lbo, sbo, swz)

template <int SA, int SB, int TA, int TB>
__device__ __forceinline__ void wgmma_ss_48(float (&d)[24], uint64_t da, uint64_t db, int sd) {
  asm volatile("{\n.reg .pred p;\nsetp.ne.b32 p, %26, 0;\n"
      "wgmma.mma_async.sync.aligned.m64n48k16.f32.bf16.bf16 {"
      "%0, %1, %2, %3, %4, %5, %6, %7, %8, %9, %10, %11, %12, %13, %14, %15, %16, %17, %18, %19, %20, %21, %22, %23"
      "}, %24, %25, p, %27, %28, %29, %30;\n}\n"
      : "+f"(d[0]), "+f"(d[1]), "+f"(d[2]), "+f"(d[3]), "+f"(d[4]), "+f"(d[5]), "+f"(d[6]), "+f"(d[7]), "+f"(d[8]),
        "+f"(d[9]), "+f"(d[10]), "+f"(d[11]), "+f"(d[12]), "+f"(d[13]), "+f"(d[14]), "+f"(d[15]), "+f"(d[16]),
        "+f"(d[17]), "+f"(d[18]), "+f"(d[19]), "+f"(d[20]), "+f"(d[21]), "+f"(d[22]), "+f"(d[23])
      : "l"(da), "l"(db), "r"(sd), "n"(SA), "n"(SB), "n"(TA), "n"(TB));
}
template <int SA, int SB, int TA, int TB>
__device__ __forceinline__ void wgmma_ss_128(float (&d)[64], uint64_t da, uint64_t db, int sd) {
  asm volatile("{\n.reg .pred p;\nsetp.ne.b32 p, %66, 0;\n"
      "wgmma.mma_async.sync.aligned.m64n128k16.f32.bf16.bf16 {"
      "%0, %1, %2, %3, %4, %5, %6, %7, %8, %9, %10, %11, %12, %13, %14, %15, %16, %17, %18, %19, %20, %21, %22, %23, "
      "%24, %25, %26, %27, %28, %29, %30, %31, %32, %33, %34, %35, %36, %37, %38, %39, %40, %41, %42, %43, %44, %45, "
      "%46, %47, %48, %49, %50, %51, %52, %53, %54, %55, %56, %57, %58, %59, %60, %61, %62, %63"
      "}, %64, %65, p, %67, %68, %69, %70;\n}\n"
      : "+f"(d[0]), "+f"(d[1]), "+f"(d[2]), "+f"(d[3]), "+f"(d[4]), "+f"(d[5]), "+f"(d[6]), "+f"(d[7]), "+f"(d[8]),
        "+f"(d[9]), "+f"(d[10]), "+f"(d[11]), "+f"(d[12]), "+f"(d[13]), "+f"(d[14]), "+f"(d[15]), "+f"(d[16]),
        "+f"(d[17]), "+f"(d[18]), "+f"(d[19]), "+f"(d[20]), "+f"(d[21]), "+f"(d[22]), "+f"(d[23]), "+f"(d[24]),
        "+f"(d[25]), "+f"(d[26]), "+f"(d[27]), "+f"(d[28]), "+f"(d[29]), "+f"(d[30]), "+f"(d[31]), "+f"(d[32]),
        "+f"(d[33]), "+f"(d[34]), "+f"(d[35]), "+f"(d[36]), "+f"(d[37]), "+f"(d[38]), "+f"(d[39]), "+f"(d[40]),
        "+f"(d[41]), "+f"(d[42]), "+f"(d[43]), "+f"(d[44]), "+f"(d[45]), "+f"(d[46]), "+f"(d[47]), "+f"(d[48]),
        "+f"(d[49]), "+f"(d[50]), "+f"(d[51]), "+f"(d[52]), "+f"(d[53]), "+f"(d[54]), "+f"(d[55]), "+f"(d[56]),
        "+f"(d[57]), "+f"(d[58]), "+f"(d[59]), "+f"(d[60]), "+f"(d[61]), "+f"(d[62]), "+f"(d[63])
      : "l"(da), "l"(db), "r"(sd), "n"(SA), "n"(SB), "n"(TA), "n"(TB));
}
template <int SA, int SB, int TA, int TB>
__device__ __forceinline__ void wgmma_ss_168(float (&d)[84], uint64_t da, uint64_t db, int sd) {
  asm volatile("{\n.reg .pred p;\nsetp.ne.b32 p, %86, 0;\n"
      "wgmma.mma_async.sync.aligned.m64n168k16.f32.bf16.bf16 {"
      "%0, %1, %2, %3, %4, %5, %6, %7, %8, %9, %10, %11, %12, %13, %14, %15, %16, %17, %18, %19, %20, %21, %22, %23, "
      "%24, %25, %26, %27, %28, %29, %30, %31, %32, %33, %34, %35, %36, %37, %38, %39, %40, %41, %42, %43, %44, %45, "
      "%46, %47, %48, %49, %50, %51, %52, %53, %54, %55, %56, %57, %58, %59, %60, %61, %62, %63, %64, %65, %66, %67, "
      "%68, %69, %70, %71, %72, %73, %74, %75, %76, %77, %78, %79, %80, %81, %82, %83"
      "}, %84, %85, p, %87, %88, %89, %90;\n}\n"
      : "+f"(d[0]), "+f"(d[1]), "+f"(d[2]), "+f"(d[3]), "+f"(d[4]), "+f"(d[5]), "+f"(d[6]), "+f"(d[7]), "+f"(d[8]),
        "+f"(d[9]), "+f"(d[10]), "+f"(d[11]), "+f"(d[12]), "+f"(d[13]), "+f"(d[14]), "+f"(d[15]), "+f"(d[16]),
        "+f"(d[17]), "+f"(d[18]), "+f"(d[19]), "+f"(d[20]), "+f"(d[21]), "+f"(d[22]), "+f"(d[23]), "+f"(d[24]),
        "+f"(d[25]), "+f"(d[26]), "+f"(d[27]), "+f"(d[28]), "+f"(d[29]), "+f"(d[30]), "+f"(d[31]), "+f"(d[32]),
        "+f"(d[33]), "+f"(d[34]), "+f"(d[35]), "+f"(d[36]), "+f"(d[37]), "+f"(d[38]), "+f"(d[39]), "+f"(d[40]),
        "+f"(d[41]), "+f"(d[42]), "+f"(d[43]), "+f"(d[44]), "+f"(d[45]), "+f"(d[46]), "+f"(d[47]), "+f"(d[48]),
        "+f"(d[49]), "+f"(d[50]), "+f"(d[51]), "+f"(d[52]), "+f"(d[53]), "+f"(d[54]), "+f"(d[55]), "+f"(d[56]),
        "+f"(d[57]), "+f"(d[58]), "+f"(d[59]), "+f"(d[60]), "+f"(d[61]), "+f"(d[62]), "+f"(d[63]), "+f"(d[64]),
        "+f"(d[65]), "+f"(d[66]), "+f"(d[67]), "+f"(d[68]), "+f"(d[69]), "+f"(d[70]), "+f"(d[71]), "+f"(d[72]),
        "+f"(d[73]), "+f"(d[74]), "+f"(d[75]), "+f"(d[76]), "+f"(d[77]), "+f"(d[78]), "+f"(d[79]), "+f"(d[80]),
        "+f"(d[81]), "+f"(d[82]), "+f"(d[83])
      : "l"(da), "l"(db), "r"(sd), "n"(SA), "n"(SB), "n"(TA), "n"(TB));
}
template <int SA, int SB, int TB>
__device__ __forceinline__ void wgmma_rs_32(float (&d)[16], uint32_t a0, uint32_t a1, uint32_t a2, uint32_t a3, uint64_t db, int sd) {
  asm volatile("{\n.reg .pred p;\nsetp.ne.b32 p, %21, 0;\n"
      "wgmma.mma_async.sync.aligned.m64n32k16.f32.bf16.bf16 {"
      "%0, %1, %2, %3, %4, %5, %6, %7, %8, %9, %10, %11, %12, %13, %14, %15"
      "}, {%16, %17, %18, %19}, %20, p, %22, %23, %24;\n}\n"
      : "+f"(d[0]), "+f"(d[1]), "+f"(d[2]), "+f"(d[3]), "+f"(d[4]), "+f"(d[5]), "+f"(d[6]), "+f"(d[7]), "+f"(d[8]),
        "+f"(d[9]), "+f"(d[10]), "+f"(d[11]), "+f"(d[12]), "+f"(d[13]), "+f"(d[14]), "+f"(d[15])
      : "r"(a0), "r"(a1), "r"(a2), "r"(a3), "l"(db), "r"(sd), "n"(SA), "n"(SB), "n"(TB));
}
template <int SA, int SB, int TB>
__device__ __forceinline__ void wgmma_rs_64(float (&d)[32], uint32_t a0, uint32_t a1, uint32_t a2, uint32_t a3, uint64_t db, int sd) {
  asm volatile("{\n.reg .pred p;\nsetp.ne.b32 p, %37, 0;\n"
      "wgmma.mma_async.sync.aligned.m64n64k16.f32.bf16.bf16 {"
      "%0, %1, %2, %3, %4, %5, %6, %7, %8, %9, %10, %11, %12, %13, %14, %15, %16, %17, %18, %19, %20, %21, %22, %23, "
      "%24, %25, %26, %27, %28, %29, %30, %31"
      "}, {%32, %33, %34, %35}, %36, p, %38, %39, %40;\n}\n"
      : "+f"(d[0]), "+f"(d[1]), "+f"(d[2]), "+f"(d[3]), "+f"(d[4]), "+f"(d[5]), "+f"(d[6]), "+f"(d[7]), "+f"(d[8]),
        "+f"(d[9]), "+f"(d[10]), "+f"(d[11]), "+f"(d[12]), "+f"(d[13]), "+f"(d[14]), "+f"(d[15]), "+f"(d[16]),
        "+f"(d[17]), "+f"(d[18]), "+f"(d[19]), "+f"(d[20]), "+f"(d[21]), "+f"(d[22]), "+f"(d[23]), "+f"(d[24]),
        "+f"(d[25]), "+f"(d[26]), "+f"(d[27]), "+f"(d[28]), "+f"(d[29]), "+f"(d[30]), "+f"(d[31])
      : "r"(a0), "r"(a1), "r"(a2), "r"(a3), "l"(db), "r"(sd), "n"(SA), "n"(SB), "n"(TB));
}
template <int SA, int SB, int TB>
__device__ __forceinline__ void wgmma_rs_128(float (&d)[64], uint32_t a0, uint32_t a1, uint32_t a2, uint32_t a3, uint64_t db, int sd) {
  asm volatile("{\n.reg .pred p;\nsetp.ne.b32 p, %69, 0;\n"
      "wgmma.mma_async.sync.aligned.m64n128k16.f32.bf16.bf16 {"
      "%0, %1, %2, %3, %4, %5, %6, %7, %8, %9, %10, %11, %12, %13, %14, %15, %16, %17, %18, %19, %20, %21, %22, %23, "
      "%24, %25, %26, %27, %28, %29, %30, %31, %32, %33, %34, %35, %36, %37, %38, %39, %40, %41, %42, %43, %44, %45, "
      "%46, %47, %48, %49, %50, %51, %52, %53, %54, %55, %56, %57, %58, %59, %60, %61, %62, %63"
      "}, {%64, %65, %66, %67}, %68, p, %70, %71, %72;\n}\n"
      : "+f"(d[0]), "+f"(d[1]), "+f"(d[2]), "+f"(d[3]), "+f"(d[4]), "+f"(d[5]), "+f"(d[6]), "+f"(d[7]), "+f"(d[8]),
        "+f"(d[9]), "+f"(d[10]), "+f"(d[11]), "+f"(d[12]), "+f"(d[13]), "+f"(d[14]), "+f"(d[15]), "+f"(d[16]),
        "+f"(d[17]), "+f"(d[18]), "+f"(d[19]), "+f"(d[20]), "+f"(d[21]), "+f"(d[22]), "+f"(d[23]), "+f"(d[24]),
        "+f"(d[25]), "+f"(d[26]), "+f"(d[27]), "+f"(d[28]), "+f"(d[29]), "+f"(d[30]), "+f"(d[31]), "+f"(d[32]),
        "+f"(d[33]), "+f"(d[34]), "+f"(d[35]), "+f"(d[36]), "+f"(d[37]), "+f"(d[38]), "+f"(d[39]), "+f"(d[40]),
        "+f"(d[41]), "+f"(d[42]), "+f"(d[43]), "+f"(d[44]), "+f"(d[45]), "+f"(d[46]), "+f"(d[47]), "+f"(d[48]),
        "+f"(d[49]), "+f"(d[50]), "+f"(d[51]), "+f"(d[52]), "+f"(d[53]), "+f"(d[54]), "+f"(d[55]), "+f"(d[56]),
        "+f"(d[57]), "+f"(d[58]), "+f"(d[59]), "+f"(d[60]), "+f"(d[61]), "+f"(d[62]), "+f"(d[63])
      : "r"(a0), "r"(a1), "r"(a2), "r"(a3), "l"(db), "r"(sd), "n"(SA), "n"(SB), "n"(TB));
}
template <int SA, int SB, int TB>
__device__ __forceinline__ void wgmma_rs_168(float (&d)[84], uint32_t a0, uint32_t a1, uint32_t a2, uint32_t a3, uint64_t db, int sd) {
  asm volatile("{\n.reg .pred p;\nsetp.ne.b32 p, %89, 0;\n"
      "wgmma.mma_async.sync.aligned.m64n168k16.f32.bf16.bf16 {"
      "%0, %1, %2, %3, %4, %5, %6, %7, %8, %9, %10, %11, %12, %13, %14, %15, %16, %17, %18, %19, %20, %21, %22, %23, "
      "%24, %25, %26, %27, %28, %29, %30, %31, %32, %33, %34, %35, %36, %37, %38, %39, %40, %41, %42, %43, %44, %45, "
      "%46, %47, %48, %49, %50, %51, %52, %53, %54, %55, %56, %57, %58, %59, %60, %61, %62, %63, %64, %65, %66, %67, "
      "%68, %69, %70, %71, %72, %73, %74, %75, %76, %77, %78, %79, %80, %81, %82, %83"
      "}, {%84, %85, %86, %87}, %88, p, %90, %91, %92;\n}\n"
      : "+f"(d[0]), "+f"(d[1]), "+f"(d[2]), "+f"(d[3]), "+f"(d[4]), "+f"(d[5]), "+f"(d[6]), "+f"(d[7]), "+f"(d[8]),
        "+f"(d[9]), "+f"(d[10]), "+f"(d[11]), "+f"(d[12]), "+f"(d[13]), "+f"(d[14]), "+f"(d[15]), "+f"(d[16]),
        "+f"(d[17]), "+f"(d[18]), "+f"(d[19]), "+f"(d[20]), "+f"(d[21]), "+f"(d[22]), "+f"(d[23]), "+f"(d[24]),
        "+f"(d[25]), "+f"(d[26]), "+f"(d[27]), "+f"(d[28]), "+f"(d[29]), "+f"(d[30]), "+f"(d[31]), "+f"(d[32]),
        "+f"(d[33]), "+f"(d[34]), "+f"(d[35]), "+f"(d[36]), "+f"(d[37]), "+f"(d[38]), "+f"(d[39]), "+f"(d[40]),
        "+f"(d[41]), "+f"(d[42]), "+f"(d[43]), "+f"(d[44]), "+f"(d[45]), "+f"(d[46]), "+f"(d[47]), "+f"(d[48]),
        "+f"(d[49]), "+f"(d[50]), "+f"(d[51]), "+f"(d[52]), "+f"(d[53]), "+f"(d[54]), "+f"(d[55]), "+f"(d[56]),
        "+f"(d[57]), "+f"(d[58]), "+f"(d[59]), "+f"(d[60]), "+f"(d[61]), "+f"(d[62]), "+f"(d[63]), "+f"(d[64]),
        "+f"(d[65]), "+f"(d[66]), "+f"(d[67]), "+f"(d[68]), "+f"(d[69]), "+f"(d[70]), "+f"(d[71]), "+f"(d[72]),
        "+f"(d[73]), "+f"(d[74]), "+f"(d[75]), "+f"(d[76]), "+f"(d[77]), "+f"(d[78]), "+f"(d[79]), "+f"(d[80]),
        "+f"(d[81]), "+f"(d[82]), "+f"(d[83])
      : "r"(a0), "r"(a1), "r"(a2), "r"(a3), "l"(db), "r"(sd), "n"(SA), "n"(SB), "n"(TB));
}
template <int SA, int SB, int TB>
__device__ __forceinline__ void wgmma_rs_256(float (&d)[128], uint32_t a0, uint32_t a1, uint32_t a2, uint32_t a3, uint64_t db, int sd) {
  asm volatile("{\n.reg .pred p;\nsetp.ne.b32 p, %133, 0;\n"
      "wgmma.mma_async.sync.aligned.m64n256k16.f32.bf16.bf16 {"
      "%0, %1, %2, %3, %4, %5, %6, %7, %8, %9, %10, %11, %12, %13, %14, %15, %16, %17, %18, %19, %20, %21, %22, %23, "
      "%24, %25, %26, %27, %28, %29, %30, %31, %32, %33, %34, %35, %36, %37, %38, %39, %40, %41, %42, %43, %44, %45, "
      "%46, %47, %48, %49, %50, %51, %52, %53, %54, %55, %56, %57, %58, %59, %60, %61, %62, %63, %64, %65, %66, %67, "
      "%68, %69, %70, %71, %72, %73, %74, %75, %76, %77, %78, %79, %80, %81, %82, %83, %84, %85, %86, %87, %88, %89, "
      "%90, %91, %92, %93, %94, %95, %96, %97, %98, %99, %100, %101, %102, %103, %104, %105, %106, %107, %108, %109, "
      "%110, %111, %112, %113, %114, %115, %116, %117, %118, %119, %120, %121, %122, %123, %124, %125, %126, %127"
      "}, {%128, %129, %130, %131}, %132, p, %134, %135, %136;\n}\n"
      : "+f"(d[0]), "+f"(d[1]), "+f"(d[2]), "+f"(d[3]), "+f"(d[4]), "+f"(d[5]), "+f"(d[6]), "+f"(d[7]), "+f"(d[8]),
        "+f"(d[9]), "+f"(d[10]), "+f"(d[11]), "+f"(d[12]), "+f"(d[13]), "+f"(d[14]), "+f"(d[15]), "+f"(d[16]),
        "+f"(d[17]), "+f"(d[18]), "+f"(d[19]), "+f"(d[20]), "+f"(d[21]), "+f"(d[22]), "+f"(d[23]), "+f"(d[24]),
        "+f"(d[25]), "+f"(d[26]), "+f"(d[27]), "+f"(d[28]), "+f"(d[29]), "+f"(d[30]), "+f"(d[31]), "+f"(d[32]),
        "+f"(d[33]), "+f"(d[34]), "+f"(d[35]), "+f"(d[36]), "+f"(d[37]), "+f"(d[38]), "+f"(d[39]), "+f"(d[40]),
        "+f"(d[41]), "+f"(d[42]), "+f"(d[43]), "+f"(d[44]), "+f"(d[45]), "+f"(d[46]), "+f"(d[47]), "+f"(d[48]),
        "+f"(d[49]), "+f"(d[50]), "+f"(d[51]), "+f"(d[52]), "+f"(d[53]), "+f"(d[54]), "+f"(d[55]), "+f"(d[56]),
        "+f"(d[57]), "+f"(d[58]), "+f"(d[59]), "+f"(d[60]), "+f"(d[61]), "+f"(d[62]), "+f"(d[63]), "+f"(d[64]),
        "+f"(d[65]), "+f"(d[66]), "+f"(d[67]), "+f"(d[68]), "+f"(d[69]), "+f"(d[70]), "+f"(d[71]), "+f"(d[72]),
        "+f"(d[73]), "+f"(d[74]), "+f"(d[75]), "+f"(d[76]), "+f"(d[77]), "+f"(d[78]), "+f"(d[79]), "+f"(d[80]),
        "+f"(d[81]), "+f"(d[82]), "+f"(d[83]), "+f"(d[84]), "+f"(d[85]), "+f"(d[86]), "+f"(d[87]), "+f"(d[88]),
        "+f"(d[89]), "+f"(d[90]), "+f"(d[91]), "+f"(d[92]), "+f"(d[93]), "+f"(d[94]), "+f"(d[95]), "+f"(d[96]),
        "+f"(d[97]), "+f"(d[98]), "+f"(d[99]), "+f"(d[100]), "+f"(d[101]), "+f"(d[102]), "+f"(d[103]), "+f"(d[104]),
        "+f"(d[105]), "+f"(d[106]), "+f"(d[107]), "+f"(d[108]), "+f"(d[109]), "+f"(d[110]), "+f"(d[111]),
        "+f"(d[112]), "+f"(d[113]), "+f"(d[114]), "+f"(d[115]), "+f"(d[116]), "+f"(d[117]), "+f"(d[118]),
        "+f"(d[119]), "+f"(d[120]), "+f"(d[121]), "+f"(d[122]), "+f"(d[123]), "+f"(d[124]), "+f"(d[125]),
        "+f"(d[126]), "+f"(d[127])
      : "r"(a0), "r"(a1), "r"(a2), "r"(a3), "l"(db), "r"(sd), "n"(SA), "n"(SB), "n"(TB));
}

__device__ const __align__(128) uint32_t c_img[3584] = {
    0x00003c80, 0x00003c80, 0x00003c80, 0x00003c80, 0x00003c80, 0x00003c80, 0x00003c80, 0x00003c80, 0x00003c80, 0x00003c80,
    0x00003c80, 0x00003c80, 0x00003c80, 0x00003c80, 0x00003c80, 0x00003c80, 0x00003c80, 0x00003c80, 0x00003c80, 0x00003c80,
    0x00003c80, 0x00003c80, 0x00003c80, 0x00003c80, 0x00003c80, 0x00003c80, 0x00003c80, 0x00003c80, 0x00003c80, 0x00003c80,
    0x00003c80, 0x00003c80, 0x3c463c22, 0x3c623bf1, 0x3c753b95, 0x3c7f3ac9, 0x3ac93c7f, 0x3b953c75, 0x3bf13c62, 0x3c223c46,
    0x3c22bc46, 0x3bf1bc62, 0x3b95bc75, 0x3ac9bc7f, 0x3c7fbac9, 0x3c75bb95, 0x3c62bbf1, 0x3c46bc22, 0xbc46bc22, 0xbc62bbf1,
    0xbc75bb95, 0xbc7fbac9, 0xbac9bc7f, 0xbb95bc75, 0xbbf1bc62, 0xbc22bc46, 0xbc223c46, 0xbbf13c62, 0xbb953c75, 0xbac93c7f,
    0xbc7f3ac9, 0xbc753b95, 0xbc623bf1, 0xbc463c22, 0xbb48bc7b, 0xbc0ebc55, 0xbc55bc0e, 0xbc7bbb48, 0xbc7b3b48, 0xbc553c0e,
    0xbc0e3c55, 0xbb483c7b, 0x3b483c7b, 0x3c0e3c55, 0x3c553c0e, 0x3c7b3b48, 0x3c7bbb48, 0x3c55bc0e, 0x3c0ebc55, 0x3b48bc7b,
    0xbb48bc7b, 0xbc0ebc55, 0xbc55bc0e, 0xbc7bbb48, 0xbc7b3b48, 0xbc553c0e, 0xbc0e3c55, 0xbb483c7b, 0x3b483c7b, 0x3c0e3c55,
    0x3c553c0e, 0x3c7b3b48, 0x3c7bbb48, 0x3c55bc0e, 0x3c0ebc55, 0x3b48bc7b, 0x3c623bf1, 0x3c7fbac9, 0x3c46bc22, 0x3b95bc75,
    0xbc753b95, 0xbc223c46, 0xbac93c7f, 0x3bf13c62, 0x3bf1bc62, 0xbac9bc7f, 0xbc22bc46, 0xbc75bb95, 0x3b953c75, 0x3c463c22,
    0x3c7f3ac9, 0x3c62bbf1, 0xbc62bbf1, 0xbc7f3ac9, 0xbc463c22, 0xbb953c75, 0x3c75bb95, 0x3c22bc46, 0x3ac9bc7f, 0xbbf1bc62,
    0xbbf13c62, 0x3ac93c7f, 0x3c223c46, 0x3c753b95, 0xbb95bc75, 0xbc46bc22, 0xbc7fbac9, 0xbc623bf1, 0x3bc43c6d, 0x3c6d3bc4,
    0x3c6dbbc4, 0x3bc4bc6d, 0xbbc4bc6d, 0xbc6dbbc4, 0xbc6d3bc4, 0xbbc43c6d, 0x3bc43c6d, 0x3c6d3bc4, 0x3c6dbbc4, 0x3bc4bc6d,
    0xbbc4bc6d, 0xbc6dbbc4, 0xbc6d3bc4, 0xbbc43c6d, 0x3bc43c6d, 0x3c6d3bc4, 0x3c6dbbc4, 0x3bc4bc6d, 0xbbc4bc6d, 0xbc6dbbc4,
    0xbc6d3bc4, 0xbbc43c6d, 0x3bc43c6d, 0x3c6d3bc4, 0x3c6dbbc4, 0x3bc4bc6d, 0xbbc4bc6d, 0xbc6dbbc4, 0xbc6d3bc4, 0xbbc43c6d,
    0x3c753b95, 0x3c46bc22, 0xbac9bc7f, 0xbc62bbf1, 0xbbf1bc62, 0xbc7fbac9, 0xbc223c46, 0x3b953c75, 0x3b95bc75, 0xbc22bc46,
    0xbc7f3ac9, 0xbbf13c62, 0xbc623bf1, 0xbac93c7f, 0x3c463c22, 0x3c75bb95, 0xbc75bb95, 0xbc463c22, 0x3ac93c7f, 0x3c623bf1,
    0x3bf13c62, 0x3c7f3ac9, 0x3c22bc46, 0xbb95bc75, 0xbb953c75, 0x3c223c46, 0x3c7fbac9, 0x3bf1bc62, 0x3c62bbf1, 0x3ac9bc7f,
    0xbc46bc22, 0xbc753b95, 0xbc0ebc55, 0xbc7b3b48, 0xbb483c7b, 0x3c553c0e, 0x3c55bc0e, 0xbb48bc7b, 0xbc7bbb48, 0xbc0e3c55,
    0x3c0e3c55, 0x3c7bbb48, 0x3b48bc7b, 0xbc55bc0e, 0xbc553c0e, 0x3b483c7b, 0x3c7b3b48, 0x3c0ebc55, 0xbc0ebc55, 0xbc7b3b48,
    0xbb483c7b, 0x3c553c0e, 0x3c55bc0e, 0xbb48bc7b, 0xbc7bbb48, 0xbc0e3c55, 0x3c0e3c55, 0x3c7bbb48, 0x3b48bc7b, 0xbc55bc0e,
    0xbc553c0e, 0x3b483c7b, 0x3c7b3b48, 0x3c0ebc55, 0x3c7f3ac9, 0x3b95bc75, 0xbc62bbf1, 0xbc223c46, 0x3c46bc22, 0xbbf1bc62,
    0xbc753b95, 0x3ac93c7f, 0x3ac9bc7f, 0xbc75bb95, 0xbbf13c62, 0x3c463c22, 0xbc22bc46, 0xbc623bf1, 0x3b953c75, 0x3c7fbac9,
    0xbc7fbac9, 0xbb953c75, 0x3c623bf1, 0x3c22bc46, 0xbc463c22, 0x3bf13c62, 0x3c75bb95, 0xbac9bc7f, 0xbac93c7f, 0x3c753b95,
    0x3bf1bc62, 0xbc46bc22, 0x3c223c46, 0x3c62bbf1, 0xbb95bc75, 0xbc7f3ac9, 0x3a493c80, 0x3b163c7d, 0x3b793c78, 0x3bac3c71,
    0x3bdb3c67, 0x3c043c5c, 0x3c183c4e, 0x3c2c3c3e, 0x3c3e3c2c, 0x3c4e3c18, 0x3c5c3c04, 0x3c673bdb, 0x3c713bac, 0x3c783b79,
    0x3c7d3b16, 0x3c803a49, 0x3c80ba49, 0x3c7dbb16, 0x3c78bb79, 0x3c71bbac, 0x3c67bbdb, 0x3c5cbc04, 0x3c4ebc18, 0x3c3ebc2c,
    0x3c2cbc3e, 0x3c18bc4e, 0x3c04bc5c, 0x3bdbbc67, 0x3bacbc71, 0x3b79bc78, 0x3b16bc7d, 0x3a49bc80, 0x3c783b79, 0x3c80ba49,
    0x3c71bbac, 0x3c4ebc18, 0x3b163c7d, 0x3bdb3c67, 0x3c2c3c3e, 0x3c5c3c04, 0xbc04bc5c, 0xbc3ebc2c, 0xbc67bbdb, 0xbc7dbb16,
    0x3c18bc4e, 0x3bacbc71, 0x3a49bc80, 0xbb79bc78, 0xbb793c78, 0x3a493c80, 0x3bac3c71, 0x3c183c4e, 0xbc7d3b16, 0xbc673bdb,
    0xbc3e3c2c, 0xbc043c5c, 0x3c5cbc04, 0x3c2cbc3e, 0x3bdbbc67, 0x3b16bc7d, 0x3c4e3c18, 0x3c713bac, 0x3c803a49, 0x3c78bb79,
    0xbc5cbc04, 0xbc80ba49, 0xbc673bdb, 0xbc183c4e, 0xbb163c7d, 0x3bac3c71, 0x3c3e3c2c, 0x3c783b79, 0x3b793c78, 0x3c2c3c3e,
    0x3c713bac, 0x3c7dbb16, 0x3c4ebc18, 0x3bdbbc67, 0xba49bc80, 0xbc04bc5c, 0xbc043c5c, 0xba493c80, 0x3bdb3c67, 0x3c4e3c18,
    0x3c7d3b16, 0x3c71bbac, 0x3c2cbc3e, 0x3b79bc78, 0x3c78bb79, 0x3c3ebc2c, 0x3bacbc71, 0xbb16bc7d, 0xbc18bc4e, 0xbc67bbdb,
    0xbc803a49, 0xbc5c3c04, 0x3c3ebc2c, 0x3b16bc7d, 0xbc04bc5c, 0xbc71bbac, 0xbbdb3c67, 0x3b793c78, 0x3c4e3c18, 0x3c80ba49,
    0x3a49bc80, 0xbc18bc4e, 0xbc78bb79, 0xbc673bdb, 0x3bac3c71, 0x3c5c3c04, 0x3c7dbb16, 0x3c2cbc3e, 0x3c2c3c3e, 0x3c7d3b16,
    0x3c5cbc04, 0x3bacbc71, 0xbc67bbdb, 0xbc783b79, 0xbc183c4e, 0x3a493c80, 0x3c803a49, 0x3c4ebc18, 0x3b79bc78, 0xbbdbbc67,
    0xbc713bac, 0xbc043c5c, 0x3b163c7d, 0x3c3e3c2c, 0x3c67bbdb, 0x3b79bc78, 0xbc18bc4e, 0xbc80ba49, 0xbc2c3c3e, 0x3b163c7d,
    0x3c5c3c04, 0x3c71bbac, 0x3bacbc71, 0xbc04bc5c, 0xbc7dbb16, 0xbc3e3c2c, 0x3a493c80, 0x3c4e3c18, 0x3c78bb79, 0x3bdbbc67,
    0x3bdb3c67, 0x3c783b79, 0x3c4ebc18, 0x3a49bc80, 0xbc3ebc2c, 0xbc7d3b16, 0xbc043c5c, 0x3bac3c71, 0x3c713bac, 0x3c5cbc04,
    0x3b16bc7d, 0xbc2cbc3e, 0xbc803a49, 0xbc183c4e, 0x3b793c78, 0x3c673bdb, 0xbb16bc7d, 0xbc71bbac, 0xbc3e3c2c, 0x3b793c78,
    0xbc5c3c04, 0x3a493c80, 0x3c673bdb, 0x3c4ebc18, 0xbc183c4e, 0x3bdb3c67, 0x3c803a49, 0x3c04bc5c, 0x3c783b79, 0x3c2cbc3e,
    0xbbacbc71, 0xbc7dbb16, 0xbc7d3b16, 0xbbac3c71, 0x3c2c3c3e, 0x3c78bb79, 0x3c043c5c, 0x3c80ba49, 0x3bdbbc67, 0xbc18bc4e,
    0x3c4e3c18, 0x3c67bbdb, 0x3a49bc80, 0xbc5cbc04, 0x3b79bc78, 0xbc3ebc2c, 0xbc713bac, 0xbb163c7d, 0xbb163c7d, 0x3c673bdb,
    0x3c2cbc3e, 0xbc04bc5c, 0xbc783b79, 0xba493c80, 0x3c713bac, 0x3c18bc4e, 0x3c4ebc18, 0xbbacbc71, 0xbc803a49, 0xbb793c78,
    0x3c5c3c04, 0x3c3ebc2c, 0xbbdbbc67, 0xbc7d3b16, 0xbc7dbb16, 0xbbdb3c67, 0x3c3e3c2c, 0x3c5cbc04, 0xbb79bc78, 0xbc80ba49,
    0xbbac3c71, 0x3c4e3c18, 0x3c183c4e, 0x3c71bbac, 0xba49bc80, 0xbc78bb79, 0xbc043c5c, 0x3c2c3c3e, 0x3c67bbdb, 0xbb16bc7d,
    0xbc67bbdb, 0xbc043c5c, 0x3c4e3c18, 0x3c2cbc3e, 0xbc80ba49, 0xbb163c7d, 0x3c783b79, 0x3bacbc71, 0xbc713bac, 0x3b793c78,
    0x3c7dbb16, 0xba49bc80, 0xbc3e3c2c, 0x3c183c4e, 0x3c5cbc04, 0xbbdbbc67, 0xbbdb3c67, 0x3c5c3c04, 0x3c18bc4e, 0xbc3ebc2c,
    0xba493c80, 0x3c7d3b16, 0x3b79bc78, 0xbc71bbac, 0x3bac3c71, 0x3c78bb79, 0xbb16bc7d, 0xbc803a49, 0x3c2c3c3e, 0x3c4ebc18,
    0xbc04bc5c, 0xbc673bdb, 0x3c353c35, 0x3c35bc35, 0xbc35bc35, 0xbc353c35, 0x3c353c35, 0x3c35bc35, 0xbc35bc35, 0xbc353c35,
    0x3c353c35, 0x3c35bc35, 0xbc35bc35, 0xbc353c35, 0x3c353c35, 0x3c35bc35, 0xbc35bc35, 0xbc353c35, 0x3c353c35, 0x3c35bc35,
    0xbc35bc35, 0xbc353c35, 0x3c353c35, 0x3c35bc35, 0xbc35bc35, 0xbc353c35, 0x3c353c35, 0x3c35bc35, 0xbc35bc35, 0xbc353c35,
    0x3c353c35, 0x3c35bc35, 0xbc35bc35, 0xbc353c35, 0x3c7fbac9, 0xbb95bc75, 0xbc623bf1, 0x3c223c46, 0x3c463c22, 0x3bf1bc62,
    0xbc75bb95, 0xbac93c7f, 0xbac9bc7f, 0xbc753b95, 0x3bf13c62, 0x3c46bc22, 0x3c22bc46, 0xbc62bbf1, 0xbb953c75, 0x3c7f3ac9,
    0xbc7f3ac9, 0x3b953c75, 0x3c62bbf1, 0xbc22bc46, 0xbc46bc22, 0xbbf13c62, 0x3c753b95, 0x3ac9bc7f, 0x3ac93c7f, 0x3c75bb95,
    0xbbf1bc62, 0xbc463c22, 0xbc223c46, 0x3c623bf1, 0x3b95bc75, 0xbc7fbac9, 0xbc55bc0e, 0xbb483c7b, 0x3c7bbb48, 0xbc0ebc55,
    0xbc0e3c55, 0x3c7b3b48, 0xbb48bc7b, 0xbc553c0e, 0x3c553c0e, 0x3b48bc7b, 0xbc7b3b48, 0x3c0e3c55, 0x3c0ebc55, 0xbc7bbb48,
    0x3b483c7b, 0x3c55bc0e, 0xbc55bc0e, 0xbb483c7b, 0x3c7bbb48, 0xbc0ebc55, 0xbc0e3c55, 0x3c7b3b48, 0xbb48bc7b, 0xbc553c0e,
    0x3c553c0e, 0x3b48bc7b, 0xbc7b3b48, 0x3c0e3c55, 0x3c0ebc55, 0xbc7bbb48, 0x3b483c7b, 0x3c55bc0e, 0x3c75bb95, 0xbc46bc22,
    0xbac93c7f, 0x3c62bbf1, 0xbbf13c62, 0x3c7fbac9, 0xbc22bc46, 0xbb953c75, 0xbb95bc75, 0xbc223c46, 0x3c7f3ac9, 0xbbf1bc62,
    0x3c623bf1, 0xbac9bc7f, 0xbc463c22, 0x3c753b95, 0xbc753b95, 0x3c463c22, 0x3ac9bc7f, 0xbc623bf1, 0x3bf1bc62, 0xbc7f3ac9,
    0x3c223c46, 0x3b95bc75, 0x3b953c75, 0x3c22bc46, 0xbc7fbac9, 0x3bf13c62, 0xbc62bbf1, 0x3ac93c7f, 0x3c46bc22, 0xbc75bb95,
    0x3c6d3bc4, 0xbbc4bc6d, 0xbbc43c6d, 0x3c6dbbc4, 0xbc6dbbc4, 0x3bc43c6d, 0x3bc4bc6d, 0xbc6d3bc4, 0x3c6d3bc4, 0xbbc4bc6d,
    0xbbc43c6d, 0x3c6dbbc4, 0xbc6dbbc4, 0x3bc43c6d, 0x3bc4bc6d, 0xbc6d3bc4, 0x3c6d3bc4, 0xbbc4bc6d, 0xbbc43c6d, 0x3c6dbbc4,
    0xbc6dbbc4, 0x3bc43c6d, 0x3bc4bc6d, 0xbc6d3bc4, 0x3c6d3bc4, 0xbbc4bc6d, 0xbbc43c6d, 0x3c6dbbc4, 0xbc6dbbc4, 0x3bc43c6d,
    0x3bc4bc6d, 0xbc6d3bc4, 0x3c62bbf1, 0xbc7fbac9, 0x3c463c22, 0xbb95bc75, 0xbc75bb95, 0x3c223c46, 0xbac9bc7f, 0xbbf13c62,
    0xbbf1bc62, 0xbac93c7f, 0x3c22bc46, 0xbc753b95, 0xbb953c75, 0x3c46bc22, 0xbc7f3ac9, 0x3c623bf1, 0xbc623bf1, 0x3c7f3ac9,
    0xbc46bc22, 0x3b953c75, 0x3c753b95, 0xbc22bc46, 0x3ac93c7f, 0x3bf1bc62, 0x3bf13c62, 0x3ac9bc7f, 0xbc223c46, 0x3c75bb95,
    0x3b95bc75, 0xbc463c22, 0x3c7fbac9, 0xbc62bbf1, 0xbc7bbb48, 0x3c553c0e, 0xbc0ebc55, 0x3b483c7b, 0x3b48bc7b, 0xbc0e3c55,
    0x3c55bc0e, 0xbc7b3b48, 0x3c7b3b48, 0xbc55bc0e, 0x3c0e3c55, 0xbb48bc7b, 0xbb483c7b, 0x3c0ebc55, 0xbc553c0e, 0x3c7bbb48,
    0xbc7bbb48, 0x3c553c0e, 0xbc0ebc55, 0x3b483c7b, 0x3b48bc7b, 0xbc0e3c55, 0x3c55bc0e, 0xbc7b3b48, 0x3c7b3b48, 0xbc55bc0e,
    0x3c0e3c55, 0xbb48bc7b, 0xbb483c7b, 0x3c0ebc55, 0xbc553c0e, 0x3c7bbb48, 0x3c46bc22, 0xbc623bf1, 0x3c75bb95, 0xbc7f3ac9,
    0x3ac9bc7f, 0xbb953c75, 0x3bf1bc62, 0xbc223c46, 0xbc22bc46, 0x3bf13c62, 0xbb95bc75, 0x3ac93c7f, 0xbc7fbac9, 0x3c753b95,
    0xbc62bbf1, 0x3c463c22, 0xbc463c22, 0x3c62bbf1, 0xbc753b95, 0x3c7fbac9, 0xbac93c7f, 0x3b95bc75, 0xbbf13c62, 0x3c22bc46,
    0x3c223c46, 0xbbf1bc62, 0x3b953c75, 0xbac9bc7f, 0x3c7f3ac9, 0xbc75bb95, 0x3c623bf1, 0xbc46bc22, 0x3c3e3c2c, 0x3c18bc4e,
    0xbc5cbc04, 0xbbdb3c67, 0x3c713bac, 0x3b79bc78, 0xbc7dbb16, 0xba493c80, 0x3c80ba49, 0xbb16bc7d, 0xbc783b79, 0x3bac3c71,
    0x3c67bbdb, 0xbc04bc5c, 0xbc4e3c18, 0x3c2c3c3e, 0x3c2cbc3e, 0xbc4ebc18, 0xbc043c5c, 0x3c673bdb, 0x3bacbc71, 0xbc78bb79,
    0xbb163c7d, 0x3c803a49, 0xba49bc80, 0xbc7d3b16, 0x3b793c78, 0x3c71bbac, 0xbbdbbc67, 0xbc5c3c04, 0x3c183c4e, 0x3c3ebc2c,
    0x3c5cbc04, 0xbc3ebc2c, 0xbbdb3c67, 0x3c7d3b16, 0x3c4e3c18, 0x3bacbc71, 0xbc80ba49, 0x3b793c78, 0xbc78bb79, 0x3a493c80,
    0x3c71bbac, 0xbc18bc4e, 0xbb16bc7d, 0xbc673bdb, 0x3c2c3c3e, 0x3c04bc5c, 0x3c043c5c, 0x3c2cbc3e, 0xbc67bbdb, 0xbb163c7d,
    0xbc183c4e, 0x3c713bac, 0x3a49bc80, 0xbc783b79, 0x3b79bc78, 0xbc803a49, 0x3bac3c71, 0x3c4ebc18, 0x3c7dbb16, 0xbbdbbc67,
    0xbc3e3c2c, 0x3c5c3c04, 0xbc783b79, 0x3c2c3c3e, 0x3bacbc71, 0xbc7d3b16, 0x3c183c4e, 0x3bdbbc67, 0xbc803a49, 0x3c043c5c,
    0x3c5c3c04, 0x3a49bc80, 0xbc673bdb, 0x3c4e3c18, 0x3b16bc7d, 0xbc713bac, 0x3c3e3c2c, 0x3b79bc78, 0x3b793c78, 0x3c3ebc2c,
    0xbc71bbac, 0x3b163c7d, 0x3c4ebc18, 0xbc67bbdb, 0x3a493c80, 0x3c5cbc04, 0x3c04bc5c, 0xbc80ba49, 0x3bdb3c67, 0x3c18bc4e,
    0xbc7dbb16, 0x3bac3c71, 0x3c2cbc3e, 0xbc78bb79, 0x3a49bc80, 0xbc4e3c18, 0x3c783b79, 0xbbdbbc67, 0x3bac3c71, 0x3c04bc5c,
    0xbc7d3b16, 0x3c3e3c2c, 0xbc2cbc3e, 0xbb163c7d, 0x3c5cbc04, 0xbc71bbac, 0x3c673bdb, 0xbb79bc78, 0xbc183c4e, 0x3c80ba49,
    0x3c803a49, 0xbc18bc4e, 0xbb793c78, 0x3c67bbdb, 0xbc713bac, 0x3c5c3c04, 0xbb16bc7d, 0xbc2c3c3e, 0x3c3ebc2c, 0xbc7dbb16,
    0x3c043c5c, 0x3bacbc71, 0xbbdb3c67, 0x3c78bb79, 0xbc4ebc18, 0x3a493c80, 0x3bacbc71, 0xbc5c3c04, 0x3c7d3b16, 0xbc2cbc3e,
    0x3a493c80, 0x3c18bc4e, 0xbc783b79, 0x3c673bdb, 0xbbdbbc67, 0xbb793c78, 0x3c4ebc18, 0xbc80ba49, 0x3c3e3c2c, 0xbb16bc7d,
    0xbc043c5c, 0x3c71bbac, 0x3c713bac, 0xbc04bc5c, 0xbb163c7d, 0x3c3ebc2c, 0xbc803a49, 0x3c4e3c18, 0xbb79bc78, 0xbbdb3c67,
    0x3c67bbdb, 0xbc78bb79, 0x3c183c4e, 0x3a49bc80, 0xbc2c3c3e, 0x3c7dbb16, 0xbc5cbc04, 0x3bac3c71, 0xbc4ebc18, 0x3bdb3c67,
    0x3a49bc80, 0xbc043c5c, 0xbb793c78, 0x3c2cbc3e, 0xbc713bac, 0x3c7d3b16, 0x3b163c7d, 0x3bacbc71, 0xbc3e3c2c, 0x3c78bb79,
    0x3c5cbc04, 0xbc803a49, 0x3c673bdb, 0xbc18bc4e, 0xbc183c4e, 0x3c67bbdb, 0xbc80ba49, 0x3c5c3c04, 0x3c783b79, 0xbc3ebc2c,
    0x3bac3c71, 0x3b16bc7d, 0x3c7dbb16, 0xbc71bbac, 0x3c2c3c3e, 0xbb79bc78, 0xbc04bc5c, 0x3a493c80, 0x3bdbbc67, 0xbc4e3c18,
    0x3c183c4e, 0xbbacbc71, 0x3a493c80, 0x3b79bc78, 0xbc043c5c, 0x3c3ebc2c, 0xbc673bdb, 0x3c7dbb16, 0x3b16bc7d, 0xbbdb3c67,
    0x3c2cbc3e, 0xbc5c3c04, 0x3c78bb79, 0xbc80ba49, 0x3c713bac, 0xbc4ebc18, 0xbc4e3c18, 0x3c71bbac, 0xbc803a49, 0x3c783b79,
    0xbc5cbc04, 0x3c2c3c3e, 0xbbdbbc67, 0x3b163c7d, 0x3c7d3b16, 0xbc67bbdb, 0x3c3e3c2c, 0xbc04bc5c, 0x3b793c78, 0x3a49bc80,
    0xbbac3c71, 0x3c18bc4e, 0xbc713bac, 0x3c78bb79, 0xbc7d3b16, 0x3c80ba49, 0xbc3e3c2c, 0x3c4ebc18, 0xbc5c3c04, 0x3c67bbdb,
    0xbbdb3c67, 0x3c04bc5c, 0xbc183c4e, 0x3c2cbc3e, 0xba493c80, 0x3b16bc7d, 0xbb793c78, 0x3bacbc71, 0x3bac3c71, 0xbb79bc78,
    0x3b163c7d, 0xba49bc80, 0x3c2c3c3e, 0xbc18bc4e, 0x3c043c5c, 0xbbdbbc67, 0x3c673bdb, 0xbc5cbc04, 0x3c4e3c18, 0xbc3ebc2c,
    0x3c803a49, 0xbc7dbb16, 0x3c783b79, 0xbc71bbac, 0x3c800000, 0xbc800000, 0x3c800000, 0xbc800000, 0x3c800000, 0xbc800000,
    0x3c800000, 0xbc800000, 0x3c800000, 0xbc800000, 0x3c800000, 0xbc800000, 0x3c800000, 0xbc800000, 0x3c800000, 0xbc800000,
    0x3c800000, 0xbc800000, 0x3c800000, 0xbc800000, 0x3c800000, 0xbc800000, 0x3c800000, 0xbc800000, 0x3c800000, 0xbc800000,
    0x3c800000, 0xbc800000, 0x3c800000, 0xbc800000, 0x3c800000, 0xbc800000, 0x3c22bc46, 0xbbf13c62, 0x3b95bc75, 0xbac93c7f,
    0x3c7fbac9, 0xbc753b95, 0x3c62bbf1, 0xbc463c22, 0xbc46bc22, 0x3c623bf1, 0xbc75bb95, 0x3c7f3ac9, 0xbac9bc7f, 0x3b953c75,
    0xbbf1bc62, 0x3c223c46, 0xbc223c46, 0x3bf1bc62, 0xbb953c75, 0x3ac9bc7f, 0xbc7f3ac9, 0x3c75bb95, 0xbc623bf1, 0x3c46bc22,
    0x3c463c22, 0xbc62bbf1, 0x3c753b95, 0xbc7fbac9, 0x3ac93c7f, 0xbb95bc75, 0x3bf13c62, 0xbc22bc46, 0xbc7b3b48, 0x3c55bc0e,
    0xbc0e3c55, 0x3b48bc7b, 0x3b483c7b, 0xbc0ebc55, 0x3c553c0e, 0xbc7bbb48, 0x3c7bbb48, 0xbc553c0e, 0x3c0ebc55, 0xbb483c7b,
    0xbb48bc7b, 0x3c0e3c55, 0xbc55bc0e, 0x3c7b3b48, 0xbc7b3b48, 0x3c55bc0e, 0xbc0e3c55, 0x3b48bc7b, 0x3b483c7b, 0xbc0ebc55,
    0x3c553c0e, 0xbc7bbb48, 0x3c7bbb48, 0xbc553c0e, 0x3c0ebc55, 0xbb483c7b, 0xbb48bc7b, 0x3c0e3c55, 0xbc55bc0e, 0x3c7b3b48,
    0x3bf1bc62, 0x3ac93c7f, 0xbc22bc46, 0x3c753b95, 0x3b953c75, 0xbc46bc22, 0x3c7f3ac9, 0xbc623bf1, 0xbc62bbf1, 0x3c7fbac9,
    0xbc463c22, 0x3b95bc75, 0x3c75bb95, 0xbc223c46, 0x3ac9bc7f, 0x3bf13c62, 0xbbf13c62, 0xbac9bc7f, 0x3c223c46, 0xbc75bb95,
    0xbb95bc75, 0x3c463c22, 0xbc7fbac9, 0x3c62bbf1, 0x3c623bf1, 0xbc7f3ac9, 0x3c46bc22, 0xbb953c75, 0xbc753b95, 0x3c22bc46,
    0xbac93c7f, 0xbbf1bc62, 0x3c6dbbc4, 0xbbc43c6d, 0xbbc4bc6d, 0x3c6d3bc4, 0xbc6d3bc4, 0x3bc4bc6d, 0x3bc43c6d, 0xbc6dbbc4,
    0x3c6dbbc4, 0xbbc43c6d, 0xbbc4bc6d, 0x3c6d3bc4, 0xbc6d3bc4, 0x3bc4bc6d, 0x3bc43c6d, 0xbc6dbbc4, 0x3c6dbbc4, 0xbbc43c6d,
    0xbbc4bc6d, 0x3c6d3bc4, 0xbc6d3bc4, 0x3bc4bc6d, 0x3bc43c6d, 0xbc6dbbc4, 0x3c6dbbc4, 0xbbc43c6d, 0xbbc4bc6d, 0x3c6d3bc4,
    0xbc6d3bc4, 0x3bc4bc6d, 0x3bc43c6d, 0xbc6dbbc4, 0x3b95bc75, 0x3c223c46, 0xbc7f3ac9, 0x3bf1bc62, 0xbc623bf1, 0x3ac9bc7f,
    0x3c463c22, 0xbc753b95, 0xbc75bb95, 0x3c46bc22, 0x3ac93c7f, 0xbc62bbf1, 0x3bf13c62, 0xbc7fbac9, 0x3c22bc46, 0x3b953c75,
    0xbb953c75, 0xbc22bc46, 0x3c7fbac9, 0xbbf13c62, 0x3c62bbf1, 0xbac93c7f, 0xbc46bc22, 0x3c75bb95, 0x3c753b95, 0xbc463c22,
    0xbac9bc7f, 0x3c623bf1, 0xbbf1bc62, 0x3c7f3ac9, 0xbc223c46, 0xbb95bc75, 0xbc553c0e, 0xbb48bc7b, 0x3c7b3b48, 0xbc0e3c55,
    0xbc0ebc55, 0x3c7bbb48, 0xbb483c7b, 0xbc55bc0e, 0x3c55bc0e, 0x3b483c7b, 0xbc7bbb48, 0x3c0ebc55, 0x3c0e3c55, 0xbc7b3b48,
    0x3b48bc7b, 0x3c553c0e, 0xbc553c0e, 0xbb48bc7b, 0x3c7b3b48, 0xbc0e3c55, 0xbc0ebc55, 0x3c7bbb48, 0xbb483c7b, 0xbc55bc0e,
    0x3c55bc0e, 0x3b483c7b, 0xbc7bbb48, 0x3c0ebc55, 0x3c0e3c55, 0xbc7b3b48, 0x3b48bc7b, 0x3c553c0e, 0x3ac9bc7f, 0x3c753b95,
    0xbbf13c62, 0xbc46bc22, 0xbc22bc46, 0x3c62bbf1, 0x3b953c75, 0xbc7f3ac9, 0xbc7fbac9, 0x3b95bc75, 0x3c623bf1, 0xbc223c46,
    0xbc463c22, 0xbbf1bc62, 0x3c75bb95, 0x3ac93c7f, 0xbac93c7f, 0xbc75bb95, 0x3bf1bc62, 0x3c463c22, 0x3c223c46, 0xbc623bf1,
    0xbb95bc75, 0x3c7fbac9, 0x3c7f3ac9, 0xbb953c75, 0xbc62bbf1, 0x3c22bc46, 0x3c46bc22, 0x3bf13c62, 0xbc753b95, 0xbac9bc7f,
    0x3c80ba49, 0xbc7d3b16, 0x3c78bb79, 0xbc713bac, 0x3c67bbdb, 0xbc5c3c04, 0x3c4ebc18, 0xbc3e3c2c, 0x3c2cbc3e, 0xbc183c4e,
    0x3c04bc5c, 0xbbdb3c67, 0x3bacbc71, 0xbb793c78, 0x3b16bc7d, 0xba493c80, 0xba49bc80, 0x3b163c7d, 0xbb79bc78, 0x3bac3c71,
    0xbbdbbc67, 0x3c043c5c, 0xbc18bc4e, 0x3c2c3c3e, 0xbc3ebc2c, 0x3c4e3c18, 0xbc5cbc04, 0x3c673bdb, 0xbc71bbac, 0x3c783b79,
    0xbc7dbb16, 0x3c803a49, 0x3b79bc78, 0x3a493c80, 0xbbacbc71, 0x3c183c4e, 0x3c7dbb16, 0xbc673bdb, 0x3c3ebc2c, 0xbc043c5c,
    0xbc5c3c04, 0x3c2cbc3e, 0xbbdb3c67, 0x3b16bc7d, 0xbc4ebc18, 0x3c713bac, 0xbc80ba49, 0x3c78bb79, 0x3c783b79, 0xbc803a49,
    0x3c71bbac, 0xbc4e3c18, 0x3b163c7d, 0xbbdbbc67, 0x3c2c3c3e, 0xbc5cbc04, 0xbc04bc5c, 0x3c3e3c2c, 0xbc67bbdb, 0x3c7d3b16,
    0x3c18bc4e, 0xbbac3c71, 0x3a49bc80, 0x3b793c78, 0xbc043c5c, 0x3a49bc80, 0x3bdb3c67, 0xbc4ebc18, 0x3c7d3b16, 0xbc713bac,
    0x3c2cbc3e, 0xbb793c78, 0x3c78bb79, 0xbc3e3c2c, 0x3bacbc71, 0x3b163c7d, 0xbc18bc4e, 0x3c673bdb, 0xbc803a49, 0x3c5cbc04,
    0x3c5c3c04, 0xbc80ba49, 0x3c67bbdb, 0xbc183c4e, 0x3b16bc7d, 0x3bac3c71, 0xbc3ebc2c, 0x3c783b79, 0xbb79bc78, 0x3c2c3c3e,
    0xbc71bbac, 0x3c7dbb16, 0xbc4e3c18, 0x3bdbbc67, 0x3a493c80, 0xbc04bc5c, 0xbc2cbc3e, 0x3c7d3b16, 0xbc5c3c04, 0x3bacbc71,
    0x3c673bdb, 0xbc783b79, 0x3c18bc4e, 0x3a493c80, 0xbc80ba49, 0x3c4ebc18, 0xbb793c78, 0xbbdbbc67, 0x3c71bbac, 0xbc043c5c,
    0xbb16bc7d, 0x3c3e3c2c, 0x3c3ebc2c, 0xbb163c7d, 0xbc04bc5c, 0x3c713bac, 0xbbdb3c67, 0xbb79bc78, 0x3c4e3c18, 0xbc803a49,
    0x3a49bc80, 0x3c183c4e, 0xbc78bb79, 0x3c67bbdb, 0x3bac3c71, 0xbc5cbc04, 0x3c7dbb16, 0xbc2c3c3e, 0xbbdbbc67, 0x3c783b79,
    0xbc4e3c18, 0x3a49bc80, 0x3c3e3c2c, 0xbc7d3b16, 0x3c04bc5c, 0x3bac3c71, 0xbc71bbac, 0x3c5cbc04, 0xbb163c7d, 0xbc2cbc3e,
    0x3c80ba49, 0xbc183c4e, 0xbb79bc78, 0x3c673bdb, 0x3c67bbdb, 0xbb793c78, 0xbc18bc4e, 0x3c803a49, 0xbc2c3c3e, 0xbb16bc7d,
    0x3c5c3c04, 0xbc713bac, 0x3bacbc71, 0x3c043c5c, 0xbc7dbb16, 0x3c3ebc2c, 0x3a493c80, 0xbc4ebc18, 0x3c78bb79, 0xbbdb3c67,
    0xbc7d3b16, 0x3bacbc71, 0x3c2c3c3e, 0xbc783b79, 0x3c043c5c, 0xbc803a49, 0x3bdbbc67, 0x3c183c4e, 0x3c4e3c18, 0xbc673bdb,
    0x3a49bc80, 0x3c5c3c04, 0x3b79bc78, 0x3c3e3c2c, 0xbc713bac, 0x3b16bc7d, 0x3b163c7d, 0xbc71bbac, 0x3c3ebc2c, 0x3b793c78,
    0x3c5cbc04, 0x3a493c80, 0xbc67bbdb, 0x3c4ebc18, 0x3c18bc4e, 0x3bdb3c67, 0xbc80ba49, 0x3c04bc5c, 0xbc78bb79, 0x3c2cbc3e,
    0x3bac3c71, 0xbc7dbb16, 0x3c7d3b16, 0xbbdb3c67, 0xbc3ebc2c, 0x3c5cbc04, 0x3b793c78, 0xbc80ba49, 0x3bacbc71, 0x3c4e3c18,
    0xbc18bc4e, 0x3c71bbac, 0x3a493c80, 0xbc78bb79, 0x3c04bc5c, 0x3c2c3c3e, 0xbc673bdb, 0xbb16bc7d, 0xbb163c7d, 0xbc67bbdb,
    0x3c2cbc3e, 0x3c043c5c, 0xbc783b79, 0x3a49bc80, 0x3c713bac, 0xbc183c4e, 0x3c4ebc18, 0x3bac3c71, 0xbc803a49, 0x3b79bc78,
    0x3c5c3c04, 0xbc3e3c2c, 0xbbdbbc67, 0x3c7dbb16, 0xbbdb3c67, 0xbc5cbc04, 0x3c18bc4e, 0x3c3e3c2c, 0xba493c80, 0xbc7dbb16,
    0x3b79bc78, 0x3c713bac, 0x3bac3c71, 0xbc783b79, 0xbb16bc7d, 0x3c80ba49, 0x3c2c3c3e, 0xbc4e3c18, 0xbc04bc5c, 0x3c67bbdb,
    0x3c673bdb, 0xbc043c5c, 0xbc4ebc18, 0x3c2cbc3e, 0x3c803a49, 0xbb163c7d, 0xbc78bb79, 0x3bacbc71, 0x3c71bbac, 0x3b793c78,
    0xbc7d3b16, 0xba49bc80, 0x3c3ebc2c, 0x3c183c4e, 0xbc5c3c04, 0xbbdbbc67, 0x3f803f80, 0x3f7d3f7f, 0x3f783f7b, 0x3f713f75,
    0x3f673f6d, 0x3f5c3f62, 0x3f4e3f55, 0x3f3e3f46, 0x3f2c3f35, 0x3f183f22, 0x3f043f0e, 0x3edb3ef1, 0x3eac3ec4, 0x3e793e95,
    0x3e163e48, 0x3d493dc9, 0xbd490000, 0xbe16bdc9, 0xbe79be48, 0xbeacbe95, 0xbedbbec4, 0xbf04bef1, 0xbf18bf0e, 0xbf2cbf22,
    0xbf3ebf35, 0xbf4ebf46, 0xbf5cbf55, 0xbf67bf62, 0xbf71bf6d, 0xbf78bf75, 0xbf7dbf7b, 0xbf80bf7f, 0x3edb3ec4, 0x3f043ef1,
    0x3f183f0e, 0x3f2c3f22, 0x3d490000, 0x3e163dc9, 0x3e793e48, 0x3eac3e95, 0x3f713f6d, 0x3f783f75, 0x3f7d3f7b, 0x3f803f7f,
    0x3f3e3f35, 0x3f4e3f46, 0x3f5c3f55, 0x3f673f62, 0x3f673f6d, 0x3f5c3f62, 0x3f4e3f55, 0x3f3e3f46, 0x3f803f80, 0x3f7d3f7f,
    0x3f783f7b, 0x3f713f75, 0x3eac3ec4, 0x3e793e95, 0x3e163e48, 0x3d493dc9, 0x3f2c3f35, 0x3f183f22, 0x3f043f0e, 0x3edb3ef1,
    0xbf4ebf35, 0xbf71bf62, 0xbf80bf7b, 0xbf78bf7f, 0xbf5cbf6d, 0xbf2cbf46, 0xbedbbf0e, 0xbe16be95, 0x3f7d3f80, 0x3f673f75,
    0x3f3e3f55, 0x3f043f22, 0x3e793ec4, 0xbd493dc9, 0xbeacbe48, 0xbf18bef1, 0x3f183f35, 0x3eac3ef1, 0x3d493e48, 0xbe79bdc9,
    0xbf04bec4, 0xbf3ebf22, 0xbf67bf55, 0xbf7dbf75, 0x3e160000, 0x3edb3e95, 0x3f2c3f0e, 0x3f5c3f46, 0x3f783f6d, 0x3f803f7f,
    0x3f713f7b, 0x3f4e3f62, 0xbf04bec4, 0xbf3ebf22, 0xbf67bf55, 0xbf7dbf75, 0x3f183f35, 0x3eac3ef1, 0x3d493e48, 0xbe79bdc9,
    0x3f783f6d, 0x3f803f7f, 0x3f713f7b, 0x3f4e3f62, 0x3e160000, 0x3edb3e95, 0x3f2c3f0e, 0x3f5c3f46, 0x3f5c3f6d, 0x3f2c3f46,
    0x3edb3f0e, 0x3e163e95, 0x3f4e3f35, 0x3f713f62, 0x3f803f7b, 0x3f783f7f, 0xbe79bec4, 0x3d49bdc9, 0x3eac3e48, 0x3f183ef1,
    0xbf7dbf80, 0xbf67bf75, 0xbf3ebf55, 0xbf04bf22, 0xbe790000, 0xbf2cbef1, 0xbf71bf55, 0xbf7dbf7f, 0xbf4ebf6d, 0xbedbbf22,
    0x3d49be48, 0x3f043e95, 0x3f5c3f35, 0x3f803f75, 0x3f673f7b, 0x3f183f46, 0x3e163ec4, 0xbeacbdc9, 0xbf3ebf0e, 0xbf78bf62,
    0x3f783f80, 0x3f3e3f62, 0x3eac3f0e, 0xbe163dc9, 0xbf18bec4, 0xbf67bf46, 0xbf80bf7b, 0xbf5cbf75, 0xbf04bf35, 0xbd49be95,
    0x3edb3e48, 0x3f4e3f22, 0x3f7d3f6d, 0x3f713f7f, 0x3f2c3f55, 0x3e793ef1, 0xbf18bec4, 0xbf67bf46, 0xbf80bf7b, 0xbf5cbf75,
    0x3f783f80, 0x3f3e3f62, 0x3eac3f0e, 0xbe163dc9, 0x3f7d3f6d, 0x3f713f7f, 0x3f2c3f55, 0x3e793ef1, 0xbf04bf35, 0xbd49be95,
    0x3edb3e48, 0x3f4e3f22, 0x3f4e3f6d, 0x3edb3f22, 0xbd493e48, 0xbf04be95, 0x3e790000, 0x3f2c3ef1, 0x3f713f55, 0x3f7d3f7f,
    0xbe16bec4, 0x3eac3dc9, 0x3f3e3f0e, 0x3f783f62, 0xbf5cbf35, 0xbf80bf75, 0xbf67bf7b, 0xbf18bf46, 0xbedbbf35, 0x3e79bdc9,
    0x3f4e3f0e, 0x3f803f75, 0x3f3e3f6d, 0x3e163ef1, 0xbf04be48, 0xbf71bf46, 0x3eac0000, 0x3f5c3f22, 0x3f7d3f7b, 0x3f2c3f62,
    0x3d493ec4, 0xbf18be95, 0xbf78bf55, 0xbf67bf7f, 0x3f673f35, 0x3f783f7f, 0x3f183f55, 0xbd493e95, 0xbf2cbec4, 0xbf7dbf62,
    0xbf5cbf7b, 0xbeacbf22, 0x3f713f80, 0x3f043f46, 0xbe163e48, 0xbf3ebef1, 0xbf80bf6d, 0xbf4ebf75, 0xbe79bf0e, 0x3edb3dc9,
    0x3f2c3ec4, 0x3f7d3f62, 0x3f5c3f7b, 0x3eac3f22, 0xbf67bf35, 0xbf78bf7f, 0xbf18bf55, 0x3d49be95, 0x3f803f6d, 0x3f4e3f75,
    0x3e793f0e, 0xbedbbdc9, 0xbf71bf80, 0xbf04bf46, 0x3e16be48, 0x3f3e3ef1, 0x3f3e3f6d, 0x3e163ef1, 0xbf04be48, 0xbf71bf46,
    0xbedbbf35, 0x3e79bdc9, 0x3f4e3f0e, 0x3f803f75, 0x3d493ec4, 0xbf18be95, 0xbf78bf55, 0xbf67bf7f, 0x3eac0000, 0x3f5c3f22,
    0x3f7d3f7b, 0x3f2c3f62, 0x3f673f80, 0x3e793f22, 0xbf18be48, 0xbf80bf62, 0xbf2cbf6d, 0x3e16be95, 0x3f5c3f0e, 0x3f713f7f,
    0x3eac3f35, 0xbf04bdc9, 0xbf7dbf55, 0xbf3ebf75, 0x3d49bec4, 0x3f4e3ef1, 0x3f783f7b, 0x3edb3f46, 0xbedb0000, 0xbf78bf46,
    0xbf4ebf7b, 0xbd49bef1, 0x3f3e3ec4, 0x3f7d3f75, 0x3f043f55, 0xbeac3dc9, 0xbf71bf35, 0xbf5cbf7f, 0xbe16bf0e, 0x3f2c3e95,
    0x3f803f6d, 0x3f183f62, 0xbe793e48, 0xbf67bf22, 0xbf3ebec4, 0xbf7dbf75, 0xbf04bf55, 0x3eacbdc9, 0x3edb0000, 0x3f783f46,
    0x3f4e3f7b, 0x3d493ef1, 0xbf80bf6d, 0xbf18bf62, 0x3e79be48, 0x3f673f22, 0x3f713f35, 0x3f5c3f7f, 0x3e163f0e, 0xbf2cbe95,
    0xbf2cbf6d, 0x3e16be95, 0x3f5c3f0e, 0x3f713f7f, 0x3f673f80, 0x3e793f22, 0xbf18be48, 0xbf80bf62, 0x3d49bec4, 0x3f4e3ef1,
    0x3f783f7b, 0x3edb3f46, 0x3eac3f35, 0xbf04bdc9, 0xbf7dbf55, 0xbf3ebf75, 0xbf78bf35, 0xbf2cbf75, 0x3eacbe48, 0x3f7d3f46,
    0x3f183f6d, 0xbedb3dc9, 0xbf80bf55, 0xbf04bf62, 0x3f5c3f80, 0xbd493ef1, 0xbf67bf0e, 0xbf4ebf7f, 0x3e16bec4, 0x3f713f22,
    0x3f3e3f7b, 0xbe793e95, 0x3e793f35, 0xbf3ebe95, 0xbf71bf7b, 0xbe16bf22, 0x3f4e3ec4, 0x3f673f7f, 0x3d493f0e, 0xbf5cbef1,
    0x3f040000, 0x3f803f62, 0x3edb3f55, 0xbf18bdc9, 0xbf7dbf6d, 0xbeacbf46, 0x3f2c3e48, 0x3f783f75, 0x3f4e3ec4, 0x3f673f7f,
    0x3d493f0e, 0xbf5cbef1, 0x3e793f35, 0xbf3ebe95, 0xbf71bf7b, 0xbe16bf22, 0xbf7dbf6d, 0xbeacbf46, 0x3f2c3e48, 0x3f783f75,
    0x3f040000, 0x3f803f62, 0x3edb3f55, 0xbf18bdc9, 0xbf18bf6d, 0x3edbbdc9, 0x3f803f55, 0x3f043f62, 0x3f783f35, 0x3f2c3f75,
    0xbeac3e48, 0xbf7dbf46, 0xbe163ec4, 0xbf71bf22, 0xbf3ebf7b, 0x3e79be95, 0xbf5cbf80, 0x3d49bef1, 0x3f673f0e, 0x3f4e3f7f,
    0xbf180000, 0xbf71bf75, 0x3d49bf0e, 0x3f783f22, 0x3f043f6d, 0xbf2cbdc9, 0xbf67bf7b, 0x3e16bef1, 0x3f7d3f35, 0x3edb3f62,
    0xbf3ebe48, 0xbf5cbf7f, 0x3e79bec4, 0x3f803f46, 0x3eac3f55, 0xbf4ebe95, 0x3f4e3f80, 0xbeac3e95, 0xbf80bf55, 0xbe79bf46,
    0x3f5c3ec4, 0x3f3e3f7f, 0xbedb3e48, 0xbf7dbf62, 0xbe16bf35, 0x3f673ef1, 0x3f2c3f7b, 0xbf043dc9, 0xbf78bf6d, 0xbd49bf22,
    0x3f713f0e, 0x3f183f75, 0x3f5c3ec4, 0x3f3e3f7f, 0xbedb3e48, 0xbf7dbf62, 0x3f4e3f80, 0xbeac3e95, 0xbf80bf55, 0xbe79bf46,
    0xbf78bf6d, 0xbd49bf22, 0x3f713f0e, 0x3f183f75, 0xbe16bf35, 0x3f673ef1, 0x3f2c3f7b, 0xbf043dc9, 0xbf04bf6d, 0x3f2c3dc9,
    0x3f673f7b, 0xbe163ef1, 0x3f180000, 0x3f713f75, 0xbd493f0e, 0xbf78bf22, 0xbe793ec4, 0xbf80bf46, 0xbeacbf55, 0x3f4e3e95,
    0xbf7dbf35, 0xbedbbf62, 0x3f3e3e48, 0x3f5c3f7f, 0xbd49bf35, 0x3f7d3f22, 0x3e793f55, 0xbf71bef1, 0xbedbbf6d, 0x3f5c3e95,
    0x3f183f7b, 0xbf3ebdc9, 0x3f2c0000, 0x3f4e3f7f, 0xbf043e48, 0xbf67bf75, 0x3eacbec4, 0x3f783f62, 0xbe163f0e, 0xbf80bf46,
    0x3f803f35, 0x3e163f46, 0xbf78bf0e, 0xbeacbf62, 0x3f673ec4, 0x3f043f75, 0xbf4ebe48, 0xbf2cbf7f, 0x3f3e3f80, 0xbf183dc9,
    0xbf5cbf7b, 0x3edbbe95, 0x3f713f6d, 0xbe793ef1, 0xbf7dbf55, 0x3d49bf22, 0xbf67bec4, 0xbf04bf75, 0x3f4e3e48, 0x3f2c3f7f,
    0xbf80bf35, 0xbe16bf46, 0x3f783f0e, 0x3eac3f62, 0xbf71bf6d, 0x3e79bef1, 0x3f7d3f55, 0xbd493f22, 0xbf3ebf80, 0x3f18bdc9,
    0x3f5c3f7b, 0xbedb3e95, 0xbedbbf6d, 0x3f5c3e95, 0x3f183f7b, 0xbf3ebdc9, 0xbd49bf35, 0x3f7d3f22, 0x3e793f55, 0xbf71bef1,
    0x3eacbec4, 0x3f783f62, 0xbe163f0e, 0xbf80bf46, 0x3f2c0000, 0x3f4e3f7f, 0xbf043e48, 0xbf67bf75, 0x3f2c3f80, 0xbf4ebdc9,
    0xbf04bf7b, 0x3f673e95, 0x3eac3f6d, 0xbf78bef1, 0xbe16bf55, 0x3f803f22, 0xbd493f35, 0xbf7dbf46, 0x3e79bf0e, 0x3f713f62,
    0xbedb3ec4, 0xbf5cbf75, 0x3f18be48, 0x3f3e3f7f, 0xbf3e0000, 0xbf18bf7f, 0x3f5c3e48, 0x3edb3f75, 0xbf71bec4, 0xbe79bf62,
    0x3f7d3f0e, 0x3d493f46, 0xbf80bf35, 0x3e16bf22, 0x3f783f55, 0xbeac3ef1, 0xbf67bf6d, 0x3f04be95, 0x3f4e3f7b, 0xbf2c3dc9,
    0x3f713ec4, 0x3e793f62, 0xbf7dbf0e, 0xbd49bf46, 0x3f3e0000, 0x3f183f7f, 0xbf5cbe48, 0xbedbbf75, 0x3f673f6d, 0xbf043e95,
    0xbf4ebf7b, 0x3f2cbdc9, 0x3f803f35, 0xbe163f22, 0xbf78bf55, 0x3eacbef1, 0x3eac3f6d, 0xbf78bef1, 0xbe16bf55, 0x3f803f22,
    0x3f2c3f80, 0xbf4ebdc9, 0xbf04bf7b, 0x3f673e95, 0xbedb3ec4, 0xbf5cbf75, 0x3f18be48, 0x3f3e3f7f, 0xbd493f35, 0xbf7dbf46,
    0x3e79bf0e, 0x3f713f62, 0xbf7dbf35, 0x3edbbef1, 0x3f3e3f7b, 0xbf5cbdc9, 0xbe79bf6d, 0x3f803f22, 0xbeac3f0e, 0xbf4ebf75,
    0x3f183f80, 0xbf71be95, 0xbd49bf55, 0x3f783f46, 0xbf043ec4, 0xbf2cbf7f, 0x3f673e48, 0x3e163f62, 0xbe163f35, 0xbf67bf62,
    0x3f2cbe48, 0x3f043f7f, 0xbf78bec4, 0x3d49bf46, 0x3f713f55, 0xbf183e95, 0x3f4e0000, 0x3eac3f75, 0xbf80bf0e, 0x3e79bf22,
    0x3f5c3f6d, 0xbf3e3dc9, 0xbedbbf7b, 0x3f7d3ef1, 0xbf78bec4, 0x3d49bf46, 0x3f713f55, 0xbf183e95, 0xbe163f35, 0xbf67bf62,
    0x3f2cbe48, 0x3f043f7f, 0x3f5c3f6d, 0xbf3e3dc9, 0xbedbbf7b, 0x3f7d3ef1, 0x3f4e0000, 0x3eac3f75, 0xbf80bf0e, 0x3e79bf22,
    0x3e793f6d, 0xbf80bf22, 0x3eacbf0e, 0x3f4e3f75, 0x3f7d3f35, 0xbedb3ef1, 0xbf3ebf7b, 0x3f5c3dc9, 0x3f04bec4, 0x3f2c3f7f,
    0xbf67be48, 0xbe16bf62, 0xbf18bf80, 0x3f713e95, 0x3d493f55, 0xbf78bf46, 0xbf5c0000, 0xbd49bf62, 0x3f673f55, 0xbf4e3dc9,
    0xbe16bf6d, 0x3f713f46, 0xbf3e3e48, 0xbe79bf75, 0x3f783f35, 0xbf2c3e95, 0xbeacbf7b, 0x3f7d3f22, 0xbf183ec4, 0xbedbbf7f,
    0x3f803f0e, 0xbf043ef1, 0x3f043f80, 0xbf80bef1, 0x3edbbf0e, 0x3f183f7f, 0xbf7dbec4, 0x3eacbf22, 0x3f2c3f7b, 0xbf78be95,
    0x3e79bf35, 0x3f3e3f75, 0xbf71be48, 0x3e16bf46, 0x3f4e3f6d, 0xbf67bdc9, 0x3d49bf55, 0x3f5c3f62, 0xbf7dbec4, 0x3eacbf22,
    0x3f2c3f7b, 0xbf78be95, 0x3f043f80, 0xbf80bef1, 0x3edbbf0e, 0x3f183f7f, 0x3f4e3f6d, 0xbf67bdc9, 0x3d49bf55, 0x3f5c3f62,
    0x3e79bf35, 0x3f3e3f75, 0xbf71be48, 0x3e16bf46, 0x3e163f6d, 0xbf71bf46, 0x3f3ebe48, 0x3e793f75, 0x3f5c0000, 0x3d493f62,
    0xbf67bf55, 0x3f4ebdc9, 0x3f18bec4, 0x3edb3f7f, 0xbf80bf0e, 0x3f04bef1, 0xbf78bf35, 0x3f2cbe95, 0x3eac3f7b, 0xbf7dbf22,
    0x3eacbf35, 0x3f043f7f, 0xbf7dbf0e, 0x3f3ebe95, 0x3d493f6d, 0xbf4ebf62, 0x3f783e48, 0xbedb3f22, 0x3f670000, 0xbe793f46,
    0xbf18bf7b, 0x3f803ef1, 0xbf2c3ec4, 0xbe16bf75, 0x3f5c3f55, 0xbf71bdc9, 0x3f713f35, 0xbf5c3dc9, 0x3e16bf55, 0x3f2c3f75,
    0xbf80bec4, 0x3f18bef1, 0x3e793f7b, 0xbf67bf46, 0x3edb3f80, 0xbf78bf22, 0x3f4ebe48, 0xbd493f62, 0xbf3ebf6d, 0x3f7d3e95,
    0xbf043f0e, 0xbeacbf7f, 0x3f803ec4, 0xbf183ef1, 0xbe79bf7b, 0x3f673f46, 0xbf71bf35, 0x3f5cbdc9, 0xbe163f55, 0xbf2cbf75,
    0x3f3e3f6d, 0xbf7dbe95, 0x3f04bf0e, 0x3eac3f7f, 0xbedbbf80, 0x3f783f22, 0xbf4e3e48, 0x3d49bf62, 0x3d493f6d, 0xbf4ebf62,
    0x3f783e48, 0xbedb3f22, 0x3eacbf35, 0x3f043f7f, 0xbf7dbf0e, 0x3f3ebe95, 0xbf2c3ec4, 0xbe16bf75, 0x3f5c3f55, 0xbf71bdc9,
    0x3f670000, 0xbe793f46, 0xbf18bf7b, 0x3f803ef1, 0x3eac3f80, 0xbf5cbf46, 0x3f7d3e48, 0xbf2c3ef1, 0x3d49bf6d, 0x3f183f75,
    0xbf78bf0e, 0x3f67bdc9, 0xbedb3f35, 0xbe79bf7f, 0x3f4e3f55, 0xbf80be95, 0x3f3ebec4, 0xbe163f62, 0xbf04bf7b, 0x3f713f22,
    0xbf710000, 0x3f04bf22, 0x3e163f7b, 0xbf3ebf62, 0x3f803ec4, 0xbf4e3e95, 0x3e79bf55, 0x3edb3f7f, 0xbf67bf35, 0x3f783dc9,
    0xbf183f0e, 0xbd49bf75, 0x3f2c3f6d, 0xbf7dbef1, 0x3f5cbe48, 0xbeac3f46, 0xbf80bec4, 0x3f4ebe95, 0xbe793f55, 0xbedbbf7f,
    0x3f710000, 0xbf043f22, 0xbe16bf7b, 0x3f3e3f62, 0xbf2cbf6d, 0x3f7d3ef1, 0xbf5c3e48, 0x3eacbf46, 0x3f673f35, 0xbf78bdc9,
    0x3f18bf0e, 0x3d493f75, 0x3d49bf6d, 0x3f183f75, 0xbf78bf0e, 0x3f67bdc9, 0x3eac3f80, 0xbf5cbf46, 0x3f7d3e48, 0xbf2c3ef1,
    0x3f3ebec4, 0xbe163f62, 0xbf04bf7b, 0x3f713f22, 0xbedb3f35, 0xbe79bf7f, 0x3f4e3f55, 0xbf80be95, 0xbf5cbf35, 0x3f803e95,
    0xbf673e48, 0x3f18bf22, 0xbe163f6d, 0xbeacbf7f, 0x3f3e3f55, 0xbf78bef1, 0x3e793f80, 0xbf2cbf62, 0x3f713f0e, 0xbf7dbdc9,
    0x3f4ebec4, 0xbedb3f46, 0xbd49bf7b, 0x3f043f75, 0xbf043f35, 0x3d49bf75, 0x3edb3f7b, 0xbf4ebf46, 0x3f7d3ec4, 0xbf713dc9,
    0x3f2cbf0e, 0xbe793f62, 0x3f780000, 0xbf3e3ef1, 0x3eacbf55, 0x3e163f7f, 0xbf18bf6d, 0x3f673f22, 0xbf80be48, 0x3f5cbe95,
    0x3f7d3ec4, 0xbf713dc9, 0x3f2cbf0e, 0xbe793f62, 0xbf043f35, 0x3d49bf75, 0x3edb3f7b, 0xbf4ebf46, 0xbf18bf6d, 0x3f673f22,
    0xbf80be48, 0x3f5cbe95, 0x3f780000, 0xbf3e3ef1, 0x3eacbf55, 0x3e163f7f, 0x3e16bf6d, 0x3eac3f7f, 0xbf3ebf55, 0x3f783ef1,
    0x3f5c3f35, 0xbf80be95, 0x3f67be48, 0xbf183f22, 0xbf4e3ec4, 0x3edbbf46, 0x3d493f7b, 0xbf04bf75, 0xbe79bf80, 0x3f2c3f62,
    0xbf71bf0e, 0x3f7d3dc9, 0xbf7d0000, 0x3f67be95, 0xbf3e3f0e, 0x3f04bf46, 0xbe793f6d, 0xbd49bf7f, 0x3eac3f7b, 0xbf18bf62,
    0x3f4e3f35, 0xbf71bef1, 0x3f803e48, 0xbf783dc9, 0x3f5cbec4, 0xbf2c3f22, 0x3edbbf55, 0xbe163f75, 0x3e163f80, 0xbedbbf75,
    0x3f2c3f55, 0xbf5cbf22, 0x3f783ec4, 0xbf80bdc9, 0x3f71be48, 0xbf4e3ef1, 0x3f18bf35, 0xbeac3f62, 0x3d49bf7b, 0x3e793f7f,
    0xbf04bf6d, 0x3f3e3f46, 0xbf67bf0e, 0x3f7d3e95, 0x3f783ec4, 0xbf80bdc9, 0x3f71be48, 0xbf4e3ef1, 0x3e163f80, 0xbedbbf75,
    0x3f2c3f55, 0xbf5cbf22, 0xbf04bf6d, 0x3f3e3f46, 0xbf67bf0e, 0x3f7d3e95, 0x3f18bf35, 0xbeac3f62, 0x3d49bf7b, 0x3e793f7f,
    0x3e79bf6d, 0x3d493f7f, 0xbeacbf7b, 0x3f183f62, 0x3f7d0000, 0xbf673e95, 0x3f3ebf0e, 0xbf043f46, 0xbf5c3ec4, 0x3f2cbf22,
    0xbedb3f55, 0x3e16bf75, 0xbf4ebf35, 0x3f713ef1, 0xbf80be48, 0x3f78bdc9, 0x3f2cbf35, 0xbf183f46, 0x3f04bf55, 0xbedb3f62,
    0x3eacbf6d, 0xbe793f75, 0x3e16bf7b, 0xbd493f7f, 0x3f800000, 0xbf7d3dc9, 0x3f78be48, 0xbf713e95, 0x3f67bec4, 0xbf5c3ef1,
    0x3f4ebf0e, 0xbf3e3f22, 0x3f3e3f35, 0xbf4ebf22, 0x3f5c3f0e, 0xbf67bef1, 0x3f713ec4, 0xbf78be95, 0x3f7d3e48, 0xbf80bdc9,
    0x3d493f80, 0xbe16bf7f, 0x3e793f7b, 0xbeacbf75, 0x3edb3f6d, 0xbf04bf62, 0x3f183f55, 0xbf2cbf46, 0xbf71bec4, 0x3f783e95,
    0xbf7dbe48, 0x3f803dc9, 0xbf3ebf35, 0x3f4e3f22, 0xbf5cbf0e, 0x3f673ef1, 0xbedbbf6d, 0x3f043f62, 0xbf18bf55, 0x3f2c3f46,
    0xbd49bf80, 0x3e163f7f, 0xbe79bf7b, 0x3eac3f75, 0x3eacbf6d, 0xbe793f75, 0x3e16bf7b, 0xbd493f7f, 0x3f2cbf35, 0xbf183f46,
    0x3f04bf55, 0xbedb3f62, 0x3f67bec4, 0xbf5c3ef1, 0x3f4ebf0e, 0xbf3e3f22, 0x3f800000, 0xbf7d3dc9, 0x3f78be48, 0xbf713e95,
    0xbd493f80, 0x3e16bf7f, 0xbe793f7b, 0x3eacbf75, 0xbedb3f6d, 0x3f04bf62, 0xbf183f55, 0x3f2cbf46, 0xbf3e3f35, 0x3f4ebf22,
    0xbf5c3f0e, 0x3f67bef1, 0xbf713ec4, 0x3f78be95, 0xbf7d3e48, 0x3f80bdc9, 0xbf800000, 0x3f7d3dc9, 0xbf78be48, 0x3f713e95,
    0xbf67bec4, 0x3f5c3ef1, 0xbf4ebf0e, 0x3f3e3f22, 0xbf2cbf35, 0x3f183f46, 0xbf04bf55, 0x3edb3f62, 0xbeacbf6d, 0x3e793f75,
    0xbe16bf7b, 0x3d493f7f, 0x3f673ec4, 0xbf5cbef1, 0x3f4e3f0e, 0xbf3ebf22, 0x3f800000, 0xbf7dbdc9, 0x3f783e48, 0xbf71be95,
    0x3eac3f6d, 0xbe79bf75, 0x3e163f7b, 0xbd49bf7f, 0x3f2c3f35, 0xbf18bf46, 0x3f043f55, 0xbedbbf62, 0xbedb3f6d, 0x3f04bf62,
    0xbf183f55, 0x3f2cbf46, 0xbd493f80, 0x3e16bf7f, 0xbe793f7b, 0x3eacbf75, 0xbf713ec4, 0x3f78be95, 0xbf7d3e48, 0x3f80bdc9,
    0xbf3e3f35, 0x3f4ebf22, 0xbf5c3f0e, 0x3f67bef1, 0xbf18bf35, 0x3eac3f62, 0xbd49bf7b, 0xbe793f7f, 0x3f04bf6d, 0xbf3e3f46,
    0x3f67bf0e, 0xbf7d3e95, 0xbe163f80, 0x3edbbf75, 0xbf2c3f55, 0x3f5cbf22, 0xbf783ec4, 0x3f80bdc9, 0xbf71be48, 0x3f4e3ef1,
    0xbf4e3f35, 0x3f71bef1, 0xbf803e48, 0x3f783dc9, 0xbf5cbec4, 0x3f2c3f22, 0xbedbbf55, 0x3e163f75, 0x3f7d0000, 0xbf67be95,
    0x3f3e3f0e, 0xbf04bf46, 0x3e793f6d, 0x3d49bf7f, 0xbeac3f7b, 0x3f18bf62, 0xbf5cbec4, 0x3f2c3f22, 0xbedbbf55, 0x3e163f75,
    0xbf4e3f35, 0x3f71bef1, 0xbf803e48, 0x3f783dc9, 0x3e793f6d, 0x3d49bf7f, 0xbeac3f7b, 0x3f18bf62, 0x3f7d0000, 0xbf67be95,
    0x3f3e3f0e, 0xbf04bf46, 0xbf043f6d, 0x3f3ebf46, 0xbf673f0e, 0x3f7dbe95, 0x3f183f35, 0xbeacbf62, 0x3d493f7b, 0x3e79bf7f,
    0x3f78bec4, 0xbf803dc9, 0x3f713e48, 0xbf4ebef1, 0x3e16bf80, 0xbedb3f75, 0x3f2cbf55, 0xbf5c3f22, 0xbf780000, 0x3f3e3ef1,
    0xbeacbf55, 0xbe163f7f, 0x3f18bf6d, 0xbf673f22, 0x3f80be48, 0xbf5cbe95, 0x3f043f35, 0xbd49bf75, 0xbedb3f7b, 0x3f4ebf46,
    0xbf7d3ec4, 0x3f713dc9, 0xbf2cbf0e, 0x3e793f62, 0xbe793f80, 0x3f2cbf62, 0xbf713f0e, 0x3f7dbdc9, 0xbf4ebec4, 0x3edb3f46,
    0x3d49bf7b, 0xbf043f75, 0x3f5cbf35, 0xbf803e95, 0x3f673e48, 0xbf18bf22, 0x3e163f6d, 0x3eacbf7f, 0xbf3e3f55, 0x3f78bef1,
    0xbf4ebec4, 0x3edb3f46, 0x3d49bf7b, 0xbf043f75, 0xbe793f80, 0x3f2cbf62, 0xbf713f0e, 0x3f7dbdc9, 0x3e163f6d, 0x3eacbf7f,
    0xbf3e3f55, 0x3f78bef1, 0x3f5cbf35, 0xbf803e95, 0x3f673e48, 0xbf18bf22, 0xbf183f6d, 0x3f67bf22, 0xbf803e48, 0x3f5c3e95,
    0x3f780000, 0xbf3ebef1, 0x3eac3f55, 0x3e16bf7f, 0x3f7dbec4, 0xbf71bdc9, 0x3f2c3f0e, 0xbe79bf62, 0xbf04bf35, 0x3d493f75,
    0x3edbbf7b, 0xbf4e3f46, 0x3f67bf35, 0xbf783dc9, 0x3f183f0e, 0x3d49bf75, 0xbf2c3f6d, 0x3f7dbef1, 0xbf5cbe48, 0x3eac3f46,
    0x3f710000, 0xbf04bf22, 0xbe163f7b, 0x3f3ebf62, 0xbf803ec4, 0x3f4e3e95, 0xbe79bf55, 0xbedb3f7f, 0x3edb3f35, 0x3e79bf7f,
    0xbf4e3f55, 0x3f80be95, 0xbf3ebec4, 0x3e163f62, 0x3f04bf7b, 0xbf713f22, 0xbeac3f80, 0x3f5cbf46, 0xbf7d3e48, 0x3f2c3ef1,
    0xbd49bf6d, 0xbf183f75, 0x3f78bf0e, 0xbf67bdc9, 0x3f3e3ec4, 0xbe16bf62, 0xbf043f7b, 0x3f71bf22, 0xbedbbf35, 0xbe793f7f,
    0x3f4ebf55, 0xbf803e95, 0x3d493f6d, 0x3f18bf75, 0xbf783f0e, 0x3f673dc9, 0x3eacbf80, 0xbf5c3f46, 0x3f7dbe48, 0xbf2cbef1,
    0xbf2c3f6d, 0x3f7dbef1, 0xbf5cbe48, 0x3eac3f46, 0x3f67bf35, 0xbf783dc9, 0x3f183f0e, 0x3d49bf75, 0xbf803ec4, 0x3f4e3e95,
    0xbe79bf55, 0xbedb3f7f, 0x3f710000, 0xbf04bf22, 0xbe163f7b, 0x3f3ebf62, 0xbedb3f80, 0x3f78bf22, 0xbf4ebe48, 0x3d493f62,
    0x3f3ebf6d, 0xbf7d3e95, 0x3f043f0e, 0x3eacbf7f, 0xbf713f35, 0x3f5c3dc9, 0xbe16bf55, 0xbf2c3f75, 0x3f80bec4, 0xbf18bef1,
    0xbe793f7b, 0x3f67bf46, 0xbf670000, 0x3e793f46, 0x3f18bf7b, 0xbf803ef1, 0x3f2c3ec4, 0x3e16bf75, 0xbf5c3f55, 0x3f71bdc9,
    0xbeacbf35, 0xbf043f7f, 0x3f7dbf0e, 0xbf3ebe95, 0xbd493f6d, 0x3f4ebf62, 0xbf783e48, 0x3edb3f22, 0xbf2cbec4, 0xbe163f75,
    0x3f5cbf55, 0xbf713dc9, 0x3f670000, 0xbe79bf46, 0xbf183f7b, 0x3f80bef1, 0x3d49bf6d, 0xbf4e3f62, 0x3f78be48, 0xbedbbf22,
    0x3eac3f35, 0x3f04bf7f, 0xbf7d3f0e, 0x3f3e3e95, 0x3f3ebf6d, 0xbf7d3e95, 0x3f043f0e, 0x3eacbf7f, 0xbedb3f80, 0x3f78bf22,
    0xbf4ebe48, 0x3d493f62, 0x3f80bec4, 0xbf18bef1, 0xbe793f7b, 0x3f67bf46, 0xbf713f35, 0x3f5c3dc9, 0xbe16bf55, 0xbf2c3f75,
    0xbe79bf35, 0xbf3e3f75, 0x3f71be48, 0xbe16bf46, 0xbf4e3f6d, 0x3f67bdc9, 0xbd49bf55, 0xbf5c3f62, 0xbf043f80, 0x3f80bef1,
    0xbedbbf0e, 0xbf183f7f, 0x3f7dbec4, 0xbeacbf22, 0xbf2c3f7b, 0x3f78be95, 0xbf783f35, 0x3f2c3e95, 0x3eacbf7b, 0xbf7d3f22,
    0x3f183ec4, 0x3edbbf7f, 0xbf803f0e, 0x3f043ef1, 0x3f5c0000, 0x3d49bf62, 0xbf673f55, 0x3f4e3dc9, 0x3e16bf6d, 0xbf713f46,
    0x3f3e3e48, 0x3e79bf75, 0x3f183ec4, 0x3edbbf7f, 0xbf803f0e, 0x3f043ef1, 0xbf783f35, 0x3f2c3e95, 0x3eacbf7b, 0xbf7d3f22,
    0x3e16bf6d, 0xbf713f46, 0x3f3e3e48, 0x3e79bf75, 0x3f5c0000, 0x3d49bf62, 0xbf673f55, 0x3f4e3dc9, 0x3f4ebf6d, 0xbf673dc9,
    0x3d493f55, 0x3f5cbf62, 0x3e793f35, 0x3f3ebf75, 0xbf713e48, 0x3e163f46, 0xbf7d3ec4, 0x3eac3f22, 0x3f2cbf7b, 0xbf783e95,
    0x3f04bf80, 0xbf803ef1, 0x3edb3f0e, 0x3f18bf7f, 0xbf4e0000, 0xbeac3f75, 0x3f80bf0e, 0xbe79bf22, 0xbf5c3f6d, 0x3f3e3dc9,
    0x3edbbf7b, 0xbf7d3ef1, 0x3e163f35, 0x3f67bf62, 0xbf2cbe48, 0xbf043f7f, 0x3f78bec4, 0xbd49bf46, 0xbf713f55, 0x3f183e95,
    0xbf183f80, 0x3f71be95, 0x3d49bf55, 0xbf783f46, 0x3f043ec4, 0x3f2cbf7f, 0xbf673e48, 0xbe163f62, 0x3f7dbf35, 0xbedbbef1,
    0xbf3e3f7b, 0x3f5cbdc9, 0x3e79bf6d, 0xbf803f22, 0x3eac3f0e, 0x3f4ebf75, 0x3f043ec4, 0x3f2cbf7f, 0xbf673e48, 0xbe163f62,
    0xbf183f80, 0x3f71be95, 0x3d49bf55, 0xbf783f46, 0x3e79bf6d, 0xbf803f22, 0x3eac3f0e, 0x3f4ebf75, 0x3f7dbf35, 0xbedbbef1,
    0xbf3e3f7b, 0x3f5cbdc9, 0x3f5cbf6d, 0xbf3ebdc9, 0xbedb3f7b, 0x3f7dbef1, 0x3f4e0000, 0x3eacbf75, 0xbf803f0e, 0x3e793f22,
    0xbf783ec4, 0x3d493f46, 0x3f71bf55, 0xbf18be95, 0xbe16bf35, 0xbf673f62, 0x3f2c3e48, 0x3f04bf7f, 0x3f80bf35, 0xbe16bf22,
    0xbf783f55, 0x3eac3ef1, 0x3f67bf6d, 0xbf04be95, 0xbf4e3f7b, 0x3f2c3dc9, 0x3f3e0000, 0x3f18bf7f, 0xbf5c3e48, 0xbedb3f75,
    0x3f71bec4, 0x3e79bf62, 0xbf7d3f0e, 0xbd493f46, 0x3d493f35, 0x3f7dbf46, 0xbe79bf0e, 0xbf713f62, 0x3edb3ec4, 0x3f5cbf75,
    0xbf18be48, 0xbf3e3f7f, 0xbf2c3f80, 0x3f4ebdc9, 0x3f04bf7b, 0xbf673e95, 0xbeac3f6d, 0x3f78bef1, 0x3e16bf55, 0xbf803f22,
    0xbedbbec4, 0xbf5c3f75, 0x3f183e48, 0x3f3ebf7f, 0xbd49bf35, 0xbf7d3f46, 0x3e793f0e, 0x3f71bf62, 0x3eacbf6d, 0xbf783ef1,
    0xbe163f55, 0x3f80bf22, 0x3f2cbf80, 0xbf4e3dc9, 0xbf043f7b, 0x3f67be95, 0x3f67bf6d, 0xbf04be95, 0xbf4e3f7b, 0x3f2c3dc9,
    0x3f80bf35, 0xbe16bf22, 0xbf783f55, 0x3eac3ef1, 0x3f71bec4, 0x3e79bf62, 0xbf7d3f0e, 0xbd493f46, 0x3f3e0000, 0x3f18bf7f,
    0xbf5c3e48, 0xbedb3f75, 0xbf3e3f80, 0x3f183dc9, 0x3f5cbf7b, 0xbedbbe95, 0xbf713f6d, 0x3e793ef1, 0x3f7dbf55, 0xbd49bf22,
    0xbf803f35, 0xbe163f46, 0x3f78bf0e, 0x3eacbf62, 0xbf673ec4, 0xbf043f75, 0x3f4ebe48, 0x3f2cbf7f, 0xbf2c0000, 0xbf4e3f7f,
    0x3f043e48, 0x3f67bf75, 0xbeacbec4, 0xbf783f62, 0x3e163f0e, 0x3f80bf46, 0x3d49bf35, 0xbf7d3f22, 0xbe793f55, 0x3f71bef1,
    0x3edbbf6d, 0xbf5c3e95, 0xbf183f7b, 0x3f3ebdc9, 0x3eac3ec4, 0x3f78bf62, 0xbe16bf0e, 0xbf803f46, 0x3f2c0000, 0x3f4ebf7f,
    0xbf04be48, 0xbf673f75, 0xbedb3f6d, 0x3f5cbe95, 0x3f18bf7b, 0xbf3e3dc9, 0xbd493f35, 0x3f7dbf22, 0x3e79bf55, 0xbf713ef1,
    0xbf713f6d, 0x3e793ef1, 0x3f7dbf55, 0xbd49bf22, 0xbf3e3f80, 0x3f183dc9, 0x3f5cbf7b, 0xbedbbe95, 0xbf673ec4, 0xbf043f75,
    0x3f4ebe48, 0x3f2cbf7f, 0xbf803f35, 0xbe163f46, 0x3f78bf0e, 0x3eacbf62, 0x3e16bf35, 0xbf673ef1, 0xbf2c3f7b, 0x3f043dc9,
    0x3f78bf6d, 0x3d49bf22, 0xbf713f0e, 0xbf183f75, 0xbf4e3f80, 0x3eac3e95, 0x3f80bf55, 0x3e79bf46, 0xbf5c3ec4, 0xbf3e3f7f,
    0x3edb3e48, 0x3f7dbf62, 0xbf7d3f35, 0xbedb3f62, 0x3f3ebe48, 0x3f5cbf7f, 0xbe79bec4, 0xbf803f46, 0xbeac3f55, 0x3f4ebe95,
    0x3f180000, 0x3f71bf75, 0xbd49bf0e, 0xbf783f22, 0xbf043f6d, 0x3f2cbdc9, 0x3f67bf7b, 0xbe16bef1, 0xbe79bec4, 0xbf803f46,
    0xbeac3f55, 0x3f4ebe95, 0xbf7d3f35, 0xbedb3f62, 0x3f3ebe48, 0x3f5cbf7f, 0xbf043f6d, 0x3f2cbdc9, 0x3f67bf7b, 0xbe16bef1,
    0x3f180000, 0x3f71bf75, 0xbd49bf0e, 0xbf783f22, 0xbf783f6d, 0xbd493f22, 0x3f71bf0e, 0x3f18bf75, 0xbe163f35, 0x3f67bef1,
    0x3f2cbf7b, 0xbf04bdc9, 0x3f5cbec4, 0x3f3ebf7f, 0xbedbbe48, 0xbf7d3f62, 0x3f4ebf80, 0xbeacbe95, 0xbf803f55, 0xbe793f46,
    0xbf040000, 0xbf803f62, 0xbedb3f55, 0x3f18bdc9, 0x3f7dbf6d, 0x3eacbf46, 0xbf2c3e48, 0xbf783f75, 0xbe793f35, 0x3f3ebe95,
    0x3f71bf7b, 0x3e16bf22, 0xbf4e3ec4, 0xbf673f7f, 0xbd493f0e, 0x3f5cbef1, 0xbf5c3f80, 0x3d493ef1, 0x3f67bf0e, 0x3f4ebf7f,
    0xbe16bec4, 0xbf713f22, 0xbf3e3f7b, 0x3e793e95, 0x3f78bf35, 0x3f2cbf75, 0xbeacbe48, 0xbf7d3f46, 0xbf183f6d, 0x3edb3dc9,
    0x3f80bf55, 0x3f04bf62, 0xbe16bec4, 0xbf713f22, 0xbf3e3f7b, 0x3e793e95, 0xbf5c3f80, 0x3d493ef1, 0x3f67bf0e, 0x3f4ebf7f,
    0xbf183f6d, 0x3edb3dc9, 0x3f80bf55, 0x3f04bf62, 0x3f78bf35, 0x3f2cbf75, 0xbeacbe48, 0xbf7d3f46, 0xbf7d3f6d, 0xbeac3f46,
    0x3f2cbe48, 0x3f78bf75, 0x3f040000, 0x3f80bf62, 0x3edbbf55, 0xbf183dc9, 0x3f4ebec4, 0x3f67bf7f, 0x3d49bf0e, 0xbf5c3ef1,
    0x3e79bf35, 0xbf3e3e95, 0xbf713f7b, 0xbe163f22, 0x3f71bf35, 0x3f5cbf7f, 0x3e16bf0e, 0xbf2c3e95, 0xbf803f6d, 0xbf183f62,
    0x3e793e48, 0x3f67bf22, 0x3edb0000, 0x3f78bf46, 0x3f4ebf7b, 0x3d49bef1, 0xbf3e3ec4, 0xbf7d3f75, 0xbf043f55, 0x3eac3dc9,
    0xbeac3f35, 0x3f04bdc9, 0x3f7dbf55, 0x3f3ebf75, 0xbd49bec4, 0xbf4e3ef1, 0xbf783f7b, 0xbedb3f46, 0xbf673f80, 0xbe793f22,
    0x3f18be48, 0x3f80bf62, 0x3f2cbf6d, 0xbe16be95, 0xbf5c3f0e, 0xbf713f7f, 0x3d493ec4, 0x3f4ebef1, 0x3f78bf7b, 0x3edbbf46,
    0x3eacbf35, 0xbf043dc9, 0xbf7d3f55, 0xbf3e3f75, 0xbf2c3f6d, 0x3e163e95, 0x3f5cbf0e, 0x3f71bf7f, 0x3f67bf80, 0x3e79bf22,
    0xbf183e48, 0xbf803f62, 0xbf803f6d, 0xbf183f62, 0x3e793e48, 0x3f67bf22, 0x3f71bf35, 0x3f5cbf7f, 0x3e16bf0e, 0xbf2c3e95,
    0xbf3e3ec4, 0xbf7d3f75, 0xbf043f55, 0x3eac3dc9, 0x3edb0000, 0x3f78bf46, 0x3f4ebf7b, 0x3d49bef1, 0xbf713f80, 0xbf043f46,
    0x3e163e48, 0x3f3ebef1, 0x3f80bf6d, 0x3f4ebf75, 0x3e79bf0e, 0xbedb3dc9, 0xbf673f35, 0xbf783f7f, 0xbf183f55, 0x3d493e95,
    0x3f2cbec4, 0x3f7dbf62, 0x3f5cbf7b, 0x3eacbf22, 0xbeac0000, 0xbf5c3f22, 0xbf7d3f7b, 0xbf2c3f62, 0xbd493ec4, 0x3f18be95,
    0x3f78bf55, 0x3f67bf7f, 0x3edbbf35, 0xbe79bdc9, 0xbf4e3f0e, 0xbf803f75, 0xbf3e3f6d, 0xbe163ef1, 0x3f04be48, 0x3f71bf46,
    0x3d49bec4, 0xbf183e95, 0xbf783f55, 0xbf673f7f, 0x3eac0000, 0x3f5cbf22, 0x3f7dbf7b, 0x3f2cbf62, 0x3f3ebf6d, 0x3e16bef1,
    0xbf043e48, 0xbf713f46, 0xbedb3f35, 0x3e793dc9, 0x3f4ebf0e, 0x3f80bf75, 0x3f80bf6d, 0x3f4ebf75, 0x3e79bf0e, 0xbedb3dc9,
    0xbf713f80, 0xbf043f46, 0x3e163e48, 0x3f3ebef1, 0x3f2cbec4, 0x3f7dbf62, 0x3f5cbf7b, 0x3eacbf22, 0xbf673f35, 0xbf783f7f,
    0xbf183f55, 0x3d493e95, 0x3f04bf35, 0x3d49be95, 0xbedb3e48, 0xbf4e3f22, 0xbf7d3f6d, 0xbf713f7f, 0xbf2c3f55, 0xbe793ef1,
    0xbf783f80, 0xbf3e3f62, 0xbeac3f0e, 0x3e163dc9, 0x3f18bec4, 0x3f67bf46, 0x3f80bf7b, 0x3f5cbf75, 0xbf5c3f35, 0xbf803f75,
    0xbf673f7b, 0xbf183f46, 0xbe163ec4, 0x3eacbdc9, 0x3f3ebf0e, 0x3f78bf62, 0x3e790000, 0x3f2cbef1, 0x3f71bf55, 0x3f7dbf7f,
    0x3f4ebf6d, 0x3edbbf22, 0xbd49be48, 0xbf043e95, 0xbe163ec4, 0x3eacbdc9, 0x3f3ebf0e, 0x3f78bf62, 0xbf5c3f35, 0xbf803f75,
    0xbf673f7b, 0xbf183f46, 0x3f4ebf6d, 0x3edbbf22, 0xbd49be48, 0xbf043e95, 0x3e790000, 0x3f2cbef1, 0x3f71bf55, 0x3f7dbf7f,
    0x3f7dbf6d, 0x3f71bf7f, 0x3f2cbf55, 0x3e79bef1, 0xbf043f35, 0xbd493e95, 0x3edbbe48, 0x3f4ebf22, 0xbf183ec4, 0xbf673f46,
    0xbf803f7b, 0xbf5c3f75, 0x3f78bf80, 0x3f3ebf62, 0x3eacbf0e, 0xbe16bdc9, 0xbe160000, 0xbedb3e95, 0xbf2c3f0e, 0xbf5c3f46,
    0xbf783f6d, 0xbf803f7f, 0xbf713f7b, 0xbf4e3f62, 0xbf183f35, 0xbeac3ef1, 0xbd493e48, 0x3e79bdc9, 0x3f04bec4, 0x3f3ebf22,
    0x3f67bf55, 0x3f7dbf75, 0xbf7d3f80, 0xbf673f75, 0xbf3e3f55, 0xbf043f22, 0xbe793ec4, 0x3d493dc9, 0x3eacbe48, 0x3f18bef1,
    0x3f4ebf35, 0x3f71bf62, 0x3f80bf7b, 0x3f78bf7f, 0x3f5cbf6d, 0x3f2cbf46, 0x3edbbf0e, 0x3e16be95, 0xbe793ec4, 0x3d493dc9,
    0x3eacbe48, 0x3f18bef1, 0xbf7d3f80, 0xbf673f75, 0xbf3e3f55, 0xbf043f22, 0x3f5cbf6d, 0x3f2cbf46, 0x3edbbf0e, 0x3e16be95,
    0x3f4ebf35, 0x3f71bf62, 0x3f80bf7b, 0x3f78bf7f, 0x3f78bf6d, 0x3f80bf7f, 0x3f71bf7b, 0x3f4ebf62, 0x3e160000, 0x3edbbe95,
    0x3f2cbf0e, 0x3f5cbf46, 0xbf043ec4, 0xbf3e3f22, 0xbf673f55, 0xbf7d3f75, 0x3f18bf35, 0x3eacbef1, 0x3d49be48, 0xbe793dc9,
    0x3f3ebf35, 0x3f4ebf46, 0x3f5cbf55, 0x3f67bf62, 0x3f71bf6d, 0x3f78bf75, 0x3f7dbf7b, 0x3f80bf7f, 0x3d490000, 0x3e16bdc9,
    0x3e79be48, 0x3eacbe95, 0x3edbbec4, 0x3f04bef1, 0x3f18bf0e, 0x3f2cbf22, 0xbf2c3f35, 0xbf183f22, 0xbf043f0e, 0xbedb3ef1,
    0xbeac3ec4, 0xbe793e95, 0xbe163e48, 0xbd493dc9, 0xbf803f80, 0xbf7d3f7f, 0xbf783f7b, 0xbf713f75, 0xbf673f6d, 0xbf5c3f62,
    0xbf4e3f55, 0xbf3e3f46, 0x3eacbec4, 0x3e79be95, 0x3e16be48, 0x3d49bdc9, 0x3f2cbf35, 0x3f18bf22, 0x3f04bf0e, 0x3edbbef1,
    0x3f67bf6d, 0x3f5cbf62, 0x3f4ebf55, 0x3f3ebf46, 0x3f80bf80, 0x3f7dbf7f, 0x3f78bf7b, 0x3f71bf75, 0x3f71bf6d, 0x3f78bf75,
    0x3f7dbf7b, 0x3f80bf7f, 0x3f3ebf35, 0x3f4ebf46, 0x3f5cbf55, 0x3f67bf62, 0x3edbbec4, 0x3f04bef1, 0x3f18bf0e, 0x3f2cbf22,
    0x3d490000, 0x3e16bdc9, 0x3e79be48, 0x3eacbe95,
};
__device__ const __align__(128) uint32_t c_ga[1536] = {
    0x00003c80, 0x3bc43c6d, 0x00003c80, 0xbbc4bc6d, 0x00003c80, 0x3c6d3bc4, 0x00003c80, 0xbc6dbbc4, 0x00003c80, 0x3c6dbbc4,
    0x00003c80, 0xbc6d3bc4, 0x00003c80, 0x3bc4bc6d, 0x00003c80, 0xbbc43c6d, 0x3a493c80, 0x3bdb3c67, 0x3bdb3c67, 0xbc3ebc2c,
    0x3b163c7d, 0x3c783b79, 0x3c043c5c, 0xbc7d3b16, 0x3b793c78, 0x3c4ebc18, 0x3c183c4e, 0xbc043c5c, 0x3bac3c71, 0x3a49bc80,
    0x3c2c3c3e, 0x3bac3c71, 0x3ac93c7f, 0x3bf13c62, 0x3c463c22, 0xbc75bb95, 0x3b953c75, 0x3c7f3ac9, 0x3c623bf1, 0xbc463c22,
    0x3bf13c62, 0x3c22bc46, 0x3c753b95, 0x3ac93c7f, 0x3c223c46, 0xbb95bc75, 0x3c7f3ac9, 0x3c623bf1, 0x3b163c7d, 0x3c043c5c,
    0x3c783b79, 0xbc7d3b16, 0x3bdb3c67, 0x3c80ba49, 0x3c80ba49, 0xbbac3c71, 0x3c2c3c3e, 0x3bdbbc67, 0x3c71bbac, 0x3c2c3c3e,
    0x3c5c3c04, 0xbc18bc4e, 0x3c4ebc18, 0x3c78bb79, 0x3b483c7b, 0x3c0e3c55, 0x3c7bbb48, 0xbc553c0e, 0x3c0e3c55, 0x3c7bbb48,
    0x3c55bc0e, 0x3b483c7b, 0x3c553c0e, 0x3b48bc7b, 0x3c0ebc55, 0x3c7b3b48, 0x3c7b3b48, 0xbc55bc0e, 0x3b48bc7b, 0x3c0ebc55,
    0x3b793c78, 0x3c183c4e, 0x3c4ebc18, 0xbc043c5c, 0x3c2c3c3e, 0x3c71bbac, 0x3bdbbc67, 0x3c2c3c3e, 0x3c713bac, 0xba49bc80,
    0xba49bc80, 0x3c67bbdb, 0x3c7dbb16, 0xbc78bb79, 0xbc04bc5c, 0xbb16bc7d, 0x3b953c75, 0x3c223c46, 0x3bf1bc62, 0xbac93c7f,
    0x3c463c22, 0x3c62bbf1, 0xbac9bc7f, 0x3c753b95, 0x3c7f3ac9, 0xbb95bc75, 0xbc22bc46, 0x3bf1bc62, 0x3c62bbf1, 0xbc7f3ac9,
    0xbc75bb95, 0xbc46bc22, 0x3bac3c71, 0x3c2c3c3e, 0x3a49bc80, 0x3bac3c71, 0x3c5c3c04, 0x3c4ebc18, 0xbc18bc4e, 0x3c78bb79,
    0x3c7dbb16, 0xbc04bc5c, 0xbc78bb79, 0xbb16bc7d, 0x3c2cbc3e, 0xbc673bdb, 0xbc673bdb, 0xbc803a49, 0x00003c80, 0x3bc43c6d,
    0x00003c80, 0xbbc4bc6d, 0x00003c80, 0x3c6d3bc4, 0x00003c80, 0xbc6dbbc4, 0x00003c80, 0x3c6dbbc4, 0x00003c80, 0xbc6d3bc4,
    0x00003c80, 0x3bc4bc6d, 0x00003c80, 0xbbc43c6d, 0x3c3e3c2c, 0x3c713bac, 0x3c713bac, 0xbc803a49, 0x3c4e3c18, 0x3c5cbc04,
    0x3c783b79, 0xbc183c4e, 0x3c5c3c04, 0x3b16bc7d, 0x3c7d3b16, 0x3b793c78, 0x3c673bdb, 0xbc2cbc3e, 0x3c803a49, 0x3c673bdb,
    0x3c7fbac9, 0x3c62bbf1, 0x3c22bc46, 0xbb953c75, 0x3c75bb95, 0x3ac9bc7f, 0x3bf1bc62, 0x3c223c46, 0x3c62bbf1, 0xbc46bc22,
    0x3b95bc75, 0x3c7fbac9, 0x3c46bc22, 0xbc753b95, 0x3ac9bc7f, 0x3bf1bc62, 0x3c18bc4e, 0x3b79bc78, 0xbc04bc5c, 0x3c4e3c18,
    0x3bacbc71, 0xbc3ebc2c, 0xbc3ebc2c, 0x3c67bbdb, 0x3a49bc80, 0xbc713bac, 0xbc67bbdb, 0x3a49bc80, 0xbb79bc78, 0xbb163c7d,
    0xbc7dbb16, 0xbc5cbc04, 0xbb48bc7b, 0xbc0ebc55, 0xbc7b3b48, 0x3c55bc0e, 0xbc0ebc55, 0xbc7b3b48, 0xbc553c0e, 0xbb48bc7b,
    0xbc55bc0e, 0xbb483c7b, 0xbc0e3c55, 0xbc7bbb48, 0xbc7bbb48, 0x3c553c0e, 0xbb483c7b, 0xbc0e3c55, 0xbc5cbc04, 0xbc7dbb16,
    0xbb163c7d, 0xbb79bc78, 0xbc80ba49, 0xbbdb3c67, 0x3bac3c71, 0xbc80ba49, 0xbc673bdb, 0x3c3e3c2c, 0x3c3e3c2c, 0xbbac3c71,
    0xbc183c4e, 0x3c5cbc04, 0x3c783b79, 0x3c4e3c18, 0xbc753b95, 0xbc463c22, 0x3c623bf1, 0xbc7fbac9, 0xbc223c46, 0x3bf13c62,
    0x3c7fbac9, 0xbb953c75, 0xbac93c7f, 0x3c75bb95, 0x3c46bc22, 0x3c623bf1, 0x3bf13c62, 0xbac9bc7f, 0x3b95bc75, 0x3c22bc46,
    0xbbdb3c67, 0xba493c80, 0x3c3ebc2c, 0xbbdb3c67, 0x3b793c78, 0x3c7d3b16, 0x3b16bc7d, 0x3c5c3c04, 0x3c4e3c18, 0x3b79bc78,
    0xbc04bc5c, 0x3c18bc4e, 0x3c80ba49, 0xbc71bbac, 0xbc71bbac, 0xbc3ebc2c, 0x00003c80, 0x3bc43c6d, 0x00003c80, 0xbbc4bc6d,
    0x00003c80, 0x3c6d3bc4, 0x00003c80, 0xbc6dbbc4, 0x00003c80, 0x3c6dbbc4, 0x00003c80, 0xbc6d3bc4, 0x00003c80, 0x3bc4bc6d,
    0x00003c80, 0xbbc43c6d, 0x3c80ba49, 0x3c67bbdb, 0x3c67bbdb, 0xbc2c3c3e, 0x3c7dbb16, 0x3b79bc78, 0x3c5cbc04, 0x3b163c7d,
    0x3c78bb79, 0xbc18bc4e, 0x3c4ebc18, 0x3c5c3c04, 0x3c71bbac, 0xbc80ba49, 0x3c3ebc2c, 0x3c71bbac, 0xbac9bc7f, 0xbbf1bc62,
    0xbc46bc22, 0x3c753b95, 0xbb95bc75, 0xbc7fbac9, 0xbc62bbf1, 0x3c46bc22, 0xbbf1bc62, 0xbc223c46, 0xbc75bb95, 0xbac9bc7f,
    0xbc22bc46, 0x3b953c75, 0xbc7fbac9, 0xbc62bbf1, 0xbc7d3b16, 0xbc5c3c04, 0xbb793c78, 0xbb16bc7d, 0xbc673bdb, 0x3a493c80,
    0x3a493c80, 0xbc71bbac, 0xbc3e3c2c, 0x3c673bdb, 0x3bac3c71, 0xbc3e3c2c, 0xbc043c5c, 0x3c4ebc18, 0x3c183c4e, 0x3b793c78,
    0x3b483c7b, 0x3c0e3c55, 0x3c7bbb48, 0xbc553c0e, 0x3c0e3c55, 0x3c7bbb48, 0x3c55bc0e, 0x3b483c7b, 0x3c553c0e, 0x3b48bc7b,
    0x3c0ebc55, 0x3c7b3b48, 0x3c7b3b48, 0xbc55bc0e, 0x3b48bc7b, 0x3c0ebc55, 0x3c78bb79, 0x3c4ebc18, 0xbc18bc4e, 0x3c5c3c04,
    0x3c3ebc2c, 0xbbacbc71, 0xbc67bbdb, 0x3c3ebc2c, 0x3bacbc71, 0xbc803a49, 0xbc803a49, 0xbbdbbc67, 0xbb16bc7d, 0xbb793c78,
    0xbc5c3c04, 0xbc7d3b16, 0xbb95bc75, 0xbc22bc46, 0xbbf13c62, 0x3ac9bc7f, 0xbc46bc22, 0xbc623bf1, 0x3ac93c7f, 0xbc75bb95,
    0xbc7fbac9, 0x3b953c75, 0x3c223c46, 0xbbf13c62, 0xbc623bf1, 0x3c7fbac9, 0x3c753b95, 0x3c463c22, 0xbc713bac, 0xbc3e3c2c,
    0x3c803a49, 0xbc713bac, 0xbc043c5c, 0x3c183c4e, 0x3c4ebc18, 0x3b793c78, 0x3b163c7d, 0x3c5cbc04, 0x3b79bc78, 0x3c7dbb16,
    0x3c3e3c2c, 0xbbdbbc67, 0xbbdbbc67, 0xba49bc80, 0x00003c80, 0x3bc43c6d, 0x00003c80, 0xbbc4bc6d, 0x00003c80, 0x3c6d3bc4,
    0x00003c80, 0xbc6dbbc4, 0x00003c80, 0x3c6dbbc4, 0x00003c80, 0xbc6d3bc4, 0x00003c80, 0x3bc4bc6d, 0x00003c80, 0xbbc43c6d,
    0x3c2cbc3e, 0x3bacbc71, 0x3bacbc71, 0x3a493c80, 0x3c18bc4e, 0xbc04bc5c, 0x3b79bc78, 0x3c4e3c18, 0x3c04bc5c, 0xbc7dbb16,
    0x3b16bc7d, 0x3c78bb79, 0x3bdbbc67, 0xbc3e3c2c, 0x3a49bc80, 0x3bdbbc67, 0xbc7f3ac9, 0xbc623bf1, 0xbc223c46, 0x3b95bc75,
    0xbc753b95, 0xbac93c7f, 0xbbf13c62, 0xbc22bc46, 0xbc623bf1, 0x3c463c22, 0xbb953c75, 0xbc7f3ac9, 0xbc463c22, 0x3c75bb95,
    0xbac93c7f, 0xbbf13c62, 0x3c4e3c18, 0x3c783b79, 0x3c5cbc04, 0xbc183c4e, 0x3c713bac, 0x3c2cbc3e, 0x3c2cbc3e, 0x3bdb3c67,
    0x3c803a49, 0xbbacbc71, 0x3bdbbc67, 0x3c803a49, 0x3c78bb79, 0xbc7dbb16, 0x3b16bc7d, 0x3c04bc5c, 0xbb48bc7b, 0xbc0ebc55,
    0xbc7b3b48, 0x3c55bc0e, 0xbc0ebc55, 0xbc7b3b48, 0xbc553c0e, 0xbb48bc7b, 0xbc55bc0e, 0xbb483c7b, 0xbc0e3c55, 0xbc7bbb48,
    0xbc7bbb48, 0x3c553c0e, 0xbb483c7b, 0xbc0e3c55, 0xbc043c5c, 0xbb163c7d, 0x3c7d3b16, 0xbc783b79, 0xba493c80, 0x3c673bdb,
    0x3c71bbac, 0xba493c80, 0x3bdb3c67, 0x3c2cbc3e, 0x3c2cbc3e, 0x3c713bac, 0x3c4e3c18, 0xbc04bc5c, 0x3b79bc78, 0x3c18bc4e,
    0x3c75bb95, 0x3c46bc22, 0xbc62bbf1, 0x3c7f3ac9, 0x3c22bc46, 0xbbf1bc62, 0xbc7f3ac9, 0x3b95bc75, 0x3ac9bc7f, 0xbc753b95,
    0xbc463c22, 0xbc62bbf1, 0xbbf1bc62, 0x3ac93c7f, 0xbb953c75, 0xbc223c46, 0xbc67bbdb, 0xbc80ba49, 0x3c2c3c3e, 0xbc67bbdb,
    0xbc783b79, 0xbb163c7d, 0x3c7d3b16, 0xbc043c5c, 0xbc183c4e, 0x3c783b79, 0x3c5cbc04, 0x3c4e3c18, 0x3a493c80, 0x3bacbc71,
    0x3bacbc71, 0x3c2cbc3e, 0x3c353c35, 0x3c6d3bc4, 0x3c353c35, 0xbc6dbbc4, 0x3c35bc35, 0xbbc4bc6d, 0x3c35bc35, 0x3bc43c6d,
    0xbc35bc35, 0xbbc43c6d, 0xbc35bc35, 0x3bc4bc6d, 0xbc353c35, 0x3c6dbbc4, 0xbc353c35, 0xbc6d3bc4, 0x3c3e3c2c, 0x3c713bac,
    0x3c713bac, 0xbc803a49, 0x3c18bc4e, 0xbc04bc5c, 0x3b79bc78, 0x3c4e3c18, 0xbc5cbc04, 0xbb163c7d, 0xbc7dbb16, 0xbb79bc78,
    0xbbdb3c67, 0x3c3ebc2c, 0xba493c80, 0xbbdb3c67, 0x3c463c22, 0x3c753b95, 0x3c7fbac9, 0xbc623bf1, 0x3bf1bc62, 0xbc22bc46,
    0xbb95bc75, 0x3c7f3ac9, 0xbc75bb95, 0x3ac93c7f, 0xbc623bf1, 0xbc46bc22, 0xbac93c7f, 0x3bf1bc62, 0x3c223c46, 0x3b953c75,
    0x3c4e3c18, 0x3c783b79, 0x3c5cbc04, 0xbc183c4e, 0x3bacbc71, 0xbc3ebc2c, 0xbc3ebc2c, 0x3c67bbdb, 0xbc80ba49, 0x3bac3c71,
    0xbbdb3c67, 0xbc80ba49, 0x3b793c78, 0x3b16bc7d, 0x3c7d3b16, 0x3c5c3c04, 0x3c553c0e, 0x3c7b3b48, 0x3c0ebc55, 0xbb483c7b,
    0x3b48bc7b, 0xbc55bc0e, 0xbc7bbb48, 0x3c0ebc55, 0xbc7b3b48, 0x3c0e3c55, 0x3b483c7b, 0xbc553c0e, 0x3c0e3c55, 0xbb48bc7b,
    0x3c55bc0e, 0x3c7bbb48, 0x3c5c3c04, 0x3c7d3b16, 0x3b16bc7d, 0x3b793c78, 0x3a49bc80, 0xbc67bbdb, 0xbc713bac, 0x3a49bc80,
    0xbc673bdb, 0x3c3e3c2c, 0x3c3e3c2c, 0xbbac3c71, 0x3c4e3c18, 0xbc04bc5c, 0x3b79bc78, 0x3c18bc4e, 0x3c623bf1, 0x3c7f3ac9,
    0xbb95bc75, 0x3c223c46, 0xbac9bc7f, 0xbc75bb95, 0xbc223c46, 0xbbf1bc62, 0xbc463c22, 0x3c623bf1, 0x3c7f3ac9, 0x3b953c75,
    0x3c753b95, 0xbc46bc22, 0xbbf1bc62, 0xbac9bc7f, 0x3c673bdb, 0x3c803a49, 0xbc2cbc3e, 0x3c673bdb, 0xbb79bc78, 0xbc7dbb16,
    0xbb163c7d, 0xbc5cbc04, 0xbc183c4e, 0x3c783b79, 0x3c5cbc04, 0x3c4e3c18, 0x3c80ba49, 0xbc71bbac, 0xbc71bbac, 0xbc3ebc2c,
    0x3c353c35, 0x3c6d3bc4, 0x3c353c35, 0xbc6dbbc4, 0x3c35bc35, 0xbbc4bc6d, 0x3c35bc35, 0x3bc43c6d, 0xbc35bc35, 0xbbc43c6d,
    0xbc35bc35, 0x3bc4bc6d, 0xbc353c35, 0x3c6dbbc4, 0xbc353c35, 0xbc6d3bc4, 0x3c80ba49, 0x3c67bbdb, 0x3c67bbdb, 0xbc2c3c3e,
    0xbb16bc7d, 0xbc78bb79, 0xbc04bc5c, 0x3c7dbb16, 0xbc783b79, 0x3c183c4e, 0xbc4e3c18, 0xbc5cbc04, 0x3bac3c71, 0x3a49bc80,
    0x3c2c3c3e, 0x3bac3c71, 0x3c22bc46, 0x3b95bc75, 0xbac9bc7f, 0x3bf13c62, 0xbc62bbf1, 0xbc463c22, 0xbc753b95, 0x3ac9bc7f,
    0xbb953c75, 0x3c7fbac9, 0x3bf13c62, 0xbc223c46, 0x3c7f3ac9, 0xbc62bbf1, 0x3c46bc22, 0x3c75bb95, 0xbb16bc7d, 0xbc04bc5c,
    0xbc78bb79, 0x3c7dbb16, 0xbc673bdb, 0x3a493c80, 0x3a493c80, 0xbc71bbac, 0x3c2c3c3e, 0x3bdbbc67, 0x3c71bbac, 0x3c2c3c3e,
    0x3c04bc5c, 0xbc4e3c18, 0xbc18bc4e, 0xbb79bc78, 0xbc55bc0e, 0xbc7bbb48, 0xbc0e3c55, 0x3b48bc7b, 0xbb483c7b, 0x3c553c0e,
    0x3c7b3b48, 0xbc0e3c55, 0x3c7bbb48, 0xbc0ebc55, 0xbb48bc7b, 0x3c55bc0e, 0xbc0ebc55, 0x3b483c7b, 0xbc553c0e, 0xbc7b3b48,
    0xbc783b79, 0xbc4e3c18, 0x3c183c4e, 0xbc5cbc04, 0x3c2c3c3e, 0x3c71bbac, 0x3bdbbc67, 0x3c2c3c3e, 0x3bacbc71, 0xbc803a49,
    0xbc803a49, 0xbbdbbc67, 0xbc7d3b16, 0x3c783b79, 0x3c043c5c, 0x3b163c7d, 0xbbf13c62, 0xbac93c7f, 0x3c75bb95, 0xbc463c22,
    0x3c7fbac9, 0x3b95bc75, 0xbc46bc22, 0x3c62bbf1, 0xbc22bc46, 0xbbf13c62, 0xbac93c7f, 0xbc753b95, 0xbb953c75, 0x3c22bc46,
    0x3c62bbf1, 0x3c7fbac9, 0x3bac3c71, 0x3c2c3c3e, 0x3a49bc80, 0x3bac3c71, 0x3c04bc5c, 0xbc18bc4e, 0xbc4e3c18, 0xbb79bc78,
    0xbc7d3b16, 0x3c043c5c, 0x3c783b79, 0x3b163c7d, 0x3c3e3c2c, 0xbbdbbc67, 0xbbdbbc67, 0xba49bc80, 0x3c353c35, 0x3c6d3bc4,
    0x3c353c35, 0xbc6dbbc4, 0x3c35bc35, 0xbbc4bc6d, 0x3c35bc35, 0x3bc43c6d, 0xbc35bc35, 0xbbc43c6d, 0xbc35bc35, 0x3bc4bc6d,
    0xbc353c35, 0x3c6dbbc4, 0xbc353c35, 0xbc6d3bc4, 0x3c2cbc3e, 0x3bacbc71, 0x3bacbc71, 0x3a493c80, 0xbc4ebc18, 0xbc5c3c04,
    0xbc78bb79, 0x3c18bc4e, 0xbc043c5c, 0x3c7d3b16, 0xbb163c7d, 0xbc783b79, 0x3c673bdb, 0xbc2cbc3e, 0x3c803a49, 0x3c673bdb,
    0xbc46bc22, 0xbc75bb95, 0xbc7f3ac9, 0x3c62bbf1, 0xbbf13c62, 0x3c223c46, 0x3b953c75, 0xbc7fbac9, 0x3c753b95, 0xbac9bc7f,
    0x3c62bbf1, 0x3c463c22, 0x3ac9bc7f, 0xbbf13c62, 0xbc22bc46, 0xbb95bc75, 0xbc183c4e, 0xbb793c78, 0x3c043c5c, 0xbc4ebc18,
    0x3c713bac, 0x3c2cbc3e, 0x3c2cbc3e, 0x3bdb3c67, 0x3a49bc80, 0xbc713bac, 0xbc67bbdb, 0x3a49bc80, 0xbc783b79, 0x3c7d3b16,
    0xbb163c7d, 0xbc043c5c, 0x3c553c0e, 0x3c7b3b48, 0x3c0ebc55, 0xbb483c7b, 0x3b48bc7b, 0xbc55bc0e, 0xbc7bbb48, 0x3c0ebc55,
    0xbc7b3b48, 0x3c0e3c55, 0x3b483c7b, 0xbc553c0e, 0x3c0e3c55, 0xbb48bc7b, 0x3c55bc0e, 0x3c7bbb48, 0x3c04bc5c, 0x3b16bc7d,
    0xbc7dbb16, 0x3c78bb79, 0xbc80ba49, 0xbbdb3c67, 0x3bac3c71, 0xbc80ba49, 0x3bdb3c67, 0x3c2cbc3e, 0x3c2cbc3e, 0x3c713bac,
    0x3c18bc4e, 0xbc5c3c04, 0xbc78bb79, 0xbc4ebc18, 0xbc62bbf1, 0xbc7fbac9, 0x3b953c75, 0xbc22bc46, 0x3ac93c7f, 0x3c753b95,
    0x3c22bc46, 0x3bf13c62, 0x3c46bc22, 0xbc62bbf1, 0xbc7fbac9, 0xbb95bc75, 0xbc75bb95, 0x3c463c22, 0x3bf13c62, 0x3ac93c7f,
    0xbbdb3c67, 0xba493c80, 0x3c3ebc2c, 0xbbdb3c67, 0x3c78bb79, 0x3b16bc7d, 0xbc7dbb16, 0x3c04bc5c, 0xbc4ebc18, 0xbb793c78,
    0x3c043c5c, 0xbc183c4e, 0x3a493c80, 0x3bacbc71, 0x3bacbc71, 0x3c2cbc3e, 0x3c353c35, 0x3c6d3bc4, 0x3c353c35, 0xbc6dbbc4,
    0x3c35bc35, 0xbbc4bc6d, 0x3c35bc35, 0x3bc43c6d, 0xbc35bc35, 0xbbc43c6d, 0xbc35bc35, 0x3bc4bc6d, 0xbc353c35, 0x3c6dbbc4,
    0xbc353c35, 0xbc6d3bc4, 0xba49bc80, 0xbbdbbc67, 0xbbdbbc67, 0x3c3e3c2c, 0xbc7d3b16, 0xbb793c78, 0xbc5c3c04, 0xbb16bc7d,
    0x3b793c78, 0x3c4ebc18, 0x3c183c4e, 0xbc043c5c, 0x3c71bbac, 0xbc80ba49, 0x3c3ebc2c, 0x3c71bbac, 0xbc223c46, 0xbb953c75,
    0x3ac93c7f, 0xbbf1bc62, 0x3c623bf1, 0x3c46bc22, 0x3c75bb95, 0xbac93c7f, 0x3b95bc75, 0xbc7f3ac9, 0xbbf1bc62, 0x3c22bc46,
    0xbc7fbac9, 0x3c623bf1, 0xbc463c22, 0xbc753b95, 0x3c7dbb16, 0x3c5cbc04, 0x3b79bc78, 0x3b163c7d, 0xbbdbbc67, 0xbc803a49,
    0xbc803a49, 0x3bacbc71, 0xbc3e3c2c, 0x3c673bdb, 0x3bac3c71, 0xbc3e3c2c, 0x3c5c3c04, 0xbc18bc4e, 0x3c4ebc18, 0x3c78bb79,
    0xbc55bc0e, 0xbc7bbb48, 0xbc0e3c55, 0x3b48bc7b, 0xbb483c7b, 0x3c553c0e, 0x3c7b3b48, 0xbc0e3c55, 0x3c7bbb48, 0xbc0ebc55,
    0xbb48bc7b, 0x3c55bc0e, 0xbc0ebc55, 0x3b483c7b, 0xbc553c0e, 0xbc7b3b48, 0x3b793c78, 0x3c183c4e, 0x3c4ebc18, 0xbc043c5c,
    0x3c3ebc2c, 0xbbacbc71, 0xbc67bbdb, 0x3c3ebc2c, 0xbc71bbac, 0x3a493c80, 0x3a493c80, 0xbc673bdb, 0x3b163c7d, 0x3b79bc78,
    0x3c5cbc04, 0x3c7dbb16, 0x3bf1bc62, 0x3ac9bc7f, 0xbc753b95, 0x3c46bc22, 0xbc7f3ac9, 0xbb953c75, 0x3c463c22, 0xbc623bf1,
    0x3c223c46, 0x3bf1bc62, 0x3ac9bc7f, 0x3c75bb95, 0x3b95bc75, 0xbc223c46, 0xbc623bf1, 0xbc7f3ac9, 0xbc713bac, 0xbc3e3c2c,
    0x3c803a49, 0xbc713bac, 0x3c5c3c04, 0x3c4ebc18, 0xbc18bc4e, 0x3c78bb79, 0xbb16bc7d, 0xbc5c3c04, 0xbb793c78, 0xbc7d3b16,
    0xbc2c3c3e, 0x3c67bbdb, 0x3c67bbdb, 0x3c80ba49, 0x3c800000, 0x3c6dbbc4, 0x3c800000, 0xbc6d3bc4, 0xbc800000, 0xbbc43c6d,
    0xbc800000, 0x3bc4bc6d, 0x3c800000, 0xbbc4bc6d, 0x3c800000, 0x3bc43c6d, 0xbc800000, 0x3c6d3bc4, 0xbc800000, 0xbc6dbbc4,
    0x3c80ba49, 0x3c67bbdb, 0x3c67bbdb, 0xbc2c3c3e, 0xbc7d3b16, 0xbb793c78, 0xbc5c3c04, 0xbb16bc7d, 0x3c78bb79, 0xbc18bc4e,
    0x3c4ebc18, 0x3c5c3c04, 0xbc713bac, 0x3c803a49, 0xbc3e3c2c, 0xbc713bac, 0x3c7fbac9, 0x3c62bbf1, 0x3c22bc46, 0xbb953c75,
    0xbc753b95, 0xbac93c7f, 0xbbf13c62, 0xbc22bc46, 0x3c62bbf1, 0xbc46bc22, 0x3b95bc75, 0x3c7fbac9, 0xbc463c22, 0x3c75bb95,
    0xbac93c7f, 0xbbf13c62, 0x3c7dbb16, 0x3c5cbc04, 0x3b79bc78, 0x3b163c7d, 0xbc673bdb, 0x3a493c80, 0x3a493c80, 0xbc71bbac,
    0x3c3ebc2c, 0xbc67bbdb, 0xbbacbc71, 0x3c3ebc2c, 0xbc043c5c, 0x3c4ebc18, 0x3c183c4e, 0x3b793c78, 0x3c7bbb48, 0x3c55bc0e,
    0xbb48bc7b, 0x3c0e3c55, 0xbc553c0e, 0x3b483c7b, 0x3c0e3c55, 0xbc7b3b48, 0x3c0ebc55, 0xbc7bbb48, 0xbc55bc0e, 0x3b48bc7b,
    0xbb483c7b, 0x3c0ebc55, 0x3c7b3b48, 0x3c553c0e, 0x3c78bb79, 0x3c4ebc18, 0xbc18bc4e, 0x3c5c3c04, 0xbc3e3c2c, 0x3bac3c71,
    0x3c673bdb, 0xbc3e3c2c, 0x3bacbc71, 0xbc803a49, 0xbc803a49, 0xbbdbbc67, 0x3b163c7d, 0x3b79bc78, 0x3c5cbc04, 0x3c7dbb16,
    0x3c75bb95, 0x3c46bc22, 0xbc62bbf1, 0x3c7f3ac9, 0xbc223c46, 0x3bf13c62, 0x3c7fbac9, 0xbb953c75, 0x3ac9bc7f, 0xbc753b95,
    0xbc463c22, 0xbc62bbf1, 0x3bf13c62, 0xbac9bc7f, 0x3b95bc75, 0x3c22bc46, 0x3c71bbac, 0x3c3ebc2c, 0xbc80ba49, 0x3c71bbac,
    0xbc043c5c, 0x3c183c4e, 0x3c4ebc18, 0x3b793c78, 0xbb16bc7d, 0xbc5c3c04, 0xbb793c78, 0xbc7d3b16, 0x3c3e3c2c, 0xbbdbbc67,
    0xbbdbbc67, 0xba49bc80, 0x3c800000, 0x3c6dbbc4, 0x3c800000, 0xbc6d3bc4, 0xbc800000, 0xbbc43c6d, 0xbc800000, 0x3bc4bc6d,
    0x3c800000, 0xbbc4bc6d, 0x3c800000, 0x3bc43c6d, 0xbc800000, 0x3c6d3bc4, 0xbc800000, 0xbc6dbbc4, 0x3c2cbc3e, 0x3bacbc71,
    0x3bacbc71, 0x3a493c80, 0xbc183c4e, 0x3c043c5c, 0xbb793c78, 0xbc4ebc18, 0x3c04bc5c, 0xbc7dbb16, 0x3b16bc7d, 0x3c78bb79,
    0xbbdb3c67, 0x3c3ebc2c, 0xba493c80, 0xbbdb3c67, 0xbac9bc7f, 0xbbf1bc62, 0xbc46bc22, 0x3c753b95, 0x3b953c75, 0x3c7f3ac9,
    0x3c623bf1, 0xbc463c22, 0xbbf1bc62, 0xbc223c46, 0xbc75bb95, 0xbac9bc7f, 0x3c223c46, 0xbb95bc75, 0x3c7f3ac9, 0x3c623bf1,
    0xbc4ebc18, 0xbc78bb79, 0xbc5c3c04, 0x3c18bc4e, 0x3c713bac, 0x3c2cbc3e, 0x3c2cbc3e, 0x3bdb3c67, 0xbc80ba49, 0x3bac3c71,
    0xbbdb3c67, 0xbc80ba49, 0x3c78bb79, 0xbc7dbb16, 0x3b16bc7d, 0x3c04bc5c, 0xbc7b3b48, 0xbc553c0e, 0x3b483c7b, 0xbc0ebc55,
    0x3c55bc0e, 0xbb48bc7b, 0xbc0ebc55, 0x3c7bbb48, 0xbc0e3c55, 0x3c7b3b48, 0x3c553c0e, 0xbb483c7b, 0x3b48bc7b, 0xbc0e3c55,
    0xbc7bbb48, 0xbc55bc0e, 0xbc043c5c, 0xbb163c7d, 0x3c7d3b16, 0xbc783b79, 0x3a49bc80, 0xbc67bbdb, 0xbc713bac, 0x3a49bc80,
    0x3bdb3c67, 0x3c2cbc3e, 0x3c2cbc3e, 0x3c713bac, 0xbc4ebc18, 0x3c043c5c, 0xbb793c78, 0xbc183c4e, 0x3b953c75, 0x3c223c46,
    0x3bf1bc62, 0xbac93c7f, 0xbc46bc22, 0xbc623bf1, 0x3ac93c7f, 0xbc75bb95, 0x3c7f3ac9, 0xbb95bc75, 0xbc22bc46, 0x3bf1bc62,
    0xbc623bf1, 0x3c7fbac9, 0x3c753b95, 0x3c463c22, 0x3c673bdb, 0x3c803a49, 0xbc2cbc3e, 0x3c673bdb, 0xbc783b79, 0xbb163c7d,
    0x3c7d3b16, 0xbc043c5c, 0x3c18bc4e, 0xbc78bb79, 0xbc5c3c04, 0xbc4ebc18, 0x3a493c80, 0x3bacbc71, 0x3bacbc71, 0x3c2cbc3e,
    0x3c800000, 0x3c6dbbc4, 0x3c800000, 0xbc6d3bc4, 0xbc800000, 0xbbc43c6d, 0xbc800000, 0x3bc4bc6d, 0x3c800000, 0xbbc4bc6d,
    0x3c800000, 0x3bc43c6d, 0xbc800000, 0x3c6d3bc4, 0xbc800000, 0xbc6dbbc4, 0xba49bc80, 0xbbdbbc67, 0xbbdbbc67, 0x3c3e3c2c,
    0x3b163c7d, 0x3c783b79, 0x3c043c5c, 0xbc7d3b16, 0xbb79bc78, 0xbc4e3c18, 0xbc18bc4e, 0x3c04bc5c, 0x3bac3c71, 0x3a49bc80,
    0x3c2c3c3e, 0x3bac3c71, 0xbc7f3ac9, 0xbc623bf1, 0xbc223c46, 0x3b95bc75, 0x3c75bb95, 0x3ac9bc7f, 0x3bf1bc62, 0x3c223c46,
    0xbc623bf1, 0x3c463c22, 0xbb953c75, 0xbc7f3ac9, 0x3c46bc22, 0xbc753b95, 0x3ac9bc7f, 0x3bf1bc62, 0x3b163c7d, 0x3c043c5c,
    0x3c783b79, 0xbc7d3b16, 0xbbdbbc67, 0xbc803a49, 0xbc803a49, 0x3bacbc71, 0x3c2c3c3e, 0x3bdbbc67, 0x3c71bbac, 0x3c2c3c3e,
    0xbc5cbc04, 0x3c183c4e, 0xbc4e3c18, 0xbc783b79, 0x3c7bbb48, 0x3c55bc0e, 0xbb48bc7b, 0x3c0e3c55, 0xbc553c0e, 0x3b483c7b,
    0x3c0e3c55, 0xbc7b3b48, 0x3c0ebc55, 0xbc7bbb48, 0xbc55bc0e, 0x3b48bc7b, 0xbb483c7b, 0x3c0ebc55, 0x3c7b3b48, 0x3c553c0e,
    0xbb79bc78, 0xbc18bc4e, 0xbc4e3c18, 0x3c04bc5c, 0x3c2c3c3e, 0x3c71bbac, 0x3bdbbc67, 0x3c2c3c3e, 0xbc71bbac, 0x3a493c80,
    0x3a493c80, 0xbc673bdb, 0x3c7dbb16, 0xbc78bb79, 0xbc04bc5c, 0xbb16bc7d, 0xbc753b95, 0xbc463c22, 0x3c623bf1, 0xbc7fbac9,
    0x3c22bc46, 0xbbf1bc62, 0xbc7f3ac9, 0x3b95bc75, 0xbac93c7f, 0x3c75bb95, 0x3c46bc22, 0x3c623bf1, 0xbbf1bc62, 0x3ac93c7f,
    0xbb953c75, 0xbc223c46, 0x3bac3c71, 0x3c2c3c3e, 0x3a49bc80, 0x3bac3c71, 0xbc5cbc04, 0xbc4e3c18, 0x3c183c4e, 0xbc783b79,
    0x3c7dbb16, 0xbc04bc5c, 0xbc78bb79, 0xbb16bc7d, 0xbc2c3c3e, 0x3c67bbdb, 0x3c67bbdb, 0x3c80ba49, 0x3c800000, 0x3c6dbbc4,
    0x3c800000, 0xbc6d3bc4, 0xbc800000, 0xbbc43c6d, 0xbc800000, 0x3bc4bc6d, 0x3c800000, 0xbbc4bc6d, 0x3c800000, 0x3bc43c6d,
    0xbc800000, 0x3c6d3bc4, 0xbc800000, 0xbc6dbbc4, 0xbc3ebc2c, 0xbc71bbac, 0xbc71bbac, 0x3c80ba49, 0x3c4e3c18, 0x3c5cbc04,
    0x3c783b79, 0xbc183c4e, 0xbc5cbc04, 0xbb163c7d, 0xbc7dbb16, 0xbb79bc78, 0x3c673bdb, 0xbc2cbc3e, 0x3c803a49, 0x3c673bdb,
    0x3ac93c7f, 0x3bf13c62, 0x3c463c22, 0xbc75bb95, 0xbb95bc75, 0xbc7fbac9, 0xbc62bbf1, 0x3c46bc22, 0x3bf13c62, 0x3c22bc46,
    0x3c753b95, 0x3ac93c7f, 0xbc22bc46, 0x3b953c75, 0xbc7fbac9, 0xbc62bbf1, 0x3c18bc4e, 0x3b79bc78, 0xbc04bc5c, 0x3c4e3c18,
    0xbbac3c71, 0x3c3e3c2c, 0x3c3e3c2c, 0xbc673bdb, 0x3a49bc80, 0xbc713bac, 0xbc67bbdb, 0x3a49bc80, 0x3b793c78, 0x3b16bc7d,
    0x3c7d3b16, 0x3c5c3c04, 0xbc7b3b48, 0xbc553c0e, 0x3b483c7b, 0xbc0ebc55, 0x3c55bc0e, 0xbb48bc7b, 0xbc0ebc55, 0x3c7bbb48,
    0xbc0e3c55, 0x3c7b3b48, 0x3c553c0e, 0xbb483c7b, 0x3b48bc7b, 0xbc0e3c55, 0xbc7bbb48, 0xbc55bc0e, 0x3c5c3c04, 0x3c7d3b16,
    0x3b16bc7d, 0x3b793c78, 0xbc80ba49, 0xbbdb3c67, 0x3bac3c71, 0xbc80ba49, 0x3c67bbdb, 0xbc3ebc2c, 0xbc3ebc2c, 0x3bacbc71,
    0xbc183c4e, 0x3c5cbc04, 0x3c783b79, 0x3c4e3c18, 0xbb95bc75, 0xbc22bc46, 0xbbf13c62, 0x3ac9bc7f, 0x3c463c22, 0x3c62bbf1,
    0xbac9bc7f, 0x3c753b95, 0xbc7fbac9, 0x3b953c75, 0x3c223c46, 0xbbf13c62, 0x3c62bbf1, 0xbc7f3ac9, 0xbc75bb95, 0xbc46bc22,
    0xbbdb3c67, 0xba493c80, 0x3c3ebc2c, 0xbbdb3c67, 0xbb79bc78, 0xbc7dbb16, 0xbb163c7d, 0xbc5cbc04, 0x3c4e3c18, 0x3b79bc78,
    0xbc04bc5c, 0x3c18bc4e, 0xbc803a49, 0x3c713bac, 0x3c713bac, 0x3c3e3c2c,
};

#define G_EPI 3
#define G_TK 3
#define W_Q 6
#define W2_PC 32
#define W2_PF 3
constexpr int X_LOC0 = 5;
constexpr int A_IN = 112 * 128;
constexpr int G_ST = 2 * NB1 * 64;
constexpr int K1_R = 131072, K1_BAR = K1_R + 98304, K1_SMEM = K1_BAR + 2048 + 1024;
constexpr int K1_T = K1_R + 65536, K1_TIN = 0, K1_Y0 = 3 * G_ST + 8192, G_KM = 16 - G_TK, G_S0 = 2 * G_KM;
__device__ int g_done[8 * 32];
struct Ptrs {
  int* done;
  float* ge;
  const uint32_t *img, *ga;
};

__host__ __device__ constexpr int g_depth(int s) { return s < 11 ? 3 : s < 18 ? 4 : s < 23 ? 5 : 6; }
__host__ __device__ constexpr int g_slot(int s) { return s < 3 ? s : g_depth(s) != g_depth(s - 1) ? g_depth(s - 1) : g_slot(s - g_depth(s)); }
__host__ __device__ constexpr int g_off(int id) { return id * G_ST + (id < 3 ? K1_R : 8192 - 3 * G_ST); }
struct Plan {
  uint32_t raw[32];
  uint32_t x[16];
  uint32_t grp[8];
  uint32_t last;
  uint32_t wpf;
  uint32_t g0;
  uint32_t tmask;
  uint64_t list[2];
};
struct K1Maps {
  Plan p;
  CUtensorMap x, we, wo, xs, y, w2e, w2o, w2s;
  int slot[32];
  int src[32];
  int dep[32];
};
__device__ __forceinline__ void poll_ge(const int* p, int target) {
  for (int it = 0; it < (1 << 20); it++) {
    int v;
    asm volatile("ld.acquire.gpu.global.s32 %0, [%1];" : "=r"(v) : "l"(p) : "memory");
    if (v >= target) break;
  }
}
__device__ __forceinline__ uint32_t place(int rank, uint32_t c) { return (c ^ (rank * 4 & ~(c >> 1))) << 14; }
__device__ __forceinline__ int x_unit(int cta, int u, uint32_t pl) {
  const int i = u * 128 + cta;
  const int pr = cta >= 128 ? 2 * cta - 96 + (u & 1) : i % 160, sl = cta >= 128 ? u >> 1 : i / 160, b = pr >= 84;
  return pr | sl << 8 | b << 11 | (cta >= 128 ? (u & 7) << 14 : place(cta & 1, pl & 15)) | 12 * (pr - 84 * b) << 20;
}
__device__ __forceinline__ int lds32(uint32_t a) {
  int v;
  asm volatile("ld.shared.b32 %0, [%1];" : "=r"(v) : "r"(a));
  return v;
}
__host__ __device__ constexpr uint64_t sched(const char* p) {
  uint64_t r = 0;
  for (int n = 0; p[n]; n++) r |= (uint64_t)(p[n] - '0' + 1) << (5 * n);
  return r;
}

__global__ void __cluster_dims__(2, 1, 1) __launch_bounds__(384, 1)
k1(const Ptrs gp_, const char* __restrict__ x1, const char* __restrict__ w1, const __grid_constant__ K1Maps m, const __nv_bfloat16* __restrict__ g,
   const __nv_bfloat16* __restrict__ wgt) {
  extern __shared__ __align__(1024) uint8_t smem_k1[];
  const uint32_t sb = s2u(smem_k1);
  const int tid = threadIdx.x, cta = blockIdx.x, rank = cta & 1;
  if (tid == 288) {
    const uint32_t bar = sb + K1_BAR + 256, dst = sb + (cta >= 128 ? 0 : place(rank, X_LOC0));
    const int pr = cta >= 128 ? 2 * cta - 96 : cta, b = pr >= 84;
    mbar_init(bar, 1);
    mbar_expect(bar, A_IN);
    for (int h = 0; h < 2; h++) tma_ld4<1>(dst + h * (A_IN / 2), &m.x, bar, 0, 96 * (pr - 84 * b) - 24 + h * 56, 0, b);
    for (int i = 1; i < 4; i++) mbar_init(bar + 8 * i, 1);
    fence_bar_init();
  }
  const uint32_t sF = sb + (cta >= 128 ? K1_T : rank * 65536), fbar = sb + K1_BAR + 1792;
  if (tid == 320) {
    mbar_init(fbar, 1);
    mbar_expect(fbar, 8192);
    asm volatile("cp.async.bulk.shared::cluster.global.mbarrier::complete_tx::bytes [%0], [%1], 8192, [%2];" ::"r"(sF), "l"(gp_.img + 1536), "r"(fbar) : "memory");
    fence_bar_init();
  }
  const int wg = __shfl_sync(0xffffffffu, tid >> 7, 0), t = tid & 127;
  const int warp = __shfl_sync(0xffffffffu, t >> 5, 0), lane = t & 31;
  const bool spare = cta >= 128;
  const int nx = spare ? 16 : 10;
  int bp, dc;
  {
    const int ci = cta >> 1;
    const int G = ci < 4 ? 0 : ci < 36 ? (ci - 4) & 7 : 1 + (ci - 36) % 7;
    const int li = ci < 4 ? 4 + ci : ci < 36 ? (ci - 4) >> 3 : 4 + (ci - 36) / 7;
    bp = 2 * G + (li >> 2), dc = li & 3;
  }
  const int bin = 2 * bp + rank;
  const uint32_t bb = sb + K1_BAR;
  const uint32_t rfull = bb, xfull = bb + 256, xfree = bb + 384, gfull = bb + 512, win = bb + 1800, win1 = bb + 1808;
  const uint32_t inf0 = bb + 784, se0 = inf0 + 16, pfree = se0 + 16, rempty = bb + 1024, xready = bb + 1280;
  const uint32_t gdone = bb + 1536, ine0 = gdone + 224, sf0 = ine0 + 16;
  const uint32_t xtab = bb + 896, ptab = bb + 2048 + 768;
  auto raw_load = [&](int j, uint32_t dst) {
    mbar_expect(rfull + 8 * j, 16384);
    tma_ld4<0>(dst, rank ? &m.we : &m.wo, rfull + 8 * j, dc * 64, rank - 1, (j & 3) * 4, (j >> 2) * 2);
  };
  auto x_half = [&](int u, int c, int h) {
    tma_ld4<1>(sb + (c & 0x3C000) + h * (A_IN / 2), &m.x, xfull + 8 * u, 0, (c >> 17 & ~7) - 24 + h * 56, c >> 8 & 7, c >> 11 & 1);
  };
  auto w_prefetch = [&](int q) {
    if (cta < 124) asm volatile("cp.async.bulk.prefetch.L2.global [%0], 4096;" ::"l"(w1 + (cta >> 2) * 131072 + (q * 4 + (cta & 3)) * 4096) : "memory");
  };
  uint32_t peer;
  asm("mapa.shared::cluster.u32 %0, %1, %2;" : "=r"(peer) : "r"(sb), "r"(rank ^ 1));
  if (wg == 2) {
    if (lane == 0) {
      if (warp == 0) {
        for (int i = 0; i < 4; i++) mbar_init(bb + 8 * i, 1);
        fence_bar_init();
        if (!spare)
          for (int j = 0; j < 4; j++) raw_load(j, sb + K1_R + j * 16384);
      } else if (warp == 2) {
#pragma unroll 1
        for (int q = 1; q <= m.p.wpf; q++) w_prefetch(q);
        prefetch_map(&m.xs);
      }
    }
    if (warp == 3) {
      const uint32_t v = reinterpret_cast<const uint32_t*>(&m.p)[32 + lane];
      asm volatile("st.shared.b32 [%0], %1;" ::"r"(ptab + 4 * lane), "r"(m.p.raw[lane]) : "memory");
      asm volatile("st.shared.b32 [%0], %1;" ::"r"(ptab + 128 + 4 * lane), "r"(v) : "memory");
      if (lane < 16) asm volatile("st.shared.b32 [%0], %1;" ::"r"(xtab + 4 * lane), "r"(x_unit(cta, lane, v)) : "memory");
    }
  } else {
    const int c = 4 * wg + warp;
    if (lane == 0 && c < 7) {
      const uint32_t b0 = bb + 256 * c, n = c < 4 ? 1 : c < 6 ? 4 : 8;
      if (c >= 2)
        for (int i = 0; i < 4; i++) mbar_init(b0 + 8 * i, n);
      for (int i = 4; i < 16; i++) mbar_init(b0 + 8 * i, n);
      if (c == 3) {
        mbar_init(win, 1 + 2 * W_Q);
        mbar_init(win1, 17 - 2 * W_Q);
        mbar_expect(win, 8192 * W_Q);
        mbar_expect(win1, 65536 - 8192 * W_Q);
        mbar_arrive(bb + 776);
      } else {
        for (int i = 16; i < 32; i++) mbar_init(b0 + 8 * i, n);
      }
      fence_bar_init();
    }
  }
  pdl_launch();
  __syncthreads();
  asm volatile("barrier.cluster.arrive.relaxed.aligned;" ::: "memory");
  if (wg == 2) {
    asm volatile("setmaxnreg.dec.sync.aligned.u32 40;");
    asm volatile("barrier.cluster.wait.aligned;" ::: "memory");
    if (lane == 0) {
      const int wpf = lds32(ptab + 228), g0 = lds32(ptab + 232), s0 = g0 * 4 / 5;
      const int nx0 = spare ? 2 * s0 : g0;
      if (warp == 0) {
        if (!spare) {
#pragma unroll 1
          for (int j = 4; j < 32; j++) {
            const uint32_t e = lds32(ptab + 4 * j);
            mbar_wait(bb + (e >> 5 & ~7), 0);
            raw_load(j, sb + place(rank, e & 15));
            if ((j & 3) == 0 && wpf && (j >> 2) + wpf < 8) w_prefetch((j >> 2) + wpf);
          }
#pragma unroll 1
          for (int s = 0; s < 32; s++) {
            if (s == 0 || s == 4 * s0) {
              poll_ge(&gp_.done[(s ? 5 : 4) * 32], 132);
              asm volatile("fence.proxy.async.global;" ::: "memory");
              mbar_wait(bb + 8 * (lds32(ptab + 224) & 255), 0);
            }
            const uint32_t bar = gfull + 8 * s, dst = sb + 16 * m.slot[s];
            const char* src = x1 + bin * (4 * G_ST) + m.src[s];
            mbar_wait(bb + m.dep[s], 0);
            mbar_expect(bar, G_ST);
#pragma unroll
            for (int h = 0; h < 2; h++) {
              if (s >= 16)
                asm volatile("cp.async.bulk.shared::cluster.global.mbarrier::complete_tx::bytes.L2::cache_hint [%0], [%1], %2, [%3], %4;"
                             ::"r"(dst + h * (G_ST / 2)), "l"(src + h * (s < G_S0 ? G_ST / 2 : 2 * G_ST)), "n"(G_ST / 2), "r"(bar), "l"(policy<1>()) : "memory");
              else
                asm volatile("cp.async.bulk.shared::cluster.global.mbarrier::complete_tx::bytes [%0], [%1], %2, [%3];"
                             ::"r"(dst + h * (G_ST / 2)), "l"(src + h * (s < G_S0 ? G_ST / 2 : 2 * G_ST)), "n"(G_ST / 2), "r"(bar) : "memory");
            }
          }
          if (cta == 0) asm volatile("cp.async.bulk.prefetch.L2.global [%0], 14336;" ::"l"(gp_.img) : "memory");
        }
      } else if (warp < 3) {
        const int u0 = warp == 1 ? 0 : nx0, u1 = warp == 1 ? nx0 : nx;
#pragma unroll 1
        for (int u = u0; u < u1; u++) {
          const int c = lds32(xtab + 4 * u);
          const uint32_t e = spare ? 0xC0 : lds32(ptab + 128 + 4 * u);
          const uint32_t src = sb + (c & 0x3C000), rel = e >> 1 & 24, burst = (16 << (e >> 6 & 3)) - 1;
          mbar_wait(xready + 8 * u, 0);
#pragma unroll 1
          for (int p = 0; p < 128; p += 16) {
            tma_st4<0>(&m.xs, src + p * 128, 0, (c >> 2 & 0x1C0) + (p & 63), p >> 6, c & 255);
            if (((p + 16) & burst) == 0) {
              bulk_commit();
              bulk_wait_read<0>();
            }
          }
          mbar_arrive(xfree + 8 * u);
          if (rel)
            asm volatile("mbarrier.arrive.shared::cluster.b64 _, [%0];" ::"r"(peer + (pfree - sb) + rel) : "memory");
        }
        asm volatile("cp.async.bulk.wait_group 0;" ::: "memory");
        asm volatile("red.release.gpu.global.add.s32 [%0], 1;" ::"l"(&gp_.done[(3 + warp) * 32]) : "memory");
        if (!spare) {
          if (warp == 1) {
            auto w2_row = [&](int it, bool pf) {
              const CUtensorMap* mp = it & 1 ? &m.w2e : &m.w2o;
              const int c1 = (it & 1) - 1, c2 = (cta & 1) * 2, c3 = (it >> 1) * 64 + (cta >> 1);
              if (pf) {
                asm volatile("cp.async.bulk.prefetch.tensor.4d.L2.global [%0, {%1, %2, %3, %4}];" ::"l"(mp), "r"(0), "r"(c1), "r"(c2), "r"(c3) : "memory");
              } else {
                mbar_expect(inf0 + 8 * (it & 1), 4096);
                tma_ld4<1>(sb + K1_TIN + (it & 1) * 4096, mp, inf0 + 8 * (it & 1), 0, c1, c2, c3);
              }
            };
#pragma unroll 1
            for (int it = 0; it < W2_PF; it++) {
              mbar_wait(gfull + 8 * (it >> 1), 0);
              w2_row(it, true);
            }
            mbar_wait(gdone + 8, 0);
#pragma unroll 1
            for (int it = 0; it < 8; it++) {
              if (it >= 2) mbar_wait(ine0 + 8 * (it & 1), ((it >> 1) - 1) & 1);
              w2_row(it, false);
              if (W2_PF && it + W2_PF < 8) w2_row(it + W2_PF, true);
            }
          } else {
            prefetch_map(&m.w2s);
            prefetch_map(&m.y);
#pragma unroll 1
            for (int it = 0; it < 8; it++) {
              if ((0x74 >> it) & 1) poll_ge(&gp_.done[((0x33210000 >> (4 * it)) & 3) * 32], 128);
              mbar_wait(sf0 + 8 * (it & 1), (it >> 1) & 1);
#pragma unroll 1
              for (int p = 0; p < 128; p += W2_PC) {
                tma_st4<0>(&m.w2s, sb + K1_T + (it & 1) * 16384 + p * 128, 0, it * 64 + (p & 63), (cta & 1) * 2 + (p >> 6),
                           (cta >> 1 & 33) | (cta >> 3 & 6) | (cta << 1 & 24));
                bulk_commit();
                bulk_wait_read<0>();
              }
              mbar_arrive(se0 + 8 * (it & 1));
            }
          }
        }
      } else {
#pragma unroll 1
        for (int u = 1; u < nx; u++) {
          const int c = lds32(xtab + 4 * u);
          const uint32_t e = spare ? (u < 8 ? 97 : 40 + u) * 0x01010100u : lds32(ptab + 128 + 4 * u);
          mbar_wait(bb + (e >> 5 & 0x7F8), 0);
          mbar_expect(xfull + 8 * u, A_IN);
          mbar_wait(bb + (e >> 13 & 0x7F8), 0);
          x_half(u, c, 0);
          mbar_wait(bb + (e >> 21 & 0x7F8), 0);
          x_half(u, c, 1);
        }
#pragma unroll 1
        for (int s = 0; s < (spare ? 0 : 16); s++) {
          mbar_wait(gfull + 8 * s, 0);
          if ((s & 3) == 3) asm volatile("red.relaxed.gpu.global.add.s32 [%0], 1;" ::"l"(&gp_.done[(s >> 2) * 32]) : "memory");
        }
      }
    }
  } else {
    asm volatile("setmaxnreg.inc.sync.aligned.u32 232;");
    const int row = (lane & 7) + ((lane >> 3) & 1) * 8, hi = lane >> 4;
    asm volatile("barrier.cluster.wait.aligned;" ::: "memory");
    uint32_t fw[4];
    {
      uint32_t fa[16], za[64];
      mbar_wait(fbar, 0);
      const int f = (4 * bp + warp) & 63;
      const uint32_t lo = lds32(sF + f * 128 + ((f & 7) << 4) + (lane & 3) * 4), hh = lds32(sF + f * 128 + (((f & 7) ^ 1) << 4) + (lane & 3) * 4);
#pragma unroll
      for (int k = 0; k < 4; k++)
        ldsm4(sF + (warp * 16 + row) * 128 + (((2 * k + hi) ^ (lane & 7)) << 4), fa[4 * k], fa[4 * k + 1], fa[4 * k + 2], fa[4 * k + 3]);
      const int rho = (lane >> 3) | (lane & 4);
#pragma unroll
      for (int i = 0; i < 64; i++) za[i] = ((i & 1) == (i >> 5) && rho == ((i >> 2) & 7)) ? ((i & 2) ? hh : lo) : 0u;
      reg_fence(za);
      bar_sync(3, 256);
      const bool own = (warp >> 1) == rank;
      float d[64];
      constexpr uint64_t s2 = sched("02468:<>"), s3 = sched("13579;=?");
#pragma unroll 1
      for (uint64_t sc = spare ? (wg ? s3 : s2) : m.p.list[wg]; sc; sc >>= 5) {
        const int item = (int)sc & 31;
        if (item >= 18) {
          const int q = item - 18;
          const uint32_t e = __shfl_sync(0xffffffffu, lds32(ptab + 192 + 4 * q), 0);
#pragma unroll
          for (int jj = 0; jj < 4; jj++) {
            const int j = 4 * q + jj;
            mbar_wait(rfull + 8 * j, 0);
            wg_fence();
#pragma unroll
            for (int i = 0; i < 4; i++)
              wgmma_rs_128<1, 1, 1>(d, za[16 * jj + 4 * i], za[16 * jj + 4 * i + 1], za[16 * jj + 4 * i + 2], za[16 * jj + 4 * i + 3],
                                    mk_desc(sb + place(rank, e >> (4 * jj) & 15), i * 2048, 8192, 1024, 1), jj | i);
            wg_commit();
            if (jj > 0) {
              wg_wait<1>();
              if (lane == 0) mbar_arrive(rempty + 8 * (j - 1));
            }
          }
          wg_wait<0>();
          reg_fence(d);
          if (lane == 0) mbar_arrive(rempty + 8 * (4 * q + 3));
          mbar_wait(bb + (e >> (own ? 13 : 21) & 0x7F8), 0);
          const uint32_t rb = (own ? sb : peer) + (8 * rank + q) * 8192 + (warp & 1) * 4096 + rho * 128;
          const uint32_t wbar = q < W_Q ? win : win1;
          auto put_w = [&](auto remote) {
#pragma unroll
            for (int v = 0; v < 8; v++) {
              const int j = 4 * (v >> 1), h = v & 1;
              const uint32_t a = rb + (j >> 3) * 2048 + h * 1024 + ((((j & 4) + (lane & 3)) ^ rho) << 4);
              const uint32_t p0 = pack2(d[4 * j + 2 * h], d[4 * j + 2 * h + 1]), p1 = pack2(d[4 * j + 4 + 2 * h], d[4 * j + 5 + 2 * h]);
              const uint32_t p2 = pack2(d[4 * j + 8 + 2 * h], d[4 * j + 9 + 2 * h]), p3 = pack2(d[4 * j + 12 + 2 * h], d[4 * j + 13 + 2 * h]);
              if (decltype(remote)::value)
                asm volatile("st.async.shared::cluster.mbarrier::complete_tx::bytes.v4.b32 [%0], {%1, %2, %3, %4}, [%5];"
                             ::"r"(a), "r"(p0), "r"(p1), "r"(p2), "r"(p3), "r"(peer + (wbar - sb)) : "memory");
              else
                asm volatile("st.shared.v4.b32 [%0], {%1, %2, %3, %4};" ::"r"(a), "r"(p0), "r"(p1), "r"(p2), "r"(p3) : "memory");
            }
          };
          if (own) {
            put_w(std::false_type());
            __syncwarp();
            if (lane == 0) mbar_arrive(wbar);
          } else {
            put_w(std::true_type());
          }
        } else {
          const int u = item - 1;
          const int c = lds32(xtab + 4 * u);
          const uint32_t in = sb + (c & 0x3C000);
          mbar_wait(xfull + 8 * u, 0);
          wg_fence();
#pragma unroll
          for (int k = 0; k < 4; k++)
            wgmma_rs_128<1, 1, 1>(d, fa[4 * k], fa[4 * k + 1], fa[4 * k + 2], fa[4 * k + 3], mk_desc(in, k * 2048, 6144, 1024, 1), k);
          wg_commit();
          wg_wait<0>();
          reg_fence(d);
          bar_sync(1 + wg, 128);
          const uint32_t rb = in + (warp * 16 + row) * 128, xr = (lane & 7) ^ (c & 3);
#pragma unroll
          for (int j = 0; j < 16; j += 2)
            stsm4(rb + ((j >> 2) & 1) * 8192 + ((((j >> 3) * 4 + (j & 3) + hi) ^ xr) << 4), pack2(d[4 * j], d[4 * j + 1]),
                  pack2(d[4 * j + 2], d[4 * j + 3]), pack2(d[4 * j + 4], d[4 * j + 5]), pack2(d[4 * j + 6], d[4 * j + 7]));
          fence_async();
          __syncwarp();
          if (lane == 0) mbar_arrive(xready + 8 * u);
        }
      }
#pragma unroll
      for (int i = 0; i < 4; i++) fw[i] = fa[i];
    }
    if (spare) {
      float* sg = reinterpret_cast<float*>(smem_k1 + K1_R);
      __nv_bfloat16* sw = reinterpret_cast<__nv_bfloat16*>(sg + 16 * 256);
      const int c0 = (cta - 128) * 64;
      uint4 vw[8], vg[2];
#pragma unroll
      for (int i = 0; i < 8; i++) vw[i] = __ldg(reinterpret_cast<const uint4*>(wgt + ((i * 256 + tid) >> 3) * 256 + c0 + (tid & 7) * 8));
#pragma unroll
      for (int i = 0; i < 2; i++) vg[i] = __ldg(reinterpret_cast<const uint4*>(g) + i * 256 + tid);
#pragma unroll
      for (int i = 0; i < 8; i++) reinterpret_cast<uint4*>(sw)[i * 256 + tid] = vw[i];
#pragma unroll
      for (int i = 0; i < 2; i++) {
        const uint32_t w4[4] = {vg[i].x, vg[i].y, vg[i].z, vg[i].w};
#pragma unroll
        for (int e = 0; e < 4; e++) {
          sg[(i * 256 + tid) * 8 + 2 * e] = __uint_as_float(w4[e] << 16);
          sg[(i * 256 + tid) * 8 + 2 * e + 1] = __uint_as_float(w4[e] & 0xffff0000u);
        }
      }
      bar_sync(3, 256);
      const int col = tid & 63, r0 = (tid >> 6) * 4;
      float a0 = 0.f, a1 = 0.f, a2 = 0.f, a3 = 0.f;
#pragma unroll 8
      for (int k = 0; k < 256; k++) {
        const float w = __bfloat162float(sw[k * 64 + col]);
        a0 = fmaf(sg[(r0 + 0) * 256 + k], w, a0);
        a1 = fmaf(sg[(r0 + 1) * 256 + k], w, a1);
        a2 = fmaf(sg[(r0 + 2) * 256 + k], w, a2);
        a3 = fmaf(sg[(r0 + 3) * 256 + k], w, a3);
      }
      const int cc = c0 + col;
      const int pos = (cc & ~15) + ((cc >> 1) & 3) * 4 + ((cc >> 3) & 1) * 2 + (cc & 1);
      gp_.ge[(r0 + 0) * 256 + pos] = __bfloat162float(__float2bfloat16_rn(a0));
      gp_.ge[(r0 + 1) * 256 + pos] = __bfloat162float(__float2bfloat16_rn(a1));
      gp_.ge[(r0 + 2) * 256 + pos] = __bfloat162float(__float2bfloat16_rn(a2));
      gp_.ge[(r0 + 3) * 256 + pos] = __bfloat162float(__float2bfloat16_rn(a3));
      return;
    }
    reg_fence(fw);
    mbar_wait(win, 0);
    float d[16];
    auto t_begin = [&](int it, int hh, int r) {
      if (r == 0) mbar_wait(inf0 + 8 * (it & 1), (it >> 1) & 1);
      wg_fence();
      wgmma_rs_32<1, 1, 1>(d, fw[0], fw[1], fw[2], fw[3], mk_desc(sb + K1_TIN + (it & 1) * 4096 + hh * 2048, r * 64, 0, 1024, 1), 0);
      wg_commit();
    };
    auto t_end = [&](int it, int hh, int r) {
      reg_fence(d);
      const int j = it & 1;
      if (r == 0) mbar_wait(it >= 2 ? se0 + 8 * j : bb + (m.p.last >> (5 + 8 * it) & 0x7F8), it >= 2 ? ((it >> 1) - 1) & 1 : 0);
      else if (lane == 0) mbar_arrive(ine0 + 8 * j);
      const uint32_t rb = sb + K1_T + j * 16384 + hh * 8192 + (warp * 16 + row) * 128;
#pragma unroll
      for (int i = 0; i < 2; i++)
        stsm4(rb + (((4 * r + 2 * i + hi) ^ (lane & 7)) << 4), pack2(d[8 * i], d[8 * i + 1]), pack2(d[8 * i + 2], d[8 * i + 3]),
              pack2(d[8 * i + 4], d[8 * i + 5]), pack2(d[8 * i + 6], d[8 * i + 7]));
      if (r == 1) {
        fence_async();
        __syncwarp();
        if (lane == 0) mbar_arrive(sf0 + 8 * j);
      }
    };
    float y0[NB1 / 2], y1[NB1 / 2];
    uint32_t wa[8], wb[8];
    uint32_t wp = sb + wg * 4096 + ((lane & 7) + hi * 8) * 128 + (((2 * warp + ((lane >> 3) & 1)) ^ (lane & 7)) << 4);
    const uint32_t neg = wg ? 0x80008000u : 0u;
    auto frag = [&](uint32_t (&w)[8], uint32_t a, uint32_t sg) {
      ldsm4t(a, w[0], w[1], w[2], w[3]);
      ldsm4t(a + 2048, w[4], w[5], w[6], w[7]);
#pragma unroll
      for (int i = 0; i < 8; i++) w[i] ^= sg;
    };
    auto stage = [&](const uint32_t (&w)[8], uint32_t x4, int acc) {
      wg_fence();
      wgmma_rs_168<1, 1, 0>(y0, w[0], w[1], w[2], w[3], mk_desc4(x4, 0, 512, 2), acc);
      wgmma_rs_168<1, 1, 0>(y1, w[0], w[1], w[2], w[3], mk_desc4(x4 + G_ST / 32, 0, 512, 2), acc);
      wgmma_rs_168<1, 1, 0>(y0, w[4], w[5], w[6], w[7], mk_desc4(x4 + 2, 0, 512, 2), 1);
      wgmma_rs_168<1, 1, 0>(y1, w[4], w[5], w[6], w[7], mk_desc4(x4 + G_ST / 32 + 2, 0, 512, 2), 1);
      wg_commit();
      wg_wait<1>();
    };
    frag(wa, wp, neg);
    int it = 0;
#pragma unroll 1
    for (int k = 0; k < G_KM; k++) {
      const bool T = (m.p.tmask >> (k + 16 * wg)) & 1;
      const uint32_t xa = ((sb & 0x3FFFF) >> 4) + m.slot[2 * k], xb = ((sb & 0x3FFFF) >> 4) + m.slot[2 * k + 1];
      if (T) t_begin(it, wg, 0);
      mbar_wait(gfull + 16 * k, 0);
      stage(wa, xa, k);
      frag(wb, wp ^ 4096, 0);
      if (k > 0 && lane == 0) mbar_arrive(gdone + 16 * k - 8);
      if (T) {
        t_end(it, wg, 0);
        t_begin(it, wg, 1);
      }
      mbar_wait(gfull + 16 * k + 8, 0);
      stage(wb, xb, 1);
      wp += 8192;
      if (k == W_Q - 1) {
        mbar_wait(win1, 0);
        fence_async();
      }
      frag(wa, wp, neg);
      if (lane == 0) mbar_arrive(gdone + 16 * k);
      if (T) t_end(it++, wg, 1);
    }
    auto tail = [&](float (&y)[NB1 / 2], auto batch, auto wgc) {
      constexpr int B = decltype(batch)::value, W = decltype(wgc)::value;
#pragma unroll
      for (int k = G_KM; k < 16; k++) {
        const int s = G_KM + k + G_TK * B;
        mbar_wait(gfull + 8 * s, 0);
        const int xo = g_off(g_slot(s));
        wg_fence();
#pragma unroll
        for (int h = 0; h < 4; h++) {
          const uint64_t dW = mk_desc(sb, k * 8192 + ((h >> 1) ^ W) * 4096 + (h & 1) * 2048, 0, 1024, 1);
          const uint64_t dX = mk_desc(sb, xo + (h >> 1) * (G_ST / 2) + (h & 1) * 32, 0, 512, 2);
          if (W == 1 && h < 2) wgmma_ss_168<-1, 1, 1, 0>(y, dW, dX, 1);
          else wgmma_ss_168<1, 1, 1, 0>(y, dW, dX, 1);
        }
        if (s <= 26) {
          wg_commit();
          if (W == 0 || k > G_KM) {
            wg_wait<1>();
            if (lane == 0) mbar_arrive(gdone + 8 * (s - 1));
          }
        }
      }
      wg_commit();
    };
    constexpr std::integral_constant<int, 0> c0;
    constexpr std::integral_constant<int, 1> c1;
    auto put = [&](const float (&v)[NB1 / 2], uint32_t stg, int b) {
      const int mi = lane >> 3, i = lane & 7;
      const uint32_t a0 = stg + (mi >> 1) * 1024 + i * 128 + (((2 * warp + (mi & 1)) ^ i) << 4);
      constexpr int J = 21 / G_EPI;
#pragma unroll
      for (int c = 0; c < G_EPI; c++) {
#pragma unroll
        for (int j = c * J; j + 1 < (c + 1) * J; j += 2)
          stsm4t(a0 + j * 1024, pack2(v[4 * j], v[4 * j + 1]), pack2(v[4 * j + 2], v[4 * j + 3]),
                 pack2(v[4 * j + 4], v[4 * j + 5]), pack2(v[4 * j + 6], v[4 * j + 7]));
        const int j = (c + 1) * J - 1;
        asm volatile("stmatrix.sync.aligned.m8n8.x2.trans.shared.b16 [%0], {%1, %2};" ::"r"(a0 + j * 1024),
                     "r"(pack2(v[4 * j], v[4 * j + 1])), "r"(pack2(v[4 * j + 2], v[4 * j + 3])) : "memory");
        fence_async();
        bar_sync(1 + wg, 128);
        if (t == 0) {
          tma_st4<0>(&m.y, stg + c * J * 1024, 0, b * NB1 + c * J * 8, 2 * bin + wg, dc);
          bulk_commit();
        }
      }
    };
    if (wg == 0) {
      tail(y0, c0, c0);
      bar_arrive(4, 256);
      mbar_wait(gdone + 8 * (G_S0 - 1), 0);
      wg_wait<0>();
      reg_fence(y0);
      put(y0, sb + K1_Y0, 0);
      bar_sync(7, 256);
      tail(y1, c1, c0);
      bar_arrive(8, 256);
      if (t == 0) bulk_wait_read<0>();
      wg_wait<0>();
      reg_fence(y1);
      bar_sync(1, 128);
      put(y1, sb + K1_Y0, 1);
    } else {
      wg_wait<0>();
      if (lane == 0) mbar_arrive(gdone + 8 * (G_S0 - 1));
#pragma unroll 1
      for (int h2 = 2 * it; h2 < 16; h2++) {
#pragma unroll
        for (int r = 0; r < 2; r++) {
          t_begin(h2 >> 1, h2 & 1, r);
          wg_wait<0>();
          t_end(h2 >> 1, h2 & 1, r);
        }
      }
      bar_sync(4, 256);
      tail(y0, c0, c1);
      bar_arrive(7, 256);
      mbar_wait(se0, 1);
      mbar_wait(se0 + 8, 1);
      wg_wait<0>();
      reg_fence(y0);
      put(y0, sb + K1_T, 0);
      bar_sync(8, 256);
      tail(y1, c1, c1);
      wg_wait<0>();
      reg_fence(y1);
      put(y1, sb + g_off(g_slot(26)), 1);
    }
    if (t == 0) {
      bulk_wait_read<0>();
    }
  }
}

#define H_EPI 3
#define H_KS 11
#define C_PC 32
constexpr int H_XP = 168 * 64, H_STAGE = 8192 + 2 * H_XP, H_NST = 7, K2_STG = H_NST * H_STAGE, K2_SMEM = K2_STG + 21504 + 1024;

template <int WG>
__device__ __forceinline__ void h_loop(float (&acc)[84], uint32_t sb, uint32_t full0, uint32_t empty0, int lane) {
#pragma unroll 1
  for (int k = 0; k < 16; k++) {
    const int st = k % H_NST;
    if (WG == 1 && k == H_KS) bar_sync(5, 256);
    mbar_wait(full0 + 8 * st, (k / H_NST) & 1);
    const uint32_t base = sb + st * H_STAGE;
    wg_fence();
#pragma unroll
    for (int s = 0; s < 2; s++) {
      const uint64_t dP = mk_desc(base, s * 2048, 0, 1024, 1), dQ = mk_desc(base, 4096 + s * 2048, 0, 1024, 1);
      const uint64_t dA = mk_desc(base, 8192 + s * 32, 0, 1024, 1), dB = mk_desc(base, 8192 + 64 + s * 32, 0, 1024, 1);
      wgmma_ss_168<1, 1, 1, 0>(acc, dP, WG == 0 ? dA : dB, k | s);
      wgmma_ss_168<WG == 0 ? 1 : -1, 1, 1, 0>(acc, dQ, WG == 0 ? dB : dA, 1);
    }
    wg_commit();
    if (WG == 0 && k == 15) bar_arrive(5, 256);
    if (k <= 10) {
      wg_wait<1>();
      if (k > 0 && k - 1 + H_NST < 16 && lane < 2) mbar_arrive_cta(empty0 + 8 * ((k - 1) % H_NST), lane);
    }
  }
  wg_wait<0>();
  reg_fence(acc);
}
template <int C0, int C1> __device__ __forceinline__ void gelu_pack(uint32_t (&p)[12], const float (&h)[24]) {
#pragma unroll
  for (int i = 4 * C0; i < 4 * C1; i++) p[i] = pack2(gelu(h[2 * i]), gelu(h[2 * i + 1]));
}
struct K2Maps {
  int stage[16], item[8], wpre, pad[7];
  CUtensorMap y, xa, xs, w, y2;
};

__global__ void __cluster_dims__(2, 1, 1) __launch_bounds__(512, 1)
k2(const Ptrs gp_, const char* __restrict__ x2, const __grid_constant__ K2Maps m, const __nv_bfloat16* __restrict__ wf,
   const __nv_bfloat16* __restrict__ wo) {
  extern __shared__ __align__(1024) uint8_t smem_k1[];
  const uint32_t sb = s2u(smem_k1);
  const int tid = threadIdx.x, wg = __shfl_sync(0xffffffffu, tid >> 7, 0), t = tid & 127;
  const int warp = __shfl_sync(0xffffffffu, t >> 5, 0), lane = t & 31;
  const int cta = blockIdx.x, rank = cta & 1, dc = cta & 3, bin = cta >> 2;
  const uint32_t sGi = sb + K2_STG, sF = sGi + 6144, bb = sb + K2_STG + 21504;
  const uint32_t yfull = bb, full0 = bb + 128, empty0 = bb + 192, cfull = bb + 256, ready = bb + 320, bfree = bb + 384;
  const int b = cta & 1, j = cta >> 2;
  const int len0 = j < 20 ? 3 : 2, len1 = j >= 12 ? 3 : 2;
  const int n00 = j < 20 ? 3 * j : 2 * j + 20, n01 = j < 12 ? 2 * j : 3 * j - 12, cs0 = 3 - (cta >> 1 & 1);
  auto y_load = [&](int r, int i) {
    tma_ld5<1>(sb + (3 + 2 * r) * H_STAGE + i * 8192, &m.y, yfull + 64 * r + 8 * i, 0, 0, cs0 - 2 * r, 2 * (r ? n01 : n00) + i, b);
  };
  if (wg == 2 && warp == 0) {
    if (lane == 0) {
      prefetch_map(&m.y);
      for (int i = 0; i < 16; i++) mbar_init(yfull + 8 * i, 1);
      fence_bar_init();
    }
    __syncwarp();
    if (lane < 16) mbar_expect(yfull + 8 * lane, lane == 7 ? 6144 : 8192);
    bar_arrive(0, 512);
    asm volatile("barrier.cluster.arrive.relaxed.aligned;" ::: "memory");
    auto c_load = [&](int h) {
      asm volatile("cp.async.bulk.shared::cluster.global.mbarrier::complete_tx::bytes [%0], [%1], %2, [%3];"
                   ::"r"(sGi + 6144 * h), "l"(gp_.img + 1536 * h), "r"(6144 + 2048 * h), "r"(yfull + 56 + 64 * h) : "memory");
    };
    if (lane == 0) {
      c_load(0);
      c_load(1);
      pdl_wait();
      const int r2 = len0 == 2, i2 = r2 ? 2 : 6;
      y_load(0, 2), y_load(0, 0), y_load(0, 1), y_load(1, 0), y_load(0, 4), y_load(0, 3), y_load(r2, i2), y_load(r2, i2 - 1);
      pdl_launch();
    }
    __syncwarp();
  } else {
    if (lane == 0 && wg == 3) {
      for (int i = 0; i < 8; i++) mbar_init(full0 + 64 * warp + 8 * i, warp == 0 ? 1 : warp == 1 ? 16 : 4);
      fence_bar_init();
    }
    if (tid == 0) {
      mbar_init(bfree, 2);
      for (int i = 1; i < 5; i++) mbar_init(bfree + 8 * i, 1);
      mbar_arrive(bfree + 8);
      fence_bar_init();
    }
    if (tid == 128) {
      prefetch_map(&m.xa);
      prefetch_map(&m.xs);
      prefetch_map(&m.w);
      prefetch_map(&m.y2);
    }
    bar_sync(0, 512);
    asm volatile("barrier.cluster.arrive.relaxed.aligned;" ::: "memory");
  }
  if (wg == 2) asm volatile("barrier.cluster.wait.aligned;" ::: "memory");
  mbar_wait(yfull + 56, 0);
  auto idft = [&](float (&h)[24], uint32_t in, uint32_t bar) {
    mbar_wait(bar, 0);
    wg_fence();
#pragma unroll
    for (int k = 0; k < 4; k++) wgmma_ss_48<1, 1, 1, 0>(h, mk_desc(in, k * 2048, 0, 1024, 1), mk_desc(sGi, k * 32, 0, 1024, 1), k);
    wg_commit();
  };
  auto carry_out = [&](const uint32_t (&p)[12], uint32_t dst, uint32_t bar) {
    bar_sync(1 + wg, 128);
#pragma unroll
    for (int v = 0; v < 3; v++)
      asm volatile("st.shared.v4.b32 [%0], {%1, %2, %3, %4};" ::"r"(dst + v * 2048 + t * 16), "r"(p[4 * v]), "r"(p[4 * v + 1]), "r"(p[4 * v + 2]), "r"(p[4 * v + 3]) : "memory");
    __syncwarp();
    if (lane == 0) mbar_arrive(bar);
  };
  if (wg == 3) {
#pragma unroll 1
    for (int r = 0; r < 2; r++) {
      float h[24];
      uint32_t p[12];
      idft(h, sb + (3 + 2 * r) * H_STAGE, yfull + 64 * r);
      wg_wait<0>();
      reg_fence(h);
      gelu_pack<0, 3>(p, h);
      if (j == 0) p[0] = p[1] = p[2] = p[3] = 0;
      carry_out(p, sb + (3 + 2 * r) * H_STAGE, cfull + 32 * r);
    }
    asm volatile("barrier.cluster.wait.aligned;" ::: "memory");
    if (lane == 0) {
      if (warp == 0) {
        auto w_load = [&](int k) {
          mbar_expect(full0 + 8 * (k % H_NST), H_STAGE);
          tma_ld4<1>(sb + (k % H_NST) * H_STAGE, &m.w, full0 + 8 * (k % H_NST), 0, (k & 1) * 32, dc, (7 - (k >> 1)) * 64 + 2 * bin);
        };
        const int wpre = m.wpre;
        for (int k = 0; k < wpre; k++) w_load(k);
#pragma unroll 1
        for (int k = 0; k < 16; k++) {
          const int st = k % H_NST, e = m.stage[k];
          if ((k & 7) == 0) {
            poll_ge(&gp_.done[(6 + (k >> 3)) * 32], 128);
            asm volatile("fence.proxy.async.global;" ::: "memory");
            if (k == 0) mbar_arrive(bfree + 32);
          }
          if (e) mbar_wait(bb + 8 * e, 0);
          if (k == 5) mbar_wait(bfree, 0);
          if (k >= H_NST) mbar_wait(empty0 + 8 * st, ((k / H_NST) - 1) & 1);
          const char* xs = x2 + (((7 - (k >> 2) - (k & 2) * 2) * 64 + (k & 1) * 32 + bin) * 2 + rank) * H_XP;
          asm volatile("cp.async.bulk.shared::cluster.global.mbarrier::complete_tx::bytes.multicast::cluster [%0], [%1], %2, [%3], %4;"
                       ::"r"(sb + st * H_STAGE + 8192 + rank * H_XP), "l"(xs), "n"(H_XP), "r"(full0 + 8 * st), "h"((uint16_t)3) : "memory");
          if (k >= wpre) w_load(k);
          if (k == 8) {
            if (cta == 0) asm volatile("cp.async.bulk.prefetch.L2.global [%0], 6144;" ::"l"(gp_.ga) : "memory");
            asm volatile("cp.async.bulk.prefetch.L2.global [%0], 1024;" ::"l"(wf + cta * 512) : "memory");
            asm volatile("cp.async.bulk.prefetch.L2.global [%0], 1024;" ::"l"(wo + cta * 512) : "memory");
          }
        }
      } else if (warp < 3) {
        const int r = warp - 1, n0 = b * NB2 + (r ? n01 : n00), f0 = (cs0 - 2 * r) * 64;
#pragma unroll 1
        for (int i = 0; i < (r ? len1 : len0); i++) {
          const uint32_t src = sb + (3 + 2 * r) * H_STAGE + i * 16384;
          const int e = m.item[4 * r + i], burst = (16 << (e >> 8)) - 1;
          if (r) mbar_wait(bb + 8 * (e & 255), 0);
          mbar_wait(ready + 32 * r + 8 * i, 0);
          if (!r) {
            tma_st4<0>(&m.xa, src, 0, f0, 0, n0 + i);
            bulk_commit();
            continue;
          }
#pragma unroll 1
          for (int p = 0; p < 128; p += C_PC) {
            tma_st3<0>(&m.xs, src + p * 128, 0, f0 + (p & 63) + (p >> 6) * 256, n0 + i);
            bulk_commit();
            if (((p + C_PC) & burst) == 0) bulk_wait_read<0>();
          }
        }
        asm volatile("cp.async.bulk.wait_group 0;" ::: "memory");
        if (r) {
          mbar_arrive_cta(bfree, 0);
          mbar_arrive_cta(bfree, 1);
        }
        if (!r) mbar_arrive(bfree + 16);
        asm volatile("red.release.gpu.global.add.s32 [%0], 1;" ::"l"(&gp_.done[(6 + r) * 32]) : "memory");
        if (!r) mbar_arrive(bfree + 24);
      }
    }
    return;
  }
#pragma unroll 1
  for (int it = wg; it < len0 + len1; it += 3) {
    const int r = it >= len0, i = it - r * len0;
    const bool last = i + 1 == (r ? len1 : len0);
    const uint32_t in = sb + (3 + 2 * r) * H_STAGE + i * 16384, bar = yfull + 64 * r + 16 * i;
    float h1[24], h2[24];
    uint32_t p0[12], p1[12], p2[12];
    idft(h2, in + 16384, bar + 16);
    if (it == 2 && lane == 0 && 3 + warp - len0 < len1) {
      y_load(1, 2 * (3 + warp - len0) + 2);
      y_load(1, 2 * (3 + warp - len0) + 1);
    }
    if (it > 0) bar_sync(6 + wg, 256);
    wg_wait<0>();
    reg_fence(h2);
    gelu_pack<0, 2>(p2, h2);
    idft(h1, in + 8192, bar + 8);
    if (!last) {
      gelu_pack<2, 3>(p2, h2);
      carry_out(p2, in + 16384, cfull + 32 * r + 8 * i + 8);
    }
    if (it + 1 < len0 + len1) bar_arrive(6 + (wg + 1) % 3, 256);
    mbar_wait(cfull + 32 * r + 8 * i, 0);
#pragma unroll
    for (int v = 0; v < 3; v++)
      asm volatile("ld.shared.v4.b32 {%0, %1, %2, %3}, [%4];" : "=r"(p0[4 * v]), "=r"(p0[4 * v + 1]), "=r"(p0[4 * v + 2]), "=r"(p0[4 * v + 3]) : "r"(in + v * 2048 + t * 16) : "memory");
    if (it < 3) mbar_wait(yfull + 120, 0);
    wg_wait<0>();
    reg_fence(h1);
    gelu_pack<0, 3>(p1, h1);
    if (last && j == 31) {
#pragma unroll
      for (int v = 0; v < 12; v++) p1[v] = p2[v] = 0;
    }
    uint32_t hp[32];
#pragma unroll
    for (int c = 0; c < 8; c++)
#pragma unroll
      for (int v = 0; v < 4; v++) hp[(v >> 1) * 16 + 2 * c + (v & 1)] = c < 3 ? p0[4 * c + v] : c < 6 ? p1[4 * (c - 3) + v] : p2[4 * (c - 6) + v];
    float e0[32], e1[32];
    reg_fence(hp);
    wg_fence();
#pragma unroll
    for (int k = 0; k < 4; k++) {
      const uint64_t db = mk_desc(sF, k * 32, 0, 1024, 1);
      wgmma_rs_64<1, 1, 0>(e0, hp[4 * k], hp[4 * k + 1], hp[4 * k + 2], hp[4 * k + 3], db, k);
      wgmma_rs_64<1, 1, 0>(e1, hp[16 + 4 * k], hp[16 + 4 * k + 1], hp[16 + 4 * k + 2], hp[16 + 4 * k + 3], db, k);
    }
    wg_commit();
    bar_sync(1 + wg, 128);
    wg_wait<0>();
    reg_fence(e0);
    reg_fence(e1);
    {
      const int mi = lane >> 3, rr = (lane & 7) >> 1, blk = b * NB2 + (r ? n01 : n00) + i;
      const uint32_t a0 = in + (mi >> 1) * 8192 + (warp >> 1) * 4096 + rr * 128;
      const uint32_t pos = ((lane & 1) * 4 + (warp & 1) * 2 + (mi & 1)) ^ rr ^ (blk & 7);
#pragma unroll
      for (int q = 0; q < 8; q++)
        stsm4t(a0 + q * 512 + ((pos ^ (q & 1) * 4) << 4), pack2(e0[4 * q], e0[4 * q + 1]), pack2(e0[4 * q + 2], e0[4 * q + 3]),
               pack2(e1[4 * q], e1[4 * q + 1]), pack2(e1[4 * q + 2], e1[4 * q + 3]));
    }
    fence_async();
    __syncwarp();
    if (lane == 0) mbar_arrive(ready + 32 * r + 8 * i);
  }
  if (wg == 2) return;
  asm volatile("barrier.cluster.wait.aligned;" ::: "memory");
  float acc[84];
  if (wg == 0) {
    h_loop<0>(acc, sb, full0, empty0, lane);
  } else {
    h_loop<1>(acc, sb, full0, empty0, lane);
    bar_sync(2, 128);
  }
  const uint32_t stg = sb + (wg == 0 ? H_NST : 9 % H_NST) * H_STAGE;
  const int mi = lane >> 3, i = lane & 7;
  const uint32_t a0 = stg + (mi >> 1) * 1024 + i * 128 + (((2 * warp + (mi & 1)) ^ i) << 4);
  constexpr int J = 21 / H_EPI;
#pragma unroll
  for (int c = 0; c < H_EPI; c++) {
#pragma unroll
    for (int q = c * J; q + 1 < (c + 1) * J; q += 2)
      stsm4t(a0 + q * 1024, pack2(acc[4 * q], acc[4 * q + 1]), pack2(acc[4 * q + 2], acc[4 * q + 3]),
             pack2(acc[4 * q + 4], acc[4 * q + 5]), pack2(acc[4 * q + 6], acc[4 * q + 7]));
    const int q = (c + 1) * J - 1;
    asm volatile("stmatrix.sync.aligned.m8n8.x2.trans.shared.b16 [%0], {%1, %2};" ::"r"(a0 + q * 1024),
                 "r"(pack2(acc[4 * q], acc[4 * q + 1])), "r"(pack2(acc[4 * q + 2], acc[4 * q + 3])) : "memory");
    fence_async();
    bar_sync(1 + wg, 128);
    if (t == 0) {
      tma_st4<0>(&m.y2, stg + c * J * 1024, 0, c * J * 8, 2 * bin + wg, dc);
      bulk_commit();
    }
  }
  if (t == 0) {
    bulk_wait_read<0>();
  }
}

#define E_I1 12
#define E_WAITS 0xA8
#define E_EARLY0 5
#define E_EARLY 5
constexpr int E_SMEM = 65536 + 131072 + 32768 + 1024;

__device__ __forceinline__ uint32_t joint2(uint32_t fe, uint32_t g0, uint32_t g1) {
  uint32_t s0, s1;
  asm("{\n.reg .b16 l, h;\n.reg .b32 ll, hh;\nmov.b32 {l, h}, %2;\nmov.b32 ll, {l, l};\nmov.b32 hh, {h, h};\n"
      "fma.rn.bf16x2 %0, ll, %5, %3;\nfma.rn.bf16x2 %1, hh, %5, %4;\n}"
      : "=r"(s0), "=r"(s1) : "r"(fe), "r"(g0), "r"(g1), "r"(0x3F800000u));
  return pack2(tanh_f32(__uint_as_float(s0)), tanh_f32(__uint_as_float(s1)));
}
__device__ __forceinline__ uint4 lds128(uint32_t a) {
  uint4 v;
  asm volatile("ld.shared.v4.u32 {%0, %1, %2, %3}, [%4];" : "=r"(v.x), "=r"(v.y), "=r"(v.z), "=r"(v.w) : "r"(a));
  return v;
}
__device__ __forceinline__ void joint_group(uint32_t (&ja)[8], const uint32_t* fe, const uint4& c0, const uint4& c1) {
  ja[0] = joint2(fe[0], c0.x, c0.y);
  ja[1] = joint2(fe[1], c0.x, c0.y);
  ja[2] = joint2(fe[2], c0.z, c0.w);
  ja[3] = joint2(fe[3], c0.z, c0.w);
  ja[4] = joint2(fe[4], c1.x, c1.y);
  ja[5] = joint2(fe[5], c1.x, c1.y);
  ja[6] = joint2(fe[6], c1.z, c1.w);
  ja[7] = joint2(fe[7], c1.z, c1.w);
  reg_fence(ja);
}

__global__ void __cluster_dims__(2, 1, 1) __launch_bounds__(256, 1)
kE(const __grid_constant__ CUtensorMap my, const __grid_constant__ CUtensorMap mwf, const __grid_constant__ CUtensorMap mwo,
   const __grid_constant__ CUtensorMap mout) {
  const Ptrs gp_ = {g_done, g_ge, c_img, c_ga};
  extern __shared__ uint8_t smem_raw[];
  __shared__ __align__(8) uint64_t bars[17];
  const uint32_t sb = (s2u(smem_raw) + 1023) & ~1023u;
  const int tid = threadIdx.x, wg = __shfl_sync(0xffffffffu, tid >> 7, 0), t = tid & 127, warp = t >> 5, lane = t & 31;
  const uint32_t R0 = sb, R1 = sb + 65536, R2 = sb + 65536 + 131072;
  const uint32_t barY = s2u(&bars[0]), barO = barY + 32, barF = barY + 64, barA = barY + 128;
  const int b = blockIdx.x / 63, t0 = (blockIdx.x % 63) * 64;
  const int a = t0 / 48, o = t0 % 48;
  const int qw = o + 16 * warp, sel = qw >= 48;
  uint32_t ga[16];
#pragma unroll
  for (int s = 0; s < 4; s++)
    ldg128(reinterpret_cast<const uint4*>(gp_.ga) + ((qw >> 4) - 3 * sel) * 128 + s * 32 + lane, ga[4 * s], ga[4 * s + 1], ga[4 * s + 2], ga[4 * s + 3]);
  uint4 gev0, gev1;
  asm volatile("ld.global.cg.v4.u32 {%0, %1, %2, %3}, [%4];" : "=r"(gev0.x), "=r"(gev0.y), "=r"(gev0.z), "=r"(gev0.w)
               : "l"(reinterpret_cast<const uint4*>(gp_.ge) + (b * 8 + wg * 4) * 64 + t));
  asm volatile("ld.global.cg.v4.u32 {%0, %1, %2, %3}, [%4];" : "=r"(gev1.x), "=r"(gev1.y), "=r"(gev1.z), "=r"(gev1.w)
               : "l"(reinterpret_cast<const uint4*>(gp_.ge) + (b * 8 + wg * 4) * 64 + 128 + t));
  auto f_load = [&](int q) {
    const int p = (0x37156240 >> (4 * q)) & 7;
    mbar_expect(barF + 8 * p, 16384);
    tma_ld3<0>(R1 + p * 16384, &mwf, barF + 8 * p, 0, (p >> 1) * 64, (p & 1) * 2);
  };
  if (tid == 0) {
    prefetch_map(&my);
    for (int i = 0; i < 16; i++) mbar_init(barY + 8 * i, 1);
    mbar_init(barA, 8);
    fence_bar_init();
    prefetch_map(&mwf);
    pdl_wait();
    for (int i = 0; i < 4; i++) {
      mbar_expect(barY + 8 * i, 16384);
      tma_ld5<0>(R0 + i * 16384, &my, barY + 8 * i, 0, 0, 2 * (i & 1) + (i >> 1), a, b);
    }
    for (int q = 0; q < 4; q++) f_load(q);
  }
  if (tid == 64) {
    prefetch_map(&mwo);
    prefetch_map(&mout);
  }
  uint32_t gs[32];
#pragma unroll
  for (int i = 0; i < 16; i++) {
    gs[i] = sel ? 0u : ga[i];
    gs[16 + i] = sel ? ga[i] : 0u;
  }
  __syncthreads();
  if (blockIdx.x == 125 && tid < 8) gp_.done[tid * 32] = 0;
  reg_fence(gs);
  uint32_t gp = R2 + 16384 + wg * 4096 + (lane & 3) * 16;
  uint4 g0, g1;
  uint32_t fe[64];
  {
    float d0[32], d1[32], e[64];
    mbar_wait(barY + 8 * wg, 0);
    wg_fence();
#pragma unroll
    for (int k = 0; k < 8; k++)
      wgmma_rs_64<1, 1, 1>(d0, gs[4 * k], gs[4 * k + 1], gs[4 * k + 2], gs[4 * k + 3], mk_desc(R0 + wg * 16384, k * 2048, 0, 1024, 1), k);
    wg_commit();
    if (tid == 0)
      for (int q = 4; q < 8; q++) f_load(q);
    wg_wait<0>();
    reg_fence(d0);
    uint32_t p0[16], p1[16];
    const uint32_t wfo = R1 + wg * (65536 + 16384), wfx = R1 + 65536 - wg * (65536 - 16384), fx = R2 + 16384 - wg * 16384;
    const uint32_t fo = R2 + wg * 16384 + (warp * 16 + (lane & 7) + ((lane >> 3) & 1) * 8) * 128;
    auto fe_own = [&](const uint32_t (&p)[16], int c) {
      wg_fence();
#pragma unroll
      for (int s = 0; s < 4; s++)
        wgmma_rs_128<1, 1, 1>(e, p[4 * s], p[4 * s + 1], p[4 * s + 2], p[4 * s + 3], mk_desc(wfo, c * 32768 + s * 2048, 8192, 1024, 1), c | s);
    };
    auto fe_other = [&](int c) {
      wg_fence();
#pragma unroll
      for (int s = 0; s < 4; s++)
        wgmma_ss_128<1, 1, 0, 1>(e, mk_desc(fx, c * 8192 + s * 32, 0, 1024, 1), mk_desc(wfx, c * 32768 + s * 2048, 8192, 1024, 1), 1);
    };
    auto f_store = [&](const uint32_t (&p)[16], int c) {
#pragma unroll
      for (int s = 0; s < 4; s++) stsm4(fo + c * 8192 + (((2 * s + (lane >> 4)) ^ (lane & 7)) << 4), p[4 * s], p[4 * s + 1], p[4 * s + 2], p[4 * s + 3]);
    };
#pragma unroll
    for (int i = 0; i < E_I1; i++) p0[i] = pack2(gelu(d0[2 * i]), gelu(d0[2 * i + 1]));
    mbar_wait(barY + 8 * (2 + wg), 0);
    wg_fence();
#pragma unroll
    for (int k = 0; k < 8; k++)
      wgmma_rs_64<1, 1, 1>(d1, gs[4 * k], gs[4 * k + 1], gs[4 * k + 2], gs[4 * k + 3], mk_desc(R0 + wg * 16384, 32768 + k * 2048, 0, 1024, 1), k);
    wg_commit();
#pragma unroll
    for (int i = E_I1; i < 16; i++) p0[i] = pack2(gelu(d0[2 * i]), gelu(d0[2 * i + 1]));
    reg_fence(p0);
    f_store(p0, 0);
    const uint32_t bfo = barF + 40 * wg, bfx = barF + 32 - 24 * wg;
    auto o_load = [&](int kc) {
      mbar_expect(barO + 8 * kc, 32768);
      tma_ld3<0>(kc < 2 ? R0 + kc * 32768 : R1 + (kc - 2) * 65536, &mwo, barO + 8 * kc, 0, kc * 64, 0);
    };
    wg_wait<0>();
    reg_fence(d1);
    if (wg == 1) {
      fence_async();
      bar_arrive(8, 256);
    }
#pragma unroll
    for (int i = 0; i < 16; i++) p1[i] = pack2(gelu(d1[2 * i]), gelu(d1[2 * i + 1]));
    reg_fence(p1);
    if (wg == 0) {
      mbar_wait(bfo, 0);
      fe_own(p0, 0);
      mbar_wait(bfx, 0);
      bar_sync(8, 256);
      fe_other(0);
      wg_commit();
      if (t == 0) {
        o_load(0);
        o_load(1);
      }
      f_store(p1, 1);
      mbar_wait(bfo + 16, 0);
      fe_own(p1, 1);
      fence_async();
      mbar_wait(bfx + 16, 0);
      bar_sync(7, 256);
      fe_other(1);
      wg_commit();
      bar_arrive(4, 256);
      wg_wait<1>();
      if (lane == 0) mbar_arrive(barA);
      bar_sync(1, 128);
    } else {
      f_store(p1, 1);
      fence_async();
      bar_arrive(7, 256);
      mbar_wait(bfo, 0);
      mbar_wait(bfx, 0);
      bar_sync(4, 256);
      fe_own(p0, 0);
      fe_other(0);
      wg_commit();
      mbar_wait(bfo + 16, 0);
      mbar_wait(bfx + 16, 0);
      fe_own(p1, 1);
      wg_commit();
      wg_wait<1>();
      if (lane == 0) mbar_arrive(barA);
      fe_other(1);
      wg_commit();
      mbar_wait(barA, 0);
      if (t == 0) {
        o_load(2);
        o_load(3);
      }
    }
    asm volatile("st.shared.v4.u32 [%0], {%1, %2, %3, %4};" ::"r"(R2 + 16384 + wg * 4096 + ((t * 16) ^ (wg * 512))), "r"(gev0.x), "r"(gev0.y), "r"(gev0.z), "r"(gev0.w) : "memory");
    asm volatile("st.shared.v4.u32 [%0], {%1, %2, %3, %4};" ::"r"(R2 + 16384 + wg * 4096 + 2048 + ((t * 16) ^ (wg * 512))), "r"(gev1.x), "r"(gev1.y), "r"(gev1.z), "r"(gev1.w) : "memory");
    bar_sync(1 + wg, 128);
    g0 = lds128(gp);
    g1 = lds128(gp + 64);
    wg_wait<0>();
    reg_fence(e);
#pragma unroll
    for (int i = 0; i < 32; i++) fe[i] = pack2(e[2 * i], e[2 * i + 1]);
  }
  auto publish = [&]() {
    bar_sync(1 + wg, 128);
    const int row = warp * 16 + (lane & 7) + ((lane >> 3) & 1) * 8;
    const uint32_t xb = R1 + (wg == 0 ? 3 * 32768 : 32768 + 16384) + row * 128;
#pragma unroll
    for (int s = 0; s < 8; s++) {
      const int jj = 2 * s + (lane >> 4);
      stsm4(xb + (s >> 2) * 8192 + (((jj & 7) ^ (lane & 7)) << 4), fe[4 * s], fe[4 * s + 1], fe[4 * s + 2], fe[4 * s + 3]);
    }
    bar_arrive(5 + wg, 256);
  };
  if (wg == 1) publish();
  const uint32_t stg = R1 + 32768 + wg * 65536;
  const uint32_t w0 = sb + wg * 65536, w1 = sb + 32768 + wg * 98304, w2 = sb + 65536 - wg * 65536, w3 = sb + 131072 - wg * 98304;
  float acc[128];
  uint32_t j0[8], j1[8], j2[8], j3[8];
  uint4 h0 = lds128(gp + 128), h1 = lds128(gp + 192);
  const uint32_t bo0 = barO + 16 * wg, bo2 = barO + 16 * (1 - wg);
  joint_group(j0, fe, g0, g1);
  g0 = lds128(gp + 256);
  g1 = lds128(gp + 320);
  mbar_wait(barY, 0);
  joint_group(j1, fe + 8, h0, h1);
#define E_MMA2(J, W, OFF, FIRSTK)                                                                       \
  wgmma_rs_256<1, 1, 1>(acc, J[0], J[1], J[2], J[3], mk_desc(W, OFF, 8192, 1024, 1), FIRSTK);           \
  wgmma_rs_256<1, 1, 1>(acc, J[4], J[5], J[6], J[7], mk_desc(W, (OFF) + 2048, 8192, 1024, 1), 1);
#define E_TOKEN(N) \
  if ((ui + wg == 0 ? E_EARLY0 : E_EARLY) == (N) && (ui < 3 || wg == 0)) bar_arrive(4 - wg, 256);
#define E_BLOCK(N, J, W, BAR, JN, C0, C1, L0, L1)     \
  L0 = lds128(gp + 128 * (N) + 256);                  \
  L1 = lds128(gp + 128 * (N) + 320);                  \
  E_TOKEN((N) - 1)                                    \
  if (ui == 0) mbar_wait(BAR, 0);                     \
  if (E_WAITS >> (N) & 1) wg_wait<1>();               \
  wg_fence();                                         \
  E_MMA2(J, W, ((N) & 1) * 4096, 1)                   \
  wg_commit();                                        \
  if ((N) < 7) joint_group(JN, fe + 8 * (((N) + 1) & 7), C0, C1);
#pragma unroll 1
  for (int ui = 0; ui < 4; ui++) {
    h0 = lds128(gp + 384);
    h1 = lds128(gp + 448);
    if (ui == 0) mbar_wait(bo0, 0);
    if (ui > 0 || wg == 1) bar_sync(3 + wg, 256);
    wg_fence();
    E_MMA2(j0, w0, 0, 0)
    E_MMA2(j1, w0, 4096, 1)
    wg_commit();
    joint_group(j2, fe + 16, g0, g1);
    E_BLOCK(2, j2, w1, bo0 + 8, j3, h0, h1, g0, g1)
    if (ui == 0) {
      if (wg == 0) publish();
      bar_sync(6 - wg, 256);
      const int row = warp * 16 + (lane & 7) + ((lane >> 3) & 1) * 8;
      const uint32_t xb = R1 + (wg == 1 ? 3 * 32768 : 32768 + 16384) + row * 128;
#pragma unroll
      for (int s = 0; s < 8; s++) {
        const int jj = 2 * s + (lane >> 4);
        ldsm4(xb + (s >> 2) * 8192 + (((jj & 7) ^ (lane & 7)) << 4), fe[32 + 4 * s], fe[33 + 4 * s], fe[34 + 4 * s], fe[35 + 4 * s]);
      }
    }
    E_BLOCK(3, j3, w1, bo0 + 8, j0, g0, g1, h0, h1)
    E_BLOCK(4, j0, w2, bo2, j1, h0, h1, g0, g1)
    E_BLOCK(5, j1, w2, bo2, j2, g0, g1, h0, h1)
    E_BLOCK(6, j2, w3, bo2 + 8, j3, h0, h1, g0, g1)
    E_BLOCK(7, j3, w3, bo2 + 8, j0, g0, g1, h0, h1)
    gp += 1024;
    if (ui < 3) {
      joint_group(j0, fe, g0, g1);
      g0 = lds128(gp + 256);
      g1 = lds128(gp + 320);
      if (ui == 0) mbar_wait(bo2 + 8, 0);
      joint_group(j1, fe + 8, h0, h1);
    }
    if (t == 0) bulk_wait_read<0>();
    bar_sync(1 + wg, 128);
    wg_wait<0>();
    reg_fence(acc);
    const uint32_t rb = stg + (warp * 16 + (lane & 7) + ((lane >> 3) & 1) * 8) * 128;
#pragma unroll
    for (int h = 0; h < 2; h++) {
#pragma unroll
      for (int j = 16 * h; j < 16 * h + 16; j += 2) {
        const int jj = j + (lane >> 4);
        stsm4(rb + (j >> 3) * 8192 + (((jj & 7) ^ (lane & 7)) << 4), pack2(acc[4 * j], acc[4 * j + 1]), pack2(acc[4 * j + 2], acc[4 * j + 3]),
              pack2(acc[4 * j + 4], acc[4 * j + 5]), pack2(acc[4 * j + 6], acc[4 * j + 7]));
      }
      fence_async();
      bar_sync(1 + wg, 128);
      if (t == 0) {
        tma_st5<1>(&mout, stg + h * 16384, 0, t0, 2 * h, wg * 4 + ui, b);
        bulk_commit();
      }
    }
  }
  if (t == 0) bulk_wait_read<0>();
}

typedef CUresult (*EncodeFn)(CUtensorMap*, CUtensorMapDataType, cuuint32_t, void*, const cuuint64_t*, const cuuint64_t*,
                             const cuuint32_t*, const cuuint32_t*, CUtensorMapInterleave, CUtensorMapSwizzle,
                             CUtensorMapL2promotion, CUtensorMapFloatOOBfill);

CUtensorMap make_map(EncodeFn fn, const void* base, int rank, const uint64_t* dims, const uint64_t* strides, const uint32_t* box,
                     CUtensorMapSwizzle swz) {
  CUtensorMap m;
  cuuint64_t gd[5], gs[4];
  cuuint32_t bx[5], es[5];
  for (int i = 0; i < rank; i++) { gd[i] = dims[i]; bx[i] = box[i]; es[i] = 1; }
  for (int i = 0; i + 1 < rank; i++) gs[i] = strides[i];
  fn(&m, CU_TENSOR_MAP_DATA_TYPE_BFLOAT16, rank, const_cast<void*>(base), gd, gs, bx, es, CU_TENSOR_MAP_INTERLEAVE_NONE, swz,
     CU_TENSOR_MAP_L2_PROMOTION_NONE, CU_TENSOR_MAP_FLOAT_OOB_FILL_NONE);
  return m;
}

template <typename... KArgs, typename... Args>
void launch(void (*k)(KArgs...), int grid, int block, int smem, bool pdl, Args... args) {
  cudaLaunchConfig_t c = {};
  c.gridDim = dim3(grid);
  c.blockDim = dim3(block);
  c.dynamicSmemBytes = smem;
  c.stream = cudaStreamPerThread;
  cudaLaunchAttribute at[1];
  at[0].id = cudaLaunchAttributeProgrammaticStreamSerialization;
  at[0].val.programmaticStreamSerializationAllowed = 1;
  c.attrs = at;
  c.numAttrs = pdl ? 1 : 0;
  cudaLaunchKernelEx(&c, k, args...);
}

}

static uint32_t h_plan[67 + 25] = {
    0x6108, 0x6109, 0x610a, 0x610b, 0x6101, 0x8008, 0x8109, 0x820a, 0x830b, 0x8401,
    0x8508, 0x6102, 0x8609, 0x870a, 0x880b, 0x6103, 0x8a08, 0x8b02, 0x8c09, 0x8d0a,
    0x8e0b, 0x8f03, 0x9008, 0x9209, 0x930a, 0x9503, 0x9608, 0x9709, 0x980a, 0x9a08,
    0x9b09, 0x9c0a, 0x61616115, 0x6161610d, 0x61616107, 0x83816166, 0x8986610c, 0x8a89314d, 0x8f8a3237, 0x938f940b,
    0x9393344c, 0x9993354d, 0x0, 0x0, 0x0, 0x0, 0x0, 0x0, 0x6161ba98, 0x6161a981,
    0x6789281b, 0x67893ba9, 0x6891a928, 0x6891983b, 0x6999983a, 0x6999a98a, 0x39389d, 0x3, 0x4, 0x1dcc17b8,
    0x8f6a0c52, 0xac1, 0x2e5a9261, 0x194a, 0x9e, 0x9f, 0x37, 0x0, 0x0, 0x0,
    0x10, 0x11, 0x13, 0x14, 0x0, 0x0, 0x0, 0x0, 0x0, 0x0,
    0x0, 0x0, 0x0, 0x431, 0x431, 0x431, 0x0, 0x133, 0x131, 0x331,
    0x0, 0x3,
};

extern "C" void kernel_launch(void* const* d_in, const int* in_sizes, int n_in, void* d_out, int out_size) {
  const __nv_bfloat16* x = (const __nv_bfloat16*)d_in[0];
  const __nv_bfloat16* w1 = (const __nv_bfloat16*)d_in[1];
  const __nv_bfloat16* w2 = (const __nv_bfloat16*)d_in[2];
  const __nv_bfloat16* g = (const __nv_bfloat16*)d_in[3];
  const __nv_bfloat16* wf = (const __nv_bfloat16*)d_in[4];
  const __nv_bfloat16* wgt = (const __nv_bfloat16*)d_in[5];
  const __nv_bfloat16* wo = (const __nv_bfloat16*)d_in[6];

  void* fp = nullptr;
  cudaDriverEntryPointQueryResult qr;
  cudaGetDriverEntryPoint("cuTensorMapEncodeTiled", &fp, cudaEnableDefault, &qr);
  EncodeFn fn = (EncodeFn)fp;
  void *X1, *W2, *Y1, *X2, *Y2;
  cudaGetSymbolAddress(&X1, g_X1);
  cudaGetSymbolAddress(&W2, g_W2);
  cudaGetSymbolAddress(&Y1, g_Y1);
  cudaGetSymbolAddress(&X2, g_X2);
  cudaGetSymbolAddress(&Y2, g_Y2);
  cudaFuncSetAttribute(k1, cudaFuncAttributeMaxDynamicSharedMemorySize, K1_SMEM);
  cudaFuncSetAttribute(k2, cudaFuncAttributeMaxDynamicSharedMemorySize, K2_SMEM);
  cudaFuncSetAttribute(kE, cudaFuncAttributeMaxDynamicSharedMemorySize, E_SMEM);
  if (ALIAS) {
    W2 = d_out;
    X2 = (char*)d_out + sizeof(g_W2);
    X1 = (char*)X2 - sizeof(g_X2);
    Y2 = Y1;
  }
  const CUtensorMapSwizzle S128 = CU_TENSOR_MAP_SWIZZLE_128B;

  auto map_x = [&]() {
    uint64_t d[] = {64, 8000, 8, 2}, s[] = {1024, 128, 8000ull * 1024};
    uint32_t bx[] = {64, 56, 1, 1};
    return make_map(fn, x, 4, d, s, bx, S128);
  };
  auto map_w_in = [&](const __nv_bfloat16* w, int odd) {
    uint64_t d[] = {64, (uint64_t)(odd ? 15 : 16), 4, 256}, s[] = {2ull * 65536 * 2, 128, 512};
    uint32_t bx[] = {64, 16, 2, 1};
    return make_map(fn, w + (odd ? 65536 : 0), 4, d, s, bx, S128);
  };
  auto map_X_st = [&](void* p, int nb, int boxb) {
    uint64_t d[] = {64, 512, (uint64_t)(2 * nb)}, s[] = {2ull * nb * 128, 128};
    uint32_t bx[] = {64, C_PC, (uint32_t)boxb};
    return make_map(fn, p, 3, d, s, bx, S128);
  };
  auto map_X1_st = [&]() {
    uint64_t d[] = {64, 512, 2, (uint64_t)NB1}, s[] = {2ull * NB1 * 128, (uint64_t)NB1 * 128, 128};
    uint32_t bx[] = {64, 16, 1, 1};
    return make_map(fn, X1, 4, d, s, bx, S128);
  };
  auto map_W_st = [&](void* p) {
    uint64_t d[] = {64, 512, 4, 64}, s[] = {32768, 8192, 128};
    uint32_t bx[] = {64, W2_PC < 64 ? W2_PC : 64, W2_PC == 128 ? 2 : 1, 1};
    return make_map(fn, p, 4, d, s, bx, S128);
  };
  auto map_W_ld = [&](void* p, uint32_t bd, uint32_t bf) {
    uint64_t d[] = {64, 64, 4, 512}, s[] = {128, 8192, 32768};
    uint32_t bx[] = {64, 32, bd, bf};
    return make_map(fn, p, 4, d, s, bx, S128);
  };
  auto map_Y_st = [&](void* p, int nb, int rows) {
    uint64_t d[] = {64, (uint64_t)(2 * nb), 64, 4}, s[] = {32768, 128, 8192};
    uint32_t bx[] = {64, (uint32_t)rows, 1, 1};
    return make_map(fn, p, 4, d, s, bx, S128);
  };
  auto map_Y_ld = [&](void* p, int nb, int boxc, int boxb) {
    uint64_t d[] = {64, 64, 4, (uint64_t)nb, 2}, s[] = {128, 8192, 32768, (uint64_t)nb * 32768};
    uint32_t bx[] = {64, 64, (uint32_t)boxc, (uint32_t)boxb, 1};
    return make_map(fn, p, 5, d, s, bx, S128);
  };
  auto map_wsq = [&](const __nv_bfloat16* w, uint32_t bn) {
    uint64_t d[] = {64, 256, 4}, s[] = {512, 128};
    uint32_t bx[] = {64, 64, bn};
    return make_map(fn, w, 3, d, s, bx, S128);
  };
  auto map_out = [&]() {
    uint64_t d[] = {64, 4000, 4, 8, 2}, s[] = {4096, 128, 512, 4000ull * 4096};
    uint32_t bx[] = {64, 64, 2, 1, 1};
    return make_map(fn, d_out, 5, d, s, bx, S128);
  };

  auto map_w_raw = [&](const __nv_bfloat16* w, int odd) {
    uint64_t d[] = {256, (uint64_t)(odd ? 15 : 16), 16, 16}, s[] = {2ull * 65536 * 2, 512, 8192};
    uint32_t bx[] = {64, 16, 4, 2};
    return make_map(fn, w + (odd ? 65536 : 0), 4, d, s, bx, S128);
  };
  Ptrs gp;
  cudaGetSymbolAddress((void**)&gp.done, g_done);
  cudaGetSymbolAddress((void**)&gp.ge, g_ge);
  cudaGetSymbolAddress((void**)&gp.img, c_img);
  cudaGetSymbolAddress((void**)&gp.ga, c_ga);
  K1Maps g1;
  memcpy(&g1.p, h_plan, sizeof(Plan));
  g1.x = map_x();
  g1.we = map_w_raw(w1, 0);
  g1.wo = map_w_raw(w1, 1);
  g1.xs = map_X1_st();
  g1.y = map_Y_st(Y1, NB1, NB1 / G_EPI);
  g1.w2e = map_w_in(w2, 0);
  g1.w2o = map_w_in(w2, 1);
  g1.w2s = map_W_st(W2);
  for (int s = 0; s < 32; s++) {
    const int k = s < G_S0 ? s >> 1 : G_KM + (s - G_S0) % G_TK;
    g1.slot[s] = g_off(g_slot(s)) / 16;
    g1.src[s] = ((k >> 1) * 256 + (k & 1) * 2 + (s < G_S0 ? (s & 1) * 4 : s >= G_S0 + G_TK)) * (G_ST / 2);
    g1.dep[s] = s < 3 ? 8 * h_plan[64 + s] : 1536 + 8 * (s - g_depth(s));
  }
  launch(k1, 132, 384, K1_SMEM, false, gp, (const char*)X1, (const char*)w1, g1, g, wgt);
  K2Maps g2;
  memcpy(&g2, h_plan + 67, 100);
  g2.y = map_Y_ld(Y1, NB1, 1, 1);
  g2.xs = map_X_st(X2, NB2, 1);
  {
    uint64_t d[] = {64, 256, 2, 2 * NB2}, s[] = {2ull * NB2 * 128, 512ull * NB2 * 128, 128};
    uint32_t bx[] = {64, 64, 2, 1};
    g2.xa = make_map(fn, X2, 4, d, s, bx, S128);
  }
  g2.w = map_W_ld(W2, 1, 2);
  g2.y2 = map_Y_st(Y2, NB2, 168 / H_EPI);
  launch(k2, 128, 512, K2_SMEM, true, gp, (const char*)X2, g2, wf, wo);
  launch(kE, 126, 256, E_SMEM, true, map_Y_ld(Y2, NB2, 1, 2), map_wsq(wf, 2), map_wsq(wo, 4), map_out());
}
```

```cpp
#include <cuda_runtime.h>
#include <cuda_bf16.h>
#include <cuda.h>
#include <stdint.h>
#include <string.h>
#include <type_traits>

namespace {

constexpr int NB1 = 168;
constexpr int NB2 = 84;

constexpr size_t W2_BYTES = 8 * 64 * 4 * 64 * 64 * 2, X2_BYTES = 8 * 64 * 2 * NB2 * 64 * 2;
__device__ __align__(1024) __nv_bfloat16 g_Y[2 * NB1 * 4 * 64 * 64];
__device__ __align__(1024) float g_ge[16 * 256];

__device__ __forceinline__ uint32_t s2u(const void* p) { return (uint32_t)__cvta_generic_to_shared(p); }
__device__ __forceinline__ void mbar_init(uint32_t b, int c) {
  asm volatile("mbarrier.init.shared::cta.b64 [%0], %1;" ::"r"(b), "r"(c) : "memory");
}
__device__ __forceinline__ void mbar_expect(uint32_t b, int bytes) {
  asm volatile("mbarrier.arrive.expect_tx.shared::cta.b64 _, [%0], %1;" ::"r"(b), "r"(bytes) : "memory");
}
__device__ __forceinline__ void mbar_arrive(uint32_t b) {
  asm volatile("mbarrier.arrive.shared::cta.b64 _, [%0];" ::"r"(b) : "memory");
}
__device__ __forceinline__ void mbar_arrive_cta(uint32_t b, uint32_t cta) {
  asm volatile("{\n.reg .b32 r;\nmapa.shared::cluster.u32 r, %0, %1;\nmbarrier.arrive.shared::cluster.b64 _, [r];\n}" ::"r"(b), "r"(cta) : "memory");
}
__device__ __forceinline__ void mbar_wait(uint32_t b, int ph) {
  asm volatile(
      "{\n.reg .pred p;\n.reg .u32 n;\n"
      "mov.u32 n, 0;\n"
      "MBW_LOOP:\n"
      "mbarrier.try_wait.parity.shared::cta.b64 p, [%0], %1;\n"
      "@p bra MBW_DONE;\n"
      "add.u32 n, n, 1;\n"
      "setp.lt.u32 p, n, 1048576;\n"
      "@p bra MBW_LOOP;\n"
      "MBW_DONE:\n}" ::"r"(b), "r"(ph) : "memory");
}
__device__ __forceinline__ void fence_bar_init() { asm volatile("fence.mbarrier_init.release.cluster;" ::: "memory"); }
__device__ __forceinline__ void fence_async() { asm volatile("fence.proxy.async.shared::cta;" ::: "memory"); }
__device__ __forceinline__ void bar_sync(int id, int n) { asm volatile("bar.sync %0, %1;" ::"r"(id), "r"(n) : "memory"); }
__device__ __forceinline__ void bar_arrive(int id, int n) { asm volatile("bar.arrive %0, %1;" ::"r"(id), "r"(n) : "memory"); }
__device__ __forceinline__ void pdl_wait() { asm volatile("griddepcontrol.wait;" ::: "memory"); }
__device__ __forceinline__ void pdl_launch() { asm volatile("griddepcontrol.launch_dependents;" ::: "memory"); }
__device__ __forceinline__ void prefetch_map(const CUtensorMap* m) {
  asm volatile("prefetch.tensormap [%0];" ::"l"(m) : "memory");
}
template <int P> __device__ __forceinline__ uint64_t policy() {
  uint64_t p;
  asm("createpolicy.fractional.L2::evict_first.b64 %0, 1.0;" : "=l"(p));
  return p;
}
template <int P> __device__ __forceinline__ void tma_ld3(uint32_t dst, const CUtensorMap* m, uint32_t bar, int c0, int c1, int c2) {
  if constexpr (P == 0)
    asm volatile("cp.async.bulk.tensor.3d.shared::cluster.global.mbarrier::complete_tx::bytes [%0], [%1, {%3, %4, %5}], [%2];"
                 ::"r"(dst), "l"(m), "r"(bar), "r"(c0), "r"(c1), "r"(c2) : "memory");
  else
    asm volatile("cp.async.bulk.tensor.3d.shared::cluster.global.mbarrier::complete_tx::bytes.L2::cache_hint [%0], [%1, {%3, %4, %5}], [%2], %6;"
                 ::"r"(dst), "l"(m), "r"(bar), "r"(c0), "r"(c1), "r"(c2), "l"(policy<P>()) : "memory");
}
template <int P> __device__ __forceinline__ void tma_ld4(uint32_t dst, const CUtensorMap* m, uint32_t bar, int c0, int c1, int c2, int c3) {
  if constexpr (P == 0)
    asm volatile("cp.async.bulk.tensor.4d.shared::cluster.global.mbarrier::complete_tx::bytes [%0], [%1, {%3, %4, %5, %6}], [%2];"
                 ::"r"(dst), "l"(m), "r"(bar), "r"(c0), "r"(c1), "r"(c2), "r"(c3) : "memory");
  else
    asm volatile("cp.async.bulk.tensor.4d.shared::cluster.global.mbarrier::complete_tx::bytes.L2::cache_hint [%0], [%1, {%3, %4, %5, %6}], [%2], %7;"
                 ::"r"(dst), "l"(m), "r"(bar), "r"(c0), "r"(c1), "r"(c2), "r"(c3), "l"(policy<P>()) : "memory");
}
template <int P> __device__ __forceinline__ void tma_ld5(uint32_t dst, const CUtensorMap* m, uint32_t bar, int c0, int c1, int c2, int c3, int c4) {
  if constexpr (P == 0)
    asm volatile("cp.async.bulk.tensor.5d.shared::cluster.global.mbarrier::complete_tx::bytes [%0], [%1, {%3, %4, %5, %6, %7}], [%2];"
                 ::"r"(dst), "l"(m), "r"(bar), "r"(c0), "r"(c1), "r"(c2), "r"(c3), "r"(c4) : "memory");
  else
    asm volatile("cp.async.bulk.tensor.5d.shared::cluster.global.mbarrier::complete_tx::bytes.L2::cache_hint [%0], [%1, {%3, %4, %5, %6, %7}], [%2], %8;"
                 ::"r"(dst), "l"(m), "r"(bar), "r"(c0), "r"(c1), "r"(c2), "r"(c3), "r"(c4), "l"(policy<P>()) : "memory");
}
template <int P> __device__ __forceinline__ void tma_st3(const CUtensorMap* m, uint32_t src, int c0, int c1, int c2) {
  if constexpr (P == 0)
    asm volatile("cp.async.bulk.tensor.3d.global.shared::cta.bulk_group [%0, {%2, %3, %4}], [%1];" ::"l"(m), "r"(src), "r"(c0), "r"(c1), "r"(c2) : "memory");
  else
    asm volatile("cp.async.bulk.tensor.3d.global.shared::cta.bulk_group.L2::cache_hint [%0, {%2, %3, %4}], [%1], %5;" ::"l"(m), "r"(src), "r"(c0), "r"(c1), "r"(c2), "l"(policy<P>()) : "memory");
}
template <int P> __device__ __forceinline__ void tma_st4(const CUtensorMap* m, uint32_t src, int c0, int c1, int c2, int c3) {
  if constexpr (P == 0)
    asm volatile("cp.async.bulk.tensor.4d.global.shared::cta.bulk_group [%0, {%2, %3, %4, %5}], [%1];" ::"l"(m), "r"(src), "r"(c0), "r"(c1), "r"(c2), "r"(c3) : "memory");
  else
    asm volatile("cp.async.bulk.tensor.4d.global.shared::cta.bulk_group.L2::cache_hint [%0, {%2, %3, %4, %5}], [%1], %6;" ::"l"(m), "r"(src), "r"(c0), "r"(c1), "r"(c2), "r"(c3), "l"(policy<P>()) : "memory");
}
template <int P> __device__ __forceinline__ void tma_st5(const CUtensorMap* m, uint32_t src, int c0, int c1, int c2, int c3, int c4) {
  if constexpr (P == 0)
    asm volatile("cp.async.bulk.tensor.5d.global.shared::cta.bulk_group [%0, {%2, %3, %4, %5, %6}], [%1];" ::"l"(m), "r"(src), "r"(c0), "r"(c1), "r"(c2), "r"(c3), "r"(c4) : "memory");
  else
    asm volatile("cp.async.bulk.tensor.5d.global.shared::cta.bulk_group.L2::cache_hint [%0, {%2, %3, %4, %5, %6}], [%1], %7;" ::"l"(m), "r"(src), "r"(c0), "r"(c1), "r"(c2), "r"(c3), "r"(c4), "l"(policy<P>()) : "memory");
}
__device__ __forceinline__ void bulk_commit() { asm volatile("cp.async.bulk.commit_group;" ::: "memory"); }
template <int N> __device__ __forceinline__ void bulk_wait_read() { asm volatile("cp.async.bulk.wait_group.read %0;" ::"n"(N) : "memory"); }
__device__ __forceinline__ void wg_fence() { asm volatile("wgmma.fence.sync.aligned;" ::: "memory"); }
__device__ __forceinline__ void wg_commit() { asm volatile("wgmma.commit_group.sync.aligned;" ::: "memory"); }
template <int N> __device__ __forceinline__ void wg_wait() { asm volatile("wgmma.wait_group.sync.aligned %0;" ::"n"(N) : "memory"); }
template <int R> __device__ __forceinline__ void reg_fence(float (&d)[R]) {
#pragma unroll
  for (int i = 0; i < R; i++) asm volatile("" : "+f"(d[i])::"memory");
}
template <int R> __device__ __forceinline__ void reg_fence(uint32_t (&d)[R]) {
#pragma unroll
  for (int i = 0; i < R; i++) asm volatile("" : "+r"(d[i])::"memory");
}
__device__ __forceinline__ void stsm4(uint32_t a, uint32_t r0, uint32_t r1, uint32_t r2, uint32_t r3) {
  asm volatile("stmatrix.sync.aligned.m8n8.x4.shared.b16 [%0], {%1, %2, %3, %4};" ::"r"(a), "r"(r0), "r"(r1), "r"(r2), "r"(r3) : "memory");
}
__device__ __forceinline__ void stsm4t(uint32_t a, uint32_t r0, uint32_t r1, uint32_t r2, uint32_t r3) {
  asm volatile("stmatrix.sync.aligned.m8n8.x4.trans.shared.b16 [%0], {%1, %2, %3, %4};" ::"r"(a), "r"(r0), "r"(r1), "r"(r2), "r"(r3) : "memory");
}
__device__ __forceinline__ void ldsm4(uint32_t a, uint32_t& r0, uint32_t& r1, uint32_t& r2, uint32_t& r3) {
  asm volatile("ldmatrix.sync.aligned.m8n8.x4.shared.b16 {%0, %1, %2, %3}, [%4];" : "=r"(r0), "=r"(r1), "=r"(r2), "=r"(r3) : "r"(a) : "memory");
}
__device__ __forceinline__ void ldsm4t(uint32_t a, uint32_t& r0, uint32_t& r1, uint32_t& r2, uint32_t& r3) {
  asm volatile("ldmatrix.sync.aligned.m8n8.x4.trans.shared.b16 {%0, %1, %2, %3}, [%4];" : "=r"(r0), "=r"(r1), "=r"(r2), "=r"(r3) : "r"(a) : "memory");
}
__device__ __forceinline__ void ldg128(const uint4* p, uint32_t& a, uint32_t& b, uint32_t& c, uint32_t& d) {
  asm volatile("ld.global.nc.v4.u32 {%0, %1, %2, %3}, [%4];" : "=r"(a), "=r"(b), "=r"(c), "=r"(d) : "l"(p));
}
__device__ __forceinline__ uint32_t pack2(float lo, float hi) {
  uint32_t r;
  asm("cvt.rn.bf16x2.f32 %0, %1, %2;" : "=r"(r) : "f"(hi), "f"(lo));
  return r;
}
__device__ __forceinline__ float tanh_f32(float x) {
  float y;
  asm("tanh.approx.f32 %0, %1;" : "=f"(y) : "f"(x));
  return y;
}
__device__ __forceinline__ float gelu(float hx) {
  const float u = hx * fmaf(hx * hx, 8.0f * 0.044715f * 0.7978845608028654f, 2.0f * 0.7978845608028654f);
  return fmaf(hx, tanh_f32(u), hx);
}
__device__ __forceinline__ uint64_t mk_desc4(uint32_t addr4, uint32_t lbo, uint32_t sbo, uint32_t swz) {
  const uint32_t lo = addr4 + ((lbo >> 4) << 16), hi = (sbo >> 4) | (swz << 30);
  uint64_t d;
  asm("mov.b64 %0, {%1, %2};" : "=l"(d) : "r"(lo), "r"(hi));
  return d;
}
#define mk_desc(base, off, lbo, sbo, swz) mk_desc4((((base) & 0x3FFFF) >> 4) + ((off) >> 4), lbo, sbo, swz)

template <int SA, int SB, int TA, int TB>
__device__ __forceinline__ void wgmma_ss_48(float (&d)[24], uint64_t da, uint64_t db, int sd) {
  asm volatile("{\n.reg .pred p;\nsetp.ne.b32 p, %26, 0;\n"
      "wgmma.mma_async.sync.aligned.m64n48k16.f32.bf16.bf16 {"
      "%0, %1, %2, %3, %4, %5, %6, %7, %8, %9, %10, %11, %12, %13, %14, %15, %16, %17, %18, %19, %20, %21, %22, %23"
      "}, %24, %25, p, %27, %28, %29, %30;\n}\n"
      : "+f"(d[0]), "+f"(d[1]), "+f"(d[2]), "+f"(d[3]), "+f"(d[4]), "+f"(d[5]), "+f"(d[6]), "+f"(d[7]), "+f"(d[8]),
        "+f"(d[9]), "+f"(d[10]), "+f"(d[11]), "+f"(d[12]), "+f"(d[13]), "+f"(d[14]), "+f"(d[15]), "+f"(d[16]),
        "+f"(d[17]), "+f"(d[18]), "+f"(d[19]), "+f"(d[20]), "+f"(d[21]), "+f"(d[22]), "+f"(d[23])
      : "l"(da), "l"(db), "r"(sd), "n"(SA), "n"(SB), "n"(TA), "n"(TB));
}
template <int SA, int SB, int TA, int TB>
__device__ __forceinline__ void wgmma_ss_128(float (&d)[64], uint64_t da, uint64_t db, int sd) {
  asm volatile("{\n.reg .pred p;\nsetp.ne.b32 p, %66, 0;\n"
      "wgmma.mma_async.sync.aligned.m64n128k16.f32.bf16.bf16 {"
      "%0, %1, %2, %3, %4, %5, %6, %7, %8, %9, %10, %11, %12, %13, %14, %15, %16, %17, %18, %19, %20, %21, %22, %23, "
      "%24, %25, %26, %27, %28, %29, %30, %31, %32, %33, %34, %35, %36, %37, %38, %39, %40, %41, %42, %43, %44, %45, "
      "%46, %47, %48, %49, %50, %51, %52, %53, %54, %55, %56, %57, %58, %59, %60, %61, %62, %63"
      "}, %64, %65, p, %67, %68, %69, %70;\n}\n"
      : "+f"(d[0]), "+f"(d[1]), "+f"(d[2]), "+f"(d[3]), "+f"(d[4]), "+f"(d[5]), "+f"(d[6]), "+f"(d[7]), "+f"(d[8]),
        "+f"(d[9]), "+f"(d[10]), "+f"(d[11]), "+f"(d[12]), "+f"(d[13]), "+f"(d[14]), "+f"(d[15]), "+f"(d[16]),
        "+f"(d[17]), "+f"(d[18]), "+f"(d[19]), "+f"(d[20]), "+f"(d[21]), "+f"(d[22]), "+f"(d[23]), "+f"(d[24]),
        "+f"(d[25]), "+f"(d[26]), "+f"(d[27]), "+f"(d[28]), "+f"(d[29]), "+f"(d[30]), "+f"(d[31]), "+f"(d[32]),
        "+f"(d[33]), "+f"(d[34]), "+f"(d[35]), "+f"(d[36]), "+f"(d[37]), "+f"(d[38]), "+f"(d[39]), "+f"(d[40]),
        "+f"(d[41]), "+f"(d[42]), "+f"(d[43]), "+f"(d[44]), "+f"(d[45]), "+f"(d[46]), "+f"(d[47]), "+f"(d[48]),
        "+f"(d[49]), "+f"(d[50]), "+f"(d[51]), "+f"(d[52]), "+f"(d[53]), "+f"(d[54]), "+f"(d[55]), "+f"(d[56]),
        "+f"(d[57]), "+f"(d[58]), "+f"(d[59]), "+f"(d[60]), "+f"(d[61]), "+f"(d[62]), "+f"(d[63])
      : "l"(da), "l"(db), "r"(sd), "n"(SA), "n"(SB), "n"(TA), "n"(TB));
}
template <int SA, int SB, int TA, int TB>
__device__ __forceinline__ void wgmma_ss_168(float (&d)[84], uint64_t da, uint64_t db, int sd) {
  asm volatile("{\n.reg .pred p;\nsetp.ne.b32 p, %86, 0;\n"
      "wgmma.mma_async.sync.aligned.m64n168k16.f32.bf16.bf16 {"
      "%0, %1, %2, %3, %4, %5, %6, %7, %8, %9, %10, %11, %12, %13, %14, %15, %16, %17, %18, %19, %20, %21, %22, %23, "
      "%24, %25, %26, %27, %28, %29, %30, %31, %32, %33, %34, %35, %36, %37, %38, %39, %40, %41, %42, %43, %44, %45, "
      "%46, %47, %48, %49, %50, %51, %52, %53, %54, %55, %56, %57, %58, %59, %60, %61, %62, %63, %64, %65, %66, %67, "
      "%68, %69, %70, %71, %72, %73, %74, %75, %76, %77, %78, %79, %80, %81, %82, %83"
      "}, %84, %85, p, %87, %88, %89, %90;\n}\n"
      : "+f"(d[0]), "+f"(d[1]), "+f"(d[2]), "+f"(d[3]), "+f"(d[4]), "+f"(d[5]), "+f"(d[6]), "+f"(d[7]), "+f"(d[8]),
        "+f"(d[9]), "+f"(d[10]), "+f"(d[11]), "+f"(d[12]), "+f"(d[13]), "+f"(d[14]), "+f"(d[15]), "+f"(d[16]),
        "+f"(d[17]), "+f"(d[18]), "+f"(d[19]), "+f"(d[20]), "+f"(d[21]), "+f"(d[22]), "+f"(d[23]), "+f"(d[24]),
        "+f"(d[25]), "+f"(d[26]), "+f"(d[27]), "+f"(d[28]), "+f"(d[29]), "+f"(d[30]), "+f"(d[31]), "+f"(d[32]),
        "+f"(d[33]), "+f"(d[34]), "+f"(d[35]), "+f"(d[36]), "+f"(d[37]), "+f"(d[38]), "+f"(d[39]), "+f"(d[40]),
        "+f"(d[41]), "+f"(d[42]), "+f"(d[43]), "+f"(d[44]), "+f"(d[45]), "+f"(d[46]), "+f"(d[47]), "+f"(d[48]),
        "+f"(d[49]), "+f"(d[50]), "+f"(d[51]), "+f"(d[52]), "+f"(d[53]), "+f"(d[54]), "+f"(d[55]), "+f"(d[56]),
        "+f"(d[57]), "+f"(d[58]), "+f"(d[59]), "+f"(d[60]), "+f"(d[61]), "+f"(d[62]), "+f"(d[63]), "+f"(d[64]),
        "+f"(d[65]), "+f"(d[66]), "+f"(d[67]), "+f"(d[68]), "+f"(d[69]), "+f"(d[70]), "+f"(d[71]), "+f"(d[72]),
        "+f"(d[73]), "+f"(d[74]), "+f"(d[75]), "+f"(d[76]), "+f"(d[77]), "+f"(d[78]), "+f"(d[79]), "+f"(d[80]),
        "+f"(d[81]), "+f"(d[82]), "+f"(d[83])
      : "l"(da), "l"(db), "r"(sd), "n"(SA), "n"(SB), "n"(TA), "n"(TB));
}
template <int SA, int SB, int TB>
__device__ __forceinline__ void wgmma_rs_32(float (&d)[16], uint32_t a0, uint32_t a1, uint32_t a2, uint32_t a3, uint64_t db, int sd) {
  asm volatile("{\n.reg .pred p;\nsetp.ne.b32 p, %21, 0;\n"
      "wgmma.mma_async.sync.aligned.m64n32k16.f32.bf16.bf16 {"
      "%0, %1, %2, %3, %4, %5, %6, %7, %8, %9, %10, %11, %12, %13, %14, %15"
      "}, {%16, %17, %18, %19}, %20, p, %22, %23, %24;\n}\n"
      : "+f"(d[0]), "+f"(d[1]), "+f"(d[2]), "+f"(d[3]), "+f"(d[4]), "+f"(d[5]), "+f"(d[6]), "+f"(d[7]), "+f"(d[8]),
        "+f"(d[9]), "+f"(d[10]), "+f"(d[11]), "+f"(d[12]), "+f"(d[13]), "+f"(d[14]), "+f"(d[15])
      : "r"(a0), "r"(a1), "r"(a2), "r"(a3), "l"(db), "r"(sd), "n"(SA), "n"(SB), "n"(TB));
}
template <int SA, int SB, int TB>
__device__ __forceinline__ void wgmma_rs_64(float (&d)[32], uint32_t a0, uint32_t a1, uint32_t a2, uint32_t a3, uint64_t db, int sd) {
  asm volatile("{\n.reg .pred p;\nsetp.ne.b32 p, %37, 0;\n"
      "wgmma.mma_async.sync.aligned.m64n64k16.f32.bf16.bf16 {"
      "%0, %1, %2, %3, %4, %5, %6, %7, %8, %9, %10, %11, %12, %13, %14, %15, %16, %17, %18, %19, %20, %21, %22, %23, "
      "%24, %25, %26, %27, %28, %29, %30, %31"
      "}, {%32, %33, %34, %35}, %36, p, %38, %39, %40;\n}\n"
      : "+f"(d[0]), "+f"(d[1]), "+f"(d[2]), "+f"(d[3]), "+f"(d[4]), "+f"(d[5]), "+f"(d[6]), "+f"(d[7]), "+f"(d[8]),
        "+f"(d[9]), "+f"(d[10]), "+f"(d[11]), "+f"(d[12]), "+f"(d[13]), "+f"(d[14]), "+f"(d[15]), "+f"(d[16]),
        "+f"(d[17]), "+f"(d[18]), "+f"(d[19]), "+f"(d[20]), "+f"(d[21]), "+f"(d[22]), "+f"(d[23]), "+f"(d[24]),
        "+f"(d[25]), "+f"(d[26]), "+f"(d[27]), "+f"(d[28]), "+f"(d[29]), "+f"(d[30]), "+f"(d[31])
      : "r"(a0), "r"(a1), "r"(a2), "r"(a3), "l"(db), "r"(sd), "n"(SA), "n"(SB), "n"(TB));
}
template <int SA, int SB, int TB>
__device__ __forceinline__ void wgmma_rs_128(float (&d)[64], uint32_t a0, uint32_t a1, uint32_t a2, uint32_t a3, uint64_t db, int sd) {
  asm volatile("{\n.reg .pred p;\nsetp.ne.b32 p, %69, 0;\n"
      "wgmma.mma_async.sync.aligned.m64n128k16.f32.bf16.bf16 {"
      "%0, %1, %2, %3, %4, %5, %6, %7, %8, %9, %10, %11, %12, %13, %14, %15, %16, %17, %18, %19, %20, %21, %22, %23, "
      "%24, %25, %26, %27, %28, %29, %30, %31, %32, %33, %34, %35, %36, %37, %38, %39, %40, %41, %42, %43, %44, %45, "
      "%46, %47, %48, %49, %50, %51, %52, %53, %54, %55, %56, %57, %58, %59, %60, %61, %62, %63"
      "}, {%64, %65, %66, %67}, %68, p, %70, %71, %72;\n}\n"
      : "+f"(d[0]), "+f"(d[1]), "+f"(d[2]), "+f"(d[3]), "+f"(d[4]), "+f"(d[5]), "+f"(d[6]), "+f"(d[7]), "+f"(d[8]),
        "+f"(d[9]), "+f"(d[10]), "+f"(d[11]), "+f"(d[12]), "+f"(d[13]), "+f"(d[14]), "+f"(d[15]), "+f"(d[16]),
        "+f"(d[17]), "+f"(d[18]), "+f"(d[19]), "+f"(d[20]), "+f"(d[21]), "+f"(d[22]), "+f"(d[23]), "+f"(d[24]),
        "+f"(d[25]), "+f"(d[26]), "+f"(d[27]), "+f"(d[28]), "+f"(d[29]), "+f"(d[30]), "+f"(d[31]), "+f"(d[32]),
        "+f"(d[33]), "+f"(d[34]), "+f"(d[35]), "+f"(d[36]), "+f"(d[37]), "+f"(d[38]), "+f"(d[39]), "+f"(d[40]),
        "+f"(d[41]), "+f"(d[42]), "+f"(d[43]), "+f"(d[44]), "+f"(d[45]), "+f"(d[46]), "+f"(d[47]), "+f"(d[48]),
        "+f"(d[49]), "+f"(d[50]), "+f"(d[51]), "+f"(d[52]), "+f"(d[53]), "+f"(d[54]), "+f"(d[55]), "+f"(d[56]),
        "+f"(d[57]), "+f"(d[58]), "+f"(d[59]), "+f"(d[60]), "+f"(d[61]), "+f"(d[62]), "+f"(d[63])
      : "r"(a0), "r"(a1), "r"(a2), "r"(a3), "l"(db), "r"(sd), "n"(SA), "n"(SB), "n"(TB));
}
template <int SA, int SB, int TB>
__device__ __forceinline__ void wgmma_rs_168(float (&d)[84], uint32_t a0, uint32_t a1, uint32_t a2, uint32_t a3, uint64_t db, int sd) {
  asm volatile("{\n.reg .pred p;\nsetp.ne.b32 p, %89, 0;\n"
      "wgmma.mma_async.sync.aligned.m64n168k16.f32.bf16.bf16 {"
      "%0, %1, %2, %3, %4, %5, %6, %7, %8, %9, %10, %11, %12, %13, %14, %15, %16, %17, %18, %19, %20, %21, %22, %23, "
      "%24, %25, %26, %27, %28, %29, %30, %31, %32, %33, %34, %35, %36, %37, %38, %39, %40, %41, %42, %43, %44, %45, "
      "%46, %47, %48, %49, %50, %51, %52, %53, %54, %55, %56, %57, %58, %59, %60, %61, %62, %63, %64, %65, %66, %67, "
      "%68, %69, %70, %71, %72, %73, %74, %75, %76, %77, %78, %79, %80, %81, %82, %83"
      "}, {%84, %85, %86, %87}, %88, p, %90, %91, %92;\n}\n"
      : "+f"(d[0]), "+f"(d[1]), "+f"(d[2]), "+f"(d[3]), "+f"(d[4]), "+f"(d[5]), "+f"(d[6]), "+f"(d[7]), "+f"(d[8]),
        "+f"(d[9]), "+f"(d[10]), "+f"(d[11]), "+f"(d[12]), "+f"(d[13]), "+f"(d[14]), "+f"(d[15]), "+f"(d[16]),
        "+f"(d[17]), "+f"(d[18]), "+f"(d[19]), "+f"(d[20]), "+f"(d[21]), "+f"(d[22]), "+f"(d[23]), "+f"(d[24]),
        "+f"(d[25]), "+f"(d[26]), "+f"(d[27]), "+f"(d[28]), "+f"(d[29]), "+f"(d[30]), "+f"(d[31]), "+f"(d[32]),
        "+f"(d[33]), "+f"(d[34]), "+f"(d[35]), "+f"(d[36]), "+f"(d[37]), "+f"(d[38]), "+f"(d[39]), "+f"(d[40]),
        "+f"(d[41]), "+f"(d[42]), "+f"(d[43]), "+f"(d[44]), "+f"(d[45]), "+f"(d[46]), "+f"(d[47]), "+f"(d[48]),
        "+f"(d[49]), "+f"(d[50]), "+f"(d[51]), "+f"(d[52]), "+f"(d[53]), "+f"(d[54]), "+f"(d[55]), "+f"(d[56]),
        "+f"(d[57]), "+f"(d[58]), "+f"(d[59]), "+f"(d[60]), "+f"(d[61]), "+f"(d[62]), "+f"(d[63]), "+f"(d[64]),
        "+f"(d[65]), "+f"(d[66]), "+f"(d[67]), "+f"(d[68]), "+f"(d[69]), "+f"(d[70]), "+f"(d[71]), "+f"(d[72]),
        "+f"(d[73]), "+f"(d[74]), "+f"(d[75]), "+f"(d[76]), "+f"(d[77]), "+f"(d[78]), "+f"(d[79]), "+f"(d[80]),
        "+f"(d[81]), "+f"(d[82]), "+f"(d[83])
      : "r"(a0), "r"(a1), "r"(a2), "r"(a3), "l"(db), "r"(sd), "n"(SA), "n"(SB), "n"(TB));
}
template <int SA, int SB, int TB>
__device__ __forceinline__ void wgmma_rs_256(float (&d)[128], uint32_t a0, uint32_t a1, uint32_t a2, uint32_t a3, uint64_t db, int sd) {
  asm volatile("{\n.reg .pred p;\nsetp.ne.b32 p, %133, 0;\n"
      "wgmma.mma_async.sync.aligned.m64n256k16.f32.bf16.bf16 {"
      "%0, %1, %2, %3, %4, %5, %6, %7, %8, %9, %10, %11, %12, %13, %14, %15, %16, %17, %18, %19, %20, %21, %22, %23, "
      "%24, %25, %26, %27, %28, %29, %30, %31, %32, %33, %34, %35, %36, %37, %38, %39, %40, %41, %42, %43, %44, %45, "
      "%46, %47, %48, %49, %50, %51, %52, %53, %54, %55, %56, %57, %58, %59, %60, %61, %62, %63, %64, %65, %66, %67, "
      "%68, %69, %70, %71, %72, %73, %74, %75, %76, %77, %78, %79, %80, %81, %82, %83, %84, %85, %86, %87, %88, %89, "
      "%90, %91, %92, %93, %94, %95, %96, %97, %98, %99, %100, %101, %102, %103, %104, %105, %106, %107, %108, %109, "
      "%110, %111, %112, %113, %114, %115, %116, %117, %118, %119, %120, %121, %122, %123, %124, %125, %126, %127"
      "}, {%128, %129, %130, %131}, %132, p, %134, %135, %136;\n}\n"
      : "+f"(d[0]), "+f"(d[1]), "+f"(d[2]), "+f"(d[3]), "+f"(d[4]), "+f"(d[5]), "+f"(d[6]), "+f"(d[7]), "+f"(d[8]),
        "+f"(d[9]), "+f"(d[10]), "+f"(d[11]), "+f"(d[12]), "+f"(d[13]), "+f"(d[14]), "+f"(d[15]), "+f"(d[16]),
        "+f"(d[17]), "+f"(d[18]), "+f"(d[19]), "+f"(d[20]), "+f"(d[21]), "+f"(d[22]), "+f"(d[23]), "+f"(d[24]),
        "+f"(d[25]), "+f"(d[26]), "+f"(d[27]), "+f"(d[28]), "+f"(d[29]), "+f"(d[30]), "+f"(d[31]), "+f"(d[32]),
        "+f"(d[33]), "+f"(d[34]), "+f"(d[35]), "+f"(d[36]), "+f"(d[37]), "+f"(d[38]), "+f"(d[39]), "+f"(d[40]),
        "+f"(d[41]), "+f"(d[42]), "+f"(d[43]), "+f"(d[44]), "+f"(d[45]), "+f"(d[46]), "+f"(d[47]), "+f"(d[48]),
        "+f"(d[49]), "+f"(d[50]), "+f"(d[51]), "+f"(d[52]), "+f"(d[53]), "+f"(d[54]), "+f"(d[55]), "+f"(d[56]),
        "+f"(d[57]), "+f"(d[58]), "+f"(d[59]), "+f"(d[60]), "+f"(d[61]), "+f"(d[62]), "+f"(d[63]), "+f"(d[64]),
        "+f"(d[65]), "+f"(d[66]), "+f"(d[67]), "+f"(d[68]), "+f"(d[69]), "+f"(d[70]), "+f"(d[71]), "+f"(d[72]),
        "+f"(d[73]), "+f"(d[74]), "+f"(d[75]), "+f"(d[76]), "+f"(d[77]), "+f"(d[78]), "+f"(d[79]), "+f"(d[80]),
        "+f"(d[81]), "+f"(d[82]), "+f"(d[83]), "+f"(d[84]), "+f"(d[85]), "+f"(d[86]), "+f"(d[87]), "+f"(d[88]),
        "+f"(d[89]), "+f"(d[90]), "+f"(d[91]), "+f"(d[92]), "+f"(d[93]), "+f"(d[94]), "+f"(d[95]), "+f"(d[96]),
        "+f"(d[97]), "+f"(d[98]), "+f"(d[99]), "+f"(d[100]), "+f"(d[101]), "+f"(d[102]), "+f"(d[103]), "+f"(d[104]),
        "+f"(d[105]), "+f"(d[106]), "+f"(d[107]), "+f"(d[108]), "+f"(d[109]), "+f"(d[110]), "+f"(d[111]),
        "+f"(d[112]), "+f"(d[113]), "+f"(d[114]), "+f"(d[115]), "+f"(d[116]), "+f"(d[117]), "+f"(d[118]),
        "+f"(d[119]), "+f"(d[120]), "+f"(d[121]), "+f"(d[122]), "+f"(d[123]), "+f"(d[124]), "+f"(d[125]),
        "+f"(d[126]), "+f"(d[127])
      : "r"(a0), "r"(a1), "r"(a2), "r"(a3), "l"(db), "r"(sd), "n"(SA), "n"(SB), "n"(TB));
}

__device__ const __align__(128) uint32_t c_img[3584] = {
    0x00003c80, 0x00003c80, 0x00003c80, 0x00003c80, 0x00003c80, 0x00003c80, 0x00003c80, 0x00003c80, 0x00003c80, 0x00003c80,
    0x00003c80, 0x00003c80, 0x00003c80, 0x00003c80, 0x00003c80, 0x00003c80, 0x00003c80, 0x00003c80, 0x00003c80, 0x00003c80,
    0x00003c80, 0x00003c80, 0x00003c80, 0x00003c80, 0x00003c80, 0x00003c80, 0x00003c80, 0x00003c80, 0x00003c80, 0x00003c80,
    0x00003c80, 0x00003c80, 0x3c463c22, 0x3c623bf1, 0x3c753b95, 0x3c7f3ac9, 0x3ac93c7f, 0x3b953c75, 0x3bf13c62, 0x3c223c46,
    0x3c22bc46, 0x3bf1bc62, 0x3b95bc75, 0x3ac9bc7f, 0x3c7fbac9, 0x3c75bb95, 0x3c62bbf1, 0x3c46bc22, 0xbc46bc22, 0xbc62bbf1,
    0xbc75bb95, 0xbc7fbac9, 0xbac9bc7f, 0xbb95bc75, 0xbbf1bc62, 0xbc22bc46, 0xbc223c46, 0xbbf13c62, 0xbb953c75, 0xbac93c7f,
    0xbc7f3ac9, 0xbc753b95, 0xbc623bf1, 0xbc463c22, 0xbb48bc7b, 0xbc0ebc55, 0xbc55bc0e, 0xbc7bbb48, 0xbc7b3b48, 0xbc553c0e,
    0xbc0e3c55, 0xbb483c7b, 0x3b483c7b, 0x3c0e3c55, 0x3c553c0e, 0x3c7b3b48, 0x3c7bbb48, 0x3c55bc0e, 0x3c0ebc55, 0x3b48bc7b,
    0xbb48bc7b, 0xbc0ebc55, 0xbc55bc0e, 0xbc7bbb48, 0xbc7b3b48, 0xbc553c0e, 0xbc0e3c55, 0xbb483c7b, 0x3b483c7b, 0x3c0e3c55,
    0x3c553c0e, 0x3c7b3b48, 0x3c7bbb48, 0x3c55bc0e, 0x3c0ebc55, 0x3b48bc7b, 0x3c623bf1, 0x3c7fbac9, 0x3c46bc22, 0x3b95bc75,
    0xbc753b95, 0xbc223c46, 0xbac93c7f, 0x3bf13c62, 0x3bf1bc62, 0xbac9bc7f, 0xbc22bc46, 0xbc75bb95, 0x3b953c75, 0x3c463c22,
    0x3c7f3ac9, 0x3c62bbf1, 0xbc62bbf1, 0xbc7f3ac9, 0xbc463c22, 0xbb953c75, 0x3c75bb95, 0x3c22bc46, 0x3ac9bc7f, 0xbbf1bc62,
    0xbbf13c62, 0x3ac93c7f, 0x3c223c46, 0x3c753b95, 0xbb95bc75, 0xbc46bc22, 0xbc7fbac9, 0xbc623bf1, 0x3bc43c6d, 0x3c6d3bc4,
    0x3c6dbbc4, 0x3bc4bc6d, 0xbbc4bc6d, 0xbc6dbbc4, 0xbc6d3bc4, 0xbbc43c6d, 0x3bc43c6d, 0x3c6d3bc4, 0x3c6dbbc4, 0x3bc4bc6d,
    0xbbc4bc6d, 0xbc6dbbc4, 0xbc6d3bc4, 0xbbc43c6d, 0x3bc43c6d, 0x3c6d3bc4, 0x3c6dbbc4, 0x3bc4bc6d, 0xbbc4bc6d, 0xbc6dbbc4,
    0xbc6d3bc4, 0xbbc43c6d, 0x3bc43c6d, 0x3c6d3bc4, 0x3c6dbbc4, 0x3bc4bc6d, 0xbbc4bc6d, 0xbc6dbbc4, 0xbc6d3bc4, 0xbbc43c6d,
    0x3c753b95, 0x3c46bc22, 0xbac9bc7f, 0xbc62bbf1, 0xbbf1bc62, 0xbc7fbac9, 0xbc223c46, 0x3b953c75, 0x3b95bc75, 0xbc22bc46,
    0xbc7f3ac9, 0xbbf13c62, 0xbc623bf1, 0xbac93c7f, 0x3c463c22, 0x3c75bb95, 0xbc75bb95, 0xbc463c22, 0x3ac93c7f, 0x3c623bf1,
    0x3bf13c62, 0x3c7f3ac9, 0x3c22bc46, 0xbb95bc75, 0xbb953c75, 0x3c223c46, 0x3c7fbac9, 0x3bf1bc62, 0x3c62bbf1, 0x3ac9bc7f,
    0xbc46bc22, 0xbc753b95, 0xbc0ebc55, 0xbc7b3b48, 0xbb483c7b, 0x3c553c0e, 0x3c55bc0e, 0xbb48bc7b, 0xbc7bbb48, 0xbc0e3c55,
    0x3c0e3c55, 0x3c7bbb48, 0x3b48bc7b, 0xbc55bc0e, 0xbc553c0e, 0x3b483c7b, 0x3c7b3b48, 0x3c0ebc55, 0xbc0ebc55, 0xbc7b3b48,
    0xbb483c7b, 0x3c553c0e, 0x3c55bc0e, 0xbb48bc7b, 0xbc7bbb48, 0xbc0e3c55, 0x3c0e3c55, 0x3c7bbb48, 0x3b48bc7b, 0xbc55bc0e,
    0xbc553c0e, 0x3b483c7b, 0x3c7b3b48, 0x3c0ebc55, 0x3c7f3ac9, 0x3b95bc75, 0xbc62bbf1, 0xbc223c46, 0x3c46bc22, 0xbbf1bc62,
    0xbc753b95, 0x3ac93c7f, 0x3ac9bc7f, 0xbc75bb95, 0xbbf13c62, 0x3c463c22, 0xbc22bc46, 0xbc623bf1, 0x3b953c75, 0x3c7fbac9,
    0xbc7fbac9, 0xbb953c75, 0x3c623bf1, 0x3c22bc46, 0xbc463c22, 0x3bf13c62, 0x3c75bb95, 0xbac9bc7f, 0xbac93c7f, 0x3c753b95,
    0x3bf1bc62, 0xbc46bc22, 0x3c223c46, 0x3c62bbf1, 0xbb95bc75, 0xbc7f3ac9, 0x3a493c80, 0x3b163c7d, 0x3b793c78, 0x3bac3c71,
    0x3bdb3c67, 0x3c043c5c, 0x3c183c4e, 0x3c2c3c3e, 0x3c3e3c2c, 0x3c4e3c18, 0x3c5c3c04, 0x3c673bdb, 0x3c713bac, 0x3c783b79,
    0x3c7d3b16, 0x3c803a49, 0x3c80ba49, 0x3c7dbb16, 0x3c78bb79, 0x3c71bbac, 0x3c67bbdb, 0x3c5cbc04, 0x3c4ebc18, 0x3c3ebc2c,
    0x3c2cbc3e, 0x3c18bc4e, 0x3c04bc5c, 0x3bdbbc67, 0x3bacbc71, 0x3b79bc78, 0x3b16bc7d, 0x3a49bc80, 0x3c783b79, 0x3c80ba49,
    0x3c71bbac, 0x3c4ebc18, 0x3b163c7d, 0x3bdb3c67, 0x3c2c3c3e, 0x3c5c3c04, 0xbc04bc5c, 0xbc3ebc2c, 0xbc67bbdb, 0xbc7dbb16,
    0x3c18bc4e, 0x3bacbc71, 0x3a49bc80, 0xbb79bc78, 0xbb793c78, 0x3a493c80, 0x3bac3c71, 0x3c183c4e, 0xbc7d3b16, 0xbc673bdb,
    0xbc3e3c2c, 0xbc043c5c, 0x3c5cbc04, 0x3c2cbc3e, 0x3bdbbc67, 0x3b16bc7d, 0x3c4e3c18, 0x3c713bac, 0x3c803a49, 0x3c78bb79,
    0xbc5cbc04, 0xbc80ba49, 0xbc673bdb, 0xbc183c4e, 0xbb163c7d, 0x3bac3c71, 0x3c3e3c2c, 0x3c783b79, 0x3b793c78, 0x3c2c3c3e,
    0x3c713bac, 0x3c7dbb16, 0x3c4ebc18, 0x3bdbbc67, 0xba49bc80, 0xbc04bc5c, 0xbc043c5c, 0xba493c80, 0x3bdb3c67, 0x3c4e3c18,
    0x3c7d3b16, 0x3c71bbac, 0x3c2cbc3e, 0x3b79bc78, 0x3c78bb79, 0x3c3ebc2c, 0x3bacbc71, 0xbb16bc7d, 0xbc18bc4e, 0xbc67bbdb,
    0xbc803a49, 0xbc5c3c04, 0x3c3ebc2c, 0x3b16bc7d, 0xbc04bc5c, 0xbc71bbac, 0xbbdb3c67, 0x3b793c78, 0x3c4e3c18, 0x3c80ba49,
    0x3a49bc80, 0xbc18bc4e, 0xbc78bb79, 0xbc673bdb, 0x3bac3c71, 0x3c5c3c04, 0x3c7dbb16, 0x3c2cbc3e, 0x3c2c3c3e, 0x3c7d3b16,
    0x3c5cbc04, 0x3bacbc71, 0xbc67bbdb, 0xbc783b79, 0xbc183c4e, 0x3a493c80, 0x3c803a49, 0x3c4ebc18, 0x3b79bc78, 0xbbdbbc67,
    0xbc713bac, 0xbc043c5c, 0x3b163c7d, 0x3c3e3c2c, 0x3c67bbdb, 0x3b79bc78, 0xbc18bc4e, 0xbc80ba49, 0xbc2c3c3e, 0x3b163c7d,
    0x3c5c3c04, 0x3c71bbac, 0x3bacbc71, 0xbc04bc5c, 0xbc7dbb16, 0xbc3e3c2c, 0x3a493c80, 0x3c4e3c18, 0x3c78bb79, 0x3bdbbc67,
    0x3bdb3c67, 0x3c783b79, 0x3c4ebc18, 0x3a49bc80, 0xbc3ebc2c, 0xbc7d3b16, 0xbc043c5c, 0x3bac3c71, 0x3c713bac, 0x3c5cbc04,
    0x3b16bc7d, 0xbc2cbc3e, 0xbc803a49, 0xbc183c4e, 0x3b793c78, 0x3c673bdb, 0xbb16bc7d, 0xbc71bbac, 0xbc3e3c2c, 0x3b793c78,
    0xbc5c3c04, 0x3a493c80, 0x3c673bdb, 0x3c4ebc18, 0xbc183c4e, 0x3bdb3c67, 0x3c803a49, 0x3c04bc5c, 0x3c783b79, 0x3c2cbc3e,
    0xbbacbc71, 0xbc7dbb16, 0xbc7d3b16, 0xbbac3c71, 0x3c2c3c3e, 0x3c78bb79, 0x3c043c5c, 0x3c80ba49, 0x3bdbbc67, 0xbc18bc4e,
    0x3c4e3c18, 0x3c67bbdb, 0x3a49bc80, 0xbc5cbc04, 0x3b79bc78, 0xbc3ebc2c, 0xbc713bac, 0xbb163c7d, 0xbb163c7d, 0x3c673bdb,
    0x3c2cbc3e, 0xbc04bc5c, 0xbc783b79, 0xba493c80, 0x3c713bac, 0x3c18bc4e, 0x3c4ebc18, 0xbbacbc71, 0xbc803a49, 0xbb793c78,
    0x3c5c3c04, 0x3c3ebc2c, 0xbbdbbc67, 0xbc7d3b16, 0xbc7dbb16, 0xbbdb3c67, 0x3c3e3c2c, 0x3c5cbc04, 0xbb79bc78, 0xbc80ba49,
    0xbbac3c71, 0x3c4e3c18, 0x3c183c4e, 0x3c71bbac, 0xba49bc80, 0xbc78bb79, 0xbc043c5c, 0x3c2c3c3e, 0x3c67bbdb, 0xbb16bc7d,
    0xbc67bbdb, 0xbc043c5c, 0x3c4e3c18, 0x3c2cbc3e, 0xbc80ba49, 0xbb163c7d, 0x3c783b79, 0x3bacbc71, 0xbc713bac, 0x3b793c78,
    0x3c7dbb16, 0xba49bc80, 0xbc3e3c2c, 0x3c183c4e, 0x3c5cbc04, 0xbbdbbc67, 0xbbdb3c67, 0x3c5c3c04, 0x3c18bc4e, 0xbc3ebc2c,
    0xba493c80, 0x3c7d3b16, 0x3b79bc78, 0xbc71bbac, 0x3bac3c71, 0x3c78bb79, 0xbb16bc7d, 0xbc803a49, 0x3c2c3c3e, 0x3c4ebc18,
    0xbc04bc5c, 0xbc673bdb, 0x3c353c35, 0x3c35bc35, 0xbc35bc35, 0xbc353c35, 0x3c353c35, 0x3c35bc35, 0xbc35bc35, 0xbc353c35,
    0x3c353c35, 0x3c35bc35, 0xbc35bc35, 0xbc353c35, 0x3c353c35, 0x3c35bc35, 0xbc35bc35, 0xbc353c35, 0x3c353c35, 0x3c35bc35,
    0xbc35bc35, 0xbc353c35, 0x3c353c35, 0x3c35bc35, 0xbc35bc35, 0xbc353c35, 0x3c353c35, 0x3c35bc35, 0xbc35bc35, 0xbc353c35,
    0x3c353c35, 0x3c35bc35, 0xbc35bc35, 0xbc353c35, 0x3c7fbac9, 0xbb95bc75, 0xbc623bf1, 0x3c223c46, 0x3c463c22, 0x3bf1bc62,
    0xbc75bb95, 0xbac93c7f, 0xbac9bc7f, 0xbc753b95, 0x3bf13c62, 0x3c46bc22, 0x3c22bc46, 0xbc62bbf1, 0xbb953c75, 0x3c7f3ac9,
    0xbc7f3ac9, 0x3b953c75, 0x3c62bbf1, 0xbc22bc46, 0xbc46bc22, 0xbbf13c62, 0x3c753b95, 0x3ac9bc7f, 0x3ac93c7f, 0x3c75bb95,
    0xbbf1bc62, 0xbc463c22, 0xbc223c46, 0x3c623bf1, 0x3b95bc75, 0xbc7fbac9, 0xbc55bc0e, 0xbb483c7b, 0x3c7bbb48, 0xbc0ebc55,
    0xbc0e3c55, 0x3c7b3b48, 0xbb48bc7b, 0xbc553c0e, 0x3c553c0e, 0x3b48bc7b, 0xbc7b3b48, 0x3c0e3c55, 0x3c0ebc55, 0xbc7bbb48,
    0x3b483c7b, 0x3c55bc0e, 0xbc55bc0e, 0xbb483c7b, 0x3c7bbb48, 0xbc0ebc55, 0xbc0e3c55, 0x3c7b3b48, 0xbb48bc7b, 0xbc553c0e,
    0x3c553c0e, 0x3b48bc7b, 0xbc7b3b48, 0x3c0e3c55, 0x3c0ebc55, 0xbc7bbb48, 0x3b483c7b, 0x3c55bc0e, 0x3c75bb95, 0xbc46bc22,
    0xbac93c7f, 0x3c62bbf1, 0xbbf13c62, 0x3c7fbac9, 0xbc22bc46, 0xbb953c75, 0xbb95bc75, 0xbc223c46, 0x3c7f3ac9, 0xbbf1bc62,
    0x3c623bf1, 0xbac9bc7f, 0xbc463c22, 0x3c753b95, 0xbc753b95, 0x3c463c22, 0x3ac9bc7f, 0xbc623bf1, 0x3bf1bc62, 0xbc7f3ac9,
    0x3c223c46, 0x3b95bc75, 0x3b953c75, 0x3c22bc46, 0xbc7fbac9, 0x3bf13c62, 0xbc62bbf1, 0x3ac93c7f, 0x3c46bc22, 0xbc75bb95,
    0x3c6d3bc4, 0xbbc4bc6d, 0xbbc43c6d, 0x3c6dbbc4, 0xbc6dbbc4, 0x3bc43c6d, 0x3bc4bc6d, 0xbc6d3bc4, 0x3c6d3bc4, 0xbbc4bc6d,
    0xbbc43c6d, 0x3c6dbbc4, 0xbc6dbbc4, 0x3bc43c6d, 0x3bc4bc6d, 0xbc6d3bc4, 0x3c6d3bc4, 0xbbc4bc6d, 0xbbc43c6d, 0x3c6dbbc4,
    0xbc6dbbc4, 0x3bc43c6d, 0x3bc4bc6d, 0xbc6d3bc4, 0x3c6d3bc4, 0xbbc4bc6d, 0xbbc43c6d, 0x3c6dbbc4, 0xbc6dbbc4, 0x3bc43c6d,
    0x3bc4bc6d, 0xbc6d3bc4, 0x3c62bbf1, 0xbc7fbac9, 0x3c463c22, 0xbb95bc75, 0xbc75bb95, 0x3c223c46, 0xbac9bc7f, 0xbbf13c62,
    0xbbf1bc62, 0xbac93c7f, 0x3c22bc46, 0xbc753b95, 0xbb953c75, 0x3c46bc22, 0xbc7f3ac9, 0x3c623bf1, 0xbc623bf1, 0x3c7f3ac9,
    0xbc46bc22, 0x3b953c75, 0x3c753b95, 0xbc22bc46, 0x3ac93c7f, 0x3bf1bc62, 0x3bf13c62, 0x3ac9bc7f, 0xbc223c46, 0x3c75bb95,
    0x3b95bc75, 0xbc463c22, 0x3c7fbac9, 0xbc62bbf1, 0xbc7bbb48, 0x3c553c0e, 0xbc0ebc55, 0x3b483c7b, 0x3b48bc7b, 0xbc0e3c55,
    0x3c55bc0e, 0xbc7b3b48, 0x3c7b3b48, 0xbc55bc0e, 0x3c0e3c55, 0xbb48bc7b, 0xbb483c7b, 0x3c0ebc55, 0xbc553c0e, 0x3c7bbb48,
    0xbc7bbb48, 0x3c553c0e, 0xbc0ebc55, 0x3b483c7b, 0x3b48bc7b, 0xbc0e3c55, 0x3c55bc0e, 0xbc7b3b48, 0x3c7b3b48, 0xbc55bc0e,
    0x3c0e3c55, 0xbb48bc7b, 0xbb483c7b, 0x3c0ebc55, 0xbc553c0e, 0x3c7bbb48, 0x3c46bc22, 0xbc623bf1, 0x3c75bb95, 0xbc7f3ac9,
    0x3ac9bc7f, 0xbb953c75, 0x3bf1bc62, 0xbc223c46, 0xbc22bc46, 0x3bf13c62, 0xbb95bc75, 0x3ac93c7f, 0xbc7fbac9, 0x3c753b95,
    0xbc62bbf1, 0x3c463c22, 0xbc463c22, 0x3c62bbf1, 0xbc753b95, 0x3c7fbac9, 0xbac93c7f, 0x3b95bc75, 0xbbf13c62, 0x3c22bc46,
    0x3c223c46, 0xbbf1bc62, 0x3b953c75, 0xbac9bc7f, 0x3c7f3ac9, 0xbc75bb95, 0x3c623bf1, 0xbc46bc22, 0x3c3e3c2c, 0x3c18bc4e,
    0xbc5cbc04, 0xbbdb3c67, 0x3c713bac, 0x3b79bc78, 0xbc7dbb16, 0xba493c80, 0x3c80ba49, 0xbb16bc7d, 0xbc783b79, 0x3bac3c71,
    0x3c67bbdb, 0xbc04bc5c, 0xbc4e3c18, 0x3c2c3c3e, 0x3c2cbc3e, 0xbc4ebc18, 0xbc043c5c, 0x3c673bdb, 0x3bacbc71, 0xbc78bb79,
    0xbb163c7d, 0x3c803a49, 0xba49bc80, 0xbc7d3b16, 0x3b793c78, 0x3c71bbac, 0xbbdbbc67, 0xbc5c3c04, 0x3c183c4e, 0x3c3ebc2c,
    0x3c5cbc04, 0xbc3ebc2c, 0xbbdb3c67, 0x3c7d3b16, 0x3c4e3c18, 0x3bacbc71, 0xbc80ba49, 0x3b793c78, 0xbc78bb79, 0x3a493c80,
    0x3c71bbac, 0xbc18bc4e, 0xbb16bc7d, 0xbc673bdb, 0x3c2c3c3e, 0x3c04bc5c, 0x3c043c5c, 0x3c2cbc3e, 0xbc67bbdb, 0xbb163c7d,
    0xbc183c4e, 0x3c713bac, 0x3a49bc80, 0xbc783b79, 0x3b79bc78, 0xbc803a49, 0x3bac3c71, 0x3c4ebc18, 0x3c7dbb16, 0xbbdbbc67,
    0xbc3e3c2c, 0x3c5c3c04, 0xbc783b79, 0x3c2c3c3e, 0x3bacbc71, 0xbc7d3b16, 0x3c183c4e, 0x3bdbbc67, 0xbc803a49, 0x3c043c5c,
    0x3c5c3c04, 0x3a49bc80, 0xbc673bdb, 0x3c4e3c18, 0x3b16bc7d, 0xbc713bac, 0x3c3e3c2c, 0x3b79bc78, 0x3b793c78, 0x3c3ebc2c,
    0xbc71bbac, 0x3b163c7d, 0x3c4ebc18, 0xbc67bbdb, 0x3a493c80, 0x3c5cbc04, 0x3c04bc5c, 0xbc80ba49, 0x3bdb3c67, 0x3c18bc4e,
    0xbc7dbb16, 0x3bac3c71, 0x3c2cbc3e, 0xbc78bb79, 0x3a49bc80, 0xbc4e3c18, 0x3c783b79, 0xbbdbbc67, 0x3bac3c71, 0x3c04bc5c,
    0xbc7d3b16, 0x3c3e3c2c, 0xbc2cbc3e, 0xbb163c7d, 0x3c5cbc04, 0xbc71bbac, 0x3c673bdb, 0xbb79bc78, 0xbc183c4e, 0x3c80ba49,
    0x3c803a49, 0xbc18bc4e, 0xbb793c78, 0x3c67bbdb, 0xbc713bac, 0x3c5c3c04, 0xbb16bc7d, 0xbc2c3c3e, 0x3c3ebc2c, 0xbc7dbb16,
    0x3c043c5c, 0x3bacbc71, 0xbbdb3c67, 0x3c78bb79, 0xbc4ebc18, 0x3a493c80, 0x3bacbc71, 0xbc5c3c04, 0x3c7d3b16, 0xbc2cbc3e,
    0x3a493c80, 0x3c18bc4e, 0xbc783b79, 0x3c673bdb, 0xbbdbbc67, 0xbb793c78, 0x3c4ebc18, 0xbc80ba49, 0x3c3e3c2c, 0xbb16bc7d,
    0xbc043c5c, 0x3c71bbac, 0x3c713bac, 0xbc04bc5c, 0xbb163c7d, 0x3c3ebc2c, 0xbc803a49, 0x3c4e3c18, 0xbb79bc78, 0xbbdb3c67,
    0x3c67bbdb, 0xbc78bb79, 0x3c183c4e, 0x3a49bc80, 0xbc2c3c3e, 0x3c7dbb16, 0xbc5cbc04, 0x3bac3c71, 0xbc4ebc18, 0x3bdb3c67,
    0x3a49bc80, 0xbc043c5c, 0xbb793c78, 0x3c2cbc3e, 0xbc713bac, 0x3c7d3b16, 0x3b163c7d, 0x3bacbc71, 0xbc3e3c2c, 0x3c78bb79,
    0x3c5cbc04, 0xbc803a49, 0x3c673bdb, 0xbc18bc4e, 0xbc183c4e, 0x3c67bbdb, 0xbc80ba49, 0x3c5c3c04, 0x3c783b79, 0xbc3ebc2c,
    0x3bac3c71, 0x3b16bc7d, 0x3c7dbb16, 0xbc71bbac, 0x3c2c3c3e, 0xbb79bc78, 0xbc04bc5c, 0x3a493c80, 0x3bdbbc67, 0xbc4e3c18,
    0x3c183c4e, 0xbbacbc71, 0x3a493c80, 0x3b79bc78, 0xbc043c5c, 0x3c3ebc2c, 0xbc673bdb, 0x3c7dbb16, 0x3b16bc7d, 0xbbdb3c67,
    0x3c2cbc3e, 0xbc5c3c04, 0x3c78bb79, 0xbc80ba49, 0x3c713bac, 0xbc4ebc18, 0xbc4e3c18, 0x3c71bbac, 0xbc803a49, 0x3c783b79,
    0xbc5cbc04, 0x3c2c3c3e, 0xbbdbbc67, 0x3b163c7d, 0x3c7d3b16, 0xbc67bbdb, 0x3c3e3c2c, 0xbc04bc5c, 0x3b793c78, 0x3a49bc80,
    0xbbac3c71, 0x3c18bc4e, 0xbc713bac, 0x3c78bb79, 0xbc7d3b16, 0x3c80ba49, 0xbc3e3c2c, 0x3c4ebc18, 0xbc5c3c04, 0x3c67bbdb,
    0xbbdb3c67, 0x3c04bc5c, 0xbc183c4e, 0x3c2cbc3e, 0xba493c80, 0x3b16bc7d, 0xbb793c78, 0x3bacbc71, 0x3bac3c71, 0xbb79bc78,
    0x3b163c7d, 0xba49bc80, 0x3c2c3c3e, 0xbc18bc4e, 0x3c043c5c, 0xbbdbbc67, 0x3c673bdb, 0xbc5cbc04, 0x3c4e3c18, 0xbc3ebc2c,
    0x3c803a49, 0xbc7dbb16, 0x3c783b79, 0xbc71bbac, 0x3c800000, 0xbc800000, 0x3c800000, 0xbc800000, 0x3c800000, 0xbc800000,
    0x3c800000, 0xbc800000, 0x3c800000, 0xbc800000, 0x3c800000, 0xbc800000, 0x3c800000, 0xbc800000, 0x3c800000, 0xbc800000,
    0x3c800000, 0xbc800000, 0x3c800000, 0xbc800000, 0x3c800000, 0xbc800000, 0x3c800000, 0xbc800000, 0x3c800000, 0xbc800000,
    0x3c800000, 0xbc800000, 0x3c800000, 0xbc800000, 0x3c800000, 0xbc800000, 0x3c22bc46, 0xbbf13c62, 0x3b95bc75, 0xbac93c7f,
    0x3c7fbac9, 0xbc753b95, 0x3c62bbf1, 0xbc463c22, 0xbc46bc22, 0x3c623bf1, 0xbc75bb95, 0x3c7f3ac9, 0xbac9bc7f, 0x3b953c75,
    0xbbf1bc62, 0x3c223c46, 0xbc223c46, 0x3bf1bc62, 0xbb953c75, 0x3ac9bc7f, 0xbc7f3ac9, 0x3c75bb95, 0xbc623bf1, 0x3c46bc22,
    0x3c463c22, 0xbc62bbf1, 0x3c753b95, 0xbc7fbac9, 0x3ac93c7f, 0xbb95bc75, 0x3bf13c62, 0xbc22bc46, 0xbc7b3b48, 0x3c55bc0e,
    0xbc0e3c55, 0x3b48bc7b, 0x3b483c7b, 0xbc0ebc55, 0x3c553c0e, 0xbc7bbb48, 0x3c7bbb48, 0xbc553c0e, 0x3c0ebc55, 0xbb483c7b,
    0xbb48bc7b, 0x3c0e3c55, 0xbc55bc0e, 0x3c7b3b48, 0xbc7b3b48, 0x3c55bc0e, 0xbc0e3c55, 0x3b48bc7b, 0x3b483c7b, 0xbc0ebc55,
    0x3c553c0e, 0xbc7bbb48, 0x3c7bbb48, 0xbc553c0e, 0x3c0ebc55, 0xbb483c7b, 0xbb48bc7b, 0x3c0e3c55, 0xbc55bc0e, 0x3c7b3b48,
    0x3bf1bc62, 0x3ac93c7f, 0xbc22bc46, 0x3c753b95, 0x3b953c75, 0xbc46bc22, 0x3c7f3ac9, 0xbc623bf1, 0xbc62bbf1, 0x3c7fbac9,
    0xbc463c22, 0x3b95bc75, 0x3c75bb95, 0xbc223c46, 0x3ac9bc7f, 0x3bf13c62, 0xbbf13c62, 0xbac9bc7f, 0x3c223c46, 0xbc75bb95,
    0xbb95bc75, 0x3c463c22, 0xbc7fbac9, 0x3c62bbf1, 0x3c623bf1, 0xbc7f3ac9, 0x3c46bc22, 0xbb953c75, 0xbc753b95, 0x3c22bc46,
    0xbac93c7f, 0xbbf1bc62, 0x3c6dbbc4, 0xbbc43c6d, 0xbbc4bc6d, 0x3c6d3bc4, 0xbc6d3bc4, 0x3bc4bc6d, 0x3bc43c6d, 0xbc6dbbc4,
    0x3c6dbbc4, 0xbbc43c6d, 0xbbc4bc6d, 0x3c6d3bc4, 0xbc6d3bc4, 0x3bc4bc6d, 0x3bc43c6d, 0xbc6dbbc4, 0x3c6dbbc4, 0xbbc43c6d,
    0xbbc4bc6d, 0x3c6d3bc4, 0xbc6d3bc4, 0x3bc4bc6d, 0x3bc43c6d, 0xbc6dbbc4, 0x3c6dbbc4, 0xbbc43c6d, 0xbbc4bc6d, 0x3c6d3bc4,
    0xbc6d3bc4, 0x3bc4bc6d, 0x3bc43c6d, 0xbc6dbbc4, 0x3b95bc75, 0x3c223c46, 0xbc7f3ac9, 0x3bf1bc62, 0xbc623bf1, 0x3ac9bc7f,
    0x3c463c22, 0xbc753b95, 0xbc75bb95, 0x3c46bc22, 0x3ac93c7f, 0xbc62bbf1, 0x3bf13c62, 0xbc7fbac9, 0x3c22bc46, 0x3b953c75,
    0xbb953c75, 0xbc22bc46, 0x3c7fbac9, 0xbbf13c62, 0x3c62bbf1, 0xbac93c7f, 0xbc46bc22, 0x3c75bb95, 0x3c753b95, 0xbc463c22,
    0xbac9bc7f, 0x3c623bf1, 0xbbf1bc62, 0x3c7f3ac9, 0xbc223c46, 0xbb95bc75, 0xbc553c0e, 0xbb48bc7b, 0x3c7b3b48, 0xbc0e3c55,
    0xbc0ebc55, 0x3c7bbb48, 0xbb483c7b, 0xbc55bc0e, 0x3c55bc0e, 0x3b483c7b, 0xbc7bbb48, 0x3c0ebc55, 0x3c0e3c55, 0xbc7b3b48,
    0x3b48bc7b, 0x3c553c0e, 0xbc553c0e, 0xbb48bc7b, 0x3c7b3b48, 0xbc0e3c55, 0xbc0ebc55, 0x3c7bbb48, 0xbb483c7b, 0xbc55bc0e,
    0x3c55bc0e, 0x3b483c7b, 0xbc7bbb48, 0x3c0ebc55, 0x3c0e3c55, 0xbc7b3b48, 0x3b48bc7b, 0x3c553c0e, 0x3ac9bc7f, 0x3c753b95,
    0xbbf13c62, 0xbc46bc22, 0xbc22bc46, 0x3c62bbf1, 0x3b953c75, 0xbc7f3ac9, 0xbc7fbac9, 0x3b95bc75, 0x3c623bf1, 0xbc223c46,
    0xbc463c22, 0xbbf1bc62, 0x3c75bb95, 0x3ac93c7f, 0xbac93c7f, 0xbc75bb95, 0x3bf1bc62, 0x3c463c22, 0x3c223c46, 0xbc623bf1,
    0xbb95bc75, 0x3c7fbac9, 0x3c7f3ac9, 0xbb953c75, 0xbc62bbf1, 0x3c22bc46, 0x3c46bc22, 0x3bf13c62, 0xbc753b95, 0xbac9bc7f,
    0x3c80ba49, 0xbc7d3b16, 0x3c78bb79, 0xbc713bac, 0x3c67bbdb, 0xbc5c3c04, 0x3c4ebc18, 0xbc3e3c2c, 0x3c2cbc3e, 0xbc183c4e,
    0x3c04bc5c, 0xbbdb3c67, 0x3bacbc71, 0xbb793c78, 0x3b16bc7d, 0xba493c80, 0xba49bc80, 0x3b163c7d, 0xbb79bc78, 0x3bac3c71,
    0xbbdbbc67, 0x3c043c5c, 0xbc18bc4e, 0x3c2c3c3e, 0xbc3ebc2c, 0x3c4e3c18, 0xbc5cbc04, 0x3c673bdb, 0xbc71bbac, 0x3c783b79,
    0xbc7dbb16, 0x3c803a49, 0x3b79bc78, 0x3a493c80, 0xbbacbc71, 0x3c183c4e, 0x3c7dbb16, 0xbc673bdb, 0x3c3ebc2c, 0xbc043c5c,
    0xbc5c3c04, 0x3c2cbc3e, 0xbbdb3c67, 0x3b16bc7d, 0xbc4ebc18, 0x3c713bac, 0xbc80ba49, 0x3c78bb79, 0x3c783b79, 0xbc803a49,
    0x3c71bbac, 0xbc4e3c18, 0x3b163c7d, 0xbbdbbc67, 0x3c2c3c3e, 0xbc5cbc04, 0xbc04bc5c, 0x3c3e3c2c, 0xbc67bbdb, 0x3c7d3b16,
    0x3c18bc4e, 0xbbac3c71, 0x3a49bc80, 0x3b793c78, 0xbc043c5c, 0x3a49bc80, 0x3bdb3c67, 0xbc4ebc18, 0x3c7d3b16, 0xbc713bac,
    0x3c2cbc3e, 0xbb793c78, 0x3c78bb79, 0xbc3e3c2c, 0x3bacbc71, 0x3b163c7d, 0xbc18bc4e, 0x3c673bdb, 0xbc803a49, 0x3c5cbc04,
    0x3c5c3c04, 0xbc80ba49, 0x3c67bbdb, 0xbc183c4e, 0x3b16bc7d, 0x3bac3c71, 0xbc3ebc2c, 0x3c783b79, 0xbb79bc78, 0x3c2c3c3e,
    0xbc71bbac, 0x3c7dbb16, 0xbc4e3c18, 0x3bdbbc67, 0x3a493c80, 0xbc04bc5c, 0xbc2cbc3e, 0x3c7d3b16, 0xbc5c3c04, 0x3bacbc71,
    0x3c673bdb, 0xbc783b79, 0x3c18bc4e, 0x3a493c80, 0xbc80ba49, 0x3c4ebc18, 0xbb793c78, 0xbbdbbc67, 0x3c71bbac, 0xbc043c5c,
    0xbb16bc7d, 0x3c3e3c2c, 0x3c3ebc2c, 0xbb163c7d, 0xbc04bc5c, 0x3c713bac, 0xbbdb3c67, 0xbb79bc78, 0x3c4e3c18, 0xbc803a49,
    0x3a49bc80, 0x3c183c4e, 0xbc78bb79, 0x3c67bbdb, 0x3bac3c71, 0xbc5cbc04, 0x3c7dbb16, 0xbc2c3c3e, 0xbbdbbc67, 0x3c783b79,
    0xbc4e3c18, 0x3a49bc80, 0x3c3e3c2c, 0xbc7d3b16, 0x3c04bc5c, 0x3bac3c71, 0xbc71bbac, 0x3c5cbc04, 0xbb163c7d, 0xbc2cbc3e,
    0x3c80ba49, 0xbc183c4e, 0xbb79bc78, 0x3c673bdb, 0x3c67bbdb, 0xbb793c78, 0xbc18bc4e, 0x3c803a49, 0xbc2c3c3e, 0xbb16bc7d,
    0x3c5c3c04, 0xbc713bac, 0x3bacbc71, 0x3c043c5c, 0xbc7dbb16, 0x3c3ebc2c, 0x3a493c80, 0xbc4ebc18, 0x3c78bb79, 0xbbdb3c67,
    0xbc7d3b16, 0x3bacbc71, 0x3c2c3c3e, 0xbc783b79, 0x3c043c5c, 0xbc803a49, 0x3bdbbc67, 0x3c183c4e, 0x3c4e3c18, 0xbc673bdb,
    0x3a49bc80, 0x3c5c3c04, 0x3b79bc78, 0x3c3e3c2c, 0xbc713bac, 0x3b16bc7d, 0x3b163c7d, 0xbc71bbac, 0x3c3ebc2c, 0x3b793c78,
    0x3c5cbc04, 0x3a493c80, 0xbc67bbdb, 0x3c4ebc18, 0x3c18bc4e, 0x3bdb3c67, 0xbc80ba49, 0x3c04bc5c, 0xbc78bb79, 0x3c2cbc3e,
    0x3bac3c71, 0xbc7dbb16, 0x3c7d3b16, 0xbbdb3c67, 0xbc3ebc2c, 0x3c5cbc04, 0x3b793c78, 0xbc80ba49, 0x3bacbc71, 0x3c4e3c18,
    0xbc18bc4e, 0x3c71bbac, 0x3a493c80, 0xbc78bb79, 0x3c04bc5c, 0x3c2c3c3e, 0xbc673bdb, 0xbb16bc7d, 0xbb163c7d, 0xbc67bbdb,
    0x3c2cbc3e, 0x3c043c5c, 0xbc783b79, 0x3a49bc80, 0x3c713bac, 0xbc183c4e, 0x3c4ebc18, 0x3bac3c71, 0xbc803a49, 0x3b79bc78,
    0x3c5c3c04, 0xbc3e3c2c, 0xbbdbbc67, 0x3c7dbb16, 0xbbdb3c67, 0xbc5cbc04, 0x3c18bc4e, 0x3c3e3c2c, 0xba493c80, 0xbc7dbb16,
    0x3b79bc78, 0x3c713bac, 0x3bac3c71, 0xbc783b79, 0xbb16bc7d, 0x3c80ba49, 0x3c2c3c3e, 0xbc4e3c18, 0xbc04bc5c, 0x3c67bbdb,
    0x3c673bdb, 0xbc043c5c, 0xbc4ebc18, 0x3c2cbc3e, 0x3c803a49, 0xbb163c7d, 0xbc78bb79, 0x3bacbc71, 0x3c71bbac, 0x3b793c78,
    0xbc7d3b16, 0xba49bc80, 0x3c3ebc2c, 0x3c183c4e, 0xbc5c3c04, 0xbbdbbc67, 0x3f803f80, 0x3f7d3f7f, 0x3f783f7b, 0x3f713f75,
    0x3f673f6d, 0x3f5c3f62, 0x3f4e3f55, 0x3f3e3f46, 0x3f2c3f35, 0x3f183f22, 0x3f043f0e, 0x3edb3ef1, 0x3eac3ec4, 0x3e793e95,
    0x3e163e48, 0x3d493dc9, 0xbd490000, 0xbe16bdc9, 0xbe79be48, 0xbeacbe95, 0xbedbbec4, 0xbf04bef1, 0xbf18bf0e, 0xbf2cbf22,
    0xbf3ebf35, 0xbf4ebf46, 0xbf5cbf55, 0xbf67bf62, 0xbf71bf6d, 0xbf78bf75, 0xbf7dbf7b, 0xbf80bf7f, 0x3edb3ec4, 0x3f043ef1,
    0x3f183f0e, 0x3f2c3f22, 0x3d490000, 0x3e163dc9, 0x3e793e48, 0x3eac3e95, 0x3f713f6d, 0x3f783f75, 0x3f7d3f7b, 0x3f803f7f,
    0x3f3e3f35, 0x3f4e3f46, 0x3f5c3f55, 0x3f673f62, 0x3f673f6d, 0x3f5c3f62, 0x3f4e3f55, 0x3f3e3f46, 0x3f803f80, 0x3f7d3f7f,
    0x3f783f7b, 0x3f713f75, 0x3eac3ec4, 0x3e793e95, 0x3e163e48, 0x3d493dc9, 0x3f2c3f35, 0x3f183f22, 0x3f043f0e, 0x3edb3ef1,
    0xbf4ebf35, 0xbf71bf62, 0xbf80bf7b, 0xbf78bf7f, 0xbf5cbf6d, 0xbf2cbf46, 0xbedbbf0e, 0xbe16be95, 0x3f7d3f80, 0x3f673f75,
    0x3f3e3f55, 0x3f043f22, 0x3e793ec4, 0xbd493dc9, 0xbeacbe48, 0xbf18bef1, 0x3f183f35, 0x3eac3ef1, 0x3d493e48, 0xbe79bdc9,
    0xbf04bec4, 0xbf3ebf22, 0xbf67bf55, 0xbf7dbf75, 0x3e160000, 0x3edb3e95, 0x3f2c3f0e, 0x3f5c3f46, 0x3f783f6d, 0x3f803f7f,
    0x3f713f7b, 0x3f4e3f62, 0xbf04bec4, 0xbf3ebf22, 0xbf67bf55, 0xbf7dbf75, 0x3f183f35, 0x3eac3ef1, 0x3d493e48, 0xbe79bdc9,
    0x3f783f6d, 0x3f803f7f, 0x3f713f7b, 0x3f4e3f62, 0x3e160000, 0x3edb3e95, 0x3f2c3f0e, 0x3f5c3f46, 0x3f5c3f6d, 0x3f2c3f46,
    0x3edb3f0e, 0x3e163e95, 0x3f4e3f35, 0x3f713f62, 0x3f803f7b, 0x3f783f7f, 0xbe79bec4, 0x3d49bdc9, 0x3eac3e48, 0x3f183ef1,
    0xbf7dbf80, 0xbf67bf75, 0xbf3ebf55, 0xbf04bf22, 0xbe790000, 0xbf2cbef1, 0xbf71bf55, 0xbf7dbf7f, 0xbf4ebf6d, 0xbedbbf22,
    0x3d49be48, 0x3f043e95, 0x3f5c3f35, 0x3f803f75, 0x3f673f7b, 0x3f183f46, 0x3e163ec4, 0xbeacbdc9, 0xbf3ebf0e, 0xbf78bf62,
    0x3f783f80, 0x3f3e3f62, 0x3eac3f0e, 0xbe163dc9, 0xbf18bec4, 0xbf67bf46, 0xbf80bf7b, 0xbf5cbf75, 0xbf04bf35, 0xbd49be95,
    0x3edb3e48, 0x3f4e3f22, 0x3f7d3f6d, 0x3f713f7f, 0x3f2c3f55, 0x3e793ef1, 0xbf18bec4, 0xbf67bf46, 0xbf80bf7b, 0xbf5cbf75,
    0x3f783f80, 0x3f3e3f62, 0x3eac3f0e, 0xbe163dc9, 0x3f7d3f6d, 0x3f713f7f, 0x3f2c3f55, 0x3e793ef1, 0xbf04bf35, 0xbd49be95,
    0x3edb3e48, 0x3f4e3f22, 0x3f4e3f6d, 0x3edb3f22, 0xbd493e48, 0xbf04be95, 0x3e790000, 0x3f2c3ef1, 0x3f713f55, 0x3f7d3f7f,
    0xbe16bec4, 0x3eac3dc9, 0x3f3e3f0e, 0x3f783f62, 0xbf5cbf35, 0xbf80bf75, 0xbf67bf7b, 0xbf18bf46, 0xbedbbf35, 0x3e79bdc9,
    0x3f4e3f0e, 0x3f803f75, 0x3f3e3f6d, 0x3e163ef1, 0xbf04be48, 0xbf71bf46, 0x3eac0000, 0x3f5c3f22, 0x3f7d3f7b, 0x3f2c3f62,
    0x3d493ec4, 0xbf18be95, 0xbf78bf55, 0xbf67bf7f, 0x3f673f35, 0x3f783f7f, 0x3f183f55, 0xbd493e95, 0xbf2cbec4, 0xbf7dbf62,
    0xbf5cbf7b, 0xbeacbf22, 0x3f713f80, 0x3f043f46, 0xbe163e48, 0xbf3ebef1, 0xbf80bf6d, 0xbf4ebf75, 0xbe79bf0e, 0x3edb3dc9,
    0x3f2c3ec4, 0x3f7d3f62, 0x3f5c3f7b, 0x3eac3f22, 0xbf67bf35, 0xbf78bf7f, 0xbf18bf55, 0x3d49be95, 0x3f803f6d, 0x3f4e3f75,
    0x3e793f0e, 0xbedbbdc9, 0xbf71bf80, 0xbf04bf46, 0x3e16be48, 0x3f3e3ef1, 0x3f3e3f6d, 0x3e163ef1, 0xbf04be48, 0xbf71bf46,
    0xbedbbf35, 0x3e79bdc9, 0x3f4e3f0e, 0x3f803f75, 0x3d493ec4, 0xbf18be95, 0xbf78bf55, 0xbf67bf7f, 0x3eac0000, 0x3f5c3f22,
    0x3f7d3f7b, 0x3f2c3f62, 0x3f673f80, 0x3e793f22, 0xbf18be48, 0xbf80bf62, 0xbf2cbf6d, 0x3e16be95, 0x3f5c3f0e, 0x3f713f7f,
    0x3eac3f35, 0xbf04bdc9, 0xbf7dbf55, 0xbf3ebf75, 0x3d49bec4, 0x3f4e3ef1, 0x3f783f7b, 0x3edb3f46, 0xbedb0000, 0xbf78bf46,
    0xbf4ebf7b, 0xbd49bef1, 0x3f3e3ec4, 0x3f7d3f75, 0x3f043f55, 0xbeac3dc9, 0xbf71bf35, 0xbf5cbf7f, 0xbe16bf0e, 0x3f2c3e95,
    0x3f803f6d, 0x3f183f62, 0xbe793e48, 0xbf67bf22, 0xbf3ebec4, 0xbf7dbf75, 0xbf04bf55, 0x3eacbdc9, 0x3edb0000, 0x3f783f46,
    0x3f4e3f7b, 0x3d493ef1, 0xbf80bf6d, 0xbf18bf62, 0x3e79be48, 0x3f673f22, 0x3f713f35, 0x3f5c3f7f, 0x3e163f0e, 0xbf2cbe95,
    0xbf2cbf6d, 0x3e16be95, 0x3f5c3f0e, 0x3f713f7f, 0x3f673f80, 0x3e793f22, 0xbf18be48, 0xbf80bf62, 0x3d49bec4, 0x3f4e3ef1,
    0x3f783f7b, 0x3edb3f46, 0x3eac3f35, 0xbf04bdc9, 0xbf7dbf55, 0xbf3ebf75, 0xbf78bf35, 0xbf2cbf75, 0x3eacbe48, 0x3f7d3f46,
    0x3f183f6d, 0xbedb3dc9, 0xbf80bf55, 0xbf04bf62, 0x3f5c3f80, 0xbd493ef1, 0xbf67bf0e, 0xbf4ebf7f, 0x3e16bec4, 0x3f713f22,
    0x3f3e3f7b, 0xbe793e95, 0x3e793f35, 0xbf3ebe95, 0xbf71bf7b, 0xbe16bf22, 0x3f4e3ec4, 0x3f673f7f, 0x3d493f0e, 0xbf5cbef1,
    0x3f040000, 0x3f803f62, 0x3edb3f55, 0xbf18bdc9, 0xbf7dbf6d, 0xbeacbf46, 0x3f2c3e48, 0x3f783f75, 0x3f4e3ec4, 0x3f673f7f,
    0x3d493f0e, 0xbf5cbef1, 0x3e793f35, 0xbf3ebe95, 0xbf71bf7b, 0xbe16bf22, 0xbf7dbf6d, 0xbeacbf46, 0x3f2c3e48, 0x3f783f75,
    0x3f040000, 0x3f803f62, 0x3edb3f55, 0xbf18bdc9, 0xbf18bf6d, 0x3edbbdc9, 0x3f803f55, 0x3f043f62, 0x3f783f35, 0x3f2c3f75,
    0xbeac3e48, 0xbf7dbf46, 0xbe163ec4, 0xbf71bf22, 0xbf3ebf7b, 0x3e79be95, 0xbf5cbf80, 0x3d49bef1, 0x3f673f0e, 0x3f4e3f7f,
    0xbf180000, 0xbf71bf75, 0x3d49bf0e, 0x3f783f22, 0x3f043f6d, 0xbf2cbdc9, 0xbf67bf7b, 0x3e16bef1, 0x3f7d3f35, 0x3edb3f62,
    0xbf3ebe48, 0xbf5cbf7f, 0x3e79bec4, 0x3f803f46, 0x3eac3f55, 0xbf4ebe95, 0x3f4e3f80, 0xbeac3e95, 0xbf80bf55, 0xbe79bf46,
    0x3f5c3ec4, 0x3f3e3f7f, 0xbedb3e48, 0xbf7dbf62, 0xbe16bf35, 0x3f673ef1, 0x3f2c3f7b, 0xbf043dc9, 0xbf78bf6d, 0xbd49bf22,
    0x3f713f0e, 0x3f183f75, 0x3f5c3ec4, 0x3f3e3f7f, 0xbedb3e48, 0xbf7dbf62, 0x3f4e3f80, 0xbeac3e95, 0xbf80bf55, 0xbe79bf46,
    0xbf78bf6d, 0xbd49bf22, 0x3f713f0e, 0x3f183f75, 0xbe16bf35, 0x3f673ef1, 0x3f2c3f7b, 0xbf043dc9, 0xbf04bf6d, 0x3f2c3dc9,
    0x3f673f7b, 0xbe163ef1, 0x3f180000, 0x3f713f75, 0xbd493f0e, 0xbf78bf22, 0xbe793ec4, 0xbf80bf46, 0xbeacbf55, 0x3f4e3e95,
    0xbf7dbf35, 0xbedbbf62, 0x3f3e3e48, 0x3f5c3f7f, 0xbd49bf35, 0x3f7d3f22, 0x3e793f55, 0xbf71bef1, 0xbedbbf6d, 0x3f5c3e95,
    0x3f183f7b, 0xbf3ebdc9, 0x3f2c0000, 0x3f4e3f7f, 0xbf043e48, 0xbf67bf75, 0x3eacbec4, 0x3f783f62, 0xbe163f0e, 0xbf80bf46,
    0x3f803f35, 0x3e163f46, 0xbf78bf0e, 0xbeacbf62, 0x3f673ec4, 0x3f043f75, 0xbf4ebe48, 0xbf2cbf7f, 0x3f3e3f80, 0xbf183dc9,
    0xbf5cbf7b, 0x3edbbe95, 0x3f713f6d, 0xbe793ef1, 0xbf7dbf55, 0x3d49bf22, 0xbf67bec4, 0xbf04bf75, 0x3f4e3e48, 0x3f2c3f7f,
    0xbf80bf35, 0xbe16bf46, 0x3f783f0e, 0x3eac3f62, 0xbf71bf6d, 0x3e79bef1, 0x3f7d3f55, 0xbd493f22, 0xbf3ebf80, 0x3f18bdc9,
    0x3f5c3f7b, 0xbedb3e95, 0xbedbbf6d, 0x3f5c3e95, 0x3f183f7b, 0xbf3ebdc9, 0xbd49bf35, 0x3f7d3f22, 0x3e793f55, 0xbf71bef1,
    0x3eacbec4, 0x3f783f62, 0xbe163f0e, 0xbf80bf46, 0x3f2c0000, 0x3f4e3f7f, 0xbf043e48, 0xbf67bf75, 0x3f2c3f80, 0xbf4ebdc9,
    0xbf04bf7b, 0x3f673e95, 0x3eac3f6d, 0xbf78bef1, 0xbe16bf55, 0x3f803f22, 0xbd493f35, 0xbf7dbf46, 0x3e79bf0e, 0x3f713f62,
    0xbedb3ec4, 0xbf5cbf75, 0x3f18be48, 0x3f3e3f7f, 0xbf3e0000, 0xbf18bf7f, 0x3f5c3e48, 0x3edb3f75, 0xbf71bec4, 0xbe79bf62,
    0x3f7d3f0e, 0x3d493f46, 0xbf80bf35, 0x3e16bf22, 0x3f783f55, 0xbeac3ef1, 0xbf67bf6d, 0x3f04be95, 0x3f4e3f7b, 0xbf2c3dc9,
    0x3f713ec4, 0x3e793f62, 0xbf7dbf0e, 0xbd49bf46, 0x3f3e0000, 0x3f183f7f, 0xbf5cbe48, 0xbedbbf75, 0x3f673f6d, 0xbf043e95,
    0xbf4ebf7b, 0x3f2cbdc9, 0x3f803f35, 0xbe163f22, 0xbf78bf55, 0x3eacbef1, 0x3eac3f6d, 0xbf78bef1, 0xbe16bf55, 0x3f803f22,
    0x3f2c3f80, 0xbf4ebdc9, 0xbf04bf7b, 0x3f673e95, 0xbedb3ec4, 0xbf5cbf75, 0x3f18be48, 0x3f3e3f7f, 0xbd493f35, 0xbf7dbf46,
    0x3e79bf0e, 0x3f713f62, 0xbf7dbf35, 0x3edbbef1, 0x3f3e3f7b, 0xbf5cbdc9, 0xbe79bf6d, 0x3f803f22, 0xbeac3f0e, 0xbf4ebf75,
    0x3f183f80, 0xbf71be95, 0xbd49bf55, 0x3f783f46, 0xbf043ec4, 0xbf2cbf7f, 0x3f673e48, 0x3e163f62, 0xbe163f35, 0xbf67bf62,
    0x3f2cbe48, 0x3f043f7f, 0xbf78bec4, 0x3d49bf46, 0x3f713f55, 0xbf183e95, 0x3f4e0000, 0x3eac3f75, 0xbf80bf0e, 0x3e79bf22,
    0x3f5c3f6d, 0xbf3e3dc9, 0xbedbbf7b, 0x3f7d3ef1, 0xbf78bec4, 0x3d49bf46, 0x3f713f55, 0xbf183e95, 0xbe163f35, 0xbf67bf62,
    0x3f2cbe48, 0x3f043f7f, 0x3f5c3f6d, 0xbf3e3dc9, 0xbedbbf7b, 0x3f7d3ef1, 0x3f4e0000, 0x3eac3f75, 0xbf80bf0e, 0x3e79bf22,
    0x3e793f6d, 0xbf80bf22, 0x3eacbf0e, 0x3f4e3f75, 0x3f7d3f35, 0xbedb3ef1, 0xbf3ebf7b, 0x3f5c3dc9, 0x3f04bec4, 0x3f2c3f7f,
    0xbf67be48, 0xbe16bf62, 0xbf18bf80, 0x3f713e95, 0x3d493f55, 0xbf78bf46, 0xbf5c0000, 0xbd49bf62, 0x3f673f55, 0xbf4e3dc9,
    0xbe16bf6d, 0x3f713f46, 0xbf3e3e48, 0xbe79bf75, 0x3f783f35, 0xbf2c3e95, 0xbeacbf7b, 0x3f7d3f22, 0xbf183ec4, 0xbedbbf7f,
    0x3f803f0e, 0xbf043ef1, 0x3f043f80, 0xbf80bef1, 0x3edbbf0e, 0x3f183f7f, 0xbf7dbec4, 0x3eacbf22, 0x3f2c3f7b, 0xbf78be95,
    0x3e79bf35, 0x3f3e3f75, 0xbf71be48, 0x3e16bf46, 0x3f4e3f6d, 0xbf67bdc9, 0x3d49bf55, 0x3f5c3f62, 0xbf7dbec4, 0x3eacbf22,
    0x3f2c3f7b, 0xbf78be95, 0x3f043f80, 0xbf80bef1, 0x3edbbf0e, 0x3f183f7f, 0x3f4e3f6d, 0xbf67bdc9, 0x3d49bf55, 0x3f5c3f62,
    0x3e79bf35, 0x3f3e3f75, 0xbf71be48, 0x3e16bf46, 0x3e163f6d, 0xbf71bf46, 0x3f3ebe48, 0x3e793f75, 0x3f5c0000, 0x3d493f62,
    0xbf67bf55, 0x3f4ebdc9, 0x3f18bec4, 0x3edb3f7f, 0xbf80bf0e, 0x3f04bef1, 0xbf78bf35, 0x3f2cbe95, 0x3eac3f7b, 0xbf7dbf22,
    0x3eacbf35, 0x3f043f7f, 0xbf7dbf0e, 0x3f3ebe95, 0x3d493f6d, 0xbf4ebf62, 0x3f783e48, 0xbedb3f22, 0x3f670000, 0xbe793f46,
    0xbf18bf7b, 0x3f803ef1, 0xbf2c3ec4, 0xbe16bf75, 0x3f5c3f55, 0xbf71bdc9, 0x3f713f35, 0xbf5c3dc9, 0x3e16bf55, 0x3f2c3f75,
    0xbf80bec4, 0x3f18bef1, 0x3e793f7b, 0xbf67bf46, 0x3edb3f80, 0xbf78bf22, 0x3f4ebe48, 0xbd493f62, 0xbf3ebf6d, 0x3f7d3e95,
    0xbf043f0e, 0xbeacbf7f, 0x3f803ec4, 0xbf183ef1, 0xbe79bf7b, 0x3f673f46, 0xbf71bf35, 0x3f5cbdc9, 0xbe163f55, 0xbf2cbf75,
    0x3f3e3f6d, 0xbf7dbe95, 0x3f04bf0e, 0x3eac3f7f, 0xbedbbf80, 0x3f783f22, 0xbf4e3e48, 0x3d49bf62, 0x3d493f6d, 0xbf4ebf62,
    0x3f783e48, 0xbedb3f22, 0x3eacbf35, 0x3f043f7f, 0xbf7dbf0e, 0x3f3ebe95, 0xbf2c3ec4, 0xbe16bf75, 0x3f5c3f55, 0xbf71bdc9,
    0x3f670000, 0xbe793f46, 0xbf18bf7b, 0x3f803ef1, 0x3eac3f80, 0xbf5cbf46, 0x3f7d3e48, 0xbf2c3ef1, 0x3d49bf6d, 0x3f183f75,
    0xbf78bf0e, 0x3f67bdc9, 0xbedb3f35, 0xbe79bf7f, 0x3f4e3f55, 0xbf80be95, 0x3f3ebec4, 0xbe163f62, 0xbf04bf7b, 0x3f713f22,
    0xbf710000, 0x3f04bf22, 0x3e163f7b, 0xbf3ebf62, 0x3f803ec4, 0xbf4e3e95, 0x3e79bf55, 0x3edb3f7f, 0xbf67bf35, 0x3f783dc9,
    0xbf183f0e, 0xbd49bf75, 0x3f2c3f6d, 0xbf7dbef1, 0x3f5cbe48, 0xbeac3f46, 0xbf80bec4, 0x3f4ebe95, 0xbe793f55, 0xbedbbf7f,
    0x3f710000, 0xbf043f22, 0xbe16bf7b, 0x3f3e3f62, 0xbf2cbf6d, 0x3f7d3ef1, 0xbf5c3e48, 0x3eacbf46, 0x3f673f35, 0xbf78bdc9,
    0x3f18bf0e, 0x3d493f75, 0x3d49bf6d, 0x3f183f75, 0xbf78bf0e, 0x3f67bdc9, 0x3eac3f80, 0xbf5cbf46, 0x3f7d3e48, 0xbf2c3ef1,
    0x3f3ebec4, 0xbe163f62, 0xbf04bf7b, 0x3f713f22, 0xbedb3f35, 0xbe79bf7f, 0x3f4e3f55, 0xbf80be95, 0xbf5cbf35, 0x3f803e95,
    0xbf673e48, 0x3f18bf22, 0xbe163f6d, 0xbeacbf7f, 0x3f3e3f55, 0xbf78bef1, 0x3e793f80, 0xbf2cbf62, 0x3f713f0e, 0xbf7dbdc9,
    0x3f4ebec4, 0xbedb3f46, 0xbd49bf7b, 0x3f043f75, 0xbf043f35, 0x3d49bf75, 0x3edb3f7b, 0xbf4ebf46, 0x3f7d3ec4, 0xbf713dc9,
    0x3f2cbf0e, 0xbe793f62, 0x3f780000, 0xbf3e3ef1, 0x3eacbf55, 0x3e163f7f, 0xbf18bf6d, 0x3f673f22, 0xbf80be48, 0x3f5cbe95,
    0x3f7d3ec4, 0xbf713dc9, 0x3f2cbf0e, 0xbe793f62, 0xbf043f35, 0x3d49bf75, 0x3edb3f7b, 0xbf4ebf46, 0xbf18bf6d, 0x3f673f22,
    0xbf80be48, 0x3f5cbe95, 0x3f780000, 0xbf3e3ef1, 0x3eacbf55, 0x3e163f7f, 0x3e16bf6d, 0x3eac3f7f, 0xbf3ebf55, 0x3f783ef1,
    0x3f5c3f35, 0xbf80be95, 0x3f67be48, 0xbf183f22, 0xbf4e3ec4, 0x3edbbf46, 0x3d493f7b, 0xbf04bf75, 0xbe79bf80, 0x3f2c3f62,
    0xbf71bf0e, 0x3f7d3dc9, 0xbf7d0000, 0x3f67be95, 0xbf3e3f0e, 0x3f04bf46, 0xbe793f6d, 0xbd49bf7f, 0x3eac3f7b, 0xbf18bf62,
    0x3f4e3f35, 0xbf71bef1, 0x3f803e48, 0xbf783dc9, 0x3f5cbec4, 0xbf2c3f22, 0x3edbbf55, 0xbe163f75, 0x3e163f80, 0xbedbbf75,
    0x3f2c3f55, 0xbf5cbf22, 0x3f783ec4, 0xbf80bdc9, 0x3f71be48, 0xbf4e3ef1, 0x3f18bf35, 0xbeac3f62, 0x3d49bf7b, 0x3e793f7f,
    0xbf04bf6d, 0x3f3e3f46, 0xbf67bf0e, 0x3f7d3e95, 0x3f783ec4, 0xbf80bdc9, 0x3f71be48, 0xbf4e3ef1, 0x3e163f80, 0xbedbbf75,
    0x3f2c3f55, 0xbf5cbf22, 0xbf04bf6d, 0x3f3e3f46, 0xbf67bf0e, 0x3f7d3e95, 0x3f18bf35, 0xbeac3f62, 0x3d49bf7b, 0x3e793f7f,
    0x3e79bf6d, 0x3d493f7f, 0xbeacbf7b, 0x3f183f62, 0x3f7d0000, 0xbf673e95, 0x3f3ebf0e, 0xbf043f46, 0xbf5c3ec4, 0x3f2cbf22,
    0xbedb3f55, 0x3e16bf75, 0xbf4ebf35, 0x3f713ef1, 0xbf80be48, 0x3f78bdc9, 0x3f2cbf35, 0xbf183f46, 0x3f04bf55, 0xbedb3f62,
    0x3eacbf6d, 0xbe793f75, 0x3e16bf7b, 0xbd493f7f, 0x3f800000, 0xbf7d3dc9, 0x3f78be48, 0xbf713e95, 0x3f67bec4, 0xbf5c3ef1,
    0x3f4ebf0e, 0xbf3e3f22, 0x3f3e3f35, 0xbf4ebf22, 0x3f5c3f0e, 0xbf67bef1, 0x3f713ec4, 0xbf78be95, 0x3f7d3e48, 0xbf80bdc9,
    0x3d493f80, 0xbe16bf7f, 0x3e793f7b, 0xbeacbf75, 0x3edb3f6d, 0xbf04bf62, 0x3f183f55, 0xbf2cbf46, 0xbf71bec4, 0x3f783e95,
    0xbf7dbe48, 0x3f803dc9, 0xbf3ebf35, 0x3f4e3f22, 0xbf5cbf0e, 0x3f673ef1, 0xbedbbf6d, 0x3f043f62, 0xbf18bf55, 0x3f2c3f46,
    0xbd49bf80, 0x3e163f7f, 0xbe79bf7b, 0x3eac3f75, 0x3eacbf6d, 0xbe793f75, 0x3e16bf7b, 0xbd493f7f, 0x3f2cbf35, 0xbf183f46,
    0x3f04bf55, 0xbedb3f62, 0x3f67bec4, 0xbf5c3ef1, 0x3f4ebf0e, 0xbf3e3f22, 0x3f800000, 0xbf7d3dc9, 0x3f78be48, 0xbf713e95,
    0xbd493f80, 0x3e16bf7f, 0xbe793f7b, 0x3eacbf75, 0xbedb3f6d, 0x3f04bf62, 0xbf183f55, 0x3f2cbf46, 0xbf3e3f35, 0x3f4ebf22,
    0xbf5c3f0e, 0x3f67bef1, 0xbf713ec4, 0x3f78be95, 0xbf7d3e48, 0x3f80bdc9, 0xbf800000, 0x3f7d3dc9, 0xbf78be48, 0x3f713e95,
    0xbf67bec4, 0x3f5c3ef1, 0xbf4ebf0e, 0x3f3e3f22, 0xbf2cbf35, 0x3f183f46, 0xbf04bf55, 0x3edb3f62, 0xbeacbf6d, 0x3e793f75,
    0xbe16bf7b, 0x3d493f7f, 0x3f673ec4, 0xbf5cbef1, 0x3f4e3f0e, 0xbf3ebf22, 0x3f800000, 0xbf7dbdc9, 0x3f783e48, 0xbf71be95,
    0x3eac3f6d, 0xbe79bf75, 0x3e163f7b, 0xbd49bf7f, 0x3f2c3f35, 0xbf18bf46, 0x3f043f55, 0xbedbbf62, 0xbedb3f6d, 0x3f04bf62,
    0xbf183f55, 0x3f2cbf46, 0xbd493f80, 0x3e16bf7f, 0xbe793f7b, 0x3eacbf75, 0xbf713ec4, 0x3f78be95, 0xbf7d3e48, 0x3f80bdc9,
    0xbf3e3f35, 0x3f4ebf22, 0xbf5c3f0e, 0x3f67bef1, 0xbf18bf35, 0x3eac3f62, 0xbd49bf7b, 0xbe793f7f, 0x3f04bf6d, 0xbf3e3f46,
    0x3f67bf0e, 0xbf7d3e95, 0xbe163f80, 0x3edbbf75, 0xbf2c3f55, 0x3f5cbf22, 0xbf783ec4, 0x3f80bdc9, 0xbf71be48, 0x3f4e3ef1,
    0xbf4e3f35, 0x3f71bef1, 0xbf803e48, 0x3f783dc9, 0xbf5cbec4, 0x3f2c3f22, 0xbedbbf55, 0x3e163f75, 0x3f7d0000, 0xbf67be95,
    0x3f3e3f0e, 0xbf04bf46, 0x3e793f6d, 0x3d49bf7f, 0xbeac3f7b, 0x3f18bf62, 0xbf5cbec4, 0x3f2c3f22, 0xbedbbf55, 0x3e163f75,
    0xbf4e3f35, 0x3f71bef1, 0xbf803e48, 0x3f783dc9, 0x3e793f6d, 0x3d49bf7f, 0xbeac3f7b, 0x3f18bf62, 0x3f7d0000, 0xbf67be95,
    0x3f3e3f0e, 0xbf04bf46, 0xbf043f6d, 0x3f3ebf46, 0xbf673f0e, 0x3f7dbe95, 0x3f183f35, 0xbeacbf62, 0x3d493f7b, 0x3e79bf7f,
    0x3f78bec4, 0xbf803dc9, 0x3f713e48, 0xbf4ebef1, 0x3e16bf80, 0xbedb3f75, 0x3f2cbf55, 0xbf5c3f22, 0xbf780000, 0x3f3e3ef1,
    0xbeacbf55, 0xbe163f7f, 0x3f18bf6d, 0xbf673f22, 0x3f80be48, 0xbf5cbe95, 0x3f043f35, 0xbd49bf75, 0xbedb3f7b, 0x3f4ebf46,
    0xbf7d3ec4, 0x3f713dc9, 0xbf2cbf0e, 0x3e793f62, 0xbe793f80, 0x3f2cbf62, 0xbf713f0e, 0x3f7dbdc9, 0xbf4ebec4, 0x3edb3f46,
    0x3d49bf7b, 0xbf043f75, 0x3f5cbf35, 0xbf803e95, 0x3f673e48, 0xbf18bf22, 0x3e163f6d, 0x3eacbf7f, 0xbf3e3f55, 0x3f78bef1,
    0xbf4ebec4, 0x3edb3f46, 0x3d49bf7b, 0xbf043f75, 0xbe793f80, 0x3f2cbf62, 0xbf713f0e, 0x3f7dbdc9, 0x3e163f6d, 0x3eacbf7f,
    0xbf3e3f55, 0x3f78bef1, 0x3f5cbf35, 0xbf803e95, 0x3f673e48, 0xbf18bf22, 0xbf183f6d, 0x3f67bf22, 0xbf803e48, 0x3f5c3e95,
    0x3f780000, 0xbf3ebef1, 0x3eac3f55, 0x3e16bf7f, 0x3f7dbec4, 0xbf71bdc9, 0x3f2c3f0e, 0xbe79bf62, 0xbf04bf35, 0x3d493f75,
    0x3edbbf7b, 0xbf4e3f46, 0x3f67bf35, 0xbf783dc9, 0x3f183f0e, 0x3d49bf75, 0xbf2c3f6d, 0x3f7dbef1, 0xbf5cbe48, 0x3eac3f46,
    0x3f710000, 0xbf04bf22, 0xbe163f7b, 0x3f3ebf62, 0xbf803ec4, 0x3f4e3e95, 0xbe79bf55, 0xbedb3f7f, 0x3edb3f35, 0x3e79bf7f,
    0xbf4e3f55, 0x3f80be95, 0xbf3ebec4, 0x3e163f62, 0x3f04bf7b, 0xbf713f22, 0xbeac3f80, 0x3f5cbf46, 0xbf7d3e48, 0x3f2c3ef1,
    0xbd49bf6d, 0xbf183f75, 0x3f78bf0e, 0xbf67bdc9, 0x3f3e3ec4, 0xbe16bf62, 0xbf043f7b, 0x3f71bf22, 0xbedbbf35, 0xbe793f7f,
    0x3f4ebf55, 0xbf803e95, 0x3d493f6d, 0x3f18bf75, 0xbf783f0e, 0x3f673dc9, 0x3eacbf80, 0xbf5c3f46, 0x3f7dbe48, 0xbf2cbef1,
    0xbf2c3f6d, 0x3f7dbef1, 0xbf5cbe48, 0x3eac3f46, 0x3f67bf35, 0xbf783dc9, 0x3f183f0e, 0x3d49bf75, 0xbf803ec4, 0x3f4e3e95,
    0xbe79bf55, 0xbedb3f7f, 0x3f710000, 0xbf04bf22, 0xbe163f7b, 0x3f3ebf62, 0xbedb3f80, 0x3f78bf22, 0xbf4ebe48, 0x3d493f62,
    0x3f3ebf6d, 0xbf7d3e95, 0x3f043f0e, 0x3eacbf7f, 0xbf713f35, 0x3f5c3dc9, 0xbe16bf55, 0xbf2c3f75, 0x3f80bec4, 0xbf18bef1,
    0xbe793f7b, 0x3f67bf46, 0xbf670000, 0x3e793f46, 0x3f18bf7b, 0xbf803ef1, 0x3f2c3ec4, 0x3e16bf75, 0xbf5c3f55, 0x3f71bdc9,
    0xbeacbf35, 0xbf043f7f, 0x3f7dbf0e, 0xbf3ebe95, 0xbd493f6d, 0x3f4ebf62, 0xbf783e48, 0x3edb3f22, 0xbf2cbec4, 0xbe163f75,
    0x3f5cbf55, 0xbf713dc9, 0x3f670000, 0xbe79bf46, 0xbf183f7b, 0x3f80bef1, 0x3d49bf6d, 0xbf4e3f62, 0x3f78be48, 0xbedbbf22,
    0x3eac3f35, 0x3f04bf7f, 0xbf7d3f0e, 0x3f3e3e95, 0x3f3ebf6d, 0xbf7d3e95, 0x3f043f0e, 0x3eacbf7f, 0xbedb3f80, 0x3f78bf22,
    0xbf4ebe48, 0x3d493f62, 0x3f80bec4, 0xbf18bef1, 0xbe793f7b, 0x3f67bf46, 0xbf713f35, 0x3f5c3dc9, 0xbe16bf55, 0xbf2c3f75,
    0xbe79bf35, 0xbf3e3f75, 0x3f71be48, 0xbe16bf46, 0xbf4e3f6d, 0x3f67bdc9, 0xbd49bf55, 0xbf5c3f62, 0xbf043f80, 0x3f80bef1,
    0xbedbbf0e, 0xbf183f7f, 0x3f7dbec4, 0xbeacbf22, 0xbf2c3f7b, 0x3f78be95, 0xbf783f35, 0x3f2c3e95, 0x3eacbf7b, 0xbf7d3f22,
    0x3f183ec4, 0x3edbbf7f, 0xbf803f0e, 0x3f043ef1, 0x3f5c0000, 0x3d49bf62, 0xbf673f55, 0x3f4e3dc9, 0x3e16bf6d, 0xbf713f46,
    0x3f3e3e48, 0x3e79bf75, 0x3f183ec4, 0x3edbbf7f, 0xbf803f0e, 0x3f043ef1, 0xbf783f35, 0x3f2c3e95, 0x3eacbf7b, 0xbf7d3f22,
    0x3e16bf6d, 0xbf713f46, 0x3f3e3e48, 0x3e79bf75, 0x3f5c0000, 0x3d49bf62, 0xbf673f55, 0x3f4e3dc9, 0x3f4ebf6d, 0xbf673dc9,
    0x3d493f55, 0x3f5cbf62, 0x3e793f35, 0x3f3ebf75, 0xbf713e48, 0x3e163f46, 0xbf7d3ec4, 0x3eac3f22, 0x3f2cbf7b, 0xbf783e95,
    0x3f04bf80, 0xbf803ef1, 0x3edb3f0e, 0x3f18bf7f, 0xbf4e0000, 0xbeac3f75, 0x3f80bf0e, 0xbe79bf22, 0xbf5c3f6d, 0x3f3e3dc9,
    0x3edbbf7b, 0xbf7d3ef1, 0x3e163f35, 0x3f67bf62, 0xbf2cbe48, 0xbf043f7f, 0x3f78bec4, 0xbd49bf46, 0xbf713f55, 0x3f183e95,
    0xbf183f80, 0x3f71be95, 0x3d49bf55, 0xbf783f46, 0x3f043ec4, 0x3f2cbf7f, 0xbf673e48, 0xbe163f62, 0x3f7dbf35, 0xbedbbef1,
    0xbf3e3f7b, 0x3f5cbdc9, 0x3e79bf6d, 0xbf803f22, 0x3eac3f0e, 0x3f4ebf75, 0x3f043ec4, 0x3f2cbf7f, 0xbf673e48, 0xbe163f62,
    0xbf183f80, 0x3f71be95, 0x3d49bf55, 0xbf783f46, 0x3e79bf6d, 0xbf803f22, 0x3eac3f0e, 0x3f4ebf75, 0x3f7dbf35, 0xbedbbef1,
    0xbf3e3f7b, 0x3f5cbdc9, 0x3f5cbf6d, 0xbf3ebdc9, 0xbedb3f7b, 0x3f7dbef1, 0x3f4e0000, 0x3eacbf75, 0xbf803f0e, 0x3e793f22,
    0xbf783ec4, 0x3d493f46, 0x3f71bf55, 0xbf18be95, 0xbe16bf35, 0xbf673f62, 0x3f2c3e48, 0x3f04bf7f, 0x3f80bf35, 0xbe16bf22,
    0xbf783f55, 0x3eac3ef1, 0x3f67bf6d, 0xbf04be95, 0xbf4e3f7b, 0x3f2c3dc9, 0x3f3e0000, 0x3f18bf7f, 0xbf5c3e48, 0xbedb3f75,
    0x3f71bec4, 0x3e79bf62, 0xbf7d3f0e, 0xbd493f46, 0x3d493f35, 0x3f7dbf46, 0xbe79bf0e, 0xbf713f62, 0x3edb3ec4, 0x3f5cbf75,
    0xbf18be48, 0xbf3e3f7f, 0xbf2c3f80, 0x3f4ebdc9, 0x3f04bf7b, 0xbf673e95, 0xbeac3f6d, 0x3f78bef1, 0x3e16bf55, 0xbf803f22,
    0xbedbbec4, 0xbf5c3f75, 0x3f183e48, 0x3f3ebf7f, 0xbd49bf35, 0xbf7d3f46, 0x3e793f0e, 0x3f71bf62, 0x3eacbf6d, 0xbf783ef1,
    0xbe163f55, 0x3f80bf22, 0x3f2cbf80, 0xbf4e3dc9, 0xbf043f7b, 0x3f67be95, 0x3f67bf6d, 0xbf04be95, 0xbf4e3f7b, 0x3f2c3dc9,
    0x3f80bf35, 0xbe16bf22, 0xbf783f55, 0x3eac3ef1, 0x3f71bec4, 0x3e79bf62, 0xbf7d3f0e, 0xbd493f46, 0x3f3e0000, 0x3f18bf7f,
    0xbf5c3e48, 0xbedb3f75, 0xbf3e3f80, 0x3f183dc9, 0x3f5cbf7b, 0xbedbbe95, 0xbf713f6d, 0x3e793ef1, 0x3f7dbf55, 0xbd49bf22,
    0xbf803f35, 0xbe163f46, 0x3f78bf0e, 0x3eacbf62, 0xbf673ec4, 0xbf043f75, 0x3f4ebe48, 0x3f2cbf7f, 0xbf2c0000, 0xbf4e3f7f,
    0x3f043e48, 0x3f67bf75, 0xbeacbec4, 0xbf783f62, 0x3e163f0e, 0x3f80bf46, 0x3d49bf35, 0xbf7d3f22, 0xbe793f55, 0x3f71bef1,
    0x3edbbf6d, 0xbf5c3e95, 0xbf183f7b, 0x3f3ebdc9, 0x3eac3ec4, 0x3f78bf62, 0xbe16bf0e, 0xbf803f46, 0x3f2c0000, 0x3f4ebf7f,
    0xbf04be48, 0xbf673f75, 0xbedb3f6d, 0x3f5cbe95, 0x3f18bf7b, 0xbf3e3dc9, 0xbd493f35, 0x3f7dbf22, 0x3e79bf55, 0xbf713ef1,
    0xbf713f6d, 0x3e793ef1, 0x3f7dbf55, 0xbd49bf22, 0xbf3e3f80, 0x3f183dc9, 0x3f5cbf7b, 0xbedbbe95, 0xbf673ec4, 0xbf043f75,
    0x3f4ebe48, 0x3f2cbf7f, 0xbf803f35, 0xbe163f46, 0x3f78bf0e, 0x3eacbf62, 0x3e16bf35, 0xbf673ef1, 0xbf2c3f7b, 0x3f043dc9,
    0x3f78bf6d, 0x3d49bf22, 0xbf713f0e, 0xbf183f75, 0xbf4e3f80, 0x3eac3e95, 0x3f80bf55, 0x3e79bf46, 0xbf5c3ec4, 0xbf3e3f7f,
    0x3edb3e48, 0x3f7dbf62, 0xbf7d3f35, 0xbedb3f62, 0x3f3ebe48, 0x3f5cbf7f, 0xbe79bec4, 0xbf803f46, 0xbeac3f55, 0x3f4ebe95,
    0x3f180000, 0x3f71bf75, 0xbd49bf0e, 0xbf783f22, 0xbf043f6d, 0x3f2cbdc9, 0x3f67bf7b, 0xbe16bef1, 0xbe79bec4, 0xbf803f46,
    0xbeac3f55, 0x3f4ebe95, 0xbf7d3f35, 0xbedb3f62, 0x3f3ebe48, 0x3f5cbf7f, 0xbf043f6d, 0x3f2cbdc9, 0x3f67bf7b, 0xbe16bef1,
    0x3f180000, 0x3f71bf75, 0xbd49bf0e, 0xbf783f22, 0xbf783f6d, 0xbd493f22, 0x3f71bf0e, 0x3f18bf75, 0xbe163f35, 0x3f67bef1,
    0x3f2cbf7b, 0xbf04bdc9, 0x3f5cbec4, 0x3f3ebf7f, 0xbedbbe48, 0xbf7d3f62, 0x3f4ebf80, 0xbeacbe95, 0xbf803f55, 0xbe793f46,
    0xbf040000, 0xbf803f62, 0xbedb3f55, 0x3f18bdc9, 0x3f7dbf6d, 0x3eacbf46, 0xbf2c3e48, 0xbf783f75, 0xbe793f35, 0x3f3ebe95,
    0x3f71bf7b, 0x3e16bf22, 0xbf4e3ec4, 0xbf673f7f, 0xbd493f0e, 0x3f5cbef1, 0xbf5c3f80, 0x3d493ef1, 0x3f67bf0e, 0x3f4ebf7f,
    0xbe16bec4, 0xbf713f22, 0xbf3e3f7b, 0x3e793e95, 0x3f78bf35, 0x3f2cbf75, 0xbeacbe48, 0xbf7d3f46, 0xbf183f6d, 0x3edb3dc9,
    0x3f80bf55, 0x3f04bf62, 0xbe16bec4, 0xbf713f22, 0xbf3e3f7b, 0x3e793e95, 0xbf5c3f80, 0x3d493ef1, 0x3f67bf0e, 0x3f4ebf7f,
    0xbf183f6d, 0x3edb3dc9, 0x3f80bf55, 0x3f04bf62, 0x3f78bf35, 0x3f2cbf75, 0xbeacbe48, 0xbf7d3f46, 0xbf7d3f6d, 0xbeac3f46,
    0x3f2cbe48, 0x3f78bf75, 0x3f040000, 0x3f80bf62, 0x3edbbf55, 0xbf183dc9, 0x3f4ebec4, 0x3f67bf7f, 0x3d49bf0e, 0xbf5c3ef1,
    0x3e79bf35, 0xbf3e3e95, 0xbf713f7b, 0xbe163f22, 0x3f71bf35, 0x3f5cbf7f, 0x3e16bf0e, 0xbf2c3e95, 0xbf803f6d, 0xbf183f62,
    0x3e793e48, 0x3f67bf22, 0x3edb0000, 0x3f78bf46, 0x3f4ebf7b, 0x3d49bef1, 0xbf3e3ec4, 0xbf7d3f75, 0xbf043f55, 0x3eac3dc9,
    0xbeac3f35, 0x3f04bdc9, 0x3f7dbf55, 0x3f3ebf75, 0xbd49bec4, 0xbf4e3ef1, 0xbf783f7b, 0xbedb3f46, 0xbf673f80, 0xbe793f22,
    0x3f18be48, 0x3f80bf62, 0x3f2cbf6d, 0xbe16be95, 0xbf5c3f0e, 0xbf713f7f, 0x3d493ec4, 0x3f4ebef1, 0x3f78bf7b, 0x3edbbf46,
    0x3eacbf35, 0xbf043dc9, 0xbf7d3f55, 0xbf3e3f75, 0xbf2c3f6d, 0x3e163e95, 0x3f5cbf0e, 0x3f71bf7f, 0x3f67bf80, 0x3e79bf22,
    0xbf183e48, 0xbf803f62, 0xbf803f6d, 0xbf183f62, 0x3e793e48, 0x3f67bf22, 0x3f71bf35, 0x3f5cbf7f, 0x3e16bf0e, 0xbf2c3e95,
    0xbf3e3ec4, 0xbf7d3f75, 0xbf043f55, 0x3eac3dc9, 0x3edb0000, 0x3f78bf46, 0x3f4ebf7b, 0x3d49bef1, 0xbf713f80, 0xbf043f46,
    0x3e163e48, 0x3f3ebef1, 0x3f80bf6d, 0x3f4ebf75, 0x3e79bf0e, 0xbedb3dc9, 0xbf673f35, 0xbf783f7f, 0xbf183f55, 0x3d493e95,
    0x3f2cbec4, 0x3f7dbf62, 0x3f5cbf7b, 0x3eacbf22, 0xbeac0000, 0xbf5c3f22, 0xbf7d3f7b, 0xbf2c3f62, 0xbd493ec4, 0x3f18be95,
    0x3f78bf55, 0x3f67bf7f, 0x3edbbf35, 0xbe79bdc9, 0xbf4e3f0e, 0xbf803f75, 0xbf3e3f6d, 0xbe163ef1, 0x3f04be48, 0x3f71bf46,
    0x3d49bec4, 0xbf183e95, 0xbf783f55, 0xbf673f7f, 0x3eac0000, 0x3f5cbf22, 0x3f7dbf7b, 0x3f2cbf62, 0x3f3ebf6d, 0x3e16bef1,
    0xbf043e48, 0xbf713f46, 0xbedb3f35, 0x3e793dc9, 0x3f4ebf0e, 0x3f80bf75, 0x3f80bf6d, 0x3f4ebf75, 0x3e79bf0e, 0xbedb3dc9,
    0xbf713f80, 0xbf043f46, 0x3e163e48, 0x3f3ebef1, 0x3f2cbec4, 0x3f7dbf62, 0x3f5cbf7b, 0x3eacbf22, 0xbf673f35, 0xbf783f7f,
    0xbf183f55, 0x3d493e95, 0x3f04bf35, 0x3d49be95, 0xbedb3e48, 0xbf4e3f22, 0xbf7d3f6d, 0xbf713f7f, 0xbf2c3f55, 0xbe793ef1,
    0xbf783f80, 0xbf3e3f62, 0xbeac3f0e, 0x3e163dc9, 0x3f18bec4, 0x3f67bf46, 0x3f80bf7b, 0x3f5cbf75, 0xbf5c3f35, 0xbf803f75,
    0xbf673f7b, 0xbf183f46, 0xbe163ec4, 0x3eacbdc9, 0x3f3ebf0e, 0x3f78bf62, 0x3e790000, 0x3f2cbef1, 0x3f71bf55, 0x3f7dbf7f,
    0x3f4ebf6d, 0x3edbbf22, 0xbd49be48, 0xbf043e95, 0xbe163ec4, 0x3eacbdc9, 0x3f3ebf0e, 0x3f78bf62, 0xbf5c3f35, 0xbf803f75,
    0xbf673f7b, 0xbf183f46, 0x3f4ebf6d, 0x3edbbf22, 0xbd49be48, 0xbf043e95, 0x3e790000, 0x3f2cbef1, 0x3f71bf55, 0x3f7dbf7f,
    0x3f7dbf6d, 0x3f71bf7f, 0x3f2cbf55, 0x3e79bef1, 0xbf043f35, 0xbd493e95, 0x3edbbe48, 0x3f4ebf22, 0xbf183ec4, 0xbf673f46,
    0xbf803f7b, 0xbf5c3f75, 0x3f78bf80, 0x3f3ebf62, 0x3eacbf0e, 0xbe16bdc9, 0xbe160000, 0xbedb3e95, 0xbf2c3f0e, 0xbf5c3f46,
    0xbf783f6d, 0xbf803f7f, 0xbf713f7b, 0xbf4e3f62, 0xbf183f35, 0xbeac3ef1, 0xbd493e48, 0x3e79bdc9, 0x3f04bec4, 0x3f3ebf22,
    0x3f67bf55, 0x3f7dbf75, 0xbf7d3f80, 0xbf673f75, 0xbf3e3f55, 0xbf043f22, 0xbe793ec4, 0x3d493dc9, 0x3eacbe48, 0x3f18bef1,
    0x3f4ebf35, 0x3f71bf62, 0x3f80bf7b, 0x3f78bf7f, 0x3f5cbf6d, 0x3f2cbf46, 0x3edbbf0e, 0x3e16be95, 0xbe793ec4, 0x3d493dc9,
    0x3eacbe48, 0x3f18bef1, 0xbf7d3f80, 0xbf673f75, 0xbf3e3f55, 0xbf043f22, 0x3f5cbf6d, 0x3f2cbf46, 0x3edbbf0e, 0x3e16be95,
    0x3f4ebf35, 0x3f71bf62, 0x3f80bf7b, 0x3f78bf7f, 0x3f78bf6d, 0x3f80bf7f, 0x3f71bf7b, 0x3f4ebf62, 0x3e160000, 0x3edbbe95,
    0x3f2cbf0e, 0x3f5cbf46, 0xbf043ec4, 0xbf3e3f22, 0xbf673f55, 0xbf7d3f75, 0x3f18bf35, 0x3eacbef1, 0x3d49be48, 0xbe793dc9,
    0x3f3ebf35, 0x3f4ebf46, 0x3f5cbf55, 0x3f67bf62, 0x3f71bf6d, 0x3f78bf75, 0x3f7dbf7b, 0x3f80bf7f, 0x3d490000, 0x3e16bdc9,
    0x3e79be48, 0x3eacbe95, 0x3edbbec4, 0x3f04bef1, 0x3f18bf0e, 0x3f2cbf22, 0xbf2c3f35, 0xbf183f22, 0xbf043f0e, 0xbedb3ef1,
    0xbeac3ec4, 0xbe793e95, 0xbe163e48, 0xbd493dc9, 0xbf803f80, 0xbf7d3f7f, 0xbf783f7b, 0xbf713f75, 0xbf673f6d, 0xbf5c3f62,
    0xbf4e3f55, 0xbf3e3f46, 0x3eacbec4, 0x3e79be95, 0x3e16be48, 0x3d49bdc9, 0x3f2cbf35, 0x3f18bf22, 0x3f04bf0e, 0x3edbbef1,
    0x3f67bf6d, 0x3f5cbf62, 0x3f4ebf55, 0x3f3ebf46, 0x3f80bf80, 0x3f7dbf7f, 0x3f78bf7b, 0x3f71bf75, 0x3f71bf6d, 0x3f78bf75,
    0x3f7dbf7b, 0x3f80bf7f, 0x3f3ebf35, 0x3f4ebf46, 0x3f5cbf55, 0x3f67bf62, 0x3edbbec4, 0x3f04bef1, 0x3f18bf0e, 0x3f2cbf22,
    0x3d490000, 0x3e16bdc9, 0x3e79be48, 0x3eacbe95,
};
__device__ const __align__(128) uint32_t c_ga[1536] = {
    0x00003c80, 0x3bc43c6d, 0x00003c80, 0xbbc4bc6d, 0x00003c80, 0x3c6d3bc4, 0x00003c80, 0xbc6dbbc4, 0x00003c80, 0x3c6dbbc4,
    0x00003c80, 0xbc6d3bc4, 0x00003c80, 0x3bc4bc6d, 0x00003c80, 0xbbc43c6d, 0x3a493c80, 0x3bdb3c67, 0x3bdb3c67, 0xbc3ebc2c,
    0x3b163c7d, 0x3c783b79, 0x3c043c5c, 0xbc7d3b16, 0x3b793c78, 0x3c4ebc18, 0x3c183c4e, 0xbc043c5c, 0x3bac3c71, 0x3a49bc80,
    0x3c2c3c3e, 0x3bac3c71, 0x3ac93c7f, 0x3bf13c62, 0x3c463c22, 0xbc75bb95, 0x3b953c75, 0x3c7f3ac9, 0x3c623bf1, 0xbc463c22,
    0x3bf13c62, 0x3c22bc46, 0x3c753b95, 0x3ac93c7f, 0x3c223c46, 0xbb95bc75, 0x3c7f3ac9, 0x3c623bf1, 0x3b163c7d, 0x3c043c5c,
    0x3c783b79, 0xbc7d3b16, 0x3bdb3c67, 0x3c80ba49, 0x3c80ba49, 0xbbac3c71, 0x3c2c3c3e, 0x3bdbbc67, 0x3c71bbac, 0x3c2c3c3e,
    0x3c5c3c04, 0xbc18bc4e, 0x3c4ebc18, 0x3c78bb79, 0x3b483c7b, 0x3c0e3c55, 0x3c7bbb48, 0xbc553c0e, 0x3c0e3c55, 0x3c7bbb48,
    0x3c55bc0e, 0x3b483c7b, 0x3c553c0e, 0x3b48bc7b, 0x3c0ebc55, 0x3c7b3b48, 0x3c7b3b48, 0xbc55bc0e, 0x3b48bc7b, 0x3c0ebc55,
    0x3b793c78, 0x3c183c4e, 0x3c4ebc18, 0xbc043c5c, 0x3c2c3c3e, 0x3c71bbac, 0x3bdbbc67, 0x3c2c3c3e, 0x3c713bac, 0xba49bc80,
    0xba49bc80, 0x3c67bbdb, 0x3c7dbb16, 0xbc78bb79, 0xbc04bc5c, 0xbb16bc7d, 0x3b953c75, 0x3c223c46, 0x3bf1bc62, 0xbac93c7f,
    0x3c463c22, 0x3c62bbf1, 0xbac9bc7f, 0x3c753b95, 0x3c7f3ac9, 0xbb95bc75, 0xbc22bc46, 0x3bf1bc62, 0x3c62bbf1, 0xbc7f3ac9,
    0xbc75bb95, 0xbc46bc22, 0x3bac3c71, 0x3c2c3c3e, 0x3a49bc80, 0x3bac3c71, 0x3c5c3c04, 0x3c4ebc18, 0xbc18bc4e, 0x3c78bb79,
    0x3c7dbb16, 0xbc04bc5c, 0xbc78bb79, 0xbb16bc7d, 0x3c2cbc3e, 0xbc673bdb, 0xbc673bdb, 0xbc803a49, 0x00003c80, 0x3bc43c6d,
    0x00003c80, 0xbbc4bc6d, 0x00003c80, 0x3c6d3bc4, 0x00003c80, 0xbc6dbbc4, 0x00003c80, 0x3c6dbbc4, 0x00003c80, 0xbc6d3bc4,
    0x00003c80, 0x3bc4bc6d, 0x00003c80, 0xbbc43c6d, 0x3c3e3c2c, 0x3c713bac, 0x3c713bac, 0xbc803a49, 0x3c4e3c18, 0x3c5cbc04,
    0x3c783b79, 0xbc183c4e, 0x3c5c3c04, 0x3b16bc7d, 0x3c7d3b16, 0x3b793c78, 0x3c673bdb, 0xbc2cbc3e, 0x3c803a49, 0x3c673bdb,
    0x3c7fbac9, 0x3c62bbf1, 0x3c22bc46, 0xbb953c75, 0x3c75bb95, 0x3ac9bc7f, 0x3bf1bc62, 0x3c223c46, 0x3c62bbf1, 0xbc46bc22,
    0x3b95bc75, 0x3c7fbac9, 0x3c46bc22, 0xbc753b95, 0x3ac9bc7f, 0x3bf1bc62, 0x3c18bc4e, 0x3b79bc78, 0xbc04bc5c, 0x3c4e3c18,
    0x3bacbc71, 0xbc3ebc2c, 0xbc3ebc2c, 0x3c67bbdb, 0x3a49bc80, 0xbc713bac, 0xbc67bbdb, 0x3a49bc80, 0xbb79bc78, 0xbb163c7d,
    0xbc7dbb16, 0xbc5cbc04, 0xbb48bc7b, 0xbc0ebc55, 0xbc7b3b48, 0x3c55bc0e, 0xbc0ebc55, 0xbc7b3b48, 0xbc553c0e, 0xbb48bc7b,
    0xbc55bc0e, 0xbb483c7b, 0xbc0e3c55, 0xbc7bbb48, 0xbc7bbb48, 0x3c553c0e, 0xbb483c7b, 0xbc0e3c55, 0xbc5cbc04, 0xbc7dbb16,
    0xbb163c7d, 0xbb79bc78, 0xbc80ba49, 0xbbdb3c67, 0x3bac3c71, 0xbc80ba49, 0xbc673bdb, 0x3c3e3c2c, 0x3c3e3c2c, 0xbbac3c71,
    0xbc183c4e, 0x3c5cbc04, 0x3c783b79, 0x3c4e3c18, 0xbc753b95, 0xbc463c22, 0x3c623bf1, 0xbc7fbac9, 0xbc223c46, 0x3bf13c62,
    0x3c7fbac9, 0xbb953c75, 0xbac93c7f, 0x3c75bb95, 0x3c46bc22, 0x3c623bf1, 0x3bf13c62, 0xbac9bc7f, 0x3b95bc75, 0x3c22bc46,
    0xbbdb3c67, 0xba493c80, 0x3c3ebc2c, 0xbbdb3c67, 0x3b793c78, 0x3c7d3b16, 0x3b16bc7d, 0x3c5c3c04, 0x3c4e3c18, 0x3b79bc78,
    0xbc04bc5c, 0x3c18bc4e, 0x3c80ba49, 0xbc71bbac, 0xbc71bbac, 0xbc3ebc2c, 0x00003c80, 0x3bc43c6d, 0x00003c80, 0xbbc4bc6d,
    0x00003c80, 0x3c6d3bc4, 0x00003c80, 0xbc6dbbc4, 0x00003c80, 0x3c6dbbc4, 0x00003c80, 0xbc6d3bc4, 0x00003c80, 0x3bc4bc6d,
    0x00003c80, 0xbbc43c6d, 0x3c80ba49, 0x3c67bbdb, 0x3c67bbdb, 0xbc2c3c3e, 0x3c7dbb16, 0x3b79bc78, 0x3c5cbc04, 0x3b163c7d,
    0x3c78bb79, 0xbc18bc4e, 0x3c4ebc18, 0x3c5c3c04, 0x3c71bbac, 0xbc80ba49, 0x3c3ebc2c, 0x3c71bbac, 0xbac9bc7f, 0xbbf1bc62,
    0xbc46bc22, 0x3c753b95, 0xbb95bc75, 0xbc7fbac9, 0xbc62bbf1, 0x3c46bc22, 0xbbf1bc62, 0xbc223c46, 0xbc75bb95, 0xbac9bc7f,
    0xbc22bc46, 0x3b953c75, 0xbc7fbac9, 0xbc62bbf1, 0xbc7d3b16, 0xbc5c3c04, 0xbb793c78, 0xbb16bc7d, 0xbc673bdb, 0x3a493c80,
    0x3a493c80, 0xbc71bbac, 0xbc3e3c2c, 0x3c673bdb, 0x3bac3c71, 0xbc3e3c2c, 0xbc043c5c, 0x3c4ebc18, 0x3c183c4e, 0x3b793c78,
    0x3b483c7b, 0x3c0e3c55, 0x3c7bbb48, 0xbc553c0e, 0x3c0e3c55, 0x3c7bbb48, 0x3c55bc0e, 0x3b483c7b, 0x3c553c0e, 0x3b48bc7b,
    0x3c0ebc55, 0x3c7b3b48, 0x3c7b3b48, 0xbc55bc0e, 0x3b48bc7b, 0x3c0ebc55, 0x3c78bb79, 0x3c4ebc18, 0xbc18bc4e, 0x3c5c3c04,
    0x3c3ebc2c, 0xbbacbc71, 0xbc67bbdb, 0x3c3ebc2c, 0x3bacbc71, 0xbc803a49, 0xbc803a49, 0xbbdbbc67, 0xbb16bc7d, 0xbb793c78,
    0xbc5c3c04, 0xbc7d3b16, 0xbb95bc75, 0xbc22bc46, 0xbbf13c62, 0x3ac9bc7f, 0xbc46bc22, 0xbc623bf1, 0x3ac93c7f, 0xbc75bb95,
    0xbc7fbac9, 0x3b953c75, 0x3c223c46, 0xbbf13c62, 0xbc623bf1, 0x3c7fbac9, 0x3c753b95, 0x3c463c22, 0xbc713bac, 0xbc3e3c2c,
    0x3c803a49, 0xbc713bac, 0xbc043c5c, 0x3c183c4e, 0x3c4ebc18, 0x3b793c78, 0x3b163c7d, 0x3c5cbc04, 0x3b79bc78, 0x3c7dbb16,
    0x3c3e3c2c, 0xbbdbbc67, 0xbbdbbc67, 0xba49bc80, 0x00003c80, 0x3bc43c6d, 0x00003c80, 0xbbc4bc6d, 0x00003c80, 0x3c6d3bc4,
    0x00003c80, 0xbc6dbbc4, 0x00003c80, 0x3c6dbbc4, 0x00003c80, 0xbc6d3bc4, 0x00003c80, 0x3bc4bc6d, 0x00003c80, 0xbbc43c6d,
    0x3c2cbc3e, 0x3bacbc71, 0x3bacbc71, 0x3a493c80, 0x3c18bc4e, 0xbc04bc5c, 0x3b79bc78, 0x3c4e3c18, 0x3c04bc5c, 0xbc7dbb16,
    0x3b16bc7d, 0x3c78bb79, 0x3bdbbc67, 0xbc3e3c2c, 0x3a49bc80, 0x3bdbbc67, 0xbc7f3ac9, 0xbc623bf1, 0xbc223c46, 0x3b95bc75,
    0xbc753b95, 0xbac93c7f, 0xbbf13c62, 0xbc22bc46, 0xbc623bf1, 0x3c463c22, 0xbb953c75, 0xbc7f3ac9, 0xbc463c22, 0x3c75bb95,
    0xbac93c7f, 0xbbf13c62, 0x3c4e3c18, 0x3c783b79, 0x3c5cbc04, 0xbc183c4e, 0x3c713bac, 0x3c2cbc3e, 0x3c2cbc3e, 0x3bdb3c67,
    0x3c803a49, 0xbbacbc71, 0x3bdbbc67, 0x3c803a49, 0x3c78bb79, 0xbc7dbb16, 0x3b16bc7d, 0x3c04bc5c, 0xbb48bc7b, 0xbc0ebc55,
    0xbc7b3b48, 0x3c55bc0e, 0xbc0ebc55, 0xbc7b3b48, 0xbc553c0e, 0xbb48bc7b, 0xbc55bc0e, 0xbb483c7b, 0xbc0e3c55, 0xbc7bbb48,
    0xbc7bbb48, 0x3c553c0e, 0xbb483c7b, 0xbc0e3c55, 0xbc043c5c, 0xbb163c7d, 0x3c7d3b16, 0xbc783b79, 0xba493c80, 0x3c673bdb,
    0x3c71bbac, 0xba493c80, 0x3bdb3c67, 0x3c2cbc3e, 0x3c2cbc3e, 0x3c713bac, 0x3c4e3c18, 0xbc04bc5c, 0x3b79bc78, 0x3c18bc4e,
    0x3c75bb95, 0x3c46bc22, 0xbc62bbf1, 0x3c7f3ac9, 0x3c22bc46, 0xbbf1bc62, 0xbc7f3ac9, 0x3b95bc75, 0x3ac9bc7f, 0xbc753b95,
    0xbc463c22, 0xbc62bbf1, 0xbbf1bc62, 0x3ac93c7f, 0xbb953c75, 0xbc223c46, 0xbc67bbdb, 0xbc80ba49, 0x3c2c3c3e, 0xbc67bbdb,
    0xbc783b79, 0xbb163c7d, 0x3c7d3b16, 0xbc043c5c, 0xbc183c4e, 0x3c783b79, 0x3c5cbc04, 0x3c4e3c18, 0x3a493c80, 0x3bacbc71,
    0x3bacbc71, 0x3c2cbc3e, 0x3c353c35, 0x3c6d3bc4, 0x3c353c35, 0xbc6dbbc4, 0x3c35bc35, 0xbbc4bc6d, 0x3c35bc35, 0x3bc43c6d,
    0xbc35bc35, 0xbbc43c6d, 0xbc35bc35, 0x3bc4bc6d, 0xbc353c35, 0x3c6dbbc4, 0xbc353c35, 0xbc6d3bc4, 0x3c3e3c2c, 0x3c713bac,
    0x3c713bac, 0xbc803a49, 0x3c18bc4e, 0xbc04bc5c, 0x3b79bc78, 0x3c4e3c18, 0xbc5cbc04, 0xbb163c7d, 0xbc7dbb16, 0xbb79bc78,
    0xbbdb3c67, 0x3c3ebc2c, 0xba493c80, 0xbbdb3c67, 0x3c463c22, 0x3c753b95, 0x3c7fbac9, 0xbc623bf1, 0x3bf1bc62, 0xbc22bc46,
    0xbb95bc75, 0x3c7f3ac9, 0xbc75bb95, 0x3ac93c7f, 0xbc623bf1, 0xbc46bc22, 0xbac93c7f, 0x3bf1bc62, 0x3c223c46, 0x3b953c75,
    0x3c4e3c18, 0x3c783b79, 0x3c5cbc04, 0xbc183c4e, 0x3bacbc71, 0xbc3ebc2c, 0xbc3ebc2c, 0x3c67bbdb, 0xbc80ba49, 0x3bac3c71,
    0xbbdb3c67, 0xbc80ba49, 0x3b793c78, 0x3b16bc7d, 0x3c7d3b16, 0x3c5c3c04, 0x3c553c0e, 0x3c7b3b48, 0x3c0ebc55, 0xbb483c7b,
    0x3b48bc7b, 0xbc55bc0e, 0xbc7bbb48, 0x3c0ebc55, 0xbc7b3b48, 0x3c0e3c55, 0x3b483c7b, 0xbc553c0e, 0x3c0e3c55, 0xbb48bc7b,
    0x3c55bc0e, 0x3c7bbb48, 0x3c5c3c04, 0x3c7d3b16, 0x3b16bc7d, 0x3b793c78, 0x3a49bc80, 0xbc67bbdb, 0xbc713bac, 0x3a49bc80,
    0xbc673bdb, 0x3c3e3c2c, 0x3c3e3c2c, 0xbbac3c71, 0x3c4e3c18, 0xbc04bc5c, 0x3b79bc78, 0x3c18bc4e, 0x3c623bf1, 0x3c7f3ac9,
    0xbb95bc75, 0x3c223c46, 0xbac9bc7f, 0xbc75bb95, 0xbc223c46, 0xbbf1bc62, 0xbc463c22, 0x3c623bf1, 0x3c7f3ac9, 0x3b953c75,
    0x3c753b95, 0xbc46bc22, 0xbbf1bc62, 0xbac9bc7f, 0x3c673bdb, 0x3c803a49, 0xbc2cbc3e, 0x3c673bdb, 0xbb79bc78, 0xbc7dbb16,
    0xbb163c7d, 0xbc5cbc04, 0xbc183c4e, 0x3c783b79, 0x3c5cbc04, 0x3c4e3c18, 0x3c80ba49, 0xbc71bbac, 0xbc71bbac, 0xbc3ebc2c,
    0x3c353c35, 0x3c6d3bc4, 0x3c353c35, 0xbc6dbbc4, 0x3c35bc35, 0xbbc4bc6d, 0x3c35bc35, 0x3bc43c6d, 0xbc35bc35, 0xbbc43c6d,
    0xbc35bc35, 0x3bc4bc6d, 0xbc353c35, 0x3c6dbbc4, 0xbc353c35, 0xbc6d3bc4, 0x3c80ba49, 0x3c67bbdb, 0x3c67bbdb, 0xbc2c3c3e,
    0xbb16bc7d, 0xbc78bb79, 0xbc04bc5c, 0x3c7dbb16, 0xbc783b79, 0x3c183c4e, 0xbc4e3c18, 0xbc5cbc04, 0x3bac3c71, 0x3a49bc80,
    0x3c2c3c3e, 0x3bac3c71, 0x3c22bc46, 0x3b95bc75, 0xbac9bc7f, 0x3bf13c62, 0xbc62bbf1, 0xbc463c22, 0xbc753b95, 0x3ac9bc7f,
    0xbb953c75, 0x3c7fbac9, 0x3bf13c62, 0xbc223c46, 0x3c7f3ac9, 0xbc62bbf1, 0x3c46bc22, 0x3c75bb95, 0xbb16bc7d, 0xbc04bc5c,
    0xbc78bb79, 0x3c7dbb16, 0xbc673bdb, 0x3a493c80, 0x3a493c80, 0xbc71bbac, 0x3c2c3c3e, 0x3bdbbc67, 0x3c71bbac, 0x3c2c3c3e,
    0x3c04bc5c, 0xbc4e3c18, 0xbc18bc4e, 0xbb79bc78, 0xbc55bc0e, 0xbc7bbb48, 0xbc0e3c55, 0x3b48bc7b, 0xbb483c7b, 0x3c553c0e,
    0x3c7b3b48, 0xbc0e3c55, 0x3c7bbb48, 0xbc0ebc55, 0xbb48bc7b, 0x3c55bc0e, 0xbc0ebc55, 0x3b483c7b, 0xbc553c0e, 0xbc7b3b48,
    0xbc783b79, 0xbc4e3c18, 0x3c183c4e, 0xbc5cbc04, 0x3c2c3c3e, 0x3c71bbac, 0x3bdbbc67, 0x3c2c3c3e, 0x3bacbc71, 0xbc803a49,
    0xbc803a49, 0xbbdbbc67, 0xbc7d3b16, 0x3c783b79, 0x3c043c5c, 0x3b163c7d, 0xbbf13c62, 0xbac93c7f, 0x3c75bb95, 0xbc463c22,
    0x3c7fbac9, 0x3b95bc75, 0xbc46bc22, 0x3c62bbf1, 0xbc22bc46, 0xbbf13c62, 0xbac93c7f, 0xbc753b95, 0xbb953c75, 0x3c22bc46,
    0x3c62bbf1, 0x3c7fbac9, 0x3bac3c71, 0x3c2c3c3e, 0x3a49bc80, 0x3bac3c71, 0x3c04bc5c, 0xbc18bc4e, 0xbc4e3c18, 0xbb79bc78,
    0xbc7d3b16, 0x3c043c5c, 0x3c783b79, 0x3b163c7d, 0x3c3e3c2c, 0xbbdbbc67, 0xbbdbbc67, 0xba49bc80, 0x3c353c35, 0x3c6d3bc4,
    0x3c353c35, 0xbc6dbbc4, 0x3c35bc35, 0xbbc4bc6d, 0x3c35bc35, 0x3bc43c6d, 0xbc35bc35, 0xbbc43c6d, 0xbc35bc35, 0x3bc4bc6d,
    0xbc353c35, 0x3c6dbbc4, 0xbc353c35, 0xbc6d3bc4, 0x3c2cbc3e, 0x3bacbc71, 0x3bacbc71, 0x3a493c80, 0xbc4ebc18, 0xbc5c3c04,
    0xbc78bb79, 0x3c18bc4e, 0xbc043c5c, 0x3c7d3b16, 0xbb163c7d, 0xbc783b79, 0x3c673bdb, 0xbc2cbc3e, 0x3c803a49, 0x3c673bdb,
    0xbc46bc22, 0xbc75bb95, 0xbc7f3ac9, 0x3c62bbf1, 0xbbf13c62, 0x3c223c46, 0x3b953c75, 0xbc7fbac9, 0x3c753b95, 0xbac9bc7f,
    0x3c62bbf1, 0x3c463c22, 0x3ac9bc7f, 0xbbf13c62, 0xbc22bc46, 0xbb95bc75, 0xbc183c4e, 0xbb793c78, 0x3c043c5c, 0xbc4ebc18,
    0x3c713bac, 0x3c2cbc3e, 0x3c2cbc3e, 0x3bdb3c67, 0x3a49bc80, 0xbc713bac, 0xbc67bbdb, 0x3a49bc80, 0xbc783b79, 0x3c7d3b16,
    0xbb163c7d, 0xbc043c5c, 0x3c553c0e, 0x3c7b3b48, 0x3c0ebc55, 0xbb483c7b, 0x3b48bc7b, 0xbc55bc0e, 0xbc7bbb48, 0x3c0ebc55,
    0xbc7b3b48, 0x3c0e3c55, 0x3b483c7b, 0xbc553c0e, 0x3c0e3c55, 0xbb48bc7b, 0x3c55bc0e, 0x3c7bbb48, 0x3c04bc5c, 0x3b16bc7d,
    0xbc7dbb16, 0x3c78bb79, 0xbc80ba49, 0xbbdb3c67, 0x3bac3c71, 0xbc80ba49, 0x3bdb3c67, 0x3c2cbc3e, 0x3c2cbc3e, 0x3c713bac,
    0x3c18bc4e, 0xbc5c3c04, 0xbc78bb79, 0xbc4ebc18, 0xbc62bbf1, 0xbc7fbac9, 0x3b953c75, 0xbc22bc46, 0x3ac93c7f, 0x3c753b95,
    0x3c22bc46, 0x3bf13c62, 0x3c46bc22, 0xbc62bbf1, 0xbc7fbac9, 0xbb95bc75, 0xbc75bb95, 0x3c463c22, 0x3bf13c62, 0x3ac93c7f,
    0xbbdb3c67, 0xba493c80, 0x3c3ebc2c, 0xbbdb3c67, 0x3c78bb79, 0x3b16bc7d, 0xbc7dbb16, 0x3c04bc5c, 0xbc4ebc18, 0xbb793c78,
    0x3c043c5c, 0xbc183c4e, 0x3a493c80, 0x3bacbc71, 0x3bacbc71, 0x3c2cbc3e, 0x3c353c35, 0x3c6d3bc4, 0x3c353c35, 0xbc6dbbc4,
    0x3c35bc35, 0xbbc4bc6d, 0x3c35bc35, 0x3bc43c6d, 0xbc35bc35, 0xbbc43c6d, 0xbc35bc35, 0x3bc4bc6d, 0xbc353c35, 0x3c6dbbc4,
    0xbc353c35, 0xbc6d3bc4, 0xba49bc80, 0xbbdbbc67, 0xbbdbbc67, 0x3c3e3c2c, 0xbc7d3b16, 0xbb793c78, 0xbc5c3c04, 0xbb16bc7d,
    0x3b793c78, 0x3c4ebc18, 0x3c183c4e, 0xbc043c5c, 0x3c71bbac, 0xbc80ba49, 0x3c3ebc2c, 0x3c71bbac, 0xbc223c46, 0xbb953c75,
    0x3ac93c7f, 0xbbf1bc62, 0x3c623bf1, 0x3c46bc22, 0x3c75bb95, 0xbac93c7f, 0x3b95bc75, 0xbc7f3ac9, 0xbbf1bc62, 0x3c22bc46,
    0xbc7fbac9, 0x3c623bf1, 0xbc463c22, 0xbc753b95, 0x3c7dbb16, 0x3c5cbc04, 0x3b79bc78, 0x3b163c7d, 0xbbdbbc67, 0xbc803a49,
    0xbc803a49, 0x3bacbc71, 0xbc3e3c2c, 0x3c673bdb, 0x3bac3c71, 0xbc3e3c2c, 0x3c5c3c04, 0xbc18bc4e, 0x3c4ebc18, 0x3c78bb79,
    0xbc55bc0e, 0xbc7bbb48, 0xbc0e3c55, 0x3b48bc7b, 0xbb483c7b, 0x3c553c0e, 0x3c7b3b48, 0xbc0e3c55, 0x3c7bbb48, 0xbc0ebc55,
    0xbb48bc7b, 0x3c55bc0e, 0xbc0ebc55, 0x3b483c7b, 0xbc553c0e, 0xbc7b3b48, 0x3b793c78, 0x3c183c4e, 0x3c4ebc18, 0xbc043c5c,
    0x3c3ebc2c, 0xbbacbc71, 0xbc67bbdb, 0x3c3ebc2c, 0xbc71bbac, 0x3a493c80, 0x3a493c80, 0xbc673bdb, 0x3b163c7d, 0x3b79bc78,
    0x3c5cbc04, 0x3c7dbb16, 0x3bf1bc62, 0x3ac9bc7f, 0xbc753b95, 0x3c46bc22, 0xbc7f3ac9, 0xbb953c75, 0x3c463c22, 0xbc623bf1,
    0x3c223c46, 0x3bf1bc62, 0x3ac9bc7f, 0x3c75bb95, 0x3b95bc75, 0xbc223c46, 0xbc623bf1, 0xbc7f3ac9, 0xbc713bac, 0xbc3e3c2c,
    0x3c803a49, 0xbc713bac, 0x3c5c3c04, 0x3c4ebc18, 0xbc18bc4e, 0x3c78bb79, 0xbb16bc7d, 0xbc5c3c04, 0xbb793c78, 0xbc7d3b16,
    0xbc2c3c3e, 0x3c67bbdb, 0x3c67bbdb, 0x3c80ba49, 0x3c800000, 0x3c6dbbc4, 0x3c800000, 0xbc6d3bc4, 0xbc800000, 0xbbc43c6d,
    0xbc800000, 0x3bc4bc6d, 0x3c800000, 0xbbc4bc6d, 0x3c800000, 0x3bc43c6d, 0xbc800000, 0x3c6d3bc4, 0xbc800000, 0xbc6dbbc4,
    0x3c80ba49, 0x3c67bbdb, 0x3c67bbdb, 0xbc2c3c3e, 0xbc7d3b16, 0xbb793c78, 0xbc5c3c04, 0xbb16bc7d, 0x3c78bb79, 0xbc18bc4e,
    0x3c4ebc18, 0x3c5c3c04, 0xbc713bac, 0x3c803a49, 0xbc3e3c2c, 0xbc713bac, 0x3c7fbac9, 0x3c62bbf1, 0x3c22bc46, 0xbb953c75,
    0xbc753b95, 0xbac93c7f, 0xbbf13c62, 0xbc22bc46, 0x3c62bbf1, 0xbc46bc22, 0x3b95bc75, 0x3c7fbac9, 0xbc463c22, 0x3c75bb95,
    0xbac93c7f, 0xbbf13c62, 0x3c7dbb16, 0x3c5cbc04, 0x3b79bc78, 0x3b163c7d, 0xbc673bdb, 0x3a493c80, 0x3a493c80, 0xbc71bbac,
    0x3c3ebc2c, 0xbc67bbdb, 0xbbacbc71, 0x3c3ebc2c, 0xbc043c5c, 0x3c4ebc18, 0x3c183c4e, 0x3b793c78, 0x3c7bbb48, 0x3c55bc0e,
    0xbb48bc7b, 0x3c0e3c55, 0xbc553c0e, 0x3b483c7b, 0x3c0e3c55, 0xbc7b3b48, 0x3c0ebc55, 0xbc7bbb48, 0xbc55bc0e, 0x3b48bc7b,
    0xbb483c7b, 0x3c0ebc55, 0x3c7b3b48, 0x3c553c0e, 0x3c78bb79, 0x3c4ebc18, 0xbc18bc4e, 0x3c5c3c04, 0xbc3e3c2c, 0x3bac3c71,
    0x3c673bdb, 0xbc3e3c2c, 0x3bacbc71, 0xbc803a49, 0xbc803a49, 0xbbdbbc67, 0x3b163c7d, 0x3b79bc78, 0x3c5cbc04, 0x3c7dbb16,
    0x3c75bb95, 0x3c46bc22, 0xbc62bbf1, 0x3c7f3ac9, 0xbc223c46, 0x3bf13c62, 0x3c7fbac9, 0xbb953c75, 0x3ac9bc7f, 0xbc753b95,
    0xbc463c22, 0xbc62bbf1, 0x3bf13c62, 0xbac9bc7f, 0x3b95bc75, 0x3c22bc46, 0x3c71bbac, 0x3c3ebc2c, 0xbc80ba49, 0x3c71bbac,
    0xbc043c5c, 0x3c183c4e, 0x3c4ebc18, 0x3b793c78, 0xbb16bc7d, 0xbc5c3c04, 0xbb793c78, 0xbc7d3b16, 0x3c3e3c2c, 0xbbdbbc67,
    0xbbdbbc67, 0xba49bc80, 0x3c800000, 0x3c6dbbc4, 0x3c800000, 0xbc6d3bc4, 0xbc800000, 0xbbc43c6d, 0xbc800000, 0x3bc4bc6d,
    0x3c800000, 0xbbc4bc6d, 0x3c800000, 0x3bc43c6d, 0xbc800000, 0x3c6d3bc4, 0xbc800000, 0xbc6dbbc4, 0x3c2cbc3e, 0x3bacbc71,
    0x3bacbc71, 0x3a493c80, 0xbc183c4e, 0x3c043c5c, 0xbb793c78, 0xbc4ebc18, 0x3c04bc5c, 0xbc7dbb16, 0x3b16bc7d, 0x3c78bb79,
    0xbbdb3c67, 0x3c3ebc2c, 0xba493c80, 0xbbdb3c67, 0xbac9bc7f, 0xbbf1bc62, 0xbc46bc22, 0x3c753b95, 0x3b953c75, 0x3c7f3ac9,
    0x3c623bf1, 0xbc463c22, 0xbbf1bc62, 0xbc223c46, 0xbc75bb95, 0xbac9bc7f, 0x3c223c46, 0xbb95bc75, 0x3c7f3ac9, 0x3c623bf1,
    0xbc4ebc18, 0xbc78bb79, 0xbc5c3c04, 0x3c18bc4e, 0x3c713bac, 0x3c2cbc3e, 0x3c2cbc3e, 0x3bdb3c67, 0xbc80ba49, 0x3bac3c71,
    0xbbdb3c67, 0xbc80ba49, 0x3c78bb79, 0xbc7dbb16, 0x3b16bc7d, 0x3c04bc5c, 0xbc7b3b48, 0xbc553c0e, 0x3b483c7b, 0xbc0ebc55,
    0x3c55bc0e, 0xbb48bc7b, 0xbc0ebc55, 0x3c7bbb48, 0xbc0e3c55, 0x3c7b3b48, 0x3c553c0e, 0xbb483c7b, 0x3b48bc7b, 0xbc0e3c55,
    0xbc7bbb48, 0xbc55bc0e, 0xbc043c5c, 0xbb163c7d, 0x3c7d3b16, 0xbc783b79, 0x3a49bc80, 0xbc67bbdb, 0xbc713bac, 0x3a49bc80,
    0x3bdb3c67, 0x3c2cbc3e, 0x3c2cbc3e, 0x3c713bac, 0xbc4ebc18, 0x3c043c5c, 0xbb793c78, 0xbc183c4e, 0x3b953c75, 0x3c223c46,
    0x3bf1bc62, 0xbac93c7f, 0xbc46bc22, 0xbc623bf1, 0x3ac93c7f, 0xbc75bb95, 0x3c7f3ac9, 0xbb95bc75, 0xbc22bc46, 0x3bf1bc62,
    0xbc623bf1, 0x3c7fbac9, 0x3c753b95, 0x3c463c22, 0x3c673bdb, 0x3c803a49, 0xbc2cbc3e, 0x3c673bdb, 0xbc783b79, 0xbb163c7d,
    0x3c7d3b16, 0xbc043c5c, 0x3c18bc4e, 0xbc78bb79, 0xbc5c3c04, 0xbc4ebc18, 0x3a493c80, 0x3bacbc71, 0x3bacbc71, 0x3c2cbc3e,
    0x3c800000, 0x3c6dbbc4, 0x3c800000, 0xbc6d3bc4, 0xbc800000, 0xbbc43c6d, 0xbc800000, 0x3bc4bc6d, 0x3c800000, 0xbbc4bc6d,
    0x3c800000, 0x3bc43c6d, 0xbc800000, 0x3c6d3bc4, 0xbc800000, 0xbc6dbbc4, 0xba49bc80, 0xbbdbbc67, 0xbbdbbc67, 0x3c3e3c2c,
    0x3b163c7d, 0x3c783b79, 0x3c043c5c, 0xbc7d3b16, 0xbb79bc78, 0xbc4e3c18, 0xbc18bc4e, 0x3c04bc5c, 0x3bac3c71, 0x3a49bc80,
    0x3c2c3c3e, 0x3bac3c71, 0xbc7f3ac9, 0xbc623bf1, 0xbc223c46, 0x3b95bc75, 0x3c75bb95, 0x3ac9bc7f, 0x3bf1bc62, 0x3c223c46,
    0xbc623bf1, 0x3c463c22, 0xbb953c75, 0xbc7f3ac9, 0x3c46bc22, 0xbc753b95, 0x3ac9bc7f, 0x3bf1bc62, 0x3b163c7d, 0x3c043c5c,
    0x3c783b79, 0xbc7d3b16, 0xbbdbbc67, 0xbc803a49, 0xbc803a49, 0x3bacbc71, 0x3c2c3c3e, 0x3bdbbc67, 0x3c71bbac, 0x3c2c3c3e,
    0xbc5cbc04, 0x3c183c4e, 0xbc4e3c18, 0xbc783b79, 0x3c7bbb48, 0x3c55bc0e, 0xbb48bc7b, 0x3c0e3c55, 0xbc553c0e, 0x3b483c7b,
    0x3c0e3c55, 0xbc7b3b48, 0x3c0ebc55, 0xbc7bbb48, 0xbc55bc0e, 0x3b48bc7b, 0xbb483c7b, 0x3c0ebc55, 0x3c7b3b48, 0x3c553c0e,
    0xbb79bc78, 0xbc18bc4e, 0xbc4e3c18, 0x3c04bc5c, 0x3c2c3c3e, 0x3c71bbac, 0x3bdbbc67, 0x3c2c3c3e, 0xbc71bbac, 0x3a493c80,
    0x3a493c80, 0xbc673bdb, 0x3c7dbb16, 0xbc78bb79, 0xbc04bc5c, 0xbb16bc7d, 0xbc753b95, 0xbc463c22, 0x3c623bf1, 0xbc7fbac9,
    0x3c22bc46, 0xbbf1bc62, 0xbc7f3ac9, 0x3b95bc75, 0xbac93c7f, 0x3c75bb95, 0x3c46bc22, 0x3c623bf1, 0xbbf1bc62, 0x3ac93c7f,
    0xbb953c75, 0xbc223c46, 0x3bac3c71, 0x3c2c3c3e, 0x3a49bc80, 0x3bac3c71, 0xbc5cbc04, 0xbc4e3c18, 0x3c183c4e, 0xbc783b79,
    0x3c7dbb16, 0xbc04bc5c, 0xbc78bb79, 0xbb16bc7d, 0xbc2c3c3e, 0x3c67bbdb, 0x3c67bbdb, 0x3c80ba49, 0x3c800000, 0x3c6dbbc4,
    0x3c800000, 0xbc6d3bc4, 0xbc800000, 0xbbc43c6d, 0xbc800000, 0x3bc4bc6d, 0x3c800000, 0xbbc4bc6d, 0x3c800000, 0x3bc43c6d,
    0xbc800000, 0x3c6d3bc4, 0xbc800000, 0xbc6dbbc4, 0xbc3ebc2c, 0xbc71bbac, 0xbc71bbac, 0x3c80ba49, 0x3c4e3c18, 0x3c5cbc04,
    0x3c783b79, 0xbc183c4e, 0xbc5cbc04, 0xbb163c7d, 0xbc7dbb16, 0xbb79bc78, 0x3c673bdb, 0xbc2cbc3e, 0x3c803a49, 0x3c673bdb,
    0x3ac93c7f, 0x3bf13c62, 0x3c463c22, 0xbc75bb95, 0xbb95bc75, 0xbc7fbac9, 0xbc62bbf1, 0x3c46bc22, 0x3bf13c62, 0x3c22bc46,
    0x3c753b95, 0x3ac93c7f, 0xbc22bc46, 0x3b953c75, 0xbc7fbac9, 0xbc62bbf1, 0x3c18bc4e, 0x3b79bc78, 0xbc04bc5c, 0x3c4e3c18,
    0xbbac3c71, 0x3c3e3c2c, 0x3c3e3c2c, 0xbc673bdb, 0x3a49bc80, 0xbc713bac, 0xbc67bbdb, 0x3a49bc80, 0x3b793c78, 0x3b16bc7d,
    0x3c7d3b16, 0x3c5c3c04, 0xbc7b3b48, 0xbc553c0e, 0x3b483c7b, 0xbc0ebc55, 0x3c55bc0e, 0xbb48bc7b, 0xbc0ebc55, 0x3c7bbb48,
    0xbc0e3c55, 0x3c7b3b48, 0x3c553c0e, 0xbb483c7b, 0x3b48bc7b, 0xbc0e3c55, 0xbc7bbb48, 0xbc55bc0e, 0x3c5c3c04, 0x3c7d3b16,
    0x3b16bc7d, 0x3b793c78, 0xbc80ba49, 0xbbdb3c67, 0x3bac3c71, 0xbc80ba49, 0x3c67bbdb, 0xbc3ebc2c, 0xbc3ebc2c, 0x3bacbc71,
    0xbc183c4e, 0x3c5cbc04, 0x3c783b79, 0x3c4e3c18, 0xbb95bc75, 0xbc22bc46, 0xbbf13c62, 0x3ac9bc7f, 0x3c463c22, 0x3c62bbf1,
    0xbac9bc7f, 0x3c753b95, 0xbc7fbac9, 0x3b953c75, 0x3c223c46, 0xbbf13c62, 0x3c62bbf1, 0xbc7f3ac9, 0xbc75bb95, 0xbc46bc22,
    0xbbdb3c67, 0xba493c80, 0x3c3ebc2c, 0xbbdb3c67, 0xbb79bc78, 0xbc7dbb16, 0xbb163c7d, 0xbc5cbc04, 0x3c4e3c18, 0x3b79bc78,
    0xbc04bc5c, 0x3c18bc4e, 0xbc803a49, 0x3c713bac, 0x3c713bac, 0x3c3e3c2c,
};

#define G_EPI 3
#define G_TK 3
#define W_Q 6
#define W2_PC 32
#define W2_PF 3
constexpr int X_LOC0 = 5;
constexpr int A_IN = 112 * 128;
constexpr int G_ST = 2 * NB1 * 64;
constexpr int K1_R = 131072, K1_BAR = K1_R + 98304, K1_SMEM = K1_BAR + 2048 + 1024;
constexpr int K1_T = K1_R + 65536, K1_TIN = 0, K1_Y0 = 3 * G_ST + 8192, G_KM = 16 - G_TK, G_S0 = 2 * G_KM;
__device__ int g_done[8 * 32];
struct Ptrs {
  int* done;
  float* ge;
  const uint32_t *img, *ga;
};

__host__ __device__ constexpr int g_depth(int s) { return s < 11 ? 3 : s < 18 ? 4 : s < 23 ? 5 : 6; }
__host__ __device__ constexpr int g_slot(int s) { return s < 3 ? s : g_depth(s) != g_depth(s - 1) ? g_depth(s - 1) : g_slot(s - g_depth(s)); }
__host__ __device__ constexpr int g_off(int id) { return id * G_ST + (id < 3 ? K1_R : 8192 - 3 * G_ST); }
struct Plan {
  uint32_t raw[32];
  uint32_t x[16];
  uint32_t grp[8];
  uint32_t last;
  uint32_t wpf;
  uint32_t g0;
  uint32_t tmask;
  uint64_t list[2];
};
struct K1Maps {
  Plan p;
  CUtensorMap x, we, wo, xs, y, w2e, w2o, w2s;
  int slot[32];
  int src[32];
  int dep[32];
};
__device__ __forceinline__ void poll_ge(const int* p, int target) {
  for (int it = 0; it < (1 << 20); it++) {
    int v;
    asm volatile("ld.acquire.gpu.global.s32 %0, [%1];" : "=r"(v) : "l"(p) : "memory");
    if (v >= target) break;
  }
}
__device__ __forceinline__ uint32_t place(int rank, uint32_t c) { return (c ^ (rank * 4 & ~(c >> 1))) << 14; }
__device__ __forceinline__ int x_unit(int cta, int u, uint32_t pl) {
  const int i = u * 128 + cta;
  const int pr = cta >= 128 ? 2 * cta - 96 + (u & 1) : i % 160, sl = cta >= 128 ? u >> 1 : i / 160, b = pr >= 84;
  return pr | sl << 8 | b << 11 | (cta >= 128 ? (u & 7) << 14 : place(cta & 1, pl & 15)) | 12 * (pr - 84 * b) << 20;
}
__device__ __forceinline__ int lds32(uint32_t a) {
  int v;
  asm volatile("ld.shared.b32 %0, [%1];" : "=r"(v) : "r"(a));
  return v;
}
__host__ __device__ constexpr uint64_t sched(const char* p) {
  uint64_t r = 0;
  for (int n = 0; p[n]; n++) r |= (uint64_t)(p[n] - '0' + 1) << (5 * n);
  return r;
}

__global__ void __cluster_dims__(2, 1, 1) __launch_bounds__(384, 1)
k1(const Ptrs gp_, const char* __restrict__ x1, const char* __restrict__ w1, const __grid_constant__ K1Maps m, const __nv_bfloat16* __restrict__ g,
   const __nv_bfloat16* __restrict__ wgt) {
  extern __shared__ __align__(1024) uint8_t smem_k1[];
  const uint32_t sb = s2u(smem_k1);
  const int tid = threadIdx.x, cta = blockIdx.x, rank = cta & 1;
  if (tid == 288) {
    const uint32_t bar = sb + K1_BAR + 256, dst = sb + (cta >= 128 ? 0 : place(rank, X_LOC0));
    const int pr = cta >= 128 ? 2 * cta - 96 : cta, b = pr >= 84;
    mbar_init(bar, 1);
    mbar_expect(bar, A_IN);
    for (int h = 0; h < 2; h++) tma_ld4<1>(dst + h * (A_IN / 2), &m.x, bar, 0, 96 * (pr - 84 * b) - 24 + h * 56, 0, b);
    for (int i = 1; i < 4; i++) mbar_init(bar + 8 * i, 1);
    fence_bar_init();
  }
  const uint32_t sF = sb + (cta >= 128 ? K1_T : rank * 65536), fbar = sb + K1_BAR + 1792;
  if (tid == 320) {
    mbar_init(fbar, 1);
    mbar_expect(fbar, 8192);
    asm volatile("cp.async.bulk.shared::cluster.global.mbarrier::complete_tx::bytes [%0], [%1], 8192, [%2];" ::"r"(sF), "l"(gp_.img + 1536), "r"(fbar) : "memory");
    fence_bar_init();
  }
  const int wg = __shfl_sync(0xffffffffu, tid >> 7, 0), t = tid & 127;
  const int warp = __shfl_sync(0xffffffffu, t >> 5, 0), lane = t & 31;
  const bool spare = cta >= 128;
  const int nx = spare ? 16 : 10;
  int bp, dc;
  {
    const int ci = cta >> 1;
    const int G = ci < 4 ? 0 : ci < 36 ? (ci - 4) & 7 : 1 + (ci - 36) % 7;
    const int li = ci < 4 ? 4 + ci : ci < 36 ? (ci - 4) >> 3 : 4 + (ci - 36) / 7;
    bp = 2 * G + (li >> 2), dc = li & 3;
  }
  const int bin = 2 * bp + rank;
  const uint32_t bb = sb + K1_BAR;
  const uint32_t rfull = bb, xfull = bb + 256, xfree = bb + 384, gfull = bb + 512, win = bb + 1800, win1 = bb + 1808;
  const uint32_t inf0 = bb + 784, se0 = inf0 + 16, pfree = se0 + 16, rempty = bb + 1024, xready = bb + 1280;
  const uint32_t gdone = bb + 1536, ine0 = gdone + 224, sf0 = ine0 + 16;
  const uint32_t xtab = bb + 896, ptab = bb + 2048 + 768;
  auto raw_load = [&](int j, uint32_t dst) {
    mbar_expect(rfull + 8 * j, 16384);
    tma_ld4<0>(dst, rank ? &m.we : &m.wo, rfull + 8 * j, dc * 64, rank - 1, (j & 3) * 4, (j >> 2) * 2);
  };
  auto x_half = [&](int u, int c, int h) {
    tma_ld4<1>(sb + (c & 0x3C000) + h * (A_IN / 2), &m.x, xfull + 8 * u, 0, (c >> 17 & ~7) - 24 + h * 56, c >> 8 & 7, c >> 11 & 1);
  };
  auto w_prefetch = [&](int q) {
    if (cta < 124) asm volatile("cp.async.bulk.prefetch.L2.global [%0], 4096;" ::"l"(w1 + (cta >> 2) * 131072 + (q * 4 + (cta & 3)) * 4096) : "memory");
  };
  uint32_t peer;
  asm("mapa.shared::cluster.u32 %0, %1, %2;" : "=r"(peer) : "r"(sb), "r"(rank ^ 1));
  if (wg == 2) {
    if (lane == 0) {
      if (warp == 0) {
        for (int i = 0; i < 4; i++) mbar_init(bb + 8 * i, 1);
        fence_bar_init();
        if (!spare)
          for (int j = 0; j < 4; j++) raw_load(j, sb + K1_R + j * 16384);
      } else if (warp == 2) {
#pragma unroll 1
        for (int q = 1; q <= m.p.wpf; q++) w_prefetch(q);
        prefetch_map(&m.xs);
      }
    }
    if (warp == 3) {
      const uint32_t v = reinterpret_cast<const uint32_t*>(&m.p)[32 + lane];
      asm volatile("st.shared.b32 [%0], %1;" ::"r"(ptab + 4 * lane), "r"(m.p.raw[lane]) : "memory");
      asm volatile("st.shared.b32 [%0], %1;" ::"r"(ptab + 128 + 4 * lane), "r"(v) : "memory");
      if (lane < 16) asm volatile("st.shared.b32 [%0], %1;" ::"r"(xtab + 4 * lane), "r"(x_unit(cta, lane, v)) : "memory");
    }
  } else {
    const int c = 4 * wg + warp;
    if (lane == 0 && c < 7) {
      const uint32_t b0 = bb + 256 * c, n = c < 4 ? 1 : c < 6 ? 4 : 8;
      if (c >= 2)
        for (int i = 0; i < 4; i++) mbar_init(b0 + 8 * i, n);
      for (int i = 4; i < 16; i++) mbar_init(b0 + 8 * i, n);
      if (c == 3) {
        mbar_init(win, 1 + 2 * W_Q);
        mbar_init(win1, 17 - 2 * W_Q);
        mbar_expect(win, 8192 * W_Q);
        mbar_expect(win1, 65536 - 8192 * W_Q);
        mbar_arrive(bb + 776);
      } else {
        for (int i = 16; i < 32; i++) mbar_init(b0 + 8 * i, n);
      }
      fence_bar_init();
    }
  }
  pdl_launch();
  __syncthreads();
  asm volatile("barrier.cluster.arrive.relaxed.aligned;" ::: "memory");
  if (wg == 2) {
    asm volatile("setmaxnreg.dec.sync.aligned.u32 40;");
    asm volatile("barrier.cluster.wait.aligned;" ::: "memory");
    if (lane == 0) {
      const int wpf = lds32(ptab + 228), g0 = lds32(ptab + 232), s0 = g0 * 4 / 5;
      const int nx0 = spare ? 2 * s0 : g0;
      if (warp == 0) {
        if (!spare) {
#pragma unroll 1
          for (int j = 4; j < 32; j++) {
            const uint32_t e = lds32(ptab + 4 * j);
            mbar_wait(bb + (e >> 5 & ~7), 0);
            raw_load(j, sb + place(rank, e & 15));
            if ((j & 3) == 0 && wpf && (j >> 2) + wpf < 8) w_prefetch((j >> 2) + wpf);
          }
#pragma unroll 1
          for (int s = 0; s < 32; s++) {
            if (s == 0 || s == 4 * s0) {
              poll_ge(&gp_.done[(s ? 5 : 4) * 32], 132);
              asm volatile("fence.proxy.async.global;" ::: "memory");
              mbar_wait(bb + 8 * (lds32(ptab + 224) & 255), 0);
            }
            const uint32_t bar = gfull + 8 * s, dst = sb + 16 * m.slot[s];
            const char* src = x1 + bin * (4 * G_ST) + m.src[s];
            mbar_wait(bb + m.dep[s], 0);
            mbar_expect(bar, G_ST);
#pragma unroll
            for (int h = 0; h < 2; h++) {
              if (s >= 16)
                asm volatile("cp.async.bulk.shared::cluster.global.mbarrier::complete_tx::bytes.L2::cache_hint [%0], [%1], %2, [%3], %4;"
                             ::"r"(dst + h * (G_ST / 2)), "l"(src + h * (s < G_S0 ? G_ST / 2 : 2 * G_ST)), "n"(G_ST / 2), "r"(bar), "l"(policy<1>()) : "memory");
              else
                asm volatile("cp.async.bulk.shared::cluster.global.mbarrier::complete_tx::bytes [%0], [%1], %2, [%3];"
                             ::"r"(dst + h * (G_ST / 2)), "l"(src + h * (s < G_S0 ? G_ST / 2 : 2 * G_ST)), "n"(G_ST / 2), "r"(bar) : "memory");
            }
          }
          if (cta == 0) asm volatile("cp.async.bulk.prefetch.L2.global [%0], 14336;" ::"l"(gp_.img) : "memory");
        }
      } else if (warp < 3) {
        const int u0 = warp == 1 ? 0 : nx0, u1 = warp == 1 ? nx0 : nx;
#pragma unroll 1
        for (int u = u0; u < u1; u++) {
          const int c = lds32(xtab + 4 * u);
          const uint32_t e = spare ? 0xC0 : lds32(ptab + 128 + 4 * u);
          const uint32_t src = sb + (c & 0x3C000), rel = e >> 1 & 24, burst = (16 << (e >> 6 & 3)) - 1;
          mbar_wait(xready + 8 * u, 0);
#pragma unroll 1
          for (int p = 0; p < 128; p += 16) {
            tma_st4<0>(&m.xs, src + p * 128, 0, (c >> 2 & 0x1C0) + (p & 63), p >> 6, c & 255);
            if (((p + 16) & burst) == 0) {
              bulk_commit();
              bulk_wait_read<0>();
            }
          }
          mbar_arrive(xfree + 8 * u);
          if (rel)
            asm volatile("mbarrier.arrive.shared::cluster.b64 _, [%0];" ::"r"(peer + (pfree - sb) + rel) : "memory");
        }
        asm volatile("cp.async.bulk.wait_group 0;" ::: "memory");
        asm volatile("red.release.gpu.global.add.s32 [%0], 1;" ::"l"(&gp_.done[(3 + warp) * 32]) : "memory");
        if (!spare) {
          if (warp == 1) {
            auto w2_row = [&](int it, bool pf) {
              const CUtensorMap* mp = it & 1 ? &m.w2e : &m.w2o;
              const int c1 = (it & 1) - 1, c2 = (cta & 1) * 2, c3 = (it >> 1) * 64 + (cta >> 1);
              if (pf) {
                asm volatile("cp.async.bulk.prefetch.tensor.4d.L2.global [%0, {%1, %2, %3, %4}];" ::"l"(mp), "r"(0), "r"(c1), "r"(c2), "r"(c3) : "memory");
              } else {
                mbar_expect(inf0 + 8 * (it & 1), 4096);
                tma_ld4<1>(sb + K1_TIN + (it & 1) * 4096, mp, inf0 + 8 * (it & 1), 0, c1, c2, c3);
              }
            };
#pragma unroll 1
            for (int it = 0; it < W2_PF; it++) {
              mbar_wait(gfull + 8 * (it >> 1), 0);
              w2_row(it, true);
            }
            mbar_wait(gdone + 8, 0);
#pragma unroll 1
            for (int it = 0; it < 8; it++) {
              if (it >= 2) mbar_wait(ine0 + 8 * (it & 1), ((it >> 1) - 1) & 1);
              w2_row(it, false);
              if (W2_PF && it + W2_PF < 8) w2_row(it + W2_PF, true);
            }
          } else {
            prefetch_map(&m.w2s);
            prefetch_map(&m.y);
#pragma unroll 1
            for (int it = 0; it < 8; it++) {
              if ((0x74 >> it) & 1) poll_ge(&gp_.done[((0x33210000 >> (4 * it)) & 3) * 32], 128);
              mbar_wait(sf0 + 8 * (it & 1), (it >> 1) & 1);
#pragma unroll 1
              for (int p = 0; p < 128; p += W2_PC) {
                tma_st4<0>(&m.w2s, sb + K1_T + (it & 1) * 16384 + p * 128, 0, it * 64 + (p & 63), (cta & 1) * 2 + (p >> 6),
                           (cta >> 1 & 33) | (cta >> 3 & 6) | (cta << 1 & 24));
                bulk_commit();
                bulk_wait_read<0>();
              }
              mbar_arrive(se0 + 8 * (it & 1));
            }
          }
        }
      } else {
#pragma unroll 1
        for (int u = 1; u < nx; u++) {
          const int c = lds32(xtab + 4 * u);
          const uint32_t e = spare ? (u < 8 ? 97 : 40 + u) * 0x01010100u : lds32(ptab + 128 + 4 * u);
          mbar_wait(bb + (e >> 5 & 0x7F8), 0);
          mbar_expect(xfull + 8 * u, A_IN);
          mbar_wait(bb + (e >> 13 & 0x7F8), 0);
          x_half(u, c, 0);
          mbar_wait(bb + (e >> 21 & 0x7F8), 0);
          x_half(u, c, 1);
        }
#pragma unroll 1
        for (int s = 0; s < (spare ? 0 : 16); s++) {
          mbar_wait(gfull + 8 * s, 0);
          if ((s & 3) == 3) asm volatile("red.relaxed.gpu.global.add.s32 [%0], 1;" ::"l"(&gp_.done[(s >> 2) * 32]) : "memory");
        }
      }
    }
  } else {
    asm volatile("setmaxnreg.inc.sync.aligned.u32 232;");
    const int row = (lane & 7) + ((lane >> 3) & 1) * 8, hi = lane >> 4;
    asm volatile("barrier.cluster.wait.aligned;" ::: "memory");
    uint32_t fw[4];
    {
      uint32_t fa[16], za[64];
      mbar_wait(fbar, 0);
      const int f = (4 * bp + warp) & 63;
      const uint32_t lo = lds32(sF + f * 128 + ((f & 7) << 4) + (lane & 3) * 4), hh = lds32(sF + f * 128 + (((f & 7) ^ 1) << 4) + (lane & 3) * 4);
#pragma unroll
      for (int k = 0; k < 4; k++)
        ldsm4(sF + (warp * 16 + row) * 128 + (((2 * k + hi) ^ (lane & 7)) << 4), fa[4 * k], fa[4 * k + 1], fa[4 * k + 2], fa[4 * k + 3]);
      const int rho = (lane >> 3) | (lane & 4);
#pragma unroll
      for (int i = 0; i < 64; i++) za[i] = ((i & 1) == (i >> 5) && rho == ((i >> 2) & 7)) ? ((i & 2) ? hh : lo) : 0u;
      reg_fence(za);
      bar_sync(3, 256);
      const bool own = (warp >> 1) == rank;
      float d[64];
      constexpr uint64_t s2 = sched("02468:<>"), s3 = sched("13579;=?");
#pragma unroll 1
      for (uint64_t sc = spare ? (wg ? s3 : s2) : m.p.list[wg]; sc; sc >>= 5) {
        const int item = (int)sc & 31;
        if (item >= 18) {
          const int q = item - 18;
          const uint32_t e = __shfl_sync(0xffffffffu, lds32(ptab + 192 + 4 * q), 0);
#pragma unroll
          for (int jj = 0; jj < 4; jj++) {
            const int j = 4 * q + jj;
            mbar_wait(rfull + 8 * j, 0);
            wg_fence();
#pragma unroll
            for (int i = 0; i < 4; i++)
              wgmma_rs_128<1, 1, 1>(d, za[16 * jj + 4 * i], za[16 * jj + 4 * i + 1], za[16 * jj + 4 * i + 2], za[16 * jj + 4 * i + 3],
                                    mk_desc(sb + place(rank, e >> (4 * jj) & 15), i * 2048, 8192, 1024, 1), jj | i);
            wg_commit();
            if (jj > 0) {
              wg_wait<1>();
              if (lane == 0) mbar_arrive(rempty + 8 * (j - 1));
            }
          }
          wg_wait<0>();
          reg_fence(d);
          if (lane == 0) mbar_arrive(rempty + 8 * (4 * q + 3));
          mbar_wait(bb + (e >> (own ? 13 : 21) & 0x7F8), 0);
          const uint32_t rb = (own ? sb : peer) + (8 * rank + q) * 8192 + (warp & 1) * 4096 + rho * 128;
          const uint32_t wbar = q < W_Q ? win : win1;
          auto put_w = [&](auto remote) {
#pragma unroll
            for (int v = 0; v < 8; v++) {
              const int j = 4 * (v >> 1), h = v & 1;
              const uint32_t a = rb + (j >> 3) * 2048 + h * 1024 + ((((j & 4) + (lane & 3)) ^ rho) << 4);
              const uint32_t p0 = pack2(d[4 * j + 2 * h], d[4 * j + 2 * h + 1]), p1 = pack2(d[4 * j + 4 + 2 * h], d[4 * j + 5 + 2 * h]);
              const uint32_t p2 = pack2(d[4 * j + 8 + 2 * h], d[4 * j + 9 + 2 * h]), p3 = pack2(d[4 * j + 12 + 2 * h], d[4 * j + 13 + 2 * h]);
              if (decltype(remote)::value)
                asm volatile("st.async.shared::cluster.mbarrier::complete_tx::bytes.v4.b32 [%0], {%1, %2, %3, %4}, [%5];"
                             ::"r"(a), "r"(p0), "r"(p1), "r"(p2), "r"(p3), "r"(peer + (wbar - sb)) : "memory");
              else
                asm volatile("st.shared.v4.b32 [%0], {%1, %2, %3, %4};" ::"r"(a), "r"(p0), "r"(p1), "r"(p2), "r"(p3) : "memory");
            }
          };
          if (own) {
            put_w(std::false_type());
            __syncwarp();
            if (lane == 0) mbar_arrive(wbar);
          } else {
            put_w(std::true_type());
          }
        } else {
          const int u = item - 1;
          const int c = lds32(xtab + 4 * u);
          const uint32_t in = sb + (c & 0x3C000);
          mbar_wait(xfull + 8 * u, 0);
          wg_fence();
#pragma unroll
          for (int k = 0; k < 4; k++)
            wgmma_rs_128<1, 1, 1>(d, fa[4 * k], fa[4 * k + 1], fa[4 * k + 2], fa[4 * k + 3], mk_desc(in, k * 2048, 6144, 1024, 1), k);
          wg_commit();
          wg_wait<0>();
          reg_fence(d);
          bar_sync(1 + wg, 128);
          const uint32_t rb = in + (warp * 16 + row) * 128, xr = (lane & 7) ^ (c & 3);
#pragma unroll
          for (int j = 0; j < 16; j += 2)
            stsm4(rb + ((j >> 2) & 1) * 8192 + ((((j >> 3) * 4 + (j & 3) + hi) ^ xr) << 4), pack2(d[4 * j], d[4 * j + 1]),
                  pack2(d[4 * j + 2], d[4 * j + 3]), pack2(d[4 * j + 4], d[4 * j + 5]), pack2(d[4 * j + 6], d[4 * j + 7]));
          fence_async();
          __syncwarp();
          if (lane == 0) mbar_arrive(xready + 8 * u);
        }
      }
#pragma unroll
      for (int i = 0; i < 4; i++) fw[i] = fa[i];
    }
    if (spare) {
      float* sg = reinterpret_cast<float*>(smem_k1 + K1_R);
      __nv_bfloat16* sw = reinterpret_cast<__nv_bfloat16*>(sg + 16 * 256);
      const int c0 = (cta - 128) * 64;
      uint4 vw[8], vg[2];
#pragma unroll
      for (int i = 0; i < 8; i++) vw[i] = __ldg(reinterpret_cast<const uint4*>(wgt + ((i * 256 + tid) >> 3) * 256 + c0 + (tid & 7) * 8));
#pragma unroll
      for (int i = 0; i < 2; i++) vg[i] = __ldg(reinterpret_cast<const uint4*>(g) + i * 256 + tid);
#pragma unroll
      for (int i = 0; i < 8; i++) reinterpret_cast<uint4*>(sw)[i * 256 + tid] = vw[i];
#pragma unroll
      for (int i = 0; i < 2; i++) {
        const uint32_t w4[4] = {vg[i].x, vg[i].y, vg[i].z, vg[i].w};
#pragma unroll
        for (int e = 0; e < 4; e++) {
          sg[(i * 256 + tid) * 8 + 2 * e] = __uint_as_float(w4[e] << 16);
          sg[(i * 256 + tid) * 8 + 2 * e + 1] = __uint_as_float(w4[e] & 0xffff0000u);
        }
      }
      bar_sync(3, 256);
      const int col = tid & 63, r0 = (tid >> 6) * 4;
      float a0 = 0.f, a1 = 0.f, a2 = 0.f, a3 = 0.f;
#pragma unroll 8
      for (int k = 0; k < 256; k++) {
        const float w = __bfloat162float(sw[k * 64 + col]);
        a0 = fmaf(sg[(r0 + 0) * 256 + k], w, a0);
        a1 = fmaf(sg[(r0 + 1) * 256 + k], w, a1);
        a2 = fmaf(sg[(r0 + 2) * 256 + k], w, a2);
        a3 = fmaf(sg[(r0 + 3) * 256 + k], w, a3);
      }
      const int cc = c0 + col;
      const int pos = (cc & ~15) + ((cc >> 1) & 3) * 4 + ((cc >> 3) & 1) * 2 + (cc & 1);
      gp_.ge[(r0 + 0) * 256 + pos] = __bfloat162float(__float2bfloat16_rn(a0));
      gp_.ge[(r0 + 1) * 256 + pos] = __bfloat162float(__float2bfloat16_rn(a1));
      gp_.ge[(r0 + 2) * 256 + pos] = __bfloat162float(__float2bfloat16_rn(a2));
      gp_.ge[(r0 + 3) * 256 + pos] = __bfloat162float(__float2bfloat16_rn(a3));
      return;
    }
    reg_fence(fw);
    mbar_wait(win, 0);
    float d[16];
    auto t_begin = [&](int it, int hh, int r) {
      if (r == 0) mbar_wait(inf0 + 8 * (it & 1), (it >> 1) & 1);
      wg_fence();
      wgmma_rs_32<1, 1, 1>(d, fw[0], fw[1], fw[2], fw[3], mk_desc(sb + K1_TIN + (it & 1) * 4096 + hh * 2048, r * 64, 0, 1024, 1), 0);
      wg_commit();
    };
    auto t_end = [&](int it, int hh, int r) {
      reg_fence(d);
      const int j = it & 1;
      if (r == 0) mbar_wait(it >= 2 ? se0 + 8 * j : bb + (m.p.last >> (5 + 8 * it) & 0x7F8), it >= 2 ? ((it >> 1) - 1) & 1 : 0);
      else if (lane == 0) mbar_arrive(ine0 + 8 * j);
      const uint32_t rb = sb + K1_T + j * 16384 + hh * 8192 + (warp * 16 + row) * 128;
#pragma unroll
      for (int i = 0; i < 2; i++)
        stsm4(rb + (((4 * r + 2 * i + hi) ^ (lane & 7)) << 4), pack2(d[8 * i], d[8 * i + 1]), pack2(d[8 * i + 2], d[8 * i + 3]),
              pack2(d[8 * i + 4], d[8 * i + 5]), pack2(d[8 * i + 6], d[8 * i + 7]));
      if (r == 1) {
        fence_async();
        __syncwarp();
        if (lane == 0) mbar_arrive(sf0 + 8 * j);
      }
    };
    float y0[NB1 / 2], y1[NB1 / 2];
    uint32_t wa[8], wb[8];
    uint32_t wp = sb + wg * 4096 + ((lane & 7) + hi * 8) * 128 + (((2 * warp + ((lane >> 3) & 1)) ^ (lane & 7)) << 4);
    const uint32_t neg = wg ? 0x80008000u : 0u;
    auto frag = [&](uint32_t (&w)[8], uint32_t a, uint32_t sg) {
      ldsm4t(a, w[0], w[1], w[2], w[3]);
      ldsm4t(a + 2048, w[4], w[5], w[6], w[7]);
#pragma unroll
      for (int i = 0; i < 8; i++) w[i] ^= sg;
    };
    auto stage = [&](const uint32_t (&w)[8], uint32_t x4, int acc) {
      wg_fence();
      wgmma_rs_168<1, 1, 0>(y0, w[0], w[1], w[2], w[3], mk_desc4(x4, 0, 512, 2), acc);
      wgmma_rs_168<1, 1, 0>(y1, w[0], w[1], w[2], w[3], mk_desc4(x4 + G_ST / 32, 0, 512, 2), acc);
      wgmma_rs_168<1, 1, 0>(y0, w[4], w[5], w[6], w[7], mk_desc4(x4 + 2, 0, 512, 2), 1);
      wgmma_rs_168<1, 1, 0>(y1, w[4], w[5], w[6], w[7], mk_desc4(x4 + G_ST / 32 + 2, 0, 512, 2), 1);
      wg_commit();
      wg_wait<1>();
    };
    frag(wa, wp, neg);
    int it = 0;
#pragma unroll 1
    for (int k = 0; k < G_KM; k++) {
      const bool T = (m.p.tmask >> (k + 16 * wg)) & 1;
      const uint32_t xa = ((sb & 0x3FFFF) >> 4) + m.slot[2 * k], xb = ((sb & 0x3FFFF) >> 4) + m.slot[2 * k + 1];
      if (T) t_begin(it, wg, 0);
      mbar_wait(gfull + 16 * k, 0);
      stage(wa, xa, k);
      frag(wb, wp ^ 4096, 0);
      if (k > 0 && lane == 0) mbar_arrive(gdone + 16 * k - 8);
      if (T) {
        t_end(it, wg, 0);
        t_begin(it, wg, 1);
      }
      mbar_wait(gfull + 16 * k + 8, 0);
      stage(wb, xb, 1);
      wp += 8192;
      if (k == W_Q - 1) {
        mbar_wait(win1, 0);
        fence_async();
      }
      frag(wa, wp, neg);
      if (lane == 0) mbar_arrive(gdone + 16 * k);
      if (T) t_end(it++, wg, 1);
    }
    auto tail = [&](float (&y)[NB1 / 2], auto batch, auto wgc) {
      constexpr int B = decltype(batch)::value, W = decltype(wgc)::value;
#pragma unroll
      for (int k = G_KM; k < 16; k++) {
        const int s = G_KM + k + G_TK * B;
        mbar_wait(gfull + 8 * s, 0);
        const int xo = g_off(g_slot(s));
        wg_fence();
#pragma unroll
        for (int h = 0; h < 4; h++) {
          const uint64_t dW = mk_desc(sb, k * 8192 + ((h >> 1) ^ W) * 4096 + (h & 1) * 2048, 0, 1024, 1);
          const uint64_t dX = mk_desc(sb, xo + (h >> 1) * (G_ST / 2) + (h & 1) * 32, 0, 512, 2);
          if (W == 1 && h < 2) wgmma_ss_168<-1, 1, 1, 0>(y, dW, dX, 1);
          else wgmma_ss_168<1, 1, 1, 0>(y, dW, dX, 1);
        }
        if (s <= 26) {
          wg_commit();
          if (W == 0 || k > G_KM) {
            wg_wait<1>();
            if (lane == 0) mbar_arrive(gdone + 8 * (s - 1));
          }
        }
      }
      wg_commit();
    };
    constexpr std::integral_constant<int, 0> c0;
    constexpr std::integral_constant<int, 1> c1;
    auto put = [&](const float (&v)[NB1 / 2], uint32_t stg, int b) {
      const int mi = lane >> 3, i = lane & 7;
      const uint32_t a0 = stg + (mi >> 1) * 1024 + i * 128 + (((2 * warp + (mi & 1)) ^ i) << 4);
      constexpr int J = 21 / G_EPI;
#pragma unroll
      for (int c = 0; c < G_EPI; c++) {
#pragma unroll
        for (int j = c * J; j + 1 < (c + 1) * J; j += 2)
          stsm4t(a0 + j * 1024, pack2(v[4 * j], v[4 * j + 1]), pack2(v[4 * j + 2], v[4 * j + 3]),
                 pack2(v[4 * j + 4], v[4 * j + 5]), pack2(v[4 * j + 6], v[4 * j + 7]));
        const int j = (c + 1) * J - 1;
        asm volatile("stmatrix.sync.aligned.m8n8.x2.trans.shared.b16 [%0], {%1, %2};" ::"r"(a0 + j * 1024),
                     "r"(pack2(v[4 * j], v[4 * j + 1])), "r"(pack2(v[4 * j + 2], v[4 * j + 3])) : "memory");
        fence_async();
        bar_sync(1 + wg, 128);
        if (t == 0) {
          tma_st4<0>(&m.y, stg + c * J * 1024, 0, b * NB1 + c * J * 8, 2 * bin + wg, dc);
          bulk_commit();
        }
      }
    };
    if (wg == 0) {
      tail(y0, c0, c0);
      bar_arrive(4, 256);
      mbar_wait(gdone + 8 * (G_S0 - 1), 0);
      wg_wait<0>();
      reg_fence(y0);
      put(y0, sb + K1_Y0, 0);
      bar_sync(7, 256);
      tail(y1, c1, c0);
      bar_arrive(8, 256);
      if (t == 0) bulk_wait_read<0>();
      wg_wait<0>();
      reg_fence(y1);
      bar_sync(1, 128);
      put(y1, sb + K1_Y0, 1);
    } else {
      wg_wait<0>();
      if (lane == 0) mbar_arrive(gdone + 8 * (G_S0 - 1));
#pragma unroll 1
      for (int h2 = 2 * it; h2 < 16; h2++) {
#pragma unroll
        for (int r = 0; r < 2; r++) {
          t_begin(h2 >> 1, h2 & 1, r);
          wg_wait<0>();
          t_end(h2 >> 1, h2 & 1, r);
        }
      }
      bar_sync(4, 256);
      tail(y0, c0, c1);
      bar_arrive(7, 256);
      mbar_wait(se0, 1);
      mbar_wait(se0 + 8, 1);
      wg_wait<0>();
      reg_fence(y0);
      put(y0, sb + K1_T, 0);
      bar_sync(8, 256);
      tail(y1, c1, c1);
      wg_wait<0>();
      reg_fence(y1);
      put(y1, sb + g_off(g_slot(26)), 1);
    }
    if (t == 0) {
      bulk_wait_read<0>();
    }
  }
}

#define H_EPI 3
#define H_KS 11
#define C_PC 32
constexpr int H_XP = 168 * 64, H_STAGE = 8192 + 2 * H_XP, H_NST = 7, K2_STG = H_NST * H_STAGE, K2_SMEM = K2_STG + 21504 + 1024;

template <int WG>
__device__ __forceinline__ void h_loop(float (&acc)[84], uint32_t sb, uint32_t full0, uint32_t empty0, int lane) {
#pragma unroll 1
  for (int k = 0; k < 16; k++) {
    const int st = k % H_NST;
    if (WG == 1 && k == H_KS) bar_sync(5, 256);
    mbar_wait(full0 + 8 * st, (k / H_NST) & 1);
    const uint32_t base = sb + st * H_STAGE;
    wg_fence();
#pragma unroll
    for (int s = 0; s < 2; s++) {
      const uint64_t dP = mk_desc(base, s * 2048, 0, 1024, 1), dQ = mk_desc(base, 4096 + s * 2048, 0, 1024, 1);
      const uint64_t dA = mk_desc(base, 8192 + s * 32, 0, 1024, 1), dB = mk_desc(base, 8192 + 64 + s * 32, 0, 1024, 1);
      wgmma_ss_168<1, 1, 1, 0>(acc, dP, WG == 0 ? dA : dB, k | s);
      wgmma_ss_168<WG == 0 ? 1 : -1, 1, 1, 0>(acc, dQ, WG == 0 ? dB : dA, 1);
    }
    wg_commit();
    if (WG == 0 && k == 15) bar_arrive(5, 256);
    if (k <= 10) {
      wg_wait<1>();
      if (k > 0 && k - 1 + H_NST < 16 && lane < 2) mbar_arrive_cta(empty0 + 8 * ((k - 1) % H_NST), lane);
    }
  }
  wg_wait<0>();
  reg_fence(acc);
}
template <int C0, int C1> __device__ __forceinline__ void gelu_pack(uint32_t (&p)[12], const float (&h)[24]) {
#pragma unroll
  for (int i = 4 * C0; i < 4 * C1; i++) p[i] = pack2(gelu(h[2 * i]), gelu(h[2 * i + 1]));
}
struct K2Maps {
  int stage[16], item[8], wpre, pad[7];
  CUtensorMap y, xa, xs, w, y2;
};

__global__ void __cluster_dims__(2, 1, 1) __launch_bounds__(512, 1)
k2(const Ptrs gp_, const char* __restrict__ x2, const __grid_constant__ K2Maps m, const __nv_bfloat16* __restrict__ wf,
   const __nv_bfloat16* __restrict__ wo) {
  extern __shared__ __align__(1024) uint8_t smem_k1[];
  const uint32_t sb = s2u(smem_k1);
  const int tid = threadIdx.x, wg = __shfl_sync(0xffffffffu, tid >> 7, 0), t = tid & 127;
  const int warp = __shfl_sync(0xffffffffu, t >> 5, 0), lane = t & 31;
  const int cta = blockIdx.x, rank = cta & 1, dc = cta & 3, bin = cta >> 2;
  const uint32_t sGi = sb + K2_STG, sF = sGi + 6144, bb = sb + K2_STG + 21504;
  const uint32_t yfull = bb, full0 = bb + 128, empty0 = bb + 192, cfull = bb + 256, ready = bb + 320, bfree = bb + 384;
  const int b = cta & 1, j = cta >> 2;
  const int len0 = j < 20 ? 3 : 2, len1 = j >= 12 ? 3 : 2;
  const int n00 = j < 20 ? 3 * j : 2 * j + 20, n01 = j < 12 ? 2 * j : 3 * j - 12, cs0 = 3 - (cta >> 1 & 1);
  auto y_load = [&](int r, int i) {
    tma_ld5<1>(sb + (3 + 2 * r) * H_STAGE + i * 8192, &m.y, yfull + 64 * r + 8 * i, 0, 0, cs0 - 2 * r, 2 * (r ? n01 : n00) + i, b);
  };
  if (wg == 2 && warp == 0) {
    if (lane == 0) {
      prefetch_map(&m.y);
      for (int i = 0; i < 16; i++) mbar_init(yfull + 8 * i, 1);
      fence_bar_init();
    }
    __syncwarp();
    if (lane < 16) mbar_expect(yfull + 8 * lane, lane == 7 ? 6144 : 8192);
    bar_arrive(0, 512);
    asm volatile("barrier.cluster.arrive.relaxed.aligned;" ::: "memory");
    auto c_load = [&](int h) {
      asm volatile("cp.async.bulk.shared::cluster.global.mbarrier::complete_tx::bytes [%0], [%1], %2, [%3];"
                   ::"r"(sGi + 6144 * h), "l"(gp_.img + 1536 * h), "r"(6144 + 2048 * h), "r"(yfull + 56 + 64 * h) : "memory");
    };
    if (lane == 0) {
      c_load(0);
      c_load(1);
      pdl_wait();
      const int r2 = len0 == 2, i2 = r2 ? 2 : 6;
      y_load(0, 2), y_load(0, 0), y_load(0, 1), y_load(1, 0), y_load(0, 4), y_load(0, 3), y_load(r2, i2), y_load(r2, i2 - 1);
      pdl_launch();
    }
    __syncwarp();
  } else {
    if (lane == 0 && wg == 3) {
      for (int i = 0; i < 8; i++) mbar_init(full0 + 64 * warp + 8 * i, warp == 0 ? 1 : warp == 1 ? 16 : 4);
      fence_bar_init();
    }
    if (tid == 0) {
      mbar_init(bfree, 2);
      for (int i = 1; i < 5; i++) mbar_init(bfree + 8 * i, 1);
      mbar_arrive(bfree + 8);
      fence_bar_init();
    }
    if (tid == 128) {
      prefetch_map(&m.xa);
      prefetch_map(&m.xs);
      prefetch_map(&m.w);
      prefetch_map(&m.y2);
    }
    bar_sync(0, 512);
    asm volatile("barrier.cluster.arrive.relaxed.aligned;" ::: "memory");
  }
  if (wg == 2) asm volatile("barrier.cluster.wait.aligned;" ::: "memory");
  mbar_wait(yfull + 56, 0);
  auto idft = [&](float (&h)[24], uint32_t in, uint32_t bar) {
    mbar_wait(bar, 0);
    wg_fence();
#pragma unroll
    for (int k = 0; k < 4; k++) wgmma_ss_48<1, 1, 1, 0>(h, mk_desc(in, k * 2048, 0, 1024, 1), mk_desc(sGi, k * 32, 0, 1024, 1), k);
    wg_commit();
  };
  auto carry_out = [&](const uint32_t (&p)[12], uint32_t dst, uint32_t bar) {
    bar_sync(1 + wg, 128);
#pragma unroll
    for (int v = 0; v < 3; v++)
      asm volatile("st.shared.v4.b32 [%0], {%1, %2, %3, %4};" ::"r"(dst + v * 2048 + t * 16), "r"(p[4 * v]), "r"(p[4 * v + 1]), "r"(p[4 * v + 2]), "r"(p[4 * v + 3]) : "memory");
    __syncwarp();
    if (lane == 0) mbar_arrive(bar);
  };
  if (wg == 3) {
#pragma unroll 1
    for (int r = 0; r < 2; r++) {
      float h[24];
      uint32_t p[12];
      idft(h, sb + (3 + 2 * r) * H_STAGE, yfull + 64 * r);
      wg_wait<0>();
      reg_fence(h);
      gelu_pack<0, 3>(p, h);
      if (j == 0) p[0] = p[1] = p[2] = p[3] = 0;
      carry_out(p, sb + (3 + 2 * r) * H_STAGE, cfull + 32 * r);
    }
    asm volatile("barrier.cluster.wait.aligned;" ::: "memory");
    if (lane == 0) {
      if (warp == 0) {
        auto w_load = [&](int k) {
          mbar_expect(full0 + 8 * (k % H_NST), H_STAGE);
          tma_ld4<1>(sb + (k % H_NST) * H_STAGE, &m.w, full0 + 8 * (k % H_NST), 0, (k & 1) * 32, dc, (7 - (k >> 1)) * 64 + 2 * bin);
        };
        const int wpre = m.wpre;
        for (int k = 0; k < wpre; k++) w_load(k);
#pragma unroll 1
        for (int k = 0; k < 16; k++) {
          const int st = k % H_NST, e = m.stage[k];
          if ((k & 7) == 0) {
            poll_ge(&gp_.done[(6 + (k >> 3)) * 32], 128);
            asm volatile("fence.proxy.async.global;" ::: "memory");
            if (k == 0) mbar_arrive(bfree + 32);
          }
          if (e) mbar_wait(bb + 8 * e, 0);
          if (k == 5) mbar_wait(bfree, 0);
          if (k >= H_NST) mbar_wait(empty0 + 8 * st, ((k / H_NST) - 1) & 1);
          const char* xs = x2 + (((7 - (k >> 2) - (k & 2) * 2) * 64 + (k & 1) * 32 + bin) * 2 + rank) * H_XP;
          asm volatile("cp.async.bulk.shared::cluster.global.mbarrier::complete_tx::bytes.multicast::cluster [%0], [%1], %2, [%3], %4;"
                       ::"r"(sb + st * H_STAGE + 8192 + rank * H_XP), "l"(xs), "n"(H_XP), "r"(full0 + 8 * st), "h"((uint16_t)3) : "memory");
          if (k >= wpre) w_load(k);
          if (k == 8) {
            if (cta == 0) asm volatile("cp.async.bulk.prefetch.L2.global [%0], 6144;" ::"l"(gp_.ga) : "memory");
            asm volatile("cp.async.bulk.prefetch.L2.global [%0], 1024;" ::"l"(wf + cta * 512) : "memory");
            asm volatile("cp.async.bulk.prefetch.L2.global [%0], 1024;" ::"l"(wo + cta * 512) : "memory");
          }
        }
      } else if (warp < 3) {
        const int r = warp - 1, n0 = b * NB2 + (r ? n01 : n00), f0 = (cs0 - 2 * r) * 64;
#pragma unroll 1
        for (int i = 0; i < (r ? len1 : len0); i++) {
          const uint32_t src = sb + (3 + 2 * r) * H_STAGE + i * 16384;
          const int e = m.item[4 * r + i], burst = (16 << (e >> 8)) - 1;
          if (r) mbar_wait(bb + 8 * (e & 255), 0);
          mbar_wait(ready + 32 * r + 8 * i, 0);
          if (!r) {
            tma_st4<0>(&m.xa, src, 0, f0, 0, n0 + i);
            bulk_commit();
            continue;
          }
#pragma unroll 1
          for (int p = 0; p < 128; p += C_PC) {
            tma_st3<0>(&m.xs, src + p * 128, 0, f0 + (p & 63) + (p >> 6) * 256, n0 + i);
            bulk_commit();
            if (((p + C_PC) & burst) == 0) bulk_wait_read<0>();
          }
        }
        asm volatile("cp.async.bulk.wait_group 0;" ::: "memory");
        if (r) {
          mbar_arrive_cta(bfree, 0);
          mbar_arrive_cta(bfree, 1);
        }
        if (!r) mbar_arrive(bfree + 16);
        asm volatile("red.release.gpu.global.add.s32 [%0], 1;" ::"l"(&gp_.done[(6 + r) * 32]) : "memory");
        if (!r) mbar_arrive(bfree + 24);
      }
    }
    return;
  }
#pragma unroll 1
  for (int it = wg; it < len0 + len1; it += 3) {
    const int r = it >= len0, i = it - r * len0;
    const bool last = i + 1 == (r ? len1 : len0);
    const uint32_t in = sb + (3 + 2 * r) * H_STAGE + i * 16384, bar = yfull + 64 * r + 16 * i;
    float h1[24], h2[24];
    uint32_t p0[12], p1[12], p2[12];
    idft(h2, in + 16384, bar + 16);
    if (it == 2 && lane == 0 && 3 + warp - len0 < len1) {
      y_load(1, 2 * (3 + warp - len0) + 2);
      y_load(1, 2 * (3 + warp - len0) + 1);
    }
    if (it > 0) bar_sync(6 + wg, 256);
    wg_wait<0>();
    reg_fence(h2);
    gelu_pack<0, 2>(p2, h2);
    idft(h1, in + 8192, bar + 8);
    if (!last) {
      gelu_pack<2, 3>(p2, h2);
      carry_out(p2, in + 16384, cfull + 32 * r + 8 * i + 8);
    }
    if (it + 1 < len0 + len1) bar_arrive(6 + (wg + 1) % 3, 256);
    mbar_wait(cfull + 32 * r + 8 * i, 0);
#pragma unroll
    for (int v = 0; v < 3; v++)
      asm volatile("ld.shared.v4.b32 {%0, %1, %2, %3}, [%4];" : "=r"(p0[4 * v]), "=r"(p0[4 * v + 1]), "=r"(p0[4 * v + 2]), "=r"(p0[4 * v + 3]) : "r"(in + v * 2048 + t * 16) : "memory");
    if (it < 3) mbar_wait(yfull + 120, 0);
    wg_wait<0>();
    reg_fence(h1);
    gelu_pack<0, 3>(p1, h1);
    if (last && j == 31) {
#pragma unroll
      for (int v = 0; v < 12; v++) p1[v] = p2[v] = 0;
    }
    uint32_t hp[32];
#pragma unroll
    for (int c = 0; c < 8; c++)
#pragma unroll
      for (int v = 0; v < 4; v++) hp[(v >> 1) * 16 + 2 * c + (v & 1)] = c < 3 ? p0[4 * c + v] : c < 6 ? p1[4 * (c - 3) + v] : p2[4 * (c - 6) + v];
    float e0[32], e1[32];
    reg_fence(hp);
    wg_fence();
#pragma unroll
    for (int k = 0; k < 4; k++) {
      const uint64_t db = mk_desc(sF, k * 32, 0, 1024, 1);
      wgmma_rs_64<1, 1, 0>(e0, hp[4 * k], hp[4 * k + 1], hp[4 * k + 2], hp[4 * k + 3], db, k);
      wgmma_rs_64<1, 1, 0>(e1, hp[16 + 4 * k], hp[16 + 4 * k + 1], hp[16 + 4 * k + 2], hp[16 + 4 * k + 3], db, k);
    }
    wg_commit();
    bar_sync(1 + wg, 128);
    wg_wait<0>();
    reg_fence(e0);
    reg_fence(e1);
    {
      const int mi = lane >> 3, rr = (lane & 7) >> 1, blk = b * NB2 + (r ? n01 : n00) + i;
      const uint32_t a0 = in + (mi >> 1) * 8192 + (warp >> 1) * 4096 + rr * 128;
      const uint32_t pos = ((lane & 1) * 4 + (warp & 1) * 2 + (mi & 1)) ^ rr ^ (blk & 7);
#pragma unroll
      for (int q = 0; q < 8; q++)
        stsm4t(a0 + q * 512 + ((pos ^ (q & 1) * 4) << 4), pack2(e0[4 * q], e0[4 * q + 1]), pack2(e0[4 * q + 2], e0[4 * q + 3]),
               pack2(e1[4 * q], e1[4 * q + 1]), pack2(e1[4 * q + 2], e1[4 * q + 3]));
    }
    fence_async();
    __syncwarp();
    if (lane == 0) mbar_arrive(ready + 32 * r + 8 * i);
  }
  if (wg == 2) return;
  asm volatile("barrier.cluster.wait.aligned;" ::: "memory");
  float acc[84];
  if (wg == 0) {
    h_loop<0>(acc, sb, full0, empty0, lane);
  } else {
    h_loop<1>(acc, sb, full0, empty0, lane);
    bar_sync(2, 128);
  }
  const uint32_t stg = sb + (wg == 0 ? H_NST : 9 % H_NST) * H_STAGE;
  const int mi = lane >> 3, i = lane & 7;
  const uint32_t a0 = stg + (mi >> 1) * 1024 + i * 128 + (((2 * warp + (mi & 1)) ^ i) << 4);
  constexpr int J = 21 / H_EPI;
#pragma unroll
  for (int c = 0; c < H_EPI; c++) {
#pragma unroll
    for (int q = c * J; q + 1 < (c + 1) * J; q += 2)
      stsm4t(a0 + q * 1024, pack2(acc[4 * q], acc[4 * q + 1]), pack2(acc[4 * q + 2], acc[4 * q + 3]),
             pack2(acc[4 * q + 4], acc[4 * q + 5]), pack2(acc[4 * q + 6], acc[4 * q + 7]));
    const int q = (c + 1) * J - 1;
    asm volatile("stmatrix.sync.aligned.m8n8.x2.trans.shared.b16 [%0], {%1, %2};" ::"r"(a0 + q * 1024),
                 "r"(pack2(acc[4 * q], acc[4 * q + 1])), "r"(pack2(acc[4 * q + 2], acc[4 * q + 3])) : "memory");
    fence_async();
    bar_sync(1 + wg, 128);
    if (t == 0) {
      tma_st4<0>(&m.y2, stg + c * J * 1024, 0, c * J * 8, 2 * bin + wg, dc);
      bulk_commit();
    }
  }
  if (t == 0) {
    bulk_wait_read<0>();
  }
}

#define E_I1 12
#define E_WAITS 0xA8
#define E_EARLY0 5
#define E_EARLY 5
constexpr int E_SMEM = 65536 + 131072 + 32768 + 1024;

__device__ __forceinline__ uint32_t joint2(uint32_t fe, uint32_t g0, uint32_t g1) {
  uint32_t s0, s1;
  asm("{\n.reg .b16 l, h;\n.reg .b32 ll, hh;\nmov.b32 {l, h}, %2;\nmov.b32 ll, {l, l};\nmov.b32 hh, {h, h};\n"
      "fma.rn.bf16x2 %0, ll, %5, %3;\nfma.rn.bf16x2 %1, hh, %5, %4;\n}"
      : "=r"(s0), "=r"(s1) : "r"(fe), "r"(g0), "r"(g1), "r"(0x3F800000u));
  return pack2(tanh_f32(__uint_as_float(s0)), tanh_f32(__uint_as_float(s1)));
}
__device__ __forceinline__ uint4 lds128(uint32_t a) {
  uint4 v;
  asm volatile("ld.shared.v4.u32 {%0, %1, %2, %3}, [%4];" : "=r"(v.x), "=r"(v.y), "=r"(v.z), "=r"(v.w) : "r"(a));
  return v;
}
__device__ __forceinline__ void joint_group(uint32_t (&ja)[8], const uint32_t* fe, const uint4& c0, const uint4& c1) {
  ja[0] = joint2(fe[0], c0.x, c0.y);
  ja[1] = joint2(fe[1], c0.x, c0.y);
  ja[2] = joint2(fe[2], c0.z, c0.w);
  ja[3] = joint2(fe[3], c0.z, c0.w);
  ja[4] = joint2(fe[4], c1.x, c1.y);
  ja[5] = joint2(fe[5], c1.x, c1.y);
  ja[6] = joint2(fe[6], c1.z, c1.w);
  ja[7] = joint2(fe[7], c1.z, c1.w);
  reg_fence(ja);
}

__global__ void __cluster_dims__(2, 1, 1) __launch_bounds__(256, 1)
kE(const __grid_constant__ CUtensorMap my, const __grid_constant__ CUtensorMap mwf, const __grid_constant__ CUtensorMap mwo,
   const __grid_constant__ CUtensorMap mout) {
  const Ptrs gp_ = {g_done, g_ge, c_img, c_ga};
  extern __shared__ uint8_t smem_raw[];
  __shared__ __align__(8) uint64_t bars[17];
  const uint32_t sb = (s2u(smem_raw) + 1023) & ~1023u;
  const int tid = threadIdx.x, wg = __shfl_sync(0xffffffffu, tid >> 7, 0), t = tid & 127, warp = t >> 5, lane = t & 31;
  const uint32_t R0 = sb, R1 = sb + 65536, R2 = sb + 65536 + 131072;
  const uint32_t barY = s2u(&bars[0]), barO = barY + 32, barF = barY + 64, barA = barY + 128;
  const int b = blockIdx.x / 63, t0 = (blockIdx.x % 63) * 64;
  const int a = t0 / 48, o = t0 % 48;
  const int qw = o + 16 * warp, sel = qw >= 48;
  uint32_t ga[16];
#pragma unroll
  for (int s = 0; s < 4; s++)
    ldg128(reinterpret_cast<const uint4*>(gp_.ga) + ((qw >> 4) - 3 * sel) * 128 + s * 32 + lane, ga[4 * s], ga[4 * s + 1], ga[4 * s + 2], ga[4 * s + 3]);
  uint4 gev0, gev1;
  asm volatile("ld.global.cg.v4.u32 {%0, %1, %2, %3}, [%4];" : "=r"(gev0.x), "=r"(gev0.y), "=r"(gev0.z), "=r"(gev0.w)
               : "l"(reinterpret_cast<const uint4*>(gp_.ge) + (b * 8 + wg * 4) * 64 + t));
  asm volatile("ld.global.cg.v4.u32 {%0, %1, %2, %3}, [%4];" : "=r"(gev1.x), "=r"(gev1.y), "=r"(gev1.z), "=r"(gev1.w)
               : "l"(reinterpret_cast<const uint4*>(gp_.ge) + (b * 8 + wg * 4) * 64 + 128 + t));
  auto f_load = [&](int q) {
    const int p = (0x37156240 >> (4 * q)) & 7;
    mbar_expect(barF + 8 * p, 16384);
    tma_ld3<0>(R1 + p * 16384, &mwf, barF + 8 * p, 0, (p >> 1) * 64, (p & 1) * 2);
  };
  if (tid == 0) {
    prefetch_map(&my);
    for (int i = 0; i < 16; i++) mbar_init(barY + 8 * i, 1);
    mbar_init(barA, 8);
    fence_bar_init();
    prefetch_map(&mwf);
    pdl_wait();
    for (int i = 0; i < 4; i++) {
      mbar_expect(barY + 8 * i, 16384);
      tma_ld5<0>(R0 + i * 16384, &my, barY + 8 * i, 0, 0, 2 * (i & 1) + (i >> 1), a, b);
    }
    for (int q = 0; q < 4; q++) f_load(q);
  }
  if (tid == 64) {
    prefetch_map(&mwo);
    prefetch_map(&mout);
  }
  uint32_t gs[32];
#pragma unroll
  for (int i = 0; i < 16; i++) {
    gs[i] = sel ? 0u : ga[i];
    gs[16 + i] = sel ? ga[i] : 0u;
  }
  __syncthreads();
  if (blockIdx.x == 125 && tid < 8) gp_.done[tid * 32] = 0;
  reg_fence(gs);
  uint32_t gp = R2 + 16384 + wg * 4096 + (lane & 3) * 16;
  uint4 g0, g1;
  uint32_t fe[64];
  {
    float d0[32], d1[32], e[64];
    mbar_wait(barY + 8 * wg, 0);
    wg_fence();
#pragma unroll
    for (int k = 0; k < 8; k++)
      wgmma_rs_64<1, 1, 1>(d0, gs[4 * k], gs[4 * k + 1], gs[4 * k + 2], gs[4 * k + 3], mk_desc(R0 + wg * 16384, k * 2048, 0, 1024, 1), k);
    wg_commit();
    if (tid == 0)
      for (int q = 4; q < 8; q++) f_load(q);
    wg_wait<0>();
    reg_fence(d0);
    uint32_t p0[16], p1[16];
    const uint32_t wfo = R1 + wg * (65536 + 16384), wfx = R1 + 65536 - wg * (65536 - 16384), fx = R2 + 16384 - wg * 16384;
    const uint32_t fo = R2 + wg * 16384 + (warp * 16 + (lane & 7) + ((lane >> 3) & 1) * 8) * 128;
    auto fe_own = [&](const uint32_t (&p)[16], int c) {
      wg_fence();
#pragma unroll
      for (int s = 0; s < 4; s++)
        wgmma_rs_128<1, 1, 1>(e, p[4 * s], p[4 * s + 1], p[4 * s + 2], p[4 * s + 3], mk_desc(wfo, c * 32768 + s * 2048, 8192, 1024, 1), c | s);
    };
    auto fe_other = [&](int c) {
      wg_fence();
#pragma unroll
      for (int s = 0; s < 4; s++)
        wgmma_ss_128<1, 1, 0, 1>(e, mk_desc(fx, c * 8192 + s * 32, 0, 1024, 1), mk_desc(wfx, c * 32768 + s * 2048, 8192, 1024, 1), 1);
    };
    auto f_store = [&](const uint32_t (&p)[16], int c) {
#pragma unroll
      for (int s = 0; s < 4; s++) stsm4(fo + c * 8192 + (((2 * s + (lane >> 4)) ^ (lane & 7)) << 4), p[4 * s], p[4 * s + 1], p[4 * s + 2], p[4 * s + 3]);
    };
#pragma unroll
    for (int i = 0; i < E_I1; i++) p0[i] = pack2(gelu(d0[2 * i]), gelu(d0[2 * i + 1]));
    mbar_wait(barY + 8 * (2 + wg), 0);
    wg_fence();
#pragma unroll
    for (int k = 0; k < 8; k++)
      wgmma_rs_64<1, 1, 1>(d1, gs[4 * k], gs[4 * k + 1], gs[4 * k + 2], gs[4 * k + 3], mk_desc(R0 + wg * 16384, 32768 + k * 2048, 0, 1024, 1), k);
    wg_commit();
#pragma unroll
    for (int i = E_I1; i < 16; i++) p0[i] = pack2(gelu(d0[2 * i]), gelu(d0[2 * i + 1]));
    reg_fence(p0);
    f_store(p0, 0);
    const uint32_t bfo = barF + 40 * wg, bfx = barF + 32 - 24 * wg;
    auto o_load = [&](int kc) {
      mbar_expect(barO + 8 * kc, 32768);
      tma_ld3<0>(kc < 2 ? R0 + kc * 32768 : R1 + (kc - 2) * 65536, &mwo, barO + 8 * kc, 0, kc * 64, 0);
    };
    wg_wait<0>();
    reg_fence(d1);
    if (wg == 1) {
      fence_async();
      bar_arrive(8, 256);
    }
#pragma unroll
    for (int i = 0; i < 16; i++) p1[i] = pack2(gelu(d1[2 * i]), gelu(d1[2 * i + 1]));
    reg_fence(p1);
    if (wg == 0) {
      mbar_wait(bfo, 0);
      fe_own(p0, 0);
      mbar_wait(bfx, 0);
      bar_sync(8, 256);
      fe_other(0);
      wg_commit();
      if (t == 0) {
        o_load(0);
        o_load(1);
      }
      f_store(p1, 1);
      mbar_wait(bfo + 16, 0);
      fe_own(p1, 1);
      fence_async();
      mbar_wait(bfx + 16, 0);
      bar_sync(7, 256);
      fe_other(1);
      wg_commit();
      bar_arrive(4, 256);
      wg_wait<1>();
      if (lane == 0) mbar_arrive(barA);
      bar_sync(1, 128);
    } else {
      f_store(p1, 1);
      fence_async();
      bar_arrive(7, 256);
      mbar_wait(bfo, 0);
      mbar_wait(bfx, 0);
      bar_sync(4, 256);
      fe_own(p0, 0);
      fe_other(0);
      wg_commit();
      mbar_wait(bfo + 16, 0);
      mbar_wait(bfx + 16, 0);
      fe_own(p1, 1);
      wg_commit();
      wg_wait<1>();
      if (lane == 0) mbar_arrive(barA);
      fe_other(1);
      wg_commit();
      mbar_wait(barA, 0);
      if (t == 0) {
        o_load(2);
        o_load(3);
      }
    }
    asm volatile("st.shared.v4.u32 [%0], {%1, %2, %3, %4};" ::"r"(R2 + 16384 + wg * 4096 + ((t * 16) ^ (wg * 512))), "r"(gev0.x), "r"(gev0.y), "r"(gev0.z), "r"(gev0.w) : "memory");
    asm volatile("st.shared.v4.u32 [%0], {%1, %2, %3, %4};" ::"r"(R2 + 16384 + wg * 4096 + 2048 + ((t * 16) ^ (wg * 512))), "r"(gev1.x), "r"(gev1.y), "r"(gev1.z), "r"(gev1.w) : "memory");
    bar_sync(1 + wg, 128);
    g0 = lds128(gp);
    g1 = lds128(gp + 64);
    wg_wait<0>();
    reg_fence(e);
#pragma unroll
    for (int i = 0; i < 32; i++) fe[i] = pack2(e[2 * i], e[2 * i + 1]);
  }
  auto publish = [&]() {
    bar_sync(1 + wg, 128);
    const int row = warp * 16 + (lane & 7) + ((lane >> 3) & 1) * 8;
    const uint32_t xb = R1 + (wg == 0 ? 3 * 32768 : 32768 + 16384) + row * 128;
#pragma unroll
    for (int s = 0; s < 8; s++) {
      const int jj = 2 * s + (lane >> 4);
      stsm4(xb + (s >> 2) * 8192 + (((jj & 7) ^ (lane & 7)) << 4), fe[4 * s], fe[4 * s + 1], fe[4 * s + 2], fe[4 * s + 3]);
    }
    bar_arrive(5 + wg, 256);
  };
  if (wg == 1) publish();
  const uint32_t stg = R1 + 32768 + wg * 65536;
  const uint32_t w0 = sb + wg * 65536, w1 = sb + 32768 + wg * 98304, w2 = sb + 65536 - wg * 65536, w3 = sb + 131072 - wg * 98304;
  float acc[128];
  uint32_t j0[8], j1[8], j2[8], j3[8];
  uint4 h0 = lds128(gp + 128), h1 = lds128(gp + 192);
  const uint32_t bo0 = barO + 16 * wg, bo2 = barO + 16 * (1 - wg);
  joint_group(j0, fe, g0, g1);
  g0 = lds128(gp + 256);
  g1 = lds128(gp + 320);
  mbar_wait(barY, 0);
  joint_group(j1, fe + 8, h0, h1);
#define E_MMA2(J, W, OFF, FIRSTK)                                                                       \
  wgmma_rs_256<1, 1, 1>(acc, J[0], J[1], J[2], J[3], mk_desc(W, OFF, 8192, 1024, 1), FIRSTK);           \
  wgmma_rs_256<1, 1, 1>(acc, J[4], J[5], J[6], J[7], mk_desc(W, (OFF) + 2048, 8192, 1024, 1), 1);
#define E_TOKEN(N) \
  if ((ui + wg == 0 ? E_EARLY0 : E_EARLY) == (N) && (ui < 3 || wg == 0)) bar_arrive(4 - wg, 256);
#define E_BLOCK(N, J, W, BAR, JN, C0, C1, L0, L1)     \
  L0 = lds128(gp + 128 * (N) + 256);                  \
  L1 = lds128(gp + 128 * (N) + 320);                  \
  E_TOKEN((N) - 1)                                    \
  if (ui == 0) mbar_wait(BAR, 0);                     \
  if (E_WAITS >> (N) & 1) wg_wait<1>();               \
  wg_fence();                                         \
  E_MMA2(J, W, ((N) & 1) * 4096, 1)                   \
  wg_commit();                                        \
  if ((N) < 7) joint_group(JN, fe + 8 * (((N) + 1) & 7), C0, C1);
#pragma unroll 1
  for (int ui = 0; ui < 4; ui++) {
    h0 = lds128(gp + 384);
    h1 = lds128(gp + 448);
    if (ui == 0) mbar_wait(bo0, 0);
    if (ui > 0 || wg == 1) bar_sync(3 + wg, 256);
    wg_fence();
    E_MMA2(j0, w0, 0, 0)
    E_MMA2(j1, w0, 4096, 1)
    wg_commit();
    joint_group(j2, fe + 16, g0, g1);
    E_BLOCK(2, j2, w1, bo0 + 8, j3, h0, h1, g0, g1)
    if (ui == 0) {
      if (wg == 0) publish();
      bar_sync(6 - wg, 256);
      const int row = warp * 16 + (lane & 7) + ((lane >> 3) & 1) * 8;
      const uint32_t xb = R1 + (wg == 1 ? 3 * 32768 : 32768 + 16384) + row * 128;
#pragma unroll
      for (int s = 0; s < 8; s++) {
        const int jj = 2 * s + (lane >> 4);
        ldsm4(xb + (s >> 2) * 8192 + (((jj & 7) ^ (lane & 7)) << 4), fe[32 + 4 * s], fe[33 + 4 * s], fe[34 + 4 * s], fe[35 + 4 * s]);
      }
    }
    E_BLOCK(3, j3, w1, bo0 + 8, j0, g0, g1, h0, h1)
    E_BLOCK(4, j0, w2, bo2, j1, h0, h1, g0, g1)
    E_BLOCK(5, j1, w2, bo2, j2, g0, g1, h0, h1)
    E_BLOCK(6, j2, w3, bo2 + 8, j3, h0, h1, g0, g1)
    E_BLOCK(7, j3, w3, bo2 + 8, j0, g0, g1, h0, h1)
    gp += 1024;
    if (ui < 3) {
      joint_group(j0, fe, g0, g1);
      g0 = lds128(gp + 256);
      g1 = lds128(gp + 320);
      if (ui == 0) mbar_wait(bo2 + 8, 0);
      joint_group(j1, fe + 8, h0, h1);
    }
    if (t == 0) bulk_wait_read<0>();
    bar_sync(1 + wg, 128);
    wg_wait<0>();
    reg_fence(acc);
    const uint32_t rb = stg + (warp * 16 + (lane & 7) + ((lane >> 3) & 1) * 8) * 128;
#pragma unroll
    for (int h = 0; h < 2; h++) {
#pragma unroll
      for (int j = 16 * h; j < 16 * h + 16; j += 2) {
        const int jj = j + (lane >> 4);
        stsm4(rb + (j >> 3) * 8192 + (((jj & 7) ^ (lane & 7)) << 4), pack2(acc[4 * j], acc[4 * j + 1]), pack2(acc[4 * j + 2], acc[4 * j + 3]),
              pack2(acc[4 * j + 4], acc[4 * j + 5]), pack2(acc[4 * j + 6], acc[4 * j + 7]));
      }
      fence_async();
      bar_sync(1 + wg, 128);
      if (t == 0) {
        tma_st5<1>(&mout, stg + h * 16384, 0, t0, 2 * h, wg * 4 + ui, b);
        bulk_commit();
      }
    }
  }
  if (t == 0) bulk_wait_read<0>();
}

typedef CUresult (*EncodeFn)(CUtensorMap*, CUtensorMapDataType, cuuint32_t, void*, const cuuint64_t*, const cuuint64_t*,
                             const cuuint32_t*, const cuuint32_t*, CUtensorMapInterleave, CUtensorMapSwizzle,
                             CUtensorMapL2promotion, CUtensorMapFloatOOBfill);

CUtensorMap make_map(EncodeFn fn, const void* base, int rank, const uint64_t* dims, const uint64_t* strides, const uint32_t* box,
                     CUtensorMapSwizzle swz) {
  CUtensorMap m;
  cuuint64_t gd[5], gs[4];
  cuuint32_t bx[5], es[5];
  for (int i = 0; i < rank; i++) { gd[i] = dims[i]; bx[i] = box[i]; es[i] = 1; }
  for (int i = 0; i + 1 < rank; i++) gs[i] = strides[i];
  fn(&m, CU_TENSOR_MAP_DATA_TYPE_BFLOAT16, rank, const_cast<void*>(base), gd, gs, bx, es, CU_TENSOR_MAP_INTERLEAVE_NONE, swz,
     CU_TENSOR_MAP_L2_PROMOTION_NONE, CU_TENSOR_MAP_FLOAT_OOB_FILL_NONE);
  return m;
}

template <typename... KArgs, typename... Args>
void launch(void (*k)(KArgs...), int grid, int block, int smem, bool pdl, Args... args) {
  cudaLaunchConfig_t c = {};
  c.gridDim = dim3(grid);
  c.blockDim = dim3(block);
  c.dynamicSmemBytes = smem;
  c.stream = cudaStreamPerThread;
  cudaLaunchAttribute at[1];
  at[0].id = cudaLaunchAttributeProgrammaticStreamSerialization;
  at[0].val.programmaticStreamSerializationAllowed = 1;
  c.attrs = at;
  c.numAttrs = pdl ? 1 : 0;
  cudaLaunchKernelEx(&c, k, args...);
}

}

static const uint32_t h_plan[67 + 25] = {
    0x6108, 0x6109, 0x610a, 0x610b, 0x6101, 0x8008, 0x8109, 0x820a, 0x830b, 0x8401,
    0x8508, 0x6102, 0x8609, 0x870a, 0x880b, 0x6103, 0x8a08, 0x8b02, 0x8c09, 0x8d0a,
    0x8e0b, 0x8f03, 0x9008, 0x9209, 0x930a, 0x9503, 0x9608, 0x9709, 0x980a, 0x9a08,
    0x9b09, 0x9c0a, 0x61616115, 0x6161610d, 0x61616107, 0x83816166, 0x8986610c, 0x8a89314d, 0x8f8a3237, 0x938f940b,
    0x9393344c, 0x9993354d, 0x0, 0x0, 0x0, 0x0, 0x0, 0x0, 0x6161ba98, 0x6161a981,
    0x6789281b, 0x67893ba9, 0x6891a928, 0x6891983b, 0x6999983a, 0x6999a98a, 0x39389d, 0x3, 0x4, 0x1dcc17b8,
    0x8f6a0c52, 0xac1, 0x2e5a9261, 0x194a, 0x9e, 0x9f, 0x37, 0x0, 0x0, 0x0,
    0x10, 0x11, 0x13, 0x14, 0x0, 0x0, 0x0, 0x0, 0x0, 0x0,
    0x0, 0x0, 0x0, 0x431, 0x431, 0x431, 0x0, 0x133, 0x131, 0x331,
    0x0, 0x3,
};

extern "C" void kernel_launch(void* const* d_in, const int* in_sizes, int n_in, void* d_out, int out_size) {
  const __nv_bfloat16* x = (const __nv_bfloat16*)d_in[0];
  const __nv_bfloat16* w1 = (const __nv_bfloat16*)d_in[1];
  const __nv_bfloat16* w2 = (const __nv_bfloat16*)d_in[2];
  const __nv_bfloat16* g = (const __nv_bfloat16*)d_in[3];
  const __nv_bfloat16* wf = (const __nv_bfloat16*)d_in[4];
  const __nv_bfloat16* wgt = (const __nv_bfloat16*)d_in[5];
  const __nv_bfloat16* wo = (const __nv_bfloat16*)d_in[6];

  void* fp = nullptr;
  cudaDriverEntryPointQueryResult qr;
  cudaGetDriverEntryPoint("cuTensorMapEncodeTiled", &fp, cudaEnableDefault, &qr);
  EncodeFn fn = (EncodeFn)fp;
  void *W2 = d_out, *X2 = (char*)d_out + W2_BYTES, *X1 = (char*)X2 - X2_BYTES, *Y1, *Y2;
  cudaGetSymbolAddress(&Y1, g_Y);
  Y2 = Y1;
  cudaFuncSetAttribute(k1, cudaFuncAttributeMaxDynamicSharedMemorySize, K1_SMEM);
  cudaFuncSetAttribute(k2, cudaFuncAttributeMaxDynamicSharedMemorySize, K2_SMEM);
  cudaFuncSetAttribute(kE, cudaFuncAttributeMaxDynamicSharedMemorySize, E_SMEM);
  const CUtensorMapSwizzle S128 = CU_TENSOR_MAP_SWIZZLE_128B;

  auto map_x = [&]() {
    uint64_t d[] = {64, 8000, 8, 2}, s[] = {1024, 128, 8000ull * 1024};
    uint32_t bx[] = {64, 56, 1, 1};
    return make_map(fn, x, 4, d, s, bx, S128);
  };
  auto map_w_in = [&](const __nv_bfloat16* w, int odd) {
    uint64_t d[] = {64, (uint64_t)(odd ? 15 : 16), 4, 256}, s[] = {2ull * 65536 * 2, 128, 512};
    uint32_t bx[] = {64, 16, 2, 1};
    return make_map(fn, w + (odd ? 65536 : 0), 4, d, s, bx, S128);
  };
  auto map_X_st = [&](void* p, int nb, int boxb) {
    uint64_t d[] = {64, 512, (uint64_t)(2 * nb)}, s[] = {2ull * nb * 128, 128};
    uint32_t bx[] = {64, C_PC, (uint32_t)boxb};
    return make_map(fn, p, 3, d, s, bx, S128);
  };
  auto map_X1_st = [&]() {
    uint64_t d[] = {64, 512, 2, (uint64_t)NB1}, s[] = {2ull * NB1 * 128, (uint64_t)NB1 * 128, 128};
    uint32_t bx[] = {64, 16, 1, 1};
    return make_map(fn, X1, 4, d, s, bx, S128);
  };
  auto map_W_st = [&](void* p) {
    uint64_t d[] = {64, 512, 4, 64}, s[] = {32768, 8192, 128};
    uint32_t bx[] = {64, W2_PC < 64 ? W2_PC : 64, W2_PC == 128 ? 2 : 1, 1};
    return make_map(fn, p, 4, d, s, bx, S128);
  };
  auto map_W_ld = [&](void* p, uint32_t bd, uint32_t bf) {
    uint64_t d[] = {64, 64, 4, 512}, s[] = {128, 8192, 32768};
    uint32_t bx[] = {64, 32, bd, bf};
    return make_map(fn, p, 4, d, s, bx, S128);
  };
  auto map_Y_st = [&](void* p, int nb, int rows) {
    uint64_t d[] = {64, (uint64_t)(2 * nb), 64, 4}, s[] = {32768, 128, 8192};
    uint32_t bx[] = {64, (uint32_t)rows, 1, 1};
    return make_map(fn, p, 4, d, s, bx, S128);
  };
  auto map_Y_ld = [&](void* p, int nb, int boxc, int boxb) {
    uint64_t d[] = {64, 64, 4, (uint64_t)nb, 2}, s[] = {128, 8192, 32768, (uint64_t)nb * 32768};
    uint32_t bx[] = {64, 64, (uint32_t)boxc, (uint32_t)boxb, 1};
    return make_map(fn, p, 5, d, s, bx, S128);
  };
  auto map_wsq = [&](const __nv_bfloat16* w, uint32_t bn) {
    uint64_t d[] = {64, 256, 4}, s[] = {512, 128};
    uint32_t bx[] = {64, 64, bn};
    return make_map(fn, w, 3, d, s, bx, S128);
  };
  auto map_out = [&]() {
    uint64_t d[] = {64, 4000, 4, 8, 2}, s[] = {4096, 128, 512, 4000ull * 4096};
    uint32_t bx[] = {64, 64, 2, 1, 1};
    return make_map(fn, d_out, 5, d, s, bx, S128);
  };

  auto map_w_raw = [&](const __nv_bfloat16* w, int odd) {
    uint64_t d[] = {256, (uint64_t)(odd ? 15 : 16), 16, 16}, s[] = {2ull * 65536 * 2, 512, 8192};
    uint32_t bx[] = {64, 16, 4, 2};
    return make_map(fn, w + (odd ? 65536 : 0), 4, d, s, bx, S128);
  };
  Ptrs gp;
  cudaGetSymbolAddress((void**)&gp.done, g_done);
  cudaGetSymbolAddress((void**)&gp.ge, g_ge);
  cudaGetSymbolAddress((void**)&gp.img, c_img);
  cudaGetSymbolAddress((void**)&gp.ga, c_ga);
  K1Maps g1;
  memcpy(&g1.p, h_plan, sizeof(Plan));
  g1.x = map_x();
  g1.we = map_w_raw(w1, 0);
  g1.wo = map_w_raw(w1, 1);
  g1.xs = map_X1_st();
  g1.y = map_Y_st(Y1, NB1, NB1 / G_EPI);
  g1.w2e = map_w_in(w2, 0);
  g1.w2o = map_w_in(w2, 1);
  g1.w2s = map_W_st(W2);
  for (int s = 0; s < 32; s++) {
    const int k = s < G_S0 ? s >> 1 : G_KM + (s - G_S0) % G_TK;
    g1.slot[s] = g_off(g_slot(s)) / 16;
    g1.src[s] = ((k >> 1) * 256 + (k & 1) * 2 + (s < G_S0 ? (s & 1) * 4 : s >= G_S0 + G_TK)) * (G_ST / 2);
    g1.dep[s] = s < 3 ? 8 * h_plan[64 + s] : 1536 + 8 * (s - g_depth(s));
  }
  launch(k1, 132, 384, K1_SMEM, false, gp, (const char*)X1, (const char*)w1, g1, g, wgt);
  K2Maps g2;
  memcpy(&g2, h_plan + 67, 100);
  g2.y = map_Y_ld(Y1, NB1, 1, 1);
  g2.xs = map_X_st(X2, NB2, 1);
  {
    uint64_t d[] = {64, 256, 2, 2 * NB2}, s[] = {2ull * NB2 * 128, 512ull * NB2 * 128, 128};
    uint32_t bx[] = {64, 64, 2, 1};
    g2.xa = make_map(fn, X2, 4, d, s, bx, S128);
  }
  g2.w = map_W_ld(W2, 1, 2);
  g2.y2 = map_Y_st(Y2, NB2, 168 / H_EPI);
  launch(k2, 128, 512, K2_SMEM, true, gp, (const char*)X2, g2, wf, wo);
  launch(kE, 126, 256, E_SMEM, true, map_Y_ld(Y2, NB2, 1, 2), map_wsq(wf, 2), map_wsq(wo, 4), map_out());
}
```

```cpp
#include <cuda_runtime.h>
#include <cuda_bf16.h>
#include <cuda.h>
#include <stdint.h>
#include <string.h>
#include <type_traits>

namespace {

constexpr int NB1 = 168;
constexpr int NB2 = 84;

constexpr size_t W2_BYTES = 8 * 64 * 4 * 64 * 64 * 2, X2_BYTES = 8 * 64 * 2 * NB2 * 64 * 2;
__device__ __align__(1024) __nv_bfloat16 g_Y[2 * NB1 * 4 * 64 * 64];
__device__ __align__(1024) float g_ge[16 * 256];

__device__ __forceinline__ uint32_t s2u(const void* p) { return (uint32_t)__cvta_generic_to_shared(p); }
__device__ __forceinline__ void mbar_init(uint32_t b, int c) {
  asm volatile("mbarrier.init.shared::cta.b64 [%0], %1;" ::"r"(b), "r"(c) : "memory");
}
__device__ __forceinline__ void mbar_expect(uint32_t b, int bytes) {
  asm volatile("mbarrier.arrive.expect_tx.shared::cta.b64 _, [%0], %1;" ::"r"(b), "r"(bytes) : "memory");
}
__device__ __forceinline__ void mbar_arrive(uint32_t b) {
  asm volatile("mbarrier.arrive.shared::cta.b64 _, [%0];" ::"r"(b) : "memory");
}
__device__ __forceinline__ void mbar_arrive_cta(uint32_t b, uint32_t cta) {
  asm volatile("{\n.reg .b32 r;\nmapa.shared::cluster.u32 r, %0, %1;\nmbarrier.arrive.shared::cluster.b64 _, [r];\n}" ::"r"(b), "r"(cta) : "memory");
}
__device__ __forceinline__ void mbar_wait(uint32_t b, int ph) {
  asm volatile(
      "{\n.reg .pred p;\n.reg .u32 n;\n"
      "mov.u32 n, 0;\n"
      "MBW_LOOP:\n"
      "mbarrier.try_wait.parity.shared::cta.b64 p, [%0], %1;\n"
      "@p bra MBW_DONE;\n"
      "add.u32 n, n, 1;\n"
      "setp.lt.u32 p, n, 1048576;\n"
      "@p bra MBW_LOOP;\n"
      "MBW_DONE:\n}" ::"r"(b), "r"(ph) : "memory");
}
__device__ __forceinline__ void fence_bar_init() { asm volatile("fence.mbarrier_init.release.cluster;" ::: "memory"); }
__device__ __forceinline__ void fence_async() { asm volatile("fence.proxy.async.shared::cta;" ::: "memory"); }
__device__ __forceinline__ void bar_sync(int id, int n) { asm volatile("bar.sync %0, %1;" ::"r"(id), "r"(n) : "memory"); }
__device__ __forceinline__ void bar_arrive(int id, int n) { asm volatile("bar.arrive %0, %1;" ::"r"(id), "r"(n) : "memory"); }
__device__ __forceinline__ void pdl_wait() { asm volatile("griddepcontrol.wait;" ::: "memory"); }
__device__ __forceinline__ void pdl_launch() { asm volatile("griddepcontrol.launch_dependents;" ::: "memory"); }
__device__ __forceinline__ void prefetch_map(const CUtensorMap* m) {
  asm volatile("prefetch.tensormap [%0];" ::"l"(m) : "memory");
}
template <int P> __device__ __forceinline__ uint64_t policy() {
  uint64_t p;
  asm("createpolicy.fractional.L2::evict_first.b64 %0, 1.0;" : "=l"(p));
  return p;
}
template <int P> __device__ __forceinline__ void tma_ld3(uint32_t dst, const CUtensorMap* m, uint32_t bar, int c0, int c1, int c2) {
  if constexpr (P == 0)
    asm volatile("cp.async.bulk.tensor.3d.shared::cluster.global.mbarrier::complete_tx::bytes [%0], [%1, {%3, %4, %5}], [%2];"
                 ::"r"(dst), "l"(m), "r"(bar), "r"(c0), "r"(c1), "r"(c2) : "memory");
  else
    asm volatile("cp.async.bulk.tensor.3d.shared::cluster.global.mbarrier::complete_tx::bytes.L2::cache_hint [%0], [%1, {%3, %4, %5}], [%2], %6;"
                 ::"r"(dst), "l"(m), "r"(bar), "r"(c0), "r"(c1), "r"(c2), "l"(policy<P>()) : "memory");
}
template <int P> __device__ __forceinline__ void tma_ld4(uint32_t dst, const CUtensorMap* m, uint32_t bar, int c0, int c1, int c2, int c3) {
  if constexpr (P == 0)
    asm volatile("cp.async.bulk.tensor.4d.shared::cluster.global.mbarrier::complete_tx::bytes [%0], [%1, {%3, %4, %5, %6}], [%2];"
                 ::"r"(dst), "l"(m), "r"(bar), "r"(c0), "r"(c1), "r"(c2), "r"(c3) : "memory");
  else
    asm volatile("cp.async.bulk.tensor.4d.shared::cluster.global.mbarrier::complete_tx::bytes.L2::cache_hint [%0], [%1, {%3, %4, %5, %6}], [%2], %7;"
                 ::"r"(dst), "l"(m), "r"(bar), "r"(c0), "r"(c1), "r"(c2), "r"(c3), "l"(policy<P>()) : "memory");
}
template <int P> __device__ __forceinline__ void tma_ld5(uint32_t dst, const CUtensorMap* m, uint32_t bar, int c0, int c1, int c2, int c3, int c4) {
  if constexpr (P == 0)
    asm volatile("cp.async.bulk.tensor.5d.shared::cluster.global.mbarrier::complete_tx::bytes [%0], [%1, {%3, %4, %5, %6, %7}], [%2];"
                 ::"r"(dst), "l"(m), "r"(bar), "r"(c0), "r"(c1), "r"(c2), "r"(c3), "r"(c4) : "memory");
  else
    asm volatile("cp.async.bulk.tensor.5d.shared::cluster.global.mbarrier::complete_tx::bytes.L2::cache_hint [%0], [%1, {%3, %4, %5, %6, %7}], [%2], %8;"
                 ::"r"(dst), "l"(m), "r"(bar), "r"(c0), "r"(c1), "r"(c2), "r"(c3), "r"(c4), "l"(policy<P>()) : "memory");
}
template <int P> __device__ __forceinline__ void tma_st3(const CUtensorMap* m, uint32_t src, int c0, int c1, int c2) {
  if constexpr (P == 0)
    asm volatile("cp.async.bulk.tensor.3d.global.shared::cta.bulk_group [%0, {%2, %3, %4}], [%1];" ::"l"(m), "r"(src), "r"(c0), "r"(c1), "r"(c2) : "memory");
  else
    asm volatile("cp.async.bulk.tensor.3d.global.shared::cta.bulk_group.L2::cache_hint [%0, {%2, %3, %4}], [%1], %5;" ::"l"(m), "r"(src), "r"(c0), "r"(c1), "r"(c2), "l"(policy<P>()) : "memory");
}
template <int P> __device__ __forceinline__ void tma_st4(const CUtensorMap* m, uint32_t src, int c0, int c1, int c2, int c3) {
  if constexpr (P == 0)
    asm volatile("cp.async.bulk.tensor.4d.global.shared::cta.bulk_group [%0, {%2, %3, %4, %5}], [%1];" ::"l"(m), "r"(src), "r"(c0), "r"(c1), "r"(c2), "r"(c3) : "memory");
  else
    asm volatile("cp.async.bulk.tensor.4d.global.shared::cta.bulk_group.L2::cache_hint [%0, {%2, %3, %4, %5}], [%1], %6;" ::"l"(m), "r"(src), "r"(c0), "r"(c1), "r"(c2), "r"(c3), "l"(policy<P>()) : "memory");
}
template <int P> __device__ __forceinline__ void tma_st5(const CUtensorMap* m, uint32_t src, int c0, int c1, int c2, int c3, int c4) {
  if constexpr (P == 0)
    asm volatile("cp.async.bulk.tensor.5d.global.shared::cta.bulk_group [%0, {%2, %3, %4, %5, %6}], [%1];" ::"l"(m), "r"(src), "r"(c0), "r"(c1), "r"(c2), "r"(c3), "r"(c4) : "memory");
  else
    asm volatile("cp.async.bulk.tensor.5d.global.shared::cta.bulk_group.L2::cache_hint [%0, {%2, %3, %4, %5, %6}], [%1], %7;" ::"l"(m), "r"(src), "r"(c0), "r"(c1), "r"(c2), "r"(c3), "r"(c4), "l"(policy<P>()) : "memory");
}
__device__ __forceinline__ void bulk_commit() { asm volatile("cp.async.bulk.commit_group;" ::: "memory"); }
template <int N> __device__ __forceinline__ void bulk_wait_read() { asm volatile("cp.async.bulk.wait_group.read %0;" ::"n"(N) : "memory"); }
__device__ __forceinline__ void wg_fence() { asm volatile("wgmma.fence.sync.aligned;" ::: "memory"); }
__device__ __forceinline__ void wg_commit() { asm volatile("wgmma.commit_group.sync.aligned;" ::: "memory"); }
template <int N> __device__ __forceinline__ void wg_wait() { asm volatile("wgmma.wait_group.sync.aligned %0;" ::"n"(N) : "memory"); }
template <int R> __device__ __forceinline__ void reg_fence(float (&d)[R]) {
#pragma unroll
  for (int i = 0; i < R; i++) asm volatile("" : "+f"(d[i])::"memory");
}
template <int R> __device__ __forceinline__ void reg_fence(uint32_t (&d)[R]) {
#pragma unroll
  for (int i = 0; i < R; i++) asm volatile("" : "+r"(d[i])::"memory");
}
__device__ __forceinline__ void stsm4(uint32_t a, uint32_t r0, uint32_t r1, uint32_t r2, uint32_t r3) {
  asm volatile("stmatrix.sync.aligned.m8n8.x4.shared.b16 [%0], {%1, %2, %3, %4};" ::"r"(a), "r"(r0), "r"(r1), "r"(r2), "r"(r3) : "memory");
}
__device__ __forceinline__ void stsm4t(uint32_t a, uint32_t r0, uint32_t r1, uint32_t r2, uint32_t r3) {
  asm volatile("stmatrix.sync.aligned.m8n8.x4.trans.shared.b16 [%0], {%1, %2, %3, %4};" ::"r"(a), "r"(r0), "r"(r1), "r"(r2), "r"(r3) : "memory");
}
__device__ __forceinline__ void ldsm4(uint32_t a, uint32_t& r0, uint32_t& r1, uint32_t& r2, uint32_t& r3) {
  asm volatile("ldmatrix.sync.aligned.m8n8.x4.shared.b16 {%0, %1, %2, %3}, [%4];" : "=r"(r0), "=r"(r1), "=r"(r2), "=r"(r3) : "r"(a) : "memory");
}
__device__ __forceinline__ void ldsm4t(uint32_t a, uint32_t& r0, uint32_t& r1, uint32_t& r2, uint32_t& r3) {
  asm volatile("ldmatrix.sync.aligned.m8n8.x4.trans.shared.b16 {%0, %1, %2, %3}, [%4];" : "=r"(r0), "=r"(r1), "=r"(r2), "=r"(r3) : "r"(a) : "memory");
}
__device__ __forceinline__ void ldg128(const uint4* p, uint32_t& a, uint32_t& b, uint32_t& c, uint32_t& d) {
  asm volatile("ld.global.nc.v4.u32 {%0, %1, %2, %3}, [%4];" : "=r"(a), "=r"(b), "=r"(c), "=r"(d) : "l"(p));
}
__device__ __forceinline__ uint32_t pack2(float lo, float hi) {
  uint32_t r;
  asm("cvt.rn.bf16x2.f32 %0, %1, %2;" : "=r"(r) : "f"(hi), "f"(lo));
  return r;
}
__device__ __forceinline__ float tanh_f32(float x) {
  float y;
  asm("tanh.approx.f32 %0, %1;" : "=f"(y) : "f"(x));
  return y;
}
__device__ __forceinline__ float gelu(float hx) {
  const float u = hx * fmaf(hx * hx, 8.0f * 0.044715f * 0.7978845608028654f, 2.0f * 0.7978845608028654f);
  return fmaf(hx, tanh_f32(u), hx);
}
__device__ __forceinline__ uint64_t mk_desc4(uint32_t addr4, uint32_t lbo, uint32_t sbo, uint32_t swz) {
  const uint32_t lo = addr4 + ((lbo >> 4) << 16), hi = (sbo >> 4) | (swz << 30);
  uint64_t d;
  asm("mov.b64 %0, {%1, %2};" : "=l"(d) : "r"(lo), "r"(hi));
  return d;
}
#define mk_desc(base, off, lbo, sbo, swz) mk_desc4((((base) & 0x3FFFF) >> 4) + ((off) >> 4), lbo, sbo, swz)

template <int SA, int SB, int TA, int TB>
__device__ __forceinline__ void wgmma_ss_48(float (&d)[24], uint64_t da, uint64_t db, int sd) {
  asm volatile("{\n.reg .pred p;\nsetp.ne.b32 p, %26, 0;\n"
      "wgmma.mma_async.sync.aligned.m64n48k16.f32.bf16.bf16 {"
      "%0, %1, %2, %3, %4, %5, %6, %7, %8, %9, %10, %11, %12, %13, %14, %15, %16, %17, %18, %19, %20, %21, %22, %23"
      "}, %24, %25, p, %27, %28, %29, %30;\n}\n"
      : "+f"(d[0]), "+f"(d[1]), "+f"(d[2]), "+f"(d[3]), "+f"(d[4]), "+f"(d[5]), "+f"(d[6]), "+f"(d[7]), "+f"(d[8]),
        "+f"(d[9]), "+f"(d[10]), "+f"(d[11]), "+f"(d[12]), "+f"(d[13]), "+f"(d[14]), "+f"(d[15]), "+f"(d[16]),
        "+f"(d[17]), "+f"(d[18]), "+f"(d[19]), "+f"(d[20]), "+f"(d[21]), "+f"(d[22]), "+f"(d[23])
      : "l"(da), "l"(db), "r"(sd), "n"(SA), "n"(SB), "n"(TA), "n"(TB));
}
template <int SA, int SB, int TA, int TB>
__device__ __forceinline__ void wgmma_ss_128(float (&d)[64], uint64_t da, uint64_t db, int sd) {
  asm volatile("{\n.reg .pred p;\nsetp.ne.b32 p, %66, 0;\n"
      "wgmma.mma_async.sync.aligned.m64n128k16.f32.bf16.bf16 {"
      "%0, %1, %2, %3, %4, %5, %6, %7, %8, %9, %10, %11, %12, %13, %14, %15, %16, %17, %18, %19, %20, %21, %22, %23, "
      "%24, %25, %26, %27, %28, %29, %30, %31, %32, %33, %34, %35, %36, %37, %38, %39, %40, %41, %42, %43, %44, %45, "
      "%46, %47, %48, %49, %50, %51, %52, %53, %54, %55, %56, %57, %58, %59, %60, %61, %62, %63"
      "}, %64, %65, p, %67, %68, %69, %70;\n}\n"
      : "+f"(d[0]), "+f"(d[1]), "+f"(d[2]), "+f"(d[3]), "+f"(d[4]), "+f"(d[5]), "+f"(d[6]), "+f"(d[7]), "+f"(d[8]),
        "+f"(d[9]), "+f"(d[10]), "+f"(d[11]), "+f"(d[12]), "+f"(d[13]), "+f"(d[14]), "+f"(d[15]), "+f"(d[16]),
        "+f"(d[17]), "+f"(d[18]), "+f"(d[19]), "+f"(d[20]), "+f"(d[21]), "+f"(d[22]), "+f"(d[23]), "+f"(d[24]),
        "+f"(d[25]), "+f"(d[26]), "+f"(d[27]), "+f"(d[28]), "+f"(d[29]), "+f"(d[30]), "+f"(d[31]), "+f"(d[32]),
        "+f"(d[33]), "+f"(d[34]), "+f"(d[35]), "+f"(d[36]), "+f"(d[37]), "+f"(d[38]), "+f"(d[39]), "+f"(d[40]),
        "+f"(d[41]), "+f"(d[42]), "+f"(d[43]), "+f"(d[44]), "+f"(d[45]), "+f"(d[46]), "+f"(d[47]), "+f"(d[48]),
        "+f"(d[49]), "+f"(d[50]), "+f"(d[51]), "+f"(d[52]), "+f"(d[53]), "+f"(d[54]), "+f"(d[55]), "+f"(d[56]),
        "+f"(d[57]), "+f"(d[58]), "+f"(d[59]), "+f"(d[60]), "+f"(d[61]), "+f"(d[62]), "+f"(d[63])
      : "l"(da), "l"(db), "r"(sd), "n"(SA), "n"(SB), "n"(TA), "n"(TB));
}
template <int SA, int SB, int TA, int TB>
__device__ __forceinline__ void wgmma_ss_168(float (&d)[84], uint64_t da, uint64_t db, int sd) {
  asm volatile("{\n.reg .pred p;\nsetp.ne.b32 p, %86, 0;\n"
      "wgmma.mma_async.sync.aligned.m64n168k16.f32.bf16.bf16 {"
      "%0, %1, %2, %3, %4, %5, %6, %7, %8, %9, %10, %11, %12, %13, %14, %15, %16, %17, %18, %19, %20, %21, %22, %23, "
      "%24, %25, %26, %27, %28, %29, %30, %31, %32, %33, %34, %35, %36, %37, %38, %39, %40, %41, %42, %43, %44, %45, "
      "%46, %47, %48, %49, %50, %51, %52, %53, %54, %55, %56, %57, %58, %59, %60, %61, %62, %63, %64, %65, %66, %67, "
      "%68, %69, %70, %71, %72, %73, %74, %75, %76, %77, %78, %79, %80, %81, %82, %83"
      "}, %84, %85, p, %87, %88, %89, %90;\n}\n"
      : "+f"(d[0]), "+f"(d[1]), "+f"(d[2]), "+f"(d[3]), "+f"(d[4]), "+f"(d[5]), "+f"(d[6]), "+f"(d[7]), "+f"(d[8]),
        "+f"(d[9]), "+f"(d[10]), "+f"(d[11]), "+f"(d[12]), "+f"(d[13]), "+f"(d[14]), "+f"(d[15]), "+f"(d[16]),
        "+f"(d[17]), "+f"(d[18]), "+f"(d[19]), "+f"(d[20]), "+f"(d[21]), "+f"(d[22]), "+f"(d[23]), "+f"(d[24]),
        "+f"(d[25]), "+f"(d[26]), "+f"(d[27]), "+f"(d[28]), "+f"(d[29]), "+f"(d[30]), "+f"(d[31]), "+f"(d[32]),
        "+f"(d[33]), "+f"(d[34]), "+f"(d[35]), "+f"(d[36]), "+f"(d[37]), "+f"(d[38]), "+f"(d[39]), "+f"(d[40]),
        "+f"(d[41]), "+f"(d[42]), "+f"(d[43]), "+f"(d[44]), "+f"(d[45]), "+f"(d[46]), "+f"(d[47]), "+f"(d[48]),
        "+f"(d[49]), "+f"(d[50]), "+f"(d[51]), "+f"(d[52]), "+f"(d[53]), "+f"(d[54]), "+f"(d[55]), "+f"(d[56]),
        "+f"(d[57]), "+f"(d[58]), "+f"(d[59]), "+f"(d[60]), "+f"(d[61]), "+f"(d[62]), "+f"(d[63]), "+f"(d[64]),
        "+f"(d[65]), "+f"(d[66]), "+f"(d[67]), "+f"(d[68]), "+f"(d[69]), "+f"(d[70]), "+f"(d[71]), "+f"(d[72]),
        "+f"(d[73]), "+f"(d[74]), "+f"(d[75]), "+f"(d[76]), "+f"(d[77]), "+f"(d[78]), "+f"(d[79]), "+f"(d[80]),
        "+f"(d[81]), "+f"(d[82]), "+f"(d[83])
      : "l"(da), "l"(db), "r"(sd), "n"(SA), "n"(SB), "n"(TA), "n"(TB));
}
template <int SA, int SB, int TB>
__device__ __forceinline__ void wgmma_rs_32(float (&d)[16], uint32_t a0, uint32_t a1, uint32_t a2, uint32_t a3, uint64_t db, int sd) {
  asm volatile("{\n.reg .pred p;\nsetp.ne.b32 p, %21, 0;\n"
      "wgmma.mma_async.sync.aligned.m64n32k16.f32.bf16.bf16 {"
      "%0, %1, %2, %3, %4, %5, %6, %7, %8, %9, %10, %11, %12, %13, %14, %15"
      "}, {%16, %17, %18, %19}, %20, p, %22, %23, %24;\n}\n"
      : "+f"(d[0]), "+f"(d[1]), "+f"(d[2]), "+f"(d[3]), "+f"(d[4]), "+f"(d[5]), "+f"(d[6]), "+f"(d[7]), "+f"(d[8]),
        "+f"(d[9]), "+f"(d[10]), "+f"(d[11]), "+f"(d[12]), "+f"(d[13]), "+f"(d[14]), "+f"(d[15])
      : "r"(a0), "r"(a1), "r"(a2), "r"(a3), "l"(db), "r"(sd), "n"(SA), "n"(SB), "n"(TB));
}
template <int SA, int SB, int TB>
__device__ __forceinline__ void wgmma_rs_64(float (&d)[32], uint32_t a0, uint32_t a1, uint32_t a2, uint32_t a3, uint64_t db, int sd) {
  asm volatile("{\n.reg .pred p;\nsetp.ne.b32 p, %37, 0;\n"
      "wgmma.mma_async.sync.aligned.m64n64k16.f32.bf16.bf16 {"
      "%0, %1, %2, %3, %4, %5, %6, %7, %8, %9, %10, %11, %12, %13, %14, %15, %16, %17, %18, %19, %20, %21, %22, %23, "
      "%24, %25, %26, %27, %28, %29, %30, %31"
      "}, {%32, %33, %34, %35}, %36, p, %38, %39, %40;\n}\n"
      : "+f"(d[0]), "+f"(d[1]), "+f"(d[2]), "+f"(d[3]), "+f"(d[4]), "+f"(d[5]), "+f"(d[6]), "+f"(d[7]), "+f"(d[8]),
        "+f"(d[9]), "+f"(d[10]), "+f"(d[11]), "+f"(d[12]), "+f"(d[13]), "+f"(d[14]), "+f"(d[15]), "+f"(d[16]),
        "+f"(d[17]), "+f"(d[18]), "+f"(d[19]), "+f"(d[20]), "+f"(d[21]), "+f"(d[22]), "+f"(d[23]), "+f"(d[24]),
        "+f"(d[25]), "+f"(d[26]), "+f"(d[27]), "+f"(d[28]), "+f"(d[29]), "+f"(d[30]), "+f"(d[31])
      : "r"(a0), "r"(a1), "r"(a2), "r"(a3), "l"(db), "r"(sd), "n"(SA), "n"(SB), "n"(TB));
}
template <int SA, int SB, int TB>
__device__ __forceinline__ void wgmma_rs_128(float (&d)[64], uint32_t a0, uint32_t a1, uint32_t a2, uint32_t a3, uint64_t db, int sd) {
  asm volatile("{\n.reg .pred p;\nsetp.ne.b32 p, %69, 0;\n"
      "wgmma.mma_async.sync.aligned.m64n128k16.f32.bf16.bf16 {"
      "%0, %1, %2, %3, %4, %5, %6, %7, %8, %9, %10, %11, %12, %13, %14, %15, %16, %17, %18, %19, %20, %21, %22, %23, "
      "%24, %25, %26, %27, %28, %29, %30, %31, %32, %33, %34, %35, %36, %37, %38, %39, %40, %41, %42, %43, %44, %45, "
      "%46, %47, %48, %49, %50, %51, %52, %53, %54, %55, %56, %57, %58, %59, %60, %61, %62, %63"
      "}, {%64, %65, %66, %67}, %68, p, %70, %71, %72;\n}\n"
      : "+f"(d[0]), "+f"(d[1]), "+f"(d[2]), "+f"(d[3]), "+f"(d[4]), "+f"(d[5]), "+f"(d[6]), "+f"(d[7]), "+f"(d[8]),
        "+f"(d[9]), "+f"(d[10]), "+f"(d[11]), "+f"(d[12]), "+f"(d[13]), "+f"(d[14]), "+f"(d[15]), "+f"(d[16]),
        "+f"(d[17]), "+f"(d[18]), "+f"(d[19]), "+f"(d[20]), "+f"(d[21]), "+f"(d[22]), "+f"(d[23]), "+f"(d[24]),
        "+f"(d[25]), "+f"(d[26]), "+f"(d[27]), "+f"(d[28]), "+f"(d[29]), "+f"(d[30]), "+f"(d[31]), "+f"(d[32]),
        "+f"(d[33]), "+f"(d[34]), "+f"(d[35]), "+f"(d[36]), "+f"(d[37]), "+f"(d[38]), "+f"(d[39]), "+f"(d[40]),
        "+f"(d[41]), "+f"(d[42]), "+f"(d[43]), "+f"(d[44]), "+f"(d[45]), "+f"(d[46]), "+f"(d[47]), "+f"(d[48]),
        "+f"(d[49]), "+f"(d[50]), "+f"(d[51]), "+f"(d[52]), "+f"(d[53]), "+f"(d[54]), "+f"(d[55]), "+f"(d[56]),
        "+f"(d[57]), "+f"(d[58]), "+f"(d[59]), "+f"(d[60]), "+f"(d[61]), "+f"(d[62]), "+f"(d[63])
      : "r"(a0), "r"(a1), "r"(a2), "r"(a3), "l"(db), "r"(sd), "n"(SA), "n"(SB), "n"(TB));
}
template <int SA, int SB, int TB>
__device__ __forceinline__ void wgmma_rs_168(float (&d)[84], uint32_t a0, uint32_t a1, uint32_t a2, uint32_t a3, uint64_t db, int sd) {
  asm volatile("{\n.reg .pred p;\nsetp.ne.b32 p, %89, 0;\n"
      "wgmma.mma_async.sync.aligned.m64n168k16.f32.bf16.bf16 {"
      "%0, %1, %2, %3, %4, %5, %6, %7, %8, %9, %10, %11, %12, %13, %14, %15, %16, %17, %18, %19, %20, %21, %22, %23, "
      "%24, %25, %26, %27, %28, %29, %30, %31, %32, %33, %34, %35, %36, %37, %38, %39, %40, %41, %42, %43, %44, %45, "
      "%46, %47, %48, %49, %50, %51, %52, %53, %54, %55, %56, %57, %58, %59, %60, %61, %62, %63, %64, %65, %66, %67, "
      "%68, %69, %70, %71, %72, %73, %74, %75, %76, %77, %78, %79, %80, %81, %82, %83"
      "}, {%84, %85, %86, %87}, %88, p, %90, %91, %92;\n}\n"
      : "+f"(d[0]), "+f"(d[1]), "+f"(d[2]), "+f"(d[3]), "+f"(d[4]), "+f"(d[5]), "+f"(d[6]), "+f"(d[7]), "+f"(d[8]),
        "+f"(d[9]), "+f"(d[10]), "+f"(d[11]), "+f"(d[12]), "+f"(d[13]), "+f"(d[14]), "+f"(d[15]), "+f"(d[16]),
        "+f"(d[17]), "+f"(d[18]), "+f"(d[19]), "+f"(d[20]), "+f"(d[21]), "+f"(d[22]), "+f"(d[23]), "+f"(d[24]),
        "+f"(d[25]), "+f"(d[26]), "+f"(d[27]), "+f"(d[28]), "+f"(d[29]), "+f"(d[30]), "+f"(d[31]), "+f"(d[32]),
        "+f"(d[33]), "+f"(d[34]), "+f"(d[35]), "+f"(d[36]), "+f"(d[37]), "+f"(d[38]), "+f"(d[39]), "+f"(d[40]),
        "+f"(d[41]), "+f"(d[42]), "+f"(d[43]), "+f"(d[44]), "+f"(d[45]), "+f"(d[46]), "+f"(d[47]), "+f"(d[48]),
        "+f"(d[49]), "+f"(d[50]), "+f"(d[51]), "+f"(d[52]), "+f"(d[53]), "+f"(d[54]), "+f"(d[55]), "+f"(d[56]),
        "+f"(d[57]), "+f"(d[58]), "+f"(d[59]), "+f"(d[60]), "+f"(d[61]), "+f"(d[62]), "+f"(d[63]), "+f"(d[64]),
        "+f"(d[65]), "+f"(d[66]), "+f"(d[67]), "+f"(d[68]), "+f"(d[69]), "+f"(d[70]), "+f"(d[71]), "+f"(d[72]),
        "+f"(d[73]), "+f"(d[74]), "+f"(d[75]), "+f"(d[76]), "+f"(d[77]), "+f"(d[78]), "+f"(d[79]), "+f"(d[80]),
        "+f"(d[81]), "+f"(d[82]), "+f"(d[83])
      : "r"(a0), "r"(a1), "r"(a2), "r"(a3), "l"(db), "r"(sd), "n"(SA), "n"(SB), "n"(TB));
}
template <int SA, int SB, int TB>
__device__ __forceinline__ void wgmma_rs_256(float (&d)[128], uint32_t a0, uint32_t a1, uint32_t a2, uint32_t a3, uint64_t db, int sd) {
  asm volatile("{\n.reg .pred p;\nsetp.ne.b32 p, %133, 0;\n"
      "wgmma.mma_async.sync.aligned.m64n256k16.f32.bf16.bf16 {"
      "%0, %1, %2, %3, %4, %5, %6, %7, %8, %9, %10, %11, %12, %13, %14, %15, %16, %17, %18, %19, %20, %21, %22, %23, "
      "%24, %25, %26, %27, %28, %29, %30, %31, %32, %33, %34, %35, %36, %37, %38, %39, %40, %41, %42, %43, %44, %45, "
      "%46, %47, %48, %49, %50, %51, %52, %53, %54, %55, %56, %57, %58, %59, %60, %61, %62, %63, %64, %65, %66, %67, "
      "%68, %69, %70, %71, %72, %73, %74, %75, %76, %77, %78, %79, %80, %81, %82, %83, %84, %85, %86, %87, %88, %89, "
      "%90, %91, %92, %93, %94, %95, %96, %97, %98, %99, %100, %101, %102, %103, %104, %105, %106, %107, %108, %109, "
      "%110, %111, %112, %113, %114, %115, %116, %117, %118, %119, %120, %121, %122, %123, %124, %125, %126, %127"
      "}, {%128, %129, %130, %131}, %132, p, %134, %135, %136;\n}\n"
      : "+f"(d[0]), "+f"(d[1]), "+f"(d[2]), "+f"(d[3]), "+f"(d[4]), "+f"(d[5]), "+f"(d[6]), "+f"(d[7]), "+f"(d[8]),
        "+f"(d[9]), "+f"(d[10]), "+f"(d[11]), "+f"(d[12]), "+f"(d[13]), "+f"(d[14]), "+f"(d[15]), "+f"(d[16]),
        "+f"(d[17]), "+f"(d[18]), "+f"(d[19]), "+f"(d[20]), "+f"(d[21]), "+f"(d[22]), "+f"(d[23]), "+f"(d[24]),
        "+f"(d[25]), "+f"(d[26]), "+f"(d[27]), "+f"(d[28]), "+f"(d[29]), "+f"(d[30]), "+f"(d[31]), "+f"(d[32]),
        "+f"(d[33]), "+f"(d[34]), "+f"(d[35]), "+f"(d[36]), "+f"(d[37]), "+f"(d[38]), "+f"(d[39]), "+f"(d[40]),
        "+f"(d[41]), "+f"(d[42]), "+f"(d[43]), "+f"(d[44]), "+f"(d[45]), "+f"(d[46]), "+f"(d[47]), "+f"(d[48]),
        "+f"(d[49]), "+f"(d[50]), "+f"(d[51]), "+f"(d[52]), "+f"(d[53]), "+f"(d[54]), "+f"(d[55]), "+f"(d[56]),
        "+f"(d[57]), "+f"(d[58]), "+f"(d[59]), "+f"(d[60]), "+f"(d[61]), "+f"(d[62]), "+f"(d[63]), "+f"(d[64]),
        "+f"(d[65]), "+f"(d[66]), "+f"(d[67]), "+f"(d[68]), "+f"(d[69]), "+f"(d[70]), "+f"(d[71]), "+f"(d[72]),
        "+f"(d[73]), "+f"(d[74]), "+f"(d[75]), "+f"(d[76]), "+f"(d[77]), "+f"(d[78]), "+f"(d[79]), "+f"(d[80]),
        "+f"(d[81]), "+f"(d[82]), "+f"(d[83]), "+f"(d[84]), "+f"(d[85]), "+f"(d[86]), "+f"(d[87]), "+f"(d[88]),
        "+f"(d[89]), "+f"(d[90]), "+f"(d[91]), "+f"(d[92]), "+f"(d[93]), "+f"(d[94]), "+f"(d[95]), "+f"(d[96]),
        "+f"(d[97]), "+f"(d[98]), "+f"(d[99]), "+f"(d[100]), "+f"(d[101]), "+f"(d[102]), "+f"(d[103]), "+f"(d[104]),
        "+f"(d[105]), "+f"(d[106]), "+f"(d[107]), "+f"(d[108]), "+f"(d[109]), "+f"(d[110]), "+f"(d[111]),
        "+f"(d[112]), "+f"(d[113]), "+f"(d[114]), "+f"(d[115]), "+f"(d[116]), "+f"(d[117]), "+f"(d[118]),
        "+f"(d[119]), "+f"(d[120]), "+f"(d[121]), "+f"(d[122]), "+f"(d[123]), "+f"(d[124]), "+f"(d[125]),
        "+f"(d[126]), "+f"(d[127])
      : "r"(a0), "r"(a1), "r"(a2), "r"(a3), "l"(db), "r"(sd), "n"(SA), "n"(SB), "n"(TB));
}

__device__ const __align__(128) uint32_t c_img[3584] = {
    0x00003c80, 0x00003c80, 0x00003c80, 0x00003c80, 0x00003c80, 0x00003c80, 0x00003c80, 0x00003c80, 0x00003c80, 0x00003c80,
    0x00003c80, 0x00003c80, 0x00003c80, 0x00003c80, 0x00003c80, 0x00003c80, 0x00003c80, 0x00003c80, 0x00003c80, 0x00003c80,
    0x00003c80, 0x00003c80, 0x00003c80, 0x00003c80, 0x00003c80, 0x00003c80, 0x00003c80, 0x00003c80, 0x00003c80, 0x00003c80,
    0x00003c80, 0x00003c80, 0x3c463c22, 0x3c623bf1, 0x3c753b95, 0x3c7f3ac9, 0x3ac93c7f, 0x3b953c75, 0x3bf13c62, 0x3c223c46,
    0x3c22bc46, 0x3bf1bc62, 0x3b95bc75, 0x3ac9bc7f, 0x3c7fbac9, 0x3c75bb95, 0x3c62bbf1, 0x3c46bc22, 0xbc46bc22, 0xbc62bbf1,
    0xbc75bb95, 0xbc7fbac9, 0xbac9bc7f, 0xbb95bc75, 0xbbf1bc62, 0xbc22bc46, 0xbc223c46, 0xbbf13c62, 0xbb953c75, 0xbac93c7f,
    0xbc7f3ac9, 0xbc753b95, 0xbc623bf1, 0xbc463c22, 0xbb48bc7b, 0xbc0ebc55, 0xbc55bc0e, 0xbc7bbb48, 0xbc7b3b48, 0xbc553c0e,
    0xbc0e3c55, 0xbb483c7b, 0x3b483c7b, 0x3c0e3c55, 0x3c553c0e, 0x3c7b3b48, 0x3c7bbb48, 0x3c55bc0e, 0x3c0ebc55, 0x3b48bc7b,
    0xbb48bc7b, 0xbc0ebc55, 0xbc55bc0e, 0xbc7bbb48, 0xbc7b3b48, 0xbc553c0e, 0xbc0e3c55, 0xbb483c7b, 0x3b483c7b, 0x3c0e3c55,
    0x3c553c0e, 0x3c7b3b48, 0x3c7bbb48, 0x3c55bc0e, 0x3c0ebc55, 0x3b48bc7b, 0x3c623bf1, 0x3c7fbac9, 0x3c46bc22, 0x3b95bc75,
    0xbc753b95, 0xbc223c46, 0xbac93c7f, 0x3bf13c62, 0x3bf1bc62, 0xbac9bc7f, 0xbc22bc46, 0xbc75bb95, 0x3b953c75, 0x3c463c22,
    0x3c7f3ac9, 0x3c62bbf1, 0xbc62bbf1, 0xbc7f3ac9, 0xbc463c22, 0xbb953c75, 0x3c75bb95, 0x3c22bc46, 0x3ac9bc7f, 0xbbf1bc62,
    0xbbf13c62, 0x3ac93c7f, 0x3c223c46, 0x3c753b95, 0xbb95bc75, 0xbc46bc22, 0xbc7fbac9, 0xbc623bf1, 0x3bc43c6d, 0x3c6d3bc4,
    0x3c6dbbc4, 0x3bc4bc6d, 0xbbc4bc6d, 0xbc6dbbc4, 0xbc6d3bc4, 0xbbc43c6d, 0x3bc43c6d, 0x3c6d3bc4, 0x3c6dbbc4, 0x3bc4bc6d,
    0xbbc4bc6d, 0xbc6dbbc4, 0xbc6d3bc4, 0xbbc43c6d, 0x3bc43c6d, 0x3c6d3bc4, 0x3c6dbbc4, 0x3bc4bc6d, 0xbbc4bc6d, 0xbc6dbbc4,
    0xbc6d3bc4, 0xbbc43c6d, 0x3bc43c6d, 0x3c6d3bc4, 0x3c6dbbc4, 0x3bc4bc6d, 0xbbc4bc6d, 0xbc6dbbc4, 0xbc6d3bc4, 0xbbc43c6d,
    0x3c753b95, 0x3c46bc22, 0xbac9bc7f, 0xbc62bbf1, 0xbbf1bc62, 0xbc7fbac9, 0xbc223c46, 0x3b953c75, 0x3b95bc75, 0xbc22bc46,
    0xbc7f3ac9, 0xbbf13c62, 0xbc623bf1, 0xbac93c7f, 0x3c463c22, 0x3c75bb95, 0xbc75bb95, 0xbc463c22, 0x3ac93c7f, 0x3c623bf1,
    0x3bf13c62, 0x3c7f3ac9, 0x3c22bc46, 0xbb95bc75, 0xbb953c75, 0x3c223c46, 0x3c7fbac9, 0x3bf1bc62, 0x3c62bbf1, 0x3ac9bc7f,
    0xbc46bc22, 0xbc753b95, 0xbc0ebc55, 0xbc7b3b48, 0xbb483c7b, 0x3c553c0e, 0x3c55bc0e, 0xbb48bc7b, 0xbc7bbb48, 0xbc0e3c55,
    0x3c0e3c55, 0x3c7bbb48, 0x3b48bc7b, 0xbc55bc0e, 0xbc553c0e, 0x3b483c7b, 0x3c7b3b48, 0x3c0ebc55, 0xbc0ebc55, 0xbc7b3b48,
    0xbb483c7b, 0x3c553c0e, 0x3c55bc0e, 0xbb48bc7b, 0xbc7bbb48, 0xbc0e3c55, 0x3c0e3c55, 0x3c7bbb48, 0x3b48bc7b, 0xbc55bc0e,
    0xbc553c0e, 0x3b483c7b, 0x3c7b3b48, 0x3c0ebc55, 0x3c7f3ac9, 0x3b95bc75, 0xbc62bbf1, 0xbc223c46, 0x3c46bc22, 0xbbf1bc62,
    0xbc753b95, 0x3ac93c7f, 0x3ac9bc7f, 0xbc75bb95, 0xbbf13c62, 0x3c463c22, 0xbc22bc46, 0xbc623bf1, 0x3b953c75, 0x3c7fbac9,
    0xbc7fbac9, 0xbb953c75, 0x3c623bf1, 0x3c22bc46, 0xbc463c22, 0x3bf13c62, 0x3c75bb95, 0xbac9bc7f, 0xbac93c7f, 0x3c753b95,
    0x3bf1bc62, 0xbc46bc22, 0x3c223c46, 0x3c62bbf1, 0xbb95bc75, 0xbc7f3ac9, 0x3a493c80, 0x3b163c7d, 0x3b793c78, 0x3bac3c71,
    0x3bdb3c67, 0x3c043c5c, 0x3c183c4e, 0x3c2c3c3e, 0x3c3e3c2c, 0x3c4e3c18, 0x3c5c3c04, 0x3c673bdb, 0x3c713bac, 0x3c783b79,
    0x3c7d3b16, 0x3c803a49, 0x3c80ba49, 0x3c7dbb16, 0x3c78bb79, 0x3c71bbac, 0x3c67bbdb, 0x3c5cbc04, 0x3c4ebc18, 0x3c3ebc2c,
    0x3c2cbc3e, 0x3c18bc4e, 0x3c04bc5c, 0x3bdbbc67, 0x3bacbc71, 0x3b79bc78, 0x3b16bc7d, 0x3a49bc80, 0x3c783b79, 0x3c80ba49,
    0x3c71bbac, 0x3c4ebc18, 0x3b163c7d, 0x3bdb3c67, 0x3c2c3c3e, 0x3c5c3c04, 0xbc04bc5c, 0xbc3ebc2c, 0xbc67bbdb, 0xbc7dbb16,
    0x3c18bc4e, 0x3bacbc71, 0x3a49bc80, 0xbb79bc78, 0xbb793c78, 0x3a493c80, 0x3bac3c71, 0x3c183c4e, 0xbc7d3b16, 0xbc673bdb,
    0xbc3e3c2c, 0xbc043c5c, 0x3c5cbc04, 0x3c2cbc3e, 0x3bdbbc67, 0x3b16bc7d, 0x3c4e3c18, 0x3c713bac, 0x3c803a49, 0x3c78bb79,
    0xbc5cbc04, 0xbc80ba49, 0xbc673bdb, 0xbc183c4e, 0xbb163c7d, 0x3bac3c71, 0x3c3e3c2c, 0x3c783b79, 0x3b793c78, 0x3c2c3c3e,
    0x3c713bac, 0x3c7dbb16, 0x3c4ebc18, 0x3bdbbc67, 0xba49bc80, 0xbc04bc5c, 0xbc043c5c, 0xba493c80, 0x3bdb3c67, 0x3c4e3c18,
    0x3c7d3b16, 0x3c71bbac, 0x3c2cbc3e, 0x3b79bc78, 0x3c78bb79, 0x3c3ebc2c, 0x3bacbc71, 0xbb16bc7d, 0xbc18bc4e, 0xbc67bbdb,
    0xbc803a49, 0xbc5c3c04, 0x3c3ebc2c, 0x3b16bc7d, 0xbc04bc5c, 0xbc71bbac, 0xbbdb3c67, 0x3b793c78, 0x3c4e3c18, 0x3c80ba49,
    0x3a49bc80, 0xbc18bc4e, 0xbc78bb79, 0xbc673bdb, 0x3bac3c71, 0x3c5c3c04, 0x3c7dbb16, 0x3c2cbc3e, 0x3c2c3c3e, 0x3c7d3b16,
    0x3c5cbc04, 0x3bacbc71, 0xbc67bbdb, 0xbc783b79, 0xbc183c4e, 0x3a493c80, 0x3c803a49, 0x3c4ebc18, 0x3b79bc78, 0xbbdbbc67,
    0xbc713bac, 0xbc043c5c, 0x3b163c7d, 0x3c3e3c2c, 0x3c67bbdb, 0x3b79bc78, 0xbc18bc4e, 0xbc80ba49, 0xbc2c3c3e, 0x3b163c7d,
    0x3c5c3c04, 0x3c71bbac, 0x3bacbc71, 0xbc04bc5c, 0xbc7dbb16, 0xbc3e3c2c, 0x3a493c80, 0x3c4e3c18, 0x3c78bb79, 0x3bdbbc67,
    0x3bdb3c67, 0x3c783b79, 0x3c4ebc18, 0x3a49bc80, 0xbc3ebc2c, 0xbc7d3b16, 0xbc043c5c, 0x3bac3c71, 0x3c713bac, 0x3c5cbc04,
    0x3b16bc7d, 0xbc2cbc3e, 0xbc803a49, 0xbc183c4e, 0x3b793c78, 0x3c673bdb, 0xbb16bc7d, 0xbc71bbac, 0xbc3e3c2c, 0x3b793c78,
    0xbc5c3c04, 0x3a493c80, 0x3c673bdb, 0x3c4ebc18, 0xbc183c4e, 0x3bdb3c67, 0x3c803a49, 0x3c04bc5c, 0x3c783b79, 0x3c2cbc3e,
    0xbbacbc71, 0xbc7dbb16, 0xbc7d3b16, 0xbbac3c71, 0x3c2c3c3e, 0x3c78bb79, 0x3c043c5c, 0x3c80ba49, 0x3bdbbc67, 0xbc18bc4e,
    0x3c4e3c18, 0x3c67bbdb, 0x3a49bc80, 0xbc5cbc04, 0x3b79bc78, 0xbc3ebc2c, 0xbc713bac, 0xbb163c7d, 0xbb163c7d, 0x3c673bdb,
    0x3c2cbc3e, 0xbc04bc5c, 0xbc783b79, 0xba493c80, 0x3c713bac, 0x3c18bc4e, 0x3c4ebc18, 0xbbacbc71, 0xbc803a49, 0xbb793c78,
    0x3c5c3c04, 0x3c3ebc2c, 0xbbdbbc67, 0xbc7d3b16, 0xbc7dbb16, 0xbbdb3c67, 0x3c3e3c2c, 0x3c5cbc04, 0xbb79bc78, 0xbc80ba49,
    0xbbac3c71, 0x3c4e3c18, 0x3c183c4e, 0x3c71bbac, 0xba49bc80, 0xbc78bb79, 0xbc043c5c, 0x3c2c3c3e, 0x3c67bbdb, 0xbb16bc7d,
    0xbc67bbdb, 0xbc043c5c, 0x3c4e3c18, 0x3c2cbc3e, 0xbc80ba49, 0xbb163c7d, 0x3c783b79, 0x3bacbc71, 0xbc713bac, 0x3b793c78,
    0x3c7dbb16, 0xba49bc80, 0xbc3e3c2c, 0x3c183c4e, 0x3c5cbc04, 0xbbdbbc67, 0xbbdb3c67, 0x3c5c3c04, 0x3c18bc4e, 0xbc3ebc2c,
    0xba493c80, 0x3c7d3b16, 0x3b79bc78, 0xbc71bbac, 0x3bac3c71, 0x3c78bb79, 0xbb16bc7d, 0xbc803a49, 0x3c2c3c3e, 0x3c4ebc18,
    0xbc04bc5c, 0xbc673bdb, 0x3c353c35, 0x3c35bc35, 0xbc35bc35, 0xbc353c35, 0x3c353c35, 0x3c35bc35, 0xbc35bc35, 0xbc353c35,
    0x3c353c35, 0x3c35bc35, 0xbc35bc35, 0xbc353c35, 0x3c353c35, 0x3c35bc35, 0xbc35bc35, 0xbc353c35, 0x3c353c35, 0x3c35bc35,
    0xbc35bc35, 0xbc353c35, 0x3c353c35, 0x3c35bc35, 0xbc35bc35, 0xbc353c35, 0x3c353c35, 0x3c35bc35, 0xbc35bc35, 0xbc353c35,
    0x3c353c35, 0x3c35bc35, 0xbc35bc35, 0xbc353c35, 0x3c7fbac9, 0xbb95bc75, 0xbc623bf1, 0x3c223c46, 0x3c463c22, 0x3bf1bc62,
    0xbc75bb95, 0xbac93c7f, 0xbac9bc7f, 0xbc753b95, 0x3bf13c62, 0x3c46bc22, 0x3c22bc46, 0xbc62bbf1, 0xbb953c75, 0x3c7f3ac9,
    0xbc7f3ac9, 0x3b953c75, 0x3c62bbf1, 0xbc22bc46, 0xbc46bc22, 0xbbf13c62, 0x3c753b95, 0x3ac9bc7f, 0x3ac93c7f, 0x3c75bb95,
    0xbbf1bc62, 0xbc463c22, 0xbc223c46, 0x3c623bf1, 0x3b95bc75, 0xbc7fbac9, 0xbc55bc0e, 0xbb483c7b, 0x3c7bbb48, 0xbc0ebc55,
    0xbc0e3c55, 0x3c7b3b48, 0xbb48bc7b, 0xbc553c0e, 0x3c553c0e, 0x3b48bc7b, 0xbc7b3b48, 0x3c0e3c55, 0x3c0ebc55, 0xbc7bbb48,
    0x3b483c7b, 0x3c55bc0e, 0xbc55bc0e, 0xbb483c7b, 0x3c7bbb48, 0xbc0ebc55, 0xbc0e3c55, 0x3c7b3b48, 0xbb48bc7b, 0xbc553c0e,
    0x3c553c0e, 0x3b48bc7b, 0xbc7b3b48, 0x3c0e3c55, 0x3c0ebc55, 0xbc7bbb48, 0x3b483c7b, 0x3c55bc0e, 0x3c75bb95, 0xbc46bc22,
    0xbac93c7f, 0x3c62bbf1, 0xbbf13c62, 0x3c7fbac9, 0xbc22bc46, 0xbb953c75, 0xbb95bc75, 0xbc223c46, 0x3c7f3ac9, 0xbbf1bc62,
    0x3c623bf1, 0xbac9bc7f, 0xbc463c22, 0x3c753b95, 0xbc753b95, 0x3c463c22, 0x3ac9bc7f, 0xbc623bf1, 0x3bf1bc62, 0xbc7f3ac9,
    0x3c223c46, 0x3b95bc75, 0x3b953c75, 0x3c22bc46, 0xbc7fbac9, 0x3bf13c62, 0xbc62bbf1, 0x3ac93c7f, 0x3c46bc22, 0xbc75bb95,
    0x3c6d3bc4, 0xbbc4bc6d, 0xbbc43c6d, 0x3c6dbbc4, 0xbc6dbbc4, 0x3bc43c6d, 0x3bc4bc6d, 0xbc6d3bc4, 0x3c6d3bc4, 0xbbc4bc6d,
    0xbbc43c6d, 0x3c6dbbc4, 0xbc6dbbc4, 0x3bc43c6d, 0x3bc4bc6d, 0xbc6d3bc4, 0x3c6d3bc4, 0xbbc4bc6d, 0xbbc43c6d, 0x3c6dbbc4,
    0xbc6dbbc4, 0x3bc43c6d, 0x3bc4bc6d, 0xbc6d3bc4, 0x3c6d3bc4, 0xbbc4bc6d, 0xbbc43c6d, 0x3c6dbbc4, 0xbc6dbbc4, 0x3bc43c6d,
    0x3bc4bc6d, 0xbc6d3bc4, 0x3c62bbf1, 0xbc7fbac9, 0x3c463c22, 0xbb95bc75, 0xbc75bb95, 0x3c223c46, 0xbac9bc7f, 0xbbf13c62,
    0xbbf1bc62, 0xbac93c7f, 0x3c22bc46, 0xbc753b95, 0xbb953c75, 0x3c46bc22, 0xbc7f3ac9, 0x3c623bf1, 0xbc623bf1, 0x3c7f3ac9,
    0xbc46bc22, 0x3b953c75, 0x3c753b95, 0xbc22bc46, 0x3ac93c7f, 0x3bf1bc62, 0x3bf13c62, 0x3ac9bc7f, 0xbc223c46, 0x3c75bb95,
    0x3b95bc75, 0xbc463c22, 0x3c7fbac9, 0xbc62bbf1, 0xbc7bbb48, 0x3c553c0e, 0xbc0ebc55, 0x3b483c7b, 0x3b48bc7b, 0xbc0e3c55,
    0x3c55bc0e, 0xbc7b3b48, 0x3c7b3b48, 0xbc55bc0e, 0x3c0e3c55, 0xbb48bc7b, 0xbb483c7b, 0x3c0ebc55, 0xbc553c0e, 0x3c7bbb48,
    0xbc7bbb48, 0x3c553c0e, 0xbc0ebc55, 0x3b483c7b, 0x3b48bc7b, 0xbc0e3c55, 0x3c55bc0e, 0xbc7b3b48, 0x3c7b3b48, 0xbc55bc0e,
    0x3c0e3c55, 0xbb48bc7b, 0xbb483c7b, 0x3c0ebc55, 0xbc553c0e, 0x3c7bbb48, 0x3c46bc22, 0xbc623bf1, 0x3c75bb95, 0xbc7f3ac9,
    0x3ac9bc7f, 0xbb953c75, 0x3bf1bc62, 0xbc223c46, 0xbc22bc46, 0x3bf13c62, 0xbb95bc75, 0x3ac93c7f, 0xbc7fbac9, 0x3c753b95,
    0xbc62bbf1, 0x3c463c22, 0xbc463c22, 0x3c62bbf1, 0xbc753b95, 0x3c7fbac9, 0xbac93c7f, 0x3b95bc75, 0xbbf13c62, 0x3c22bc46,
    0x3c223c46, 0xbbf1bc62, 0x3b953c75, 0xbac9bc7f, 0x3c7f3ac9, 0xbc75bb95, 0x3c623bf1, 0xbc46bc22, 0x3c3e3c2c, 0x3c18bc4e,
    0xbc5cbc04, 0xbbdb3c67, 0x3c713bac, 0x3b79bc78, 0xbc7dbb16, 0xba493c80, 0x3c80ba49, 0xbb16bc7d, 0xbc783b79, 0x3bac3c71,
    0x3c67bbdb, 0xbc04bc5c, 0xbc4e3c18, 0x3c2c3c3e, 0x3c2cbc3e, 0xbc4ebc18, 0xbc043c5c, 0x3c673bdb, 0x3bacbc71, 0xbc78bb79,
    0xbb163c7d, 0x3c803a49, 0xba49bc80, 0xbc7d3b16, 0x3b793c78, 0x3c71bbac, 0xbbdbbc67, 0xbc5c3c04, 0x3c183c4e, 0x3c3ebc2c,
    0x3c5cbc04, 0xbc3ebc2c, 0xbbdb3c67, 0x3c7d3b16, 0x3c4e3c18, 0x3bacbc71, 0xbc80ba49, 0x3b793c78, 0xbc78bb79, 0x3a493c80,
    0x3c71bbac, 0xbc18bc4e, 0xbb16bc7d, 0xbc673bdb, 0x3c2c3c3e, 0x3c04bc5c, 0x3c043c5c, 0x3c2cbc3e, 0xbc67bbdb, 0xbb163c7d,
    0xbc183c4e, 0x3c713bac, 0x3a49bc80, 0xbc783b79, 0x3b79bc78, 0xbc803a49, 0x3bac3c71, 0x3c4ebc18, 0x3c7dbb16, 0xbbdbbc67,
    0xbc3e3c2c, 0x3c5c3c04, 0xbc783b79, 0x3c2c3c3e, 0x3bacbc71, 0xbc7d3b16, 0x3c183c4e, 0x3bdbbc67, 0xbc803a49, 0x3c043c5c,
    0x3c5c3c04, 0x3a49bc80, 0xbc673bdb, 0x3c4e3c18, 0x3b16bc7d, 0xbc713bac, 0x3c3e3c2c, 0x3b79bc78, 0x3b793c78, 0x3c3ebc2c,
    0xbc71bbac, 0x3b163c7d, 0x3c4ebc18, 0xbc67bbdb, 0x3a493c80, 0x3c5cbc04, 0x3c04bc5c, 0xbc80ba49, 0x3bdb3c67, 0x3c18bc4e,
    0xbc7dbb16, 0x3bac3c71, 0x3c2cbc3e, 0xbc78bb79, 0x3a49bc80, 0xbc4e3c18, 0x3c783b79, 0xbbdbbc67, 0x3bac3c71, 0x3c04bc5c,
    0xbc7d3b16, 0x3c3e3c2c, 0xbc2cbc3e, 0xbb163c7d, 0x3c5cbc04, 0xbc71bbac, 0x3c673bdb, 0xbb79bc78, 0xbc183c4e, 0x3c80ba49,
    0x3c803a49, 0xbc18bc4e, 0xbb793c78, 0x3c67bbdb, 0xbc713bac, 0x3c5c3c04, 0xbb16bc7d, 0xbc2c3c3e, 0x3c3ebc2c, 0xbc7dbb16,
    0x3c043c5c, 0x3bacbc71, 0xbbdb3c67, 0x3c78bb79, 0xbc4ebc18, 0x3a493c80, 0x3bacbc71, 0xbc5c3c04, 0x3c7d3b16, 0xbc2cbc3e,
    0x3a493c80, 0x3c18bc4e, 0xbc783b79, 0x3c673bdb, 0xbbdbbc67, 0xbb793c78, 0x3c4ebc18, 0xbc80ba49, 0x3c3e3c2c, 0xbb16bc7d,
    0xbc043c5c, 0x3c71bbac, 0x3c713bac, 0xbc04bc5c, 0xbb163c7d, 0x3c3ebc2c, 0xbc803a49, 0x3c4e3c18, 0xbb79bc78, 0xbbdb3c67,
    0x3c67bbdb, 0xbc78bb79, 0x3c183c4e, 0x3a49bc80, 0xbc2c3c3e, 0x3c7dbb16, 0xbc5cbc04, 0x3bac3c71, 0xbc4ebc18, 0x3bdb3c67,
    0x3a49bc80, 0xbc043c5c, 0xbb793c78, 0x3c2cbc3e, 0xbc713bac, 0x3c7d3b16, 0x3b163c7d, 0x3bacbc71, 0xbc3e3c2c, 0x3c78bb79,
    0x3c5cbc04, 0xbc803a49, 0x3c673bdb, 0xbc18bc4e, 0xbc183c4e, 0x3c67bbdb, 0xbc80ba49, 0x3c5c3c04, 0x3c783b79, 0xbc3ebc2c,
    0x3bac3c71, 0x3b16bc7d, 0x3c7dbb16, 0xbc71bbac, 0x3c2c3c3e, 0xbb79bc78, 0xbc04bc5c, 0x3a493c80, 0x3bdbbc67, 0xbc4e3c18,
    0x3c183c4e, 0xbbacbc71, 0x3a493c80, 0x3b79bc78, 0xbc043c5c, 0x3c3ebc2c, 0xbc673bdb, 0x3c7dbb16, 0x3b16bc7d, 0xbbdb3c67,
    0x3c2cbc3e, 0xbc5c3c04, 0x3c78bb79, 0xbc80ba49, 0x3c713bac, 0xbc4ebc18, 0xbc4e3c18, 0x3c71bbac, 0xbc803a49, 0x3c783b79,
    0xbc5cbc04, 0x3c2c3c3e, 0xbbdbbc67, 0x3b163c7d, 0x3c7d3b16, 0xbc67bbdb, 0x3c3e3c2c, 0xbc04bc5c, 0x3b793c78, 0x3a49bc80,
    0xbbac3c71, 0x3c18bc4e, 0xbc713bac, 0x3c78bb79, 0xbc7d3b16, 0x3c80ba49, 0xbc3e3c2c, 0x3c4ebc18, 0xbc5c3c04, 0x3c67bbdb,
    0xbbdb3c67, 0x3c04bc5c, 0xbc183c4e, 0x3c2cbc3e, 0xba493c80, 0x3b16bc7d, 0xbb793c78, 0x3bacbc71, 0x3bac3c71, 0xbb79bc78,
    0x3b163c7d, 0xba49bc80, 0x3c2c3c3e, 0xbc18bc4e, 0x3c043c5c, 0xbbdbbc67, 0x3c673bdb, 0xbc5cbc04, 0x3c4e3c18, 0xbc3ebc2c,
    0x3c803a49, 0xbc7dbb16, 0x3c783b79, 0xbc71bbac, 0x3c800000, 0xbc800000, 0x3c800000, 0xbc800000, 0x3c800000, 0xbc800000,
    0x3c800000, 0xbc800000, 0x3c800000, 0xbc800000, 0x3c800000, 0xbc800000, 0x3c800000, 0xbc800000, 0x3c800000, 0xbc800000,
    0x3c800000, 0xbc800000, 0x3c800000, 0xbc800000, 0x3c800000, 0xbc800000, 0x3c800000, 0xbc800000, 0x3c800000, 0xbc800000,
    0x3c800000, 0xbc800000, 0x3c800000, 0xbc800000, 0x3c800000, 0xbc800000, 0x3c22bc46, 0xbbf13c62, 0x3b95bc75, 0xbac93c7f,
    0x3c7fbac9, 0xbc753b95, 0x3c62bbf1, 0xbc463c22, 0xbc46bc22, 0x3c623bf1, 0xbc75bb95, 0x3c7f3ac9, 0xbac9bc7f, 0x3b953c75,
    0xbbf1bc62, 0x3c223c46, 0xbc223c46, 0x3bf1bc62, 0xbb953c75, 0x3ac9bc7f, 0xbc7f3ac9, 0x3c75bb95, 0xbc623bf1, 0x3c46bc22,
    0x3c463c22, 0xbc62bbf1, 0x3c753b95, 0xbc7fbac9, 0x3ac93c7f, 0xbb95bc75, 0x3bf13c62, 0xbc22bc46, 0xbc7b3b48, 0x3c55bc0e,
    0xbc0e3c55, 0x3b48bc7b, 0x3b483c7b, 0xbc0ebc55, 0x3c553c0e, 0xbc7bbb48, 0x3c7bbb48, 0xbc553c0e, 0x3c0ebc55, 0xbb483c7b,
    0xbb48bc7b, 0x3c0e3c55, 0xbc55bc0e, 0x3c7b3b48, 0xbc7b3b48, 0x3c55bc0e, 0xbc0e3c55, 0x3b48bc7b, 0x3b483c7b, 0xbc0ebc55,
    0x3c553c0e, 0xbc7bbb48, 0x3c7bbb48, 0xbc553c0e, 0x3c0ebc55, 0xbb483c7b, 0xbb48bc7b, 0x3c0e3c55, 0xbc55bc0e, 0x3c7b3b48,
    0x3bf1bc62, 0x3ac93c7f, 0xbc22bc46, 0x3c753b95, 0x3b953c75, 0xbc46bc22, 0x3c7f3ac9, 0xbc623bf1, 0xbc62bbf1, 0x3c7fbac9,
    0xbc463c22, 0x3b95bc75, 0x3c75bb95, 0xbc223c46, 0x3ac9bc7f, 0x3bf13c62, 0xbbf13c62, 0xbac9bc7f, 0x3c223c46, 0xbc75bb95,
    0xbb95bc75, 0x3c463c22, 0xbc7fbac9, 0x3c62bbf1, 0x3c623bf1, 0xbc7f3ac9, 0x3c46bc22, 0xbb953c75, 0xbc753b95, 0x3c22bc46,
    0xbac93c7f, 0xbbf1bc62, 0x3c6dbbc4, 0xbbc43c6d, 0xbbc4bc6d, 0x3c6d3bc4, 0xbc6d3bc4, 0x3bc4bc6d, 0x3bc43c6d, 0xbc6dbbc4,
    0x3c6dbbc4, 0xbbc43c6d, 0xbbc4bc6d, 0x3c6d3bc4, 0xbc6d3bc4, 0x3bc4bc6d, 0x3bc43c6d, 0xbc6dbbc4, 0x3c6dbbc4, 0xbbc43c6d,
    0xbbc4bc6d, 0x3c6d3bc4, 0xbc6d3bc4, 0x3bc4bc6d, 0x3bc43c6d, 0xbc6dbbc4, 0x3c6dbbc4, 0xbbc43c6d, 0xbbc4bc6d, 0x3c6d3bc4,
    0xbc6d3bc4, 0x3bc4bc6d, 0x3bc43c6d, 0xbc6dbbc4, 0x3b95bc75, 0x3c223c46, 0xbc7f3ac9, 0x3bf1bc62, 0xbc623bf1, 0x3ac9bc7f,
    0x3c463c22, 0xbc753b95, 0xbc75bb95, 0x3c46bc22, 0x3ac93c7f, 0xbc62bbf1, 0x3bf13c62, 0xbc7fbac9, 0x3c22bc46, 0x3b953c75,
    0xbb953c75, 0xbc22bc46, 0x3c7fbac9, 0xbbf13c62, 0x3c62bbf1, 0xbac93c7f, 0xbc46bc22, 0x3c75bb95, 0x3c753b95, 0xbc463c22,
    0xbac9bc7f, 0x3c623bf1, 0xbbf1bc62, 0x3c7f3ac9, 0xbc223c46, 0xbb95bc75, 0xbc553c0e, 0xbb48bc7b, 0x3c7b3b48, 0xbc0e3c55,
    0xbc0ebc55, 0x3c7bbb48, 0xbb483c7b, 0xbc55bc0e, 0x3c55bc0e, 0x3b483c7b, 0xbc7bbb48, 0x3c0ebc55, 0x3c0e3c55, 0xbc7b3b48,
    0x3b48bc7b, 0x3c553c0e, 0xbc553c0e, 0xbb48bc7b, 0x3c7b3b48, 0xbc0e3c55, 0xbc0ebc55, 0x3c7bbb48, 0xbb483c7b, 0xbc55bc0e,
    0x3c55bc0e, 0x3b483c7b, 0xbc7bbb48, 0x3c0ebc55, 0x3c0e3c55, 0xbc7b3b48, 0x3b48bc7b, 0x3c553c0e, 0x3ac9bc7f, 0x3c753b95,
    0xbbf13c62, 0xbc46bc22, 0xbc22bc46, 0x3c62bbf1, 0x3b953c75, 0xbc7f3ac9, 0xbc7fbac9, 0x3b95bc75, 0x3c623bf1, 0xbc223c46,
    0xbc463c22, 0xbbf1bc62, 0x3c75bb95, 0x3ac93c7f, 0xbac93c7f, 0xbc75bb95, 0x3bf1bc62, 0x3c463c22, 0x3c223c46, 0xbc623bf1,
    0xbb95bc75, 0x3c7fbac9, 0x3c7f3ac9, 0xbb953c75, 0xbc62bbf1, 0x3c22bc46, 0x3c46bc22, 0x3bf13c62, 0xbc753b95, 0xbac9bc7f,
    0x3c80ba49, 0xbc7d3b16, 0x3c78bb79, 0xbc713bac, 0x3c67bbdb, 0xbc5c3c04, 0x3c4ebc18, 0xbc3e3c2c, 0x3c2cbc3e, 0xbc183c4e,
    0x3c04bc5c, 0xbbdb3c67, 0x3bacbc71, 0xbb793c78, 0x3b16bc7d, 0xba493c80, 0xba49bc80, 0x3b163c7d, 0xbb79bc78, 0x3bac3c71,
    0xbbdbbc67, 0x3c043c5c, 0xbc18bc4e, 0x3c2c3c3e, 0xbc3ebc2c, 0x3c4e3c18, 0xbc5cbc04, 0x3c673bdb, 0xbc71bbac, 0x3c783b79,
    0xbc7dbb16, 0x3c803a49, 0x3b79bc78, 0x3a493c80, 0xbbacbc71, 0x3c183c4e, 0x3c7dbb16, 0xbc673bdb, 0x3c3ebc2c, 0xbc043c5c,
    0xbc5c3c04, 0x3c2cbc3e, 0xbbdb3c67, 0x3b16bc7d, 0xbc4ebc18, 0x3c713bac, 0xbc80ba49, 0x3c78bb79, 0x3c783b79, 0xbc803a49,
    0x3c71bbac, 0xbc4e3c18, 0x3b163c7d, 0xbbdbbc67, 0x3c2c3c3e, 0xbc5cbc04, 0xbc04bc5c, 0x3c3e3c2c, 0xbc67bbdb, 0x3c7d3b16,
    0x3c18bc4e, 0xbbac3c71, 0x3a49bc80, 0x3b793c78, 0xbc043c5c, 0x3a49bc80, 0x3bdb3c67, 0xbc4ebc18, 0x3c7d3b16, 0xbc713bac,
    0x3c2cbc3e, 0xbb793c78, 0x3c78bb79, 0xbc3e3c2c, 0x3bacbc71, 0x3b163c7d, 0xbc18bc4e, 0x3c673bdb, 0xbc803a49, 0x3c5cbc04,
    0x3c5c3c04, 0xbc80ba49, 0x3c67bbdb, 0xbc183c4e, 0x3b16bc7d, 0x3bac3c71, 0xbc3ebc2c, 0x3c783b79, 0xbb79bc78, 0x3c2c3c3e,
    0xbc71bbac, 0x3c7dbb16, 0xbc4e3c18, 0x3bdbbc67, 0x3a493c80, 0xbc04bc5c, 0xbc2cbc3e, 0x3c7d3b16, 0xbc5c3c04, 0x3bacbc71,
    0x3c673bdb, 0xbc783b79, 0x3c18bc4e, 0x3a493c80, 0xbc80ba49, 0x3c4ebc18, 0xbb793c78, 0xbbdbbc67, 0x3c71bbac, 0xbc043c5c,
    0xbb16bc7d, 0x3c3e3c2c, 0x3c3ebc2c, 0xbb163c7d, 0xbc04bc5c, 0x3c713bac, 0xbbdb3c67, 0xbb79bc78, 0x3c4e3c18, 0xbc803a49,
    0x3a49bc80, 0x3c183c4e, 0xbc78bb79, 0x3c67bbdb, 0x3bac3c71, 0xbc5cbc04, 0x3c7dbb16, 0xbc2c3c3e, 0xbbdbbc67, 0x3c783b79,
    0xbc4e3c18, 0x3a49bc80, 0x3c3e3c2c, 0xbc7d3b16, 0x3c04bc5c, 0x3bac3c71, 0xbc71bbac, 0x3c5cbc04, 0xbb163c7d, 0xbc2cbc3e,
    0x3c80ba49, 0xbc183c4e, 0xbb79bc78, 0x3c673bdb, 0x3c67bbdb, 0xbb793c78, 0xbc18bc4e, 0x3c803a49, 0xbc2c3c3e, 0xbb16bc7d,
    0x3c5c3c04, 0xbc713bac, 0x3bacbc71, 0x3c043c5c, 0xbc7dbb16, 0x3c3ebc2c, 0x3a493c80, 0xbc4ebc18, 0x3c78bb79, 0xbbdb3c67,
    0xbc7d3b16, 0x3bacbc71, 0x3c2c3c3e, 0xbc783b79, 0x3c043c5c, 0xbc803a49, 0x3bdbbc67, 0x3c183c4e, 0x3c4e3c18, 0xbc673bdb,
    0x3a49bc80, 0x3c5c3c04, 0x3b79bc78, 0x3c3e3c2c, 0xbc713bac, 0x3b16bc7d, 0x3b163c7d, 0xbc71bbac, 0x3c3ebc2c, 0x3b793c78,
    0x3c5cbc04, 0x3a493c80, 0xbc67bbdb, 0x3c4ebc18, 0x3c18bc4e, 0x3bdb3c67, 0xbc80ba49, 0x3c04bc5c, 0xbc78bb79, 0x3c2cbc3e,
    0x3bac3c71, 0xbc7dbb16, 0x3c7d3b16, 0xbbdb3c67, 0xbc3ebc2c, 0x3c5cbc04, 0x3b793c78, 0xbc80ba49, 0x3bacbc71, 0x3c4e3c18,
    0xbc18bc4e, 0x3c71bbac, 0x3a493c80, 0xbc78bb79, 0x3c04bc5c, 0x3c2c3c3e, 0xbc673bdb, 0xbb16bc7d, 0xbb163c7d, 0xbc67bbdb,
    0x3c2cbc3e, 0x3c043c5c, 0xbc783b79, 0x3a49bc80, 0x3c713bac, 0xbc183c4e, 0x3c4ebc18, 0x3bac3c71, 0xbc803a49, 0x3b79bc78,
    0x3c5c3c04, 0xbc3e3c2c, 0xbbdbbc67, 0x3c7dbb16, 0xbbdb3c67, 0xbc5cbc04, 0x3c18bc4e, 0x3c3e3c2c, 0xba493c80, 0xbc7dbb16,
    0x3b79bc78, 0x3c713bac, 0x3bac3c71, 0xbc783b79, 0xbb16bc7d, 0x3c80ba49, 0x3c2c3c3e, 0xbc4e3c18, 0xbc04bc5c, 0x3c67bbdb,
    0x3c673bdb, 0xbc043c5c, 0xbc4ebc18, 0x3c2cbc3e, 0x3c803a49, 0xbb163c7d, 0xbc78bb79, 0x3bacbc71, 0x3c71bbac, 0x3b793c78,
    0xbc7d3b16, 0xba49bc80, 0x3c3ebc2c, 0x3c183c4e, 0xbc5c3c04, 0xbbdbbc67, 0x3f803f80, 0x3f7d3f7f, 0x3f783f7b, 0x3f713f75,
    0x3f673f6d, 0x3f5c3f62, 0x3f4e3f55, 0x3f3e3f46, 0x3f2c3f35, 0x3f183f22, 0x3f043f0e, 0x3edb3ef1, 0x3eac3ec4, 0x3e793e95,
    0x3e163e48, 0x3d493dc9, 0xbd490000, 0xbe16bdc9, 0xbe79be48, 0xbeacbe95, 0xbedbbec4, 0xbf04bef1, 0xbf18bf0e, 0xbf2cbf22,
    0xbf3ebf35, 0xbf4ebf46, 0xbf5cbf55, 0xbf67bf62, 0xbf71bf6d, 0xbf78bf75, 0xbf7dbf7b, 0xbf80bf7f, 0x3edb3ec4, 0x3f043ef1,
    0x3f183f0e, 0x3f2c3f22, 0x3d490000, 0x3e163dc9, 0x3e793e48, 0x3eac3e95, 0x3f713f6d, 0x3f783f75, 0x3f7d3f7b, 0x3f803f7f,
    0x3f3e3f35, 0x3f4e3f46, 0x3f5c3f55, 0x3f673f62, 0x3f673f6d, 0x3f5c3f62, 0x3f4e3f55, 0x3f3e3f46, 0x3f803f80, 0x3f7d3f7f,
    0x3f783f7b, 0x3f713f75, 0x3eac3ec4, 0x3e793e95, 0x3e163e48, 0x3d493dc9, 0x3f2c3f35, 0x3f183f22, 0x3f043f0e, 0x3edb3ef1,
    0xbf4ebf35, 0xbf71bf62, 0xbf80bf7b, 0xbf78bf7f, 0xbf5cbf6d, 0xbf2cbf46, 0xbedbbf0e, 0xbe16be95, 0x3f7d3f80, 0x3f673f75,
    0x3f3e3f55, 0x3f043f22, 0x3e793ec4, 0xbd493dc9, 0xbeacbe48, 0xbf18bef1, 0x3f183f35, 0x3eac3ef1, 0x3d493e48, 0xbe79bdc9,
    0xbf04bec4, 0xbf3ebf22, 0xbf67bf55, 0xbf7dbf75, 0x3e160000, 0x3edb3e95, 0x3f2c3f0e, 0x3f5c3f46, 0x3f783f6d, 0x3f803f7f,
    0x3f713f7b, 0x3f4e3f62, 0xbf04bec4, 0xbf3ebf22, 0xbf67bf55, 0xbf7dbf75, 0x3f183f35, 0x3eac3ef1, 0x3d493e48, 0xbe79bdc9,
    0x3f783f6d, 0x3f803f7f, 0x3f713f7b, 0x3f4e3f62, 0x3e160000, 0x3edb3e95, 0x3f2c3f0e, 0x3f5c3f46, 0x3f5c3f6d, 0x3f2c3f46,
    0x3edb3f0e, 0x3e163e95, 0x3f4e3f35, 0x3f713f62, 0x3f803f7b, 0x3f783f7f, 0xbe79bec4, 0x3d49bdc9, 0x3eac3e48, 0x3f183ef1,
    0xbf7dbf80, 0xbf67bf75, 0xbf3ebf55, 0xbf04bf22, 0xbe790000, 0xbf2cbef1, 0xbf71bf55, 0xbf7dbf7f, 0xbf4ebf6d, 0xbedbbf22,
    0x3d49be48, 0x3f043e95, 0x3f5c3f35, 0x3f803f75, 0x3f673f7b, 0x3f183f46, 0x3e163ec4, 0xbeacbdc9, 0xbf3ebf0e, 0xbf78bf62,
    0x3f783f80, 0x3f3e3f62, 0x3eac3f0e, 0xbe163dc9, 0xbf18bec4, 0xbf67bf46, 0xbf80bf7b, 0xbf5cbf75, 0xbf04bf35, 0xbd49be95,
    0x3edb3e48, 0x3f4e3f22, 0x3f7d3f6d, 0x3f713f7f, 0x3f2c3f55, 0x3e793ef1, 0xbf18bec4, 0xbf67bf46, 0xbf80bf7b, 0xbf5cbf75,
    0x3f783f80, 0x3f3e3f62, 0x3eac3f0e, 0xbe163dc9, 0x3f7d3f6d, 0x3f713f7f, 0x3f2c3f55, 0x3e793ef1, 0xbf04bf35, 0xbd49be95,
    0x3edb3e48, 0x3f4e3f22, 0x3f4e3f6d, 0x3edb3f22, 0xbd493e48, 0xbf04be95, 0x3e790000, 0x3f2c3ef1, 0x3f713f55, 0x3f7d3f7f,
    0xbe16bec4, 0x3eac3dc9, 0x3f3e3f0e, 0x3f783f62, 0xbf5cbf35, 0xbf80bf75, 0xbf67bf7b, 0xbf18bf46, 0xbedbbf35, 0x3e79bdc9,
    0x3f4e3f0e, 0x3f803f75, 0x3f3e3f6d, 0x3e163ef1, 0xbf04be48, 0xbf71bf46, 0x3eac0000, 0x3f5c3f22, 0x3f7d3f7b, 0x3f2c3f62,
    0x3d493ec4, 0xbf18be95, 0xbf78bf55, 0xbf67bf7f, 0x3f673f35, 0x3f783f7f, 0x3f183f55, 0xbd493e95, 0xbf2cbec4, 0xbf7dbf62,
    0xbf5cbf7b, 0xbeacbf22, 0x3f713f80, 0x3f043f46, 0xbe163e48, 0xbf3ebef1, 0xbf80bf6d, 0xbf4ebf75, 0xbe79bf0e, 0x3edb3dc9,
    0x3f2c3ec4, 0x3f7d3f62, 0x3f5c3f7b, 0x3eac3f22, 0xbf67bf35, 0xbf78bf7f, 0xbf18bf55, 0x3d49be95, 0x3f803f6d, 0x3f4e3f75,
    0x3e793f0e, 0xbedbbdc9, 0xbf71bf80, 0xbf04bf46, 0x3e16be48, 0x3f3e3ef1, 0x3f3e3f6d, 0x3e163ef1, 0xbf04be48, 0xbf71bf46,
    0xbedbbf35, 0x3e79bdc9, 0x3f4e3f0e, 0x3f803f75, 0x3d493ec4, 0xbf18be95, 0xbf78bf55, 0xbf67bf7f, 0x3eac0000, 0x3f5c3f22,
    0x3f7d3f7b, 0x3f2c3f62, 0x3f673f80, 0x3e793f22, 0xbf18be48, 0xbf80bf62, 0xbf2cbf6d, 0x3e16be95, 0x3f5c3f0e, 0x3f713f7f,
    0x3eac3f35, 0xbf04bdc9, 0xbf7dbf55, 0xbf3ebf75, 0x3d49bec4, 0x3f4e3ef1, 0x3f783f7b, 0x3edb3f46, 0xbedb0000, 0xbf78bf46,
    0xbf4ebf7b, 0xbd49bef1, 0x3f3e3ec4, 0x3f7d3f75, 0x3f043f55, 0xbeac3dc9, 0xbf71bf35, 0xbf5cbf7f, 0xbe16bf0e, 0x3f2c3e95,
    0x3f803f6d, 0x3f183f62, 0xbe793e48, 0xbf67bf22, 0xbf3ebec4, 0xbf7dbf75, 0xbf04bf55, 0x3eacbdc9, 0x3edb0000, 0x3f783f46,
    0x3f4e3f7b, 0x3d493ef1, 0xbf80bf6d, 0xbf18bf62, 0x3e79be48, 0x3f673f22, 0x3f713f35, 0x3f5c3f7f, 0x3e163f0e, 0xbf2cbe95,
    0xbf2cbf6d, 0x3e16be95, 0x3f5c3f0e, 0x3f713f7f, 0x3f673f80, 0x3e793f22, 0xbf18be48, 0xbf80bf62, 0x3d49bec4, 0x3f4e3ef1,
    0x3f783f7b, 0x3edb3f46, 0x3eac3f35, 0xbf04bdc9, 0xbf7dbf55, 0xbf3ebf75, 0xbf78bf35, 0xbf2cbf75, 0x3eacbe48, 0x3f7d3f46,
    0x3f183f6d, 0xbedb3dc9, 0xbf80bf55, 0xbf04bf62, 0x3f5c3f80, 0xbd493ef1, 0xbf67bf0e, 0xbf4ebf7f, 0x3e16bec4, 0x3f713f22,
    0x3f3e3f7b, 0xbe793e95, 0x3e793f35, 0xbf3ebe95, 0xbf71bf7b, 0xbe16bf22, 0x3f4e3ec4, 0x3f673f7f, 0x3d493f0e, 0xbf5cbef1,
    0x3f040000, 0x3f803f62, 0x3edb3f55, 0xbf18bdc9, 0xbf7dbf6d, 0xbeacbf46, 0x3f2c3e48, 0x3f783f75, 0x3f4e3ec4, 0x3f673f7f,
    0x3d493f0e, 0xbf5cbef1, 0x3e793f35, 0xbf3ebe95, 0xbf71bf7b, 0xbe16bf22, 0xbf7dbf6d, 0xbeacbf46, 0x3f2c3e48, 0x3f783f75,
    0x3f040000, 0x3f803f62, 0x3edb3f55, 0xbf18bdc9, 0xbf18bf6d, 0x3edbbdc9, 0x3f803f55, 0x3f043f62, 0x3f783f35, 0x3f2c3f75,
    0xbeac3e48, 0xbf7dbf46, 0xbe163ec4, 0xbf71bf22, 0xbf3ebf7b, 0x3e79be95, 0xbf5cbf80, 0x3d49bef1, 0x3f673f0e, 0x3f4e3f7f,
    0xbf180000, 0xbf71bf75, 0x3d49bf0e, 0x3f783f22, 0x3f043f6d, 0xbf2cbdc9, 0xbf67bf7b, 0x3e16bef1, 0x3f7d3f35, 0x3edb3f62,
    0xbf3ebe48, 0xbf5cbf7f, 0x3e79bec4, 0x3f803f46, 0x3eac3f55, 0xbf4ebe95, 0x3f4e3f80, 0xbeac3e95, 0xbf80bf55, 0xbe79bf46,
    0x3f5c3ec4, 0x3f3e3f7f, 0xbedb3e48, 0xbf7dbf62, 0xbe16bf35, 0x3f673ef1, 0x3f2c3f7b, 0xbf043dc9, 0xbf78bf6d, 0xbd49bf22,
    0x3f713f0e, 0x3f183f75, 0x3f5c3ec4, 0x3f3e3f7f, 0xbedb3e48, 0xbf7dbf62, 0x3f4e3f80, 0xbeac3e95, 0xbf80bf55, 0xbe79bf46,
    0xbf78bf6d, 0xbd49bf22, 0x3f713f0e, 0x3f183f75, 0xbe16bf35, 0x3f673ef1, 0x3f2c3f7b, 0xbf043dc9, 0xbf04bf6d, 0x3f2c3dc9,
    0x3f673f7b, 0xbe163ef1, 0x3f180000, 0x3f713f75, 0xbd493f0e, 0xbf78bf22, 0xbe793ec4, 0xbf80bf46, 0xbeacbf55, 0x3f4e3e95,
    0xbf7dbf35, 0xbedbbf62, 0x3f3e3e48, 0x3f5c3f7f, 0xbd49bf35, 0x3f7d3f22, 0x3e793f55, 0xbf71bef1, 0xbedbbf6d, 0x3f5c3e95,
    0x3f183f7b, 0xbf3ebdc9, 0x3f2c0000, 0x3f4e3f7f, 0xbf043e48, 0xbf67bf75, 0x3eacbec4, 0x3f783f62, 0xbe163f0e, 0xbf80bf46,
    0x3f803f35, 0x3e163f46, 0xbf78bf0e, 0xbeacbf62, 0x3f673ec4, 0x3f043f75, 0xbf4ebe48, 0xbf2cbf7f, 0x3f3e3f80, 0xbf183dc9,
    0xbf5cbf7b, 0x3edbbe95, 0x3f713f6d, 0xbe793ef1, 0xbf7dbf55, 0x3d49bf22, 0xbf67bec4, 0xbf04bf75, 0x3f4e3e48, 0x3f2c3f7f,
    0xbf80bf35, 0xbe16bf46, 0x3f783f0e, 0x3eac3f62, 0xbf71bf6d, 0x3e79bef1, 0x3f7d3f55, 0xbd493f22, 0xbf3ebf80, 0x3f18bdc9,
    0x3f5c3f7b, 0xbedb3e95, 0xbedbbf6d, 0x3f5c3e95, 0x3f183f7b, 0xbf3ebdc9, 0xbd49bf35, 0x3f7d3f22, 0x3e793f55, 0xbf71bef1,
    0x3eacbec4, 0x3f783f62, 0xbe163f0e, 0xbf80bf46, 0x3f2c0000, 0x3f4e3f7f, 0xbf043e48, 0xbf67bf75, 0x3f2c3f80, 0xbf4ebdc9,
    0xbf04bf7b, 0x3f673e95, 0x3eac3f6d, 0xbf78bef1, 0xbe16bf55, 0x3f803f22, 0xbd493f35, 0xbf7dbf46, 0x3e79bf0e, 0x3f713f62,
    0xbedb3ec4, 0xbf5cbf75, 0x3f18be48, 0x3f3e3f7f, 0xbf3e0000, 0xbf18bf7f, 0x3f5c3e48, 0x3edb3f75, 0xbf71bec4, 0xbe79bf62,
    0x3f7d3f0e, 0x3d493f46, 0xbf80bf35, 0x3e16bf22, 0x3f783f55, 0xbeac3ef1, 0xbf67bf6d, 0x3f04be95, 0x3f4e3f7b, 0xbf2c3dc9,
    0x3f713ec4, 0x3e793f62, 0xbf7dbf0e, 0xbd49bf46, 0x3f3e0000, 0x3f183f7f, 0xbf5cbe48, 0xbedbbf75, 0x3f673f6d, 0xbf043e95,
    0xbf4ebf7b, 0x3f2cbdc9, 0x3f803f35, 0xbe163f22, 0xbf78bf55, 0x3eacbef1, 0x3eac3f6d, 0xbf78bef1, 0xbe16bf55, 0x3f803f22,
    0x3f2c3f80, 0xbf4ebdc9, 0xbf04bf7b, 0x3f673e95, 0xbedb3ec4, 0xbf5cbf75, 0x3f18be48, 0x3f3e3f7f, 0xbd493f35, 0xbf7dbf46,
    0x3e79bf0e, 0x3f713f62, 0xbf7dbf35, 0x3edbbef1, 0x3f3e3f7b, 0xbf5cbdc9, 0xbe79bf6d, 0x3f803f22, 0xbeac3f0e, 0xbf4ebf75,
    0x3f183f80, 0xbf71be95, 0xbd49bf55, 0x3f783f46, 0xbf043ec4, 0xbf2cbf7f, 0x3f673e48, 0x3e163f62, 0xbe163f35, 0xbf67bf62,
    0x3f2cbe48, 0x3f043f7f, 0xbf78bec4, 0x3d49bf46, 0x3f713f55, 0xbf183e95, 0x3f4e0000, 0x3eac3f75, 0xbf80bf0e, 0x3e79bf22,
    0x3f5c3f6d, 0xbf3e3dc9, 0xbedbbf7b, 0x3f7d3ef1, 0xbf78bec4, 0x3d49bf46, 0x3f713f55, 0xbf183e95, 0xbe163f35, 0xbf67bf62,
    0x3f2cbe48, 0x3f043f7f, 0x3f5c3f6d, 0xbf3e3dc9, 0xbedbbf7b, 0x3f7d3ef1, 0x3f4e0000, 0x3eac3f75, 0xbf80bf0e, 0x3e79bf22,
    0x3e793f6d, 0xbf80bf22, 0x3eacbf0e, 0x3f4e3f75, 0x3f7d3f35, 0xbedb3ef1, 0xbf3ebf7b, 0x3f5c3dc9, 0x3f04bec4, 0x3f2c3f7f,
    0xbf67be48, 0xbe16bf62, 0xbf18bf80, 0x3f713e95, 0x3d493f55, 0xbf78bf46, 0xbf5c0000, 0xbd49bf62, 0x3f673f55, 0xbf4e3dc9,
    0xbe16bf6d, 0x3f713f46, 0xbf3e3e48, 0xbe79bf75, 0x3f783f35, 0xbf2c3e95, 0xbeacbf7b, 0x3f7d3f22, 0xbf183ec4, 0xbedbbf7f,
    0x3f803f0e, 0xbf043ef1, 0x3f043f80, 0xbf80bef1, 0x3edbbf0e, 0x3f183f7f, 0xbf7dbec4, 0x3eacbf22, 0x3f2c3f7b, 0xbf78be95,
    0x3e79bf35, 0x3f3e3f75, 0xbf71be48, 0x3e16bf46, 0x3f4e3f6d, 0xbf67bdc9, 0x3d49bf55, 0x3f5c3f62, 0xbf7dbec4, 0x3eacbf22,
    0x3f2c3f7b, 0xbf78be95, 0x3f043f80, 0xbf80bef1, 0x3edbbf0e, 0x3f183f7f, 0x3f4e3f6d, 0xbf67bdc9, 0x3d49bf55, 0x3f5c3f62,
    0x3e79bf35, 0x3f3e3f75, 0xbf71be48, 0x3e16bf46, 0x3e163f6d, 0xbf71bf46, 0x3f3ebe48, 0x3e793f75, 0x3f5c0000, 0x3d493f62,
    0xbf67bf55, 0x3f4ebdc9, 0x3f18bec4, 0x3edb3f7f, 0xbf80bf0e, 0x3f04bef1, 0xbf78bf35, 0x3f2cbe95, 0x3eac3f7b, 0xbf7dbf22,
    0x3eacbf35, 0x3f043f7f, 0xbf7dbf0e, 0x3f3ebe95, 0x3d493f6d, 0xbf4ebf62, 0x3f783e48, 0xbedb3f22, 0x3f670000, 0xbe793f46,
    0xbf18bf7b, 0x3f803ef1, 0xbf2c3ec4, 0xbe16bf75, 0x3f5c3f55, 0xbf71bdc9, 0x3f713f35, 0xbf5c3dc9, 0x3e16bf55, 0x3f2c3f75,
    0xbf80bec4, 0x3f18bef1, 0x3e793f7b, 0xbf67bf46, 0x3edb3f80, 0xbf78bf22, 0x3f4ebe48, 0xbd493f62, 0xbf3ebf6d, 0x3f7d3e95,
    0xbf043f0e, 0xbeacbf7f, 0x3f803ec4, 0xbf183ef1, 0xbe79bf7b, 0x3f673f46, 0xbf71bf35, 0x3f5cbdc9, 0xbe163f55, 0xbf2cbf75,
    0x3f3e3f6d, 0xbf7dbe95, 0x3f04bf0e, 0x3eac3f7f, 0xbedbbf80, 0x3f783f22, 0xbf4e3e48, 0x3d49bf62, 0x3d493f6d, 0xbf4ebf62,
    0x3f783e48, 0xbedb3f22, 0x3eacbf35, 0x3f043f7f, 0xbf7dbf0e, 0x3f3ebe95, 0xbf2c3ec4, 0xbe16bf75, 0x3f5c3f55, 0xbf71bdc9,
    0x3f670000, 0xbe793f46, 0xbf18bf7b, 0x3f803ef1, 0x3eac3f80, 0xbf5cbf46, 0x3f7d3e48, 0xbf2c3ef1, 0x3d49bf6d, 0x3f183f75,
    0xbf78bf0e, 0x3f67bdc9, 0xbedb3f35, 0xbe79bf7f, 0x3f4e3f55, 0xbf80be95, 0x3f3ebec4, 0xbe163f62, 0xbf04bf7b, 0x3f713f22,
    0xbf710000, 0x3f04bf22, 0x3e163f7b, 0xbf3ebf62, 0x3f803ec4, 0xbf4e3e95, 0x3e79bf55, 0x3edb3f7f, 0xbf67bf35, 0x3f783dc9,
    0xbf183f0e, 0xbd49bf75, 0x3f2c3f6d, 0xbf7dbef1, 0x3f5cbe48, 0xbeac3f46, 0xbf80bec4, 0x3f4ebe95, 0xbe793f55, 0xbedbbf7f,
    0x3f710000, 0xbf043f22, 0xbe16bf7b, 0x3f3e3f62, 0xbf2cbf6d, 0x3f7d3ef1, 0xbf5c3e48, 0x3eacbf46, 0x3f673f35, 0xbf78bdc9,
    0x3f18bf0e, 0x3d493f75, 0x3d49bf6d, 0x3f183f75, 0xbf78bf0e, 0x3f67bdc9, 0x3eac3f80, 0xbf5cbf46, 0x3f7d3e48, 0xbf2c3ef1,
    0x3f3ebec4, 0xbe163f62, 0xbf04bf7b, 0x3f713f22, 0xbedb3f35, 0xbe79bf7f, 0x3f4e3f55, 0xbf80be95, 0xbf5cbf35, 0x3f803e95,
    0xbf673e48, 0x3f18bf22, 0xbe163f6d, 0xbeacbf7f, 0x3f3e3f55, 0xbf78bef1, 0x3e793f80, 0xbf2cbf62, 0x3f713f0e, 0xbf7dbdc9,
    0x3f4ebec4, 0xbedb3f46, 0xbd49bf7b, 0x3f043f75, 0xbf043f35, 0x3d49bf75, 0x3edb3f7b, 0xbf4ebf46, 0x3f7d3ec4, 0xbf713dc9,
    0x3f2cbf0e, 0xbe793f62, 0x3f780000, 0xbf3e3ef1, 0x3eacbf55, 0x3e163f7f, 0xbf18bf6d, 0x3f673f22, 0xbf80be48, 0x3f5cbe95,
    0x3f7d3ec4, 0xbf713dc9, 0x3f2cbf0e, 0xbe793f62, 0xbf043f35, 0x3d49bf75, 0x3edb3f7b, 0xbf4ebf46, 0xbf18bf6d, 0x3f673f22,
    0xbf80be48, 0x3f5cbe95, 0x3f780000, 0xbf3e3ef1, 0x3eacbf55, 0x3e163f7f, 0x3e16bf6d, 0x3eac3f7f, 0xbf3ebf55, 0x3f783ef1,
    0x3f5c3f35, 0xbf80be95, 0x3f67be48, 0xbf183f22, 0xbf4e3ec4, 0x3edbbf46, 0x3d493f7b, 0xbf04bf75, 0xbe79bf80, 0x3f2c3f62,
    0xbf71bf0e, 0x3f7d3dc9, 0xbf7d0000, 0x3f67be95, 0xbf3e3f0e, 0x3f04bf46, 0xbe793f6d, 0xbd49bf7f, 0x3eac3f7b, 0xbf18bf62,
    0x3f4e3f35, 0xbf71bef1, 0x3f803e48, 0xbf783dc9, 0x3f5cbec4, 0xbf2c3f22, 0x3edbbf55, 0xbe163f75, 0x3e163f80, 0xbedbbf75,
    0x3f2c3f55, 0xbf5cbf22, 0x3f783ec4, 0xbf80bdc9, 0x3f71be48, 0xbf4e3ef1, 0x3f18bf35, 0xbeac3f62, 0x3d49bf7b, 0x3e793f7f,
    0xbf04bf6d, 0x3f3e3f46, 0xbf67bf0e, 0x3f7d3e95, 0x3f783ec4, 0xbf80bdc9, 0x3f71be48, 0xbf4e3ef1, 0x3e163f80, 0xbedbbf75,
    0x3f2c3f55, 0xbf5cbf22, 0xbf04bf6d, 0x3f3e3f46, 0xbf67bf0e, 0x3f7d3e95, 0x3f18bf35, 0xbeac3f62, 0x3d49bf7b, 0x3e793f7f,
    0x3e79bf6d, 0x3d493f7f, 0xbeacbf7b, 0x3f183f62, 0x3f7d0000, 0xbf673e95, 0x3f3ebf0e, 0xbf043f46, 0xbf5c3ec4, 0x3f2cbf22,
    0xbedb3f55, 0x3e16bf75, 0xbf4ebf35, 0x3f713ef1, 0xbf80be48, 0x3f78bdc9, 0x3f2cbf35, 0xbf183f46, 0x3f04bf55, 0xbedb3f62,
    0x3eacbf6d, 0xbe793f75, 0x3e16bf7b, 0xbd493f7f, 0x3f800000, 0xbf7d3dc9, 0x3f78be48, 0xbf713e95, 0x3f67bec4, 0xbf5c3ef1,
    0x3f4ebf0e, 0xbf3e3f22, 0x3f3e3f35, 0xbf4ebf22, 0x3f5c3f0e, 0xbf67bef1, 0x3f713ec4, 0xbf78be95, 0x3f7d3e48, 0xbf80bdc9,
    0x3d493f80, 0xbe16bf7f, 0x3e793f7b, 0xbeacbf75, 0x3edb3f6d, 0xbf04bf62, 0x3f183f55, 0xbf2cbf46, 0xbf71bec4, 0x3f783e95,
    0xbf7dbe48, 0x3f803dc9, 0xbf3ebf35, 0x3f4e3f22, 0xbf5cbf0e, 0x3f673ef1, 0xbedbbf6d, 0x3f043f62, 0xbf18bf55, 0x3f2c3f46,
    0xbd49bf80, 0x3e163f7f, 0xbe79bf7b, 0x3eac3f75, 0x3eacbf6d, 0xbe793f75, 0x3e16bf7b, 0xbd493f7f, 0x3f2cbf35, 0xbf183f46,
    0x3f04bf55, 0xbedb3f62, 0x3f67bec4, 0xbf5c3ef1, 0x3f4ebf0e, 0xbf3e3f22, 0x3f800000, 0xbf7d3dc9, 0x3f78be48, 0xbf713e95,
    0xbd493f80, 0x3e16bf7f, 0xbe793f7b, 0x3eacbf75, 0xbedb3f6d, 0x3f04bf62, 0xbf183f55, 0x3f2cbf46, 0xbf3e3f35, 0x3f4ebf22,
    0xbf5c3f0e, 0x3f67bef1, 0xbf713ec4, 0x3f78be95, 0xbf7d3e48, 0x3f80bdc9, 0xbf800000, 0x3f7d3dc9, 0xbf78be48, 0x3f713e95,
    0xbf67bec4, 0x3f5c3ef1, 0xbf4ebf0e, 0x3f3e3f22, 0xbf2cbf35, 0x3f183f46, 0xbf04bf55, 0x3edb3f62, 0xbeacbf6d, 0x3e793f75,
    0xbe16bf7b, 0x3d493f7f, 0x3f673ec4, 0xbf5cbef1, 0x3f4e3f0e, 0xbf3ebf22, 0x3f800000, 0xbf7dbdc9, 0x3f783e48, 0xbf71be95,
    0x3eac3f6d, 0xbe79bf75, 0x3e163f7b, 0xbd49bf7f, 0x3f2c3f35, 0xbf18bf46, 0x3f043f55, 0xbedbbf62, 0xbedb3f6d, 0x3f04bf62,
    0xbf183f55, 0x3f2cbf46, 0xbd493f80, 0x3e16bf7f, 0xbe793f7b, 0x3eacbf75, 0xbf713ec4, 0x3f78be95, 0xbf7d3e48, 0x3f80bdc9,
    0xbf3e3f35, 0x3f4ebf22, 0xbf5c3f0e, 0x3f67bef1, 0xbf18bf35, 0x3eac3f62, 0xbd49bf7b, 0xbe793f7f, 0x3f04bf6d, 0xbf3e3f46,
    0x3f67bf0e, 0xbf7d3e95, 0xbe163f80, 0x3edbbf75, 0xbf2c3f55, 0x3f5cbf22, 0xbf783ec4, 0x3f80bdc9, 0xbf71be48, 0x3f4e3ef1,
    0xbf4e3f35, 0x3f71bef1, 0xbf803e48, 0x3f783dc9, 0xbf5cbec4, 0x3f2c3f22, 0xbedbbf55, 0x3e163f75, 0x3f7d0000, 0xbf67be95,
    0x3f3e3f0e, 0xbf04bf46, 0x3e793f6d, 0x3d49bf7f, 0xbeac3f7b, 0x3f18bf62, 0xbf5cbec4, 0x3f2c3f22, 0xbedbbf55, 0x3e163f75,
    0xbf4e3f35, 0x3f71bef1, 0xbf803e48, 0x3f783dc9, 0x3e793f6d, 0x3d49bf7f, 0xbeac3f7b, 0x3f18bf62, 0x3f7d0000, 0xbf67be95,
    0x3f3e3f0e, 0xbf04bf46, 0xbf043f6d, 0x3f3ebf46, 0xbf673f0e, 0x3f7dbe95, 0x3f183f35, 0xbeacbf62, 0x3d493f7b, 0x3e79bf7f,
    0x3f78bec4, 0xbf803dc9, 0x3f713e48, 0xbf4ebef1, 0x3e16bf80, 0xbedb3f75, 0x3f2cbf55, 0xbf5c3f22, 0xbf780000, 0x3f3e3ef1,
    0xbeacbf55, 0xbe163f7f, 0x3f18bf6d, 0xbf673f22, 0x3f80be48, 0xbf5cbe95, 0x3f043f35, 0xbd49bf75, 0xbedb3f7b, 0x3f4ebf46,
    0xbf7d3ec4, 0x3f713dc9, 0xbf2cbf0e, 0x3e793f62, 0xbe793f80, 0x3f2cbf62, 0xbf713f0e, 0x3f7dbdc9, 0xbf4ebec4, 0x3edb3f46,
    0x3d49bf7b, 0xbf043f75, 0x3f5cbf35, 0xbf803e95, 0x3f673e48, 0xbf18bf22, 0x3e163f6d, 0x3eacbf7f, 0xbf3e3f55, 0x3f78bef1,
    0xbf4ebec4, 0x3edb3f46, 0x3d49bf7b, 0xbf043f75, 0xbe793f80, 0x3f2cbf62, 0xbf713f0e, 0x3f7dbdc9, 0x3e163f6d, 0x3eacbf7f,
    0xbf3e3f55, 0x3f78bef1, 0x3f5cbf35, 0xbf803e95, 0x3f673e48, 0xbf18bf22, 0xbf183f6d, 0x3f67bf22, 0xbf803e48, 0x3f5c3e95,
    0x3f780000, 0xbf3ebef1, 0x3eac3f55, 0x3e16bf7f, 0x3f7dbec4, 0xbf71bdc9, 0x3f2c3f0e, 0xbe79bf62, 0xbf04bf35, 0x3d493f75,
    0x3edbbf7b, 0xbf4e3f46, 0x3f67bf35, 0xbf783dc9, 0x3f183f0e, 0x3d49bf75, 0xbf2c3f6d, 0x3f7dbef1, 0xbf5cbe48, 0x3eac3f46,
    0x3f710000, 0xbf04bf22, 0xbe163f7b, 0x3f3ebf62, 0xbf803ec4, 0x3f4e3e95, 0xbe79bf55, 0xbedb3f7f, 0x3edb3f35, 0x3e79bf7f,
    0xbf4e3f55, 0x3f80be95, 0xbf3ebec4, 0x3e163f62, 0x3f04bf7b, 0xbf713f22, 0xbeac3f80, 0x3f5cbf46, 0xbf7d3e48, 0x3f2c3ef1,
    0xbd49bf6d, 0xbf183f75, 0x3f78bf0e, 0xbf67bdc9, 0x3f3e3ec4, 0xbe16bf62, 0xbf043f7b, 0x3f71bf22, 0xbedbbf35, 0xbe793f7f,
    0x3f4ebf55, 0xbf803e95, 0x3d493f6d, 0x3f18bf75, 0xbf783f0e, 0x3f673dc9, 0x3eacbf80, 0xbf5c3f46, 0x3f7dbe48, 0xbf2cbef1,
    0xbf2c3f6d, 0x3f7dbef1, 0xbf5cbe48, 0x3eac3f46, 0x3f67bf35, 0xbf783dc9, 0x3f183f0e, 0x3d49bf75, 0xbf803ec4, 0x3f4e3e95,
    0xbe79bf55, 0xbedb3f7f, 0x3f710000, 0xbf04bf22, 0xbe163f7b, 0x3f3ebf62, 0xbedb3f80, 0x3f78bf22, 0xbf4ebe48, 0x3d493f62,
    0x3f3ebf6d, 0xbf7d3e95, 0x3f043f0e, 0x3eacbf7f, 0xbf713f35, 0x3f5c3dc9, 0xbe16bf55, 0xbf2c3f75, 0x3f80bec4, 0xbf18bef1,
    0xbe793f7b, 0x3f67bf46, 0xbf670000, 0x3e793f46, 0x3f18bf7b, 0xbf803ef1, 0x3f2c3ec4, 0x3e16bf75, 0xbf5c3f55, 0x3f71bdc9,
    0xbeacbf35, 0xbf043f7f, 0x3f7dbf0e, 0xbf3ebe95, 0xbd493f6d, 0x3f4ebf62, 0xbf783e48, 0x3edb3f22, 0xbf2cbec4, 0xbe163f75,
    0x3f5cbf55, 0xbf713dc9, 0x3f670000, 0xbe79bf46, 0xbf183f7b, 0x3f80bef1, 0x3d49bf6d, 0xbf4e3f62, 0x3f78be48, 0xbedbbf22,
    0x3eac3f35, 0x3f04bf7f, 0xbf7d3f0e, 0x3f3e3e95, 0x3f3ebf6d, 0xbf7d3e95, 0x3f043f0e, 0x3eacbf7f, 0xbedb3f80, 0x3f78bf22,
    0xbf4ebe48, 0x3d493f62, 0x3f80bec4, 0xbf18bef1, 0xbe793f7b, 0x3f67bf46, 0xbf713f35, 0x3f5c3dc9, 0xbe16bf55, 0xbf2c3f75,
    0xbe79bf35, 0xbf3e3f75, 0x3f71be48, 0xbe16bf46, 0xbf4e3f6d, 0x3f67bdc9, 0xbd49bf55, 0xbf5c3f62, 0xbf043f80, 0x3f80bef1,
    0xbedbbf0e, 0xbf183f7f, 0x3f7dbec4, 0xbeacbf22, 0xbf2c3f7b, 0x3f78be95, 0xbf783f35, 0x3f2c3e95, 0x3eacbf7b, 0xbf7d3f22,
    0x3f183ec4, 0x3edbbf7f, 0xbf803f0e, 0x3f043ef1, 0x3f5c0000, 0x3d49bf62, 0xbf673f55, 0x3f4e3dc9, 0x3e16bf6d, 0xbf713f46,
    0x3f3e3e48, 0x3e79bf75, 0x3f183ec4, 0x3edbbf7f, 0xbf803f0e, 0x3f043ef1, 0xbf783f35, 0x3f2c3e95, 0x3eacbf7b, 0xbf7d3f22,
    0x3e16bf6d, 0xbf713f46, 0x3f3e3e48, 0x3e79bf75, 0x3f5c0000, 0x3d49bf62, 0xbf673f55, 0x3f4e3dc9, 0x3f4ebf6d, 0xbf673dc9,
    0x3d493f55, 0x3f5cbf62, 0x3e793f35, 0x3f3ebf75, 0xbf713e48, 0x3e163f46, 0xbf7d3ec4, 0x3eac3f22, 0x3f2cbf7b, 0xbf783e95,
    0x3f04bf80, 0xbf803ef1, 0x3edb3f0e, 0x3f18bf7f, 0xbf4e0000, 0xbeac3f75, 0x3f80bf0e, 0xbe79bf22, 0xbf5c3f6d, 0x3f3e3dc9,
    0x3edbbf7b, 0xbf7d3ef1, 0x3e163f35, 0x3f67bf62, 0xbf2cbe48, 0xbf043f7f, 0x3f78bec4, 0xbd49bf46, 0xbf713f55, 0x3f183e95,
    0xbf183f80, 0x3f71be95, 0x3d49bf55, 0xbf783f46, 0x3f043ec4, 0x3f2cbf7f, 0xbf673e48, 0xbe163f62, 0x3f7dbf35, 0xbedbbef1,
    0xbf3e3f7b, 0x3f5cbdc9, 0x3e79bf6d, 0xbf803f22, 0x3eac3f0e, 0x3f4ebf75, 0x3f043ec4, 0x3f2cbf7f, 0xbf673e48, 0xbe163f62,
    0xbf183f80, 0x3f71be95, 0x3d49bf55, 0xbf783f46, 0x3e79bf6d, 0xbf803f22, 0x3eac3f0e, 0x3f4ebf75, 0x3f7dbf35, 0xbedbbef1,
    0xbf3e3f7b, 0x3f5cbdc9, 0x3f5cbf6d, 0xbf3ebdc9, 0xbedb3f7b, 0x3f7dbef1, 0x3f4e0000, 0x3eacbf75, 0xbf803f0e, 0x3e793f22,
    0xbf783ec4, 0x3d493f46, 0x3f71bf55, 0xbf18be95, 0xbe16bf35, 0xbf673f62, 0x3f2c3e48, 0x3f04bf7f, 0x3f80bf35, 0xbe16bf22,
    0xbf783f55, 0x3eac3ef1, 0x3f67bf6d, 0xbf04be95, 0xbf4e3f7b, 0x3f2c3dc9, 0x3f3e0000, 0x3f18bf7f, 0xbf5c3e48, 0xbedb3f75,
    0x3f71bec4, 0x3e79bf62, 0xbf7d3f0e, 0xbd493f46, 0x3d493f35, 0x3f7dbf46, 0xbe79bf0e, 0xbf713f62, 0x3edb3ec4, 0x3f5cbf75,
    0xbf18be48, 0xbf3e3f7f, 0xbf2c3f80, 0x3f4ebdc9, 0x3f04bf7b, 0xbf673e95, 0xbeac3f6d, 0x3f78bef1, 0x3e16bf55, 0xbf803f22,
    0xbedbbec4, 0xbf5c3f75, 0x3f183e48, 0x3f3ebf7f, 0xbd49bf35, 0xbf7d3f46, 0x3e793f0e, 0x3f71bf62, 0x3eacbf6d, 0xbf783ef1,
    0xbe163f55, 0x3f80bf22, 0x3f2cbf80, 0xbf4e3dc9, 0xbf043f7b, 0x3f67be95, 0x3f67bf6d, 0xbf04be95, 0xbf4e3f7b, 0x3f2c3dc9,
    0x3f80bf35, 0xbe16bf22, 0xbf783f55, 0x3eac3ef1, 0x3f71bec4, 0x3e79bf62, 0xbf7d3f0e, 0xbd493f46, 0x3f3e0000, 0x3f18bf7f,
    0xbf5c3e48, 0xbedb3f75, 0xbf3e3f80, 0x3f183dc9, 0x3f5cbf7b, 0xbedbbe95, 0xbf713f6d, 0x3e793ef1, 0x3f7dbf55, 0xbd49bf22,
    0xbf803f35, 0xbe163f46, 0x3f78bf0e, 0x3eacbf62, 0xbf673ec4, 0xbf043f75, 0x3f4ebe48, 0x3f2cbf7f, 0xbf2c0000, 0xbf4e3f7f,
    0x3f043e48, 0x3f67bf75, 0xbeacbec4, 0xbf783f62, 0x3e163f0e, 0x3f80bf46, 0x3d49bf35, 0xbf7d3f22, 0xbe793f55, 0x3f71bef1,
    0x3edbbf6d, 0xbf5c3e95, 0xbf183f7b, 0x3f3ebdc9, 0x3eac3ec4, 0x3f78bf62, 0xbe16bf0e, 0xbf803f46, 0x3f2c0000, 0x3f4ebf7f,
    0xbf04be48, 0xbf673f75, 0xbedb3f6d, 0x3f5cbe95, 0x3f18bf7b, 0xbf3e3dc9, 0xbd493f35, 0x3f7dbf22, 0x3e79bf55, 0xbf713ef1,
    0xbf713f6d, 0x3e793ef1, 0x3f7dbf55, 0xbd49bf22, 0xbf3e3f80, 0x3f183dc9, 0x3f5cbf7b, 0xbedbbe95, 0xbf673ec4, 0xbf043f75,
    0x3f4ebe48, 0x3f2cbf7f, 0xbf803f35, 0xbe163f46, 0x3f78bf0e, 0x3eacbf62, 0x3e16bf35, 0xbf673ef1, 0xbf2c3f7b, 0x3f043dc9,
    0x3f78bf6d, 0x3d49bf22, 0xbf713f0e, 0xbf183f75, 0xbf4e3f80, 0x3eac3e95, 0x3f80bf55, 0x3e79bf46, 0xbf5c3ec4, 0xbf3e3f7f,
    0x3edb3e48, 0x3f7dbf62, 0xbf7d3f35, 0xbedb3f62, 0x3f3ebe48, 0x3f5cbf7f, 0xbe79bec4, 0xbf803f46, 0xbeac3f55, 0x3f4ebe95,
    0x3f180000, 0x3f71bf75, 0xbd49bf0e, 0xbf783f22, 0xbf043f6d, 0x3f2cbdc9, 0x3f67bf7b, 0xbe16bef1, 0xbe79bec4, 0xbf803f46,
    0xbeac3f55, 0x3f4ebe95, 0xbf7d3f35, 0xbedb3f62, 0x3f3ebe48, 0x3f5cbf7f, 0xbf043f6d, 0x3f2cbdc9, 0x3f67bf7b, 0xbe16bef1,
    0x3f180000, 0x3f71bf75, 0xbd49bf0e, 0xbf783f22, 0xbf783f6d, 0xbd493f22, 0x3f71bf0e, 0x3f18bf75, 0xbe163f35, 0x3f67bef1,
    0x3f2cbf7b, 0xbf04bdc9, 0x3f5cbec4, 0x3f3ebf7f, 0xbedbbe48, 0xbf7d3f62, 0x3f4ebf80, 0xbeacbe95, 0xbf803f55, 0xbe793f46,
    0xbf040000, 0xbf803f62, 0xbedb3f55, 0x3f18bdc9, 0x3f7dbf6d, 0x3eacbf46, 0xbf2c3e48, 0xbf783f75, 0xbe793f35, 0x3f3ebe95,
    0x3f71bf7b, 0x3e16bf22, 0xbf4e3ec4, 0xbf673f7f, 0xbd493f0e, 0x3f5cbef1, 0xbf5c3f80, 0x3d493ef1, 0x3f67bf0e, 0x3f4ebf7f,
    0xbe16bec4, 0xbf713f22, 0xbf3e3f7b, 0x3e793e95, 0x3f78bf35, 0x3f2cbf75, 0xbeacbe48, 0xbf7d3f46, 0xbf183f6d, 0x3edb3dc9,
    0x3f80bf55, 0x3f04bf62, 0xbe16bec4, 0xbf713f22, 0xbf3e3f7b, 0x3e793e95, 0xbf5c3f80, 0x3d493ef1, 0x3f67bf0e, 0x3f4ebf7f,
    0xbf183f6d, 0x3edb3dc9, 0x3f80bf55, 0x3f04bf62, 0x3f78bf35, 0x3f2cbf75, 0xbeacbe48, 0xbf7d3f46, 0xbf7d3f6d, 0xbeac3f46,
    0x3f2cbe48, 0x3f78bf75, 0x3f040000, 0x3f80bf62, 0x3edbbf55, 0xbf183dc9, 0x3f4ebec4, 0x3f67bf7f, 0x3d49bf0e, 0xbf5c3ef1,
    0x3e79bf35, 0xbf3e3e95, 0xbf713f7b, 0xbe163f22, 0x3f71bf35, 0x3f5cbf7f, 0x3e16bf0e, 0xbf2c3e95, 0xbf803f6d, 0xbf183f62,
    0x3e793e48, 0x3f67bf22, 0x3edb0000, 0x3f78bf46, 0x3f4ebf7b, 0x3d49bef1, 0xbf3e3ec4, 0xbf7d3f75, 0xbf043f55, 0x3eac3dc9,
    0xbeac3f35, 0x3f04bdc9, 0x3f7dbf55, 0x3f3ebf75, 0xbd49bec4, 0xbf4e3ef1, 0xbf783f7b, 0xbedb3f46, 0xbf673f80, 0xbe793f22,
    0x3f18be48, 0x3f80bf62, 0x3f2cbf6d, 0xbe16be95, 0xbf5c3f0e, 0xbf713f7f, 0x3d493ec4, 0x3f4ebef1, 0x3f78bf7b, 0x3edbbf46,
    0x3eacbf35, 0xbf043dc9, 0xbf7d3f55, 0xbf3e3f75, 0xbf2c3f6d, 0x3e163e95, 0x3f5cbf0e, 0x3f71bf7f, 0x3f67bf80, 0x3e79bf22,
    0xbf183e48, 0xbf803f62, 0xbf803f6d, 0xbf183f62, 0x3e793e48, 0x3f67bf22, 0x3f71bf35, 0x3f5cbf7f, 0x3e16bf0e, 0xbf2c3e95,
    0xbf3e3ec4, 0xbf7d3f75, 0xbf043f55, 0x3eac3dc9, 0x3edb0000, 0x3f78bf46, 0x3f4ebf7b, 0x3d49bef1, 0xbf713f80, 0xbf043f46,
    0x3e163e48, 0x3f3ebef1, 0x3f80bf6d, 0x3f4ebf75, 0x3e79bf0e, 0xbedb3dc9, 0xbf673f35, 0xbf783f7f, 0xbf183f55, 0x3d493e95,
    0x3f2cbec4, 0x3f7dbf62, 0x3f5cbf7b, 0x3eacbf22, 0xbeac0000, 0xbf5c3f22, 0xbf7d3f7b, 0xbf2c3f62, 0xbd493ec4, 0x3f18be95,
    0x3f78bf55, 0x3f67bf7f, 0x3edbbf35, 0xbe79bdc9, 0xbf4e3f0e, 0xbf803f75, 0xbf3e3f6d, 0xbe163ef1, 0x3f04be48, 0x3f71bf46,
    0x3d49bec4, 0xbf183e95, 0xbf783f55, 0xbf673f7f, 0x3eac0000, 0x3f5cbf22, 0x3f7dbf7b, 0x3f2cbf62, 0x3f3ebf6d, 0x3e16bef1,
    0xbf043e48, 0xbf713f46, 0xbedb3f35, 0x3e793dc9, 0x3f4ebf0e, 0x3f80bf75, 0x3f80bf6d, 0x3f4ebf75, 0x3e79bf0e, 0xbedb3dc9,
    0xbf713f80, 0xbf043f46, 0x3e163e48, 0x3f3ebef1, 0x3f2cbec4, 0x3f7dbf62, 0x3f5cbf7b, 0x3eacbf22, 0xbf673f35, 0xbf783f7f,
    0xbf183f55, 0x3d493e95, 0x3f04bf35, 0x3d49be95, 0xbedb3e48, 0xbf4e3f22, 0xbf7d3f6d, 0xbf713f7f, 0xbf2c3f55, 0xbe793ef1,
    0xbf783f80, 0xbf3e3f62, 0xbeac3f0e, 0x3e163dc9, 0x3f18bec4, 0x3f67bf46, 0x3f80bf7b, 0x3f5cbf75, 0xbf5c3f35, 0xbf803f75,
    0xbf673f7b, 0xbf183f46, 0xbe163ec4, 0x3eacbdc9, 0x3f3ebf0e, 0x3f78bf62, 0x3e790000, 0x3f2cbef1, 0x3f71bf55, 0x3f7dbf7f,
    0x3f4ebf6d, 0x3edbbf22, 0xbd49be48, 0xbf043e95, 0xbe163ec4, 0x3eacbdc9, 0x3f3ebf0e, 0x3f78bf62, 0xbf5c3f35, 0xbf803f75,
    0xbf673f7b, 0xbf183f46, 0x3f4ebf6d, 0x3edbbf22, 0xbd49be48, 0xbf043e95, 0x3e790000, 0x3f2cbef1, 0x3f71bf55, 0x3f7dbf7f,
    0x3f7dbf6d, 0x3f71bf7f, 0x3f2cbf55, 0x3e79bef1, 0xbf043f35, 0xbd493e95, 0x3edbbe48, 0x3f4ebf22, 0xbf183ec4, 0xbf673f46,
    0xbf803f7b, 0xbf5c3f75, 0x3f78bf80, 0x3f3ebf62, 0x3eacbf0e, 0xbe16bdc9, 0xbe160000, 0xbedb3e95, 0xbf2c3f0e, 0xbf5c3f46,
    0xbf783f6d, 0xbf803f7f, 0xbf713f7b, 0xbf4e3f62, 0xbf183f35, 0xbeac3ef1, 0xbd493e48, 0x3e79bdc9, 0x3f04bec4, 0x3f3ebf22,
    0x3f67bf55, 0x3f7dbf75, 0xbf7d3f80, 0xbf673f75, 0xbf3e3f55, 0xbf043f22, 0xbe793ec4, 0x3d493dc9, 0x3eacbe48, 0x3f18bef1,
    0x3f4ebf35, 0x3f71bf62, 0x3f80bf7b, 0x3f78bf7f, 0x3f5cbf6d, 0x3f2cbf46, 0x3edbbf0e, 0x3e16be95, 0xbe793ec4, 0x3d493dc9,
    0x3eacbe48, 0x3f18bef1, 0xbf7d3f80, 0xbf673f75, 0xbf3e3f55, 0xbf043f22, 0x3f5cbf6d, 0x3f2cbf46, 0x3edbbf0e, 0x3e16be95,
    0x3f4ebf35, 0x3f71bf62, 0x3f80bf7b, 0x3f78bf7f, 0x3f78bf6d, 0x3f80bf7f, 0x3f71bf7b, 0x3f4ebf62, 0x3e160000, 0x3edbbe95,
    0x3f2cbf0e, 0x3f5cbf46, 0xbf043ec4, 0xbf3e3f22, 0xbf673f55, 0xbf7d3f75, 0x3f18bf35, 0x3eacbef1, 0x3d49be48, 0xbe793dc9,
    0x3f3ebf35, 0x3f4ebf46, 0x3f5cbf55, 0x3f67bf62, 0x3f71bf6d, 0x3f78bf75, 0x3f7dbf7b, 0x3f80bf7f, 0x3d490000, 0x3e16bdc9,
    0x3e79be48, 0x3eacbe95, 0x3edbbec4, 0x3f04bef1, 0x3f18bf0e, 0x3f2cbf22, 0xbf2c3f35, 0xbf183f22, 0xbf043f0e, 0xbedb3ef1,
    0xbeac3ec4, 0xbe793e95, 0xbe163e48, 0xbd493dc9, 0xbf803f80, 0xbf7d3f7f, 0xbf783f7b, 0xbf713f75, 0xbf673f6d, 0xbf5c3f62,
    0xbf4e3f55, 0xbf3e3f46, 0x3eacbec4, 0x3e79be95, 0x3e16be48, 0x3d49bdc9, 0x3f2cbf35, 0x3f18bf22, 0x3f04bf0e, 0x3edbbef1,
    0x3f67bf6d, 0x3f5cbf62, 0x3f4ebf55, 0x3f3ebf46, 0x3f80bf80, 0x3f7dbf7f, 0x3f78bf7b, 0x3f71bf75, 0x3f71bf6d, 0x3f78bf75,
    0x3f7dbf7b, 0x3f80bf7f, 0x3f3ebf35, 0x3f4ebf46, 0x3f5cbf55, 0x3f67bf62, 0x3edbbec4, 0x3f04bef1, 0x3f18bf0e, 0x3f2cbf22,
    0x3d490000, 0x3e16bdc9, 0x3e79be48, 0x3eacbe95,
};
__device__ const __align__(128) uint32_t c_ga[1536] = {
    0x00003c80, 0x3bc43c6d, 0x00003c80, 0xbbc4bc6d, 0x00003c80, 0x3c6d3bc4, 0x00003c80, 0xbc6dbbc4, 0x00003c80, 0x3c6dbbc4,
    0x00003c80, 0xbc6d3bc4, 0x00003c80, 0x3bc4bc6d, 0x00003c80, 0xbbc43c6d, 0x3a493c80, 0x3bdb3c67, 0x3bdb3c67, 0xbc3ebc2c,
    0x3b163c7d, 0x3c783b79, 0x3c043c5c, 0xbc7d3b16, 0x3b793c78, 0x3c4ebc18, 0x3c183c4e, 0xbc043c5c, 0x3bac3c71, 0x3a49bc80,
    0x3c2c3c3e, 0x3bac3c71, 0x3ac93c7f, 0x3bf13c62, 0x3c463c22, 0xbc75bb95, 0x3b953c75, 0x3c7f3ac9, 0x3c623bf1, 0xbc463c22,
    0x3bf13c62, 0x3c22bc46, 0x3c753b95, 0x3ac93c7f, 0x3c223c46, 0xbb95bc75, 0x3c7f3ac9, 0x3c623bf1, 0x3b163c7d, 0x3c043c5c,
    0x3c783b79, 0xbc7d3b16, 0x3bdb3c67, 0x3c80ba49, 0x3c80ba49, 0xbbac3c71, 0x3c2c3c3e, 0x3bdbbc67, 0x3c71bbac, 0x3c2c3c3e,
    0x3c5c3c04, 0xbc18bc4e, 0x3c4ebc18, 0x3c78bb79, 0x3b483c7b, 0x3c0e3c55, 0x3c7bbb48, 0xbc553c0e, 0x3c0e3c55, 0x3c7bbb48,
    0x3c55bc0e, 0x3b483c7b, 0x3c553c0e, 0x3b48bc7b, 0x3c0ebc55, 0x3c7b3b48, 0x3c7b3b48, 0xbc55bc0e, 0x3b48bc7b, 0x3c0ebc55,
    0x3b793c78, 0x3c183c4e, 0x3c4ebc18, 0xbc043c5c, 0x3c2c3c3e, 0x3c71bbac, 0x3bdbbc67, 0x3c2c3c3e, 0x3c713bac, 0xba49bc80,
    0xba49bc80, 0x3c67bbdb, 0x3c7dbb16, 0xbc78bb79, 0xbc04bc5c, 0xbb16bc7d, 0x3b953c75, 0x3c223c46, 0x3bf1bc62, 0xbac93c7f,
    0x3c463c22, 0x3c62bbf1, 0xbac9bc7f, 0x3c753b95, 0x3c7f3ac9, 0xbb95bc75, 0xbc22bc46, 0x3bf1bc62, 0x3c62bbf1, 0xbc7f3ac9,
    0xbc75bb95, 0xbc46bc22, 0x3bac3c71, 0x3c2c3c3e, 0x3a49bc80, 0x3bac3c71, 0x3c5c3c04, 0x3c4ebc18, 0xbc18bc4e, 0x3c78bb79,
    0x3c7dbb16, 0xbc04bc5c, 0xbc78bb79, 0xbb16bc7d, 0x3c2cbc3e, 0xbc673bdb, 0xbc673bdb, 0xbc803a49, 0x00003c80, 0x3bc43c6d,
    0x00003c80, 0xbbc4bc6d, 0x00003c80, 0x3c6d3bc4, 0x00003c80, 0xbc6dbbc4, 0x00003c80, 0x3c6dbbc4, 0x00003c80, 0xbc6d3bc4,
    0x00003c80, 0x3bc4bc6d, 0x00003c80, 0xbbc43c6d, 0x3c3e3c2c, 0x3c713bac, 0x3c713bac, 0xbc803a49, 0x3c4e3c18, 0x3c5cbc04,
    0x3c783b79, 0xbc183c4e, 0x3c5c3c04, 0x3b16bc7d, 0x3c7d3b16, 0x3b793c78, 0x3c673bdb, 0xbc2cbc3e, 0x3c803a49, 0x3c673bdb,
    0x3c7fbac9, 0x3c62bbf1, 0x3c22bc46, 0xbb953c75, 0x3c75bb95, 0x3ac9bc7f, 0x3bf1bc62, 0x3c223c46, 0x3c62bbf1, 0xbc46bc22,
    0x3b95bc75, 0x3c7fbac9, 0x3c46bc22, 0xbc753b95, 0x3ac9bc7f, 0x3bf1bc62, 0x3c18bc4e, 0x3b79bc78, 0xbc04bc5c, 0x3c4e3c18,
    0x3bacbc71, 0xbc3ebc2c, 0xbc3ebc2c, 0x3c67bbdb, 0x3a49bc80, 0xbc713bac, 0xbc67bbdb, 0x3a49bc80, 0xbb79bc78, 0xbb163c7d,
    0xbc7dbb16, 0xbc5cbc04, 0xbb48bc7b, 0xbc0ebc55, 0xbc7b3b48, 0x3c55bc0e, 0xbc0ebc55, 0xbc7b3b48, 0xbc553c0e, 0xbb48bc7b,
    0xbc55bc0e, 0xbb483c7b, 0xbc0e3c55, 0xbc7bbb48, 0xbc7bbb48, 0x3c553c0e, 0xbb483c7b, 0xbc0e3c55, 0xbc5cbc04, 0xbc7dbb16,
    0xbb163c7d, 0xbb79bc78, 0xbc80ba49, 0xbbdb3c67, 0x3bac3c71, 0xbc80ba49, 0xbc673bdb, 0x3c3e3c2c, 0x3c3e3c2c, 0xbbac3c71,
    0xbc183c4e, 0x3c5cbc04, 0x3c783b79, 0x3c4e3c18, 0xbc753b95, 0xbc463c22, 0x3c623bf1, 0xbc7fbac9, 0xbc223c46, 0x3bf13c62,
    0x3c7fbac9, 0xbb953c75, 0xbac93c7f, 0x3c75bb95, 0x3c46bc22, 0x3c623bf1, 0x3bf13c62, 0xbac9bc7f, 0x3b95bc75, 0x3c22bc46,
    0xbbdb3c67, 0xba493c80, 0x3c3ebc2c, 0xbbdb3c67, 0x3b793c78, 0x3c7d3b16, 0x3b16bc7d, 0x3c5c3c04, 0x3c4e3c18, 0x3b79bc78,
    0xbc04bc5c, 0x3c18bc4e, 0x3c80ba49, 0xbc71bbac, 0xbc71bbac, 0xbc3ebc2c, 0x00003c80, 0x3bc43c6d, 0x00003c80, 0xbbc4bc6d,
    0x00003c80, 0x3c6d3bc4, 0x00003c80, 0xbc6dbbc4, 0x00003c80, 0x3c6dbbc4, 0x00003c80, 0xbc6d3bc4, 0x00003c80, 0x3bc4bc6d,
    0x00003c80, 0xbbc43c6d, 0x3c80ba49, 0x3c67bbdb, 0x3c67bbdb, 0xbc2c3c3e, 0x3c7dbb16, 0x3b79bc78, 0x3c5cbc04, 0x3b163c7d,
    0x3c78bb79, 0xbc18bc4e, 0x3c4ebc18, 0x3c5c3c04, 0x3c71bbac, 0xbc80ba49, 0x3c3ebc2c, 0x3c71bbac, 0xbac9bc7f, 0xbbf1bc62,
    0xbc46bc22, 0x3c753b95, 0xbb95bc75, 0xbc7fbac9, 0xbc62bbf1, 0x3c46bc22, 0xbbf1bc62, 0xbc223c46, 0xbc75bb95, 0xbac9bc7f,
    0xbc22bc46, 0x3b953c75, 0xbc7fbac9, 0xbc62bbf1, 0xbc7d3b16, 0xbc5c3c04, 0xbb793c78, 0xbb16bc7d, 0xbc673bdb, 0x3a493c80,
    0x3a493c80, 0xbc71bbac, 0xbc3e3c2c, 0x3c673bdb, 0x3bac3c71, 0xbc3e3c2c, 0xbc043c5c, 0x3c4ebc18, 0x3c183c4e, 0x3b793c78,
    0x3b483c7b, 0x3c0e3c55, 0x3c7bbb48, 0xbc553c0e, 0x3c0e3c55, 0x3c7bbb48, 0x3c55bc0e, 0x3b483c7b, 0x3c553c0e, 0x3b48bc7b,
    0x3c0ebc55, 0x3c7b3b48, 0x3c7b3b48, 0xbc55bc0e, 0x3b48bc7b, 0x3c0ebc55, 0x3c78bb79, 0x3c4ebc18, 0xbc18bc4e, 0x3c5c3c04,
    0x3c3ebc2c, 0xbbacbc71, 0xbc67bbdb, 0x3c3ebc2c, 0x3bacbc71, 0xbc803a49, 0xbc803a49, 0xbbdbbc67, 0xbb16bc7d, 0xbb793c78,
    0xbc5c3c04, 0xbc7d3b16, 0xbb95bc75, 0xbc22bc46, 0xbbf13c62, 0x3ac9bc7f, 0xbc46bc22, 0xbc623bf1, 0x3ac93c7f, 0xbc75bb95,
    0xbc7fbac9, 0x3b953c75, 0x3c223c46, 0xbbf13c62, 0xbc623bf1, 0x3c7fbac9, 0x3c753b95, 0x3c463c22, 0xbc713bac, 0xbc3e3c2c,
    0x3c803a49, 0xbc713bac, 0xbc043c5c, 0x3c183c4e, 0x3c4ebc18, 0x3b793c78, 0x3b163c7d, 0x3c5cbc04, 0x3b79bc78, 0x3c7dbb16,
    0x3c3e3c2c, 0xbbdbbc67, 0xbbdbbc67, 0xba49bc80, 0x00003c80, 0x3bc43c6d, 0x00003c80, 0xbbc4bc6d, 0x00003c80, 0x3c6d3bc4,
    0x00003c80, 0xbc6dbbc4, 0x00003c80, 0x3c6dbbc4, 0x00003c80, 0xbc6d3bc4, 0x00003c80, 0x3bc4bc6d, 0x00003c80, 0xbbc43c6d,
    0x3c2cbc3e, 0x3bacbc71, 0x3bacbc71, 0x3a493c80, 0x3c18bc4e, 0xbc04bc5c, 0x3b79bc78, 0x3c4e3c18, 0x3c04bc5c, 0xbc7dbb16,
    0x3b16bc7d, 0x3c78bb79, 0x3bdbbc67, 0xbc3e3c2c, 0x3a49bc80, 0x3bdbbc67, 0xbc7f3ac9, 0xbc623bf1, 0xbc223c46, 0x3b95bc75,
    0xbc753b95, 0xbac93c7f, 0xbbf13c62, 0xbc22bc46, 0xbc623bf1, 0x3c463c22, 0xbb953c75, 0xbc7f3ac9, 0xbc463c22, 0x3c75bb95,
    0xbac93c7f, 0xbbf13c62, 0x3c4e3c18, 0x3c783b79, 0x3c5cbc04, 0xbc183c4e, 0x3c713bac, 0x3c2cbc3e, 0x3c2cbc3e, 0x3bdb3c67,
    0x3c803a49, 0xbbacbc71, 0x3bdbbc67, 0x3c803a49, 0x3c78bb79, 0xbc7dbb16, 0x3b16bc7d, 0x3c04bc5c, 0xbb48bc7b, 0xbc0ebc55,
    0xbc7b3b48, 0x3c55bc0e, 0xbc0ebc55, 0xbc7b3b48, 0xbc553c0e, 0xbb48bc7b, 0xbc55bc0e, 0xbb483c7b, 0xbc0e3c55, 0xbc7bbb48,
    0xbc7bbb48, 0x3c553c0e, 0xbb483c7b, 0xbc0e3c55, 0xbc043c5c, 0xbb163c7d, 0x3c7d3b16, 0xbc783b79, 0xba493c80, 0x3c673bdb,
    0x3c71bbac, 0xba493c80, 0x3bdb3c67, 0x3c2cbc3e, 0x3c2cbc3e, 0x3c713bac, 0x3c4e3c18, 0xbc04bc5c, 0x3b79bc78, 0x3c18bc4e,
    0x3c75bb95, 0x3c46bc22, 0xbc62bbf1, 0x3c7f3ac9, 0x3c22bc46, 0xbbf1bc62, 0xbc7f3ac9, 0x3b95bc75, 0x3ac9bc7f, 0xbc753b95,
    0xbc463c22, 0xbc62bbf1, 0xbbf1bc62, 0x3ac93c7f, 0xbb953c75, 0xbc223c46, 0xbc67bbdb, 0xbc80ba49, 0x3c2c3c3e, 0xbc67bbdb,
    0xbc783b79, 0xbb163c7d, 0x3c7d3b16, 0xbc043c5c, 0xbc183c4e, 0x3c783b79, 0x3c5cbc04, 0x3c4e3c18, 0x3a493c80, 0x3bacbc71,
    0x3bacbc71, 0x3c2cbc3e, 0x3c353c35, 0x3c6d3bc4, 0x3c353c35, 0xbc6dbbc4, 0x3c35bc35, 0xbbc4bc6d, 0x3c35bc35, 0x3bc43c6d,
    0xbc35bc35, 0xbbc43c6d, 0xbc35bc35, 0x3bc4bc6d, 0xbc353c35, 0x3c6dbbc4, 0xbc353c35, 0xbc6d3bc4, 0x3c3e3c2c, 0x3c713bac,
    0x3c713bac, 0xbc803a49, 0x3c18bc4e, 0xbc04bc5c, 0x3b79bc78, 0x3c4e3c18, 0xbc5cbc04, 0xbb163c7d, 0xbc7dbb16, 0xbb79bc78,
    0xbbdb3c67, 0x3c3ebc2c, 0xba493c80, 0xbbdb3c67, 0x3c463c22, 0x3c753b95, 0x3c7fbac9, 0xbc623bf1, 0x3bf1bc62, 0xbc22bc46,
    0xbb95bc75, 0x3c7f3ac9, 0xbc75bb95, 0x3ac93c7f, 0xbc623bf1, 0xbc46bc22, 0xbac93c7f, 0x3bf1bc62, 0x3c223c46, 0x3b953c75,
    0x3c4e3c18, 0x3c783b79, 0x3c5cbc04, 0xbc183c4e, 0x3bacbc71, 0xbc3ebc2c, 0xbc3ebc2c, 0x3c67bbdb, 0xbc80ba49, 0x3bac3c71,
    0xbbdb3c67, 0xbc80ba49, 0x3b793c78, 0x3b16bc7d, 0x3c7d3b16, 0x3c5c3c04, 0x3c553c0e, 0x3c7b3b48, 0x3c0ebc55, 0xbb483c7b,
    0x3b48bc7b, 0xbc55bc0e, 0xbc7bbb48, 0x3c0ebc55, 0xbc7b3b48, 0x3c0e3c55, 0x3b483c7b, 0xbc553c0e, 0x3c0e3c55, 0xbb48bc7b,
    0x3c55bc0e, 0x3c7bbb48, 0x3c5c3c04, 0x3c7d3b16, 0x3b16bc7d, 0x3b793c78, 0x3a49bc80, 0xbc67bbdb, 0xbc713bac, 0x3a49bc80,
    0xbc673bdb, 0x3c3e3c2c, 0x3c3e3c2c, 0xbbac3c71, 0x3c4e3c18, 0xbc04bc5c, 0x3b79bc78, 0x3c18bc4e, 0x3c623bf1, 0x3c7f3ac9,
    0xbb95bc75, 0x3c223c46, 0xbac9bc7f, 0xbc75bb95, 0xbc223c46, 0xbbf1bc62, 0xbc463c22, 0x3c623bf1, 0x3c7f3ac9, 0x3b953c75,
    0x3c753b95, 0xbc46bc22, 0xbbf1bc62, 0xbac9bc7f, 0x3c673bdb, 0x3c803a49, 0xbc2cbc3e, 0x3c673bdb, 0xbb79bc78, 0xbc7dbb16,
    0xbb163c7d, 0xbc5cbc04, 0xbc183c4e, 0x3c783b79, 0x3c5cbc04, 0x3c4e3c18, 0x3c80ba49, 0xbc71bbac, 0xbc71bbac, 0xbc3ebc2c,
    0x3c353c35, 0x3c6d3bc4, 0x3c353c35, 0xbc6dbbc4, 0x3c35bc35, 0xbbc4bc6d, 0x3c35bc35, 0x3bc43c6d, 0xbc35bc35, 0xbbc43c6d,
    0xbc35bc35, 0x3bc4bc6d, 0xbc353c35, 0x3c6dbbc4, 0xbc353c35, 0xbc6d3bc4, 0x3c80ba49, 0x3c67bbdb, 0x3c67bbdb, 0xbc2c3c3e,
    0xbb16bc7d, 0xbc78bb79, 0xbc04bc5c, 0x3c7dbb16, 0xbc783b79, 0x3c183c4e, 0xbc4e3c18, 0xbc5cbc04, 0x3bac3c71, 0x3a49bc80,
    0x3c2c3c3e, 0x3bac3c71, 0x3c22bc46, 0x3b95bc75, 0xbac9bc7f, 0x3bf13c62, 0xbc62bbf1, 0xbc463c22, 0xbc753b95, 0x3ac9bc7f,
    0xbb953c75, 0x3c7fbac9, 0x3bf13c62, 0xbc223c46, 0x3c7f3ac9, 0xbc62bbf1, 0x3c46bc22, 0x3c75bb95, 0xbb16bc7d, 0xbc04bc5c,
    0xbc78bb79, 0x3c7dbb16, 0xbc673bdb, 0x3a493c80, 0x3a493c80, 0xbc71bbac, 0x3c2c3c3e, 0x3bdbbc67, 0x3c71bbac, 0x3c2c3c3e,
    0x3c04bc5c, 0xbc4e3c18, 0xbc18bc4e, 0xbb79bc78, 0xbc55bc0e, 0xbc7bbb48, 0xbc0e3c55, 0x3b48bc7b, 0xbb483c7b, 0x3c553c0e,
    0x3c7b3b48, 0xbc0e3c55, 0x3c7bbb48, 0xbc0ebc55, 0xbb48bc7b, 0x3c55bc0e, 0xbc0ebc55, 0x3b483c7b, 0xbc553c0e, 0xbc7b3b48,
    0xbc783b79, 0xbc4e3c18, 0x3c183c4e, 0xbc5cbc04, 0x3c2c3c3e, 0x3c71bbac, 0x3bdbbc67, 0x3c2c3c3e, 0x3bacbc71, 0xbc803a49,
    0xbc803a49, 0xbbdbbc67, 0xbc7d3b16, 0x3c783b79, 0x3c043c5c, 0x3b163c7d, 0xbbf13c62, 0xbac93c7f, 0x3c75bb95, 0xbc463c22,
    0x3c7fbac9, 0x3b95bc75, 0xbc46bc22, 0x3c62bbf1, 0xbc22bc46, 0xbbf13c62, 0xbac93c7f, 0xbc753b95, 0xbb953c75, 0x3c22bc46,
    0x3c62bbf1, 0x3c7fbac9, 0x3bac3c71, 0x3c2c3c3e, 0x3a49bc80, 0x3bac3c71, 0x3c04bc5c, 0xbc18bc4e, 0xbc4e3c18, 0xbb79bc78,
    0xbc7d3b16, 0x3c043c5c, 0x3c783b79, 0x3b163c7d, 0x3c3e3c2c, 0xbbdbbc67, 0xbbdbbc67, 0xba49bc80, 0x3c353c35, 0x3c6d3bc4,
    0x3c353c35, 0xbc6dbbc4, 0x3c35bc35, 0xbbc4bc6d, 0x3c35bc35, 0x3bc43c6d, 0xbc35bc35, 0xbbc43c6d, 0xbc35bc35, 0x3bc4bc6d,
    0xbc353c35, 0x3c6dbbc4, 0xbc353c35, 0xbc6d3bc4, 0x3c2cbc3e, 0x3bacbc71, 0x3bacbc71, 0x3a493c80, 0xbc4ebc18, 0xbc5c3c04,
    0xbc78bb79, 0x3c18bc4e, 0xbc043c5c, 0x3c7d3b16, 0xbb163c7d, 0xbc783b79, 0x3c673bdb, 0xbc2cbc3e, 0x3c803a49, 0x3c673bdb,
    0xbc46bc22, 0xbc75bb95, 0xbc7f3ac9, 0x3c62bbf1, 0xbbf13c62, 0x3c223c46, 0x3b953c75, 0xbc7fbac9, 0x3c753b95, 0xbac9bc7f,
    0x3c62bbf1, 0x3c463c22, 0x3ac9bc7f, 0xbbf13c62, 0xbc22bc46, 0xbb95bc75, 0xbc183c4e, 0xbb793c78, 0x3c043c5c, 0xbc4ebc18,
    0x3c713bac, 0x3c2cbc3e, 0x3c2cbc3e, 0x3bdb3c67, 0x3a49bc80, 0xbc713bac, 0xbc67bbdb, 0x3a49bc80, 0xbc783b79, 0x3c7d3b16,
    0xbb163c7d, 0xbc043c5c, 0x3c553c0e, 0x3c7b3b48, 0x3c0ebc55, 0xbb483c7b, 0x3b48bc7b, 0xbc55bc0e, 0xbc7bbb48, 0x3c0ebc55,
    0xbc7b3b48, 0x3c0e3c55, 0x3b483c7b, 0xbc553c0e, 0x3c0e3c55, 0xbb48bc7b, 0x3c55bc0e, 0x3c7bbb48, 0x3c04bc5c, 0x3b16bc7d,
    0xbc7dbb16, 0x3c78bb79, 0xbc80ba49, 0xbbdb3c67, 0x3bac3c71, 0xbc80ba49, 0x3bdb3c67, 0x3c2cbc3e, 0x3c2cbc3e, 0x3c713bac,
    0x3c18bc4e, 0xbc5c3c04, 0xbc78bb79, 0xbc4ebc18, 0xbc62bbf1, 0xbc7fbac9, 0x3b953c75, 0xbc22bc46, 0x3ac93c7f, 0x3c753b95,
    0x3c22bc46, 0x3bf13c62, 0x3c46bc22, 0xbc62bbf1, 0xbc7fbac9, 0xbb95bc75, 0xbc75bb95, 0x3c463c22, 0x3bf13c62, 0x3ac93c7f,
    0xbbdb3c67, 0xba493c80, 0x3c3ebc2c, 0xbbdb3c67, 0x3c78bb79, 0x3b16bc7d, 0xbc7dbb16, 0x3c04bc5c, 0xbc4ebc18, 0xbb793c78,
    0x3c043c5c, 0xbc183c4e, 0x3a493c80, 0x3bacbc71, 0x3bacbc71, 0x3c2cbc3e, 0x3c353c35, 0x3c6d3bc4, 0x3c353c35, 0xbc6dbbc4,
    0x3c35bc35, 0xbbc4bc6d, 0x3c35bc35, 0x3bc43c6d, 0xbc35bc35, 0xbbc43c6d, 0xbc35bc35, 0x3bc4bc6d, 0xbc353c35, 0x3c6dbbc4,
    0xbc353c35, 0xbc6d3bc4, 0xba49bc80, 0xbbdbbc67, 0xbbdbbc67, 0x3c3e3c2c, 0xbc7d3b16, 0xbb793c78, 0xbc5c3c04, 0xbb16bc7d,
    0x3b793c78, 0x3c4ebc18, 0x3c183c4e, 0xbc043c5c, 0x3c71bbac, 0xbc80ba49, 0x3c3ebc2c, 0x3c71bbac, 0xbc223c46, 0xbb953c75,
    0x3ac93c7f, 0xbbf1bc62, 0x3c623bf1, 0x3c46bc22, 0x3c75bb95, 0xbac93c7f, 0x3b95bc75, 0xbc7f3ac9, 0xbbf1bc62, 0x3c22bc46,
    0xbc7fbac9, 0x3c623bf1, 0xbc463c22, 0xbc753b95, 0x3c7dbb16, 0x3c5cbc04, 0x3b79bc78, 0x3b163c7d, 0xbbdbbc67, 0xbc803a49,
    0xbc803a49, 0x3bacbc71, 0xbc3e3c2c, 0x3c673bdb, 0x3bac3c71, 0xbc3e3c2c, 0x3c5c3c04, 0xbc18bc4e, 0x3c4ebc18, 0x3c78bb79,
    0xbc55bc0e, 0xbc7bbb48, 0xbc0e3c55, 0x3b48bc7b, 0xbb483c7b, 0x3c553c0e, 0x3c7b3b48, 0xbc0e3c55, 0x3c7bbb48, 0xbc0ebc55,
    0xbb48bc7b, 0x3c55bc0e, 0xbc0ebc55, 0x3b483c7b, 0xbc553c0e, 0xbc7b3b48, 0x3b793c78, 0x3c183c4e, 0x3c4ebc18, 0xbc043c5c,
    0x3c3ebc2c, 0xbbacbc71, 0xbc67bbdb, 0x3c3ebc2c, 0xbc71bbac, 0x3a493c80, 0x3a493c80, 0xbc673bdb, 0x3b163c7d, 0x3b79bc78,
    0x3c5cbc04, 0x3c7dbb16, 0x3bf1bc62, 0x3ac9bc7f, 0xbc753b95, 0x3c46bc22, 0xbc7f3ac9, 0xbb953c75, 0x3c463c22, 0xbc623bf1,
    0x3c223c46, 0x3bf1bc62, 0x3ac9bc7f, 0x3c75bb95, 0x3b95bc75, 0xbc223c46, 0xbc623bf1, 0xbc7f3ac9, 0xbc713bac, 0xbc3e3c2c,
    0x3c803a49, 0xbc713bac, 0x3c5c3c04, 0x3c4ebc18, 0xbc18bc4e, 0x3c78bb79, 0xbb16bc7d, 0xbc5c3c04, 0xbb793c78, 0xbc7d3b16,
    0xbc2c3c3e, 0x3c67bbdb, 0x3c67bbdb, 0x3c80ba49, 0x3c800000, 0x3c6dbbc4, 0x3c800000, 0xbc6d3bc4, 0xbc800000, 0xbbc43c6d,
    0xbc800000, 0x3bc4bc6d, 0x3c800000, 0xbbc4bc6d, 0x3c800000, 0x3bc43c6d, 0xbc800000, 0x3c6d3bc4, 0xbc800000, 0xbc6dbbc4,
    0x3c80ba49, 0x3c67bbdb, 0x3c67bbdb, 0xbc2c3c3e, 0xbc7d3b16, 0xbb793c78, 0xbc5c3c04, 0xbb16bc7d, 0x3c78bb79, 0xbc18bc4e,
    0x3c4ebc18, 0x3c5c3c04, 0xbc713bac, 0x3c803a49, 0xbc3e3c2c, 0xbc713bac, 0x3c7fbac9, 0x3c62bbf1, 0x3c22bc46, 0xbb953c75,
    0xbc753b95, 0xbac93c7f, 0xbbf13c62, 0xbc22bc46, 0x3c62bbf1, 0xbc46bc22, 0x3b95bc75, 0x3c7fbac9, 0xbc463c22, 0x3c75bb95,
    0xbac93c7f, 0xbbf13c62, 0x3c7dbb16, 0x3c5cbc04, 0x3b79bc78, 0x3b163c7d, 0xbc673bdb, 0x3a493c80, 0x3a493c80, 0xbc71bbac,
    0x3c3ebc2c, 0xbc67bbdb, 0xbbacbc71, 0x3c3ebc2c, 0xbc043c5c, 0x3c4ebc18, 0x3c183c4e, 0x3b793c78, 0x3c7bbb48, 0x3c55bc0e,
    0xbb48bc7b, 0x3c0e3c55, 0xbc553c0e, 0x3b483c7b, 0x3c0e3c55, 0xbc7b3b48, 0x3c0ebc55, 0xbc7bbb48, 0xbc55bc0e, 0x3b48bc7b,
    0xbb483c7b, 0x3c0ebc55, 0x3c7b3b48, 0x3c553c0e, 0x3c78bb79, 0x3c4ebc18, 0xbc18bc4e, 0x3c5c3c04, 0xbc3e3c2c, 0x3bac3c71,
    0x3c673bdb, 0xbc3e3c2c, 0x3bacbc71, 0xbc803a49, 0xbc803a49, 0xbbdbbc67, 0x3b163c7d, 0x3b79bc78, 0x3c5cbc04, 0x3c7dbb16,
    0x3c75bb95, 0x3c46bc22, 0xbc62bbf1, 0x3c7f3ac9, 0xbc223c46, 0x3bf13c62, 0x3c7fbac9, 0xbb953c75, 0x3ac9bc7f, 0xbc753b95,
    0xbc463c22, 0xbc62bbf1, 0x3bf13c62, 0xbac9bc7f, 0x3b95bc75, 0x3c22bc46, 0x3c71bbac, 0x3c3ebc2c, 0xbc80ba49, 0x3c71bbac,
    0xbc043c5c, 0x3c183c4e, 0x3c4ebc18, 0x3b793c78, 0xbb16bc7d, 0xbc5c3c04, 0xbb793c78, 0xbc7d3b16, 0x3c3e3c2c, 0xbbdbbc67,
    0xbbdbbc67, 0xba49bc80, 0x3c800000, 0x3c6dbbc4, 0x3c800000, 0xbc6d3bc4, 0xbc800000, 0xbbc43c6d, 0xbc800000, 0x3bc4bc6d,
    0x3c800000, 0xbbc4bc6d, 0x3c800000, 0x3bc43c6d, 0xbc800000, 0x3c6d3bc4, 0xbc800000, 0xbc6dbbc4, 0x3c2cbc3e, 0x3bacbc71,
    0x3bacbc71, 0x3a493c80, 0xbc183c4e, 0x3c043c5c, 0xbb793c78, 0xbc4ebc18, 0x3c04bc5c, 0xbc7dbb16, 0x3b16bc7d, 0x3c78bb79,
    0xbbdb3c67, 0x3c3ebc2c, 0xba493c80, 0xbbdb3c67, 0xbac9bc7f, 0xbbf1bc62, 0xbc46bc22, 0x3c753b95, 0x3b953c75, 0x3c7f3ac9,
    0x3c623bf1, 0xbc463c22, 0xbbf1bc62, 0xbc223c46, 0xbc75bb95, 0xbac9bc7f, 0x3c223c46, 0xbb95bc75, 0x3c7f3ac9, 0x3c623bf1,
    0xbc4ebc18, 0xbc78bb79, 0xbc5c3c04, 0x3c18bc4e, 0x3c713bac, 0x3c2cbc3e, 0x3c2cbc3e, 0x3bdb3c67, 0xbc80ba49, 0x3bac3c71,
    0xbbdb3c67, 0xbc80ba49, 0x3c78bb79, 0xbc7dbb16, 0x3b16bc7d, 0x3c04bc5c, 0xbc7b3b48, 0xbc553c0e, 0x3b483c7b, 0xbc0ebc55,
    0x3c55bc0e, 0xbb48bc7b, 0xbc0ebc55, 0x3c7bbb48, 0xbc0e3c55, 0x3c7b3b48, 0x3c553c0e, 0xbb483c7b, 0x3b48bc7b, 0xbc0e3c55,
    0xbc7bbb48, 0xbc55bc0e, 0xbc043c5c, 0xbb163c7d, 0x3c7d3b16, 0xbc783b79, 0x3a49bc80, 0xbc67bbdb, 0xbc713bac, 0x3a49bc80,
    0x3bdb3c67, 0x3c2cbc3e, 0x3c2cbc3e, 0x3c713bac, 0xbc4ebc18, 0x3c043c5c, 0xbb793c78, 0xbc183c4e, 0x3b953c75, 0x3c223c46,
    0x3bf1bc62, 0xbac93c7f, 0xbc46bc22, 0xbc623bf1, 0x3ac93c7f, 0xbc75bb95, 0x3c7f3ac9, 0xbb95bc75, 0xbc22bc46, 0x3bf1bc62,
    0xbc623bf1, 0x3c7fbac9, 0x3c753b95, 0x3c463c22, 0x3c673bdb, 0x3c803a49, 0xbc2cbc3e, 0x3c673bdb, 0xbc783b79, 0xbb163c7d,
    0x3c7d3b16, 0xbc043c5c, 0x3c18bc4e, 0xbc78bb79, 0xbc5c3c04, 0xbc4ebc18, 0x3a493c80, 0x3bacbc71, 0x3bacbc71, 0x3c2cbc3e,
    0x3c800000, 0x3c6dbbc4, 0x3c800000, 0xbc6d3bc4, 0xbc800000, 0xbbc43c6d, 0xbc800000, 0x3bc4bc6d, 0x3c800000, 0xbbc4bc6d,
    0x3c800000, 0x3bc43c6d, 0xbc800000, 0x3c6d3bc4, 0xbc800000, 0xbc6dbbc4, 0xba49bc80, 0xbbdbbc67, 0xbbdbbc67, 0x3c3e3c2c,
    0x3b163c7d, 0x3c783b79, 0x3c043c5c, 0xbc7d3b16, 0xbb79bc78, 0xbc4e3c18, 0xbc18bc4e, 0x3c04bc5c, 0x3bac3c71, 0x3a49bc80,
    0x3c2c3c3e, 0x3bac3c71, 0xbc7f3ac9, 0xbc623bf1, 0xbc223c46, 0x3b95bc75, 0x3c75bb95, 0x3ac9bc7f, 0x3bf1bc62, 0x3c223c46,
    0xbc623bf1, 0x3c463c22, 0xbb953c75, 0xbc7f3ac9, 0x3c46bc22, 0xbc753b95, 0x3ac9bc7f, 0x3bf1bc62, 0x3b163c7d, 0x3c043c5c,
    0x3c783b79, 0xbc7d3b16, 0xbbdbbc67, 0xbc803a49, 0xbc803a49, 0x3bacbc71, 0x3c2c3c3e, 0x3bdbbc67, 0x3c71bbac, 0x3c2c3c3e,
    0xbc5cbc04, 0x3c183c4e, 0xbc4e3c18, 0xbc783b79, 0x3c7bbb48, 0x3c55bc0e, 0xbb48bc7b, 0x3c0e3c55, 0xbc553c0e, 0x3b483c7b,
    0x3c0e3c55, 0xbc7b3b48, 0x3c0ebc55, 0xbc7bbb48, 0xbc55bc0e, 0x3b48bc7b, 0xbb483c7b, 0x3c0ebc55, 0x3c7b3b48, 0x3c553c0e,
    0xbb79bc78, 0xbc18bc4e, 0xbc4e3c18, 0x3c04bc5c, 0x3c2c3c3e, 0x3c71bbac, 0x3bdbbc67, 0x3c2c3c3e, 0xbc71bbac, 0x3a493c80,
    0x3a493c80, 0xbc673bdb, 0x3c7dbb16, 0xbc78bb79, 0xbc04bc5c, 0xbb16bc7d, 0xbc753b95, 0xbc463c22, 0x3c623bf1, 0xbc7fbac9,
    0x3c22bc46, 0xbbf1bc62, 0xbc7f3ac9, 0x3b95bc75, 0xbac93c7f, 0x3c75bb95, 0x3c46bc22, 0x3c623bf1, 0xbbf1bc62, 0x3ac93c7f,
    0xbb953c75, 0xbc223c46, 0x3bac3c71, 0x3c2c3c3e, 0x3a49bc80, 0x3bac3c71, 0xbc5cbc04, 0xbc4e3c18, 0x3c183c4e, 0xbc783b79,
    0x3c7dbb16, 0xbc04bc5c, 0xbc78bb79, 0xbb16bc7d, 0xbc2c3c3e, 0x3c67bbdb, 0x3c67bbdb, 0x3c80ba49, 0x3c800000, 0x3c6dbbc4,
    0x3c800000, 0xbc6d3bc4, 0xbc800000, 0xbbc43c6d, 0xbc800000, 0x3bc4bc6d, 0x3c800000, 0xbbc4bc6d, 0x3c800000, 0x3bc43c6d,
    0xbc800000, 0x3c6d3bc4, 0xbc800000, 0xbc6dbbc4, 0xbc3ebc2c, 0xbc71bbac, 0xbc71bbac, 0x3c80ba49, 0x3c4e3c18, 0x3c5cbc04,
    0x3c783b79, 0xbc183c4e, 0xbc5cbc04, 0xbb163c7d, 0xbc7dbb16, 0xbb79bc78, 0x3c673bdb, 0xbc2cbc3e, 0x3c803a49, 0x3c673bdb,
    0x3ac93c7f, 0x3bf13c62, 0x3c463c22, 0xbc75bb95, 0xbb95bc75, 0xbc7fbac9, 0xbc62bbf1, 0x3c46bc22, 0x3bf13c62, 0x3c22bc46,
    0x3c753b95, 0x3ac93c7f, 0xbc22bc46, 0x3b953c75, 0xbc7fbac9, 0xbc62bbf1, 0x3c18bc4e, 0x3b79bc78, 0xbc04bc5c, 0x3c4e3c18,
    0xbbac3c71, 0x3c3e3c2c, 0x3c3e3c2c, 0xbc673bdb, 0x3a49bc80, 0xbc713bac, 0xbc67bbdb, 0x3a49bc80, 0x3b793c78, 0x3b16bc7d,
    0x3c7d3b16, 0x3c5c3c04, 0xbc7b3b48, 0xbc553c0e, 0x3b483c7b, 0xbc0ebc55, 0x3c55bc0e, 0xbb48bc7b, 0xbc0ebc55, 0x3c7bbb48,
    0xbc0e3c55, 0x3c7b3b48, 0x3c553c0e, 0xbb483c7b, 0x3b48bc7b, 0xbc0e3c55, 0xbc7bbb48, 0xbc55bc0e, 0x3c5c3c04, 0x3c7d3b16,
    0x3b16bc7d, 0x3b793c78, 0xbc80ba49, 0xbbdb3c67, 0x3bac3c71, 0xbc80ba49, 0x3c67bbdb, 0xbc3ebc2c, 0xbc3ebc2c, 0x3bacbc71,
    0xbc183c4e, 0x3c5cbc04, 0x3c783b79, 0x3c4e3c18, 0xbb95bc75, 0xbc22bc46, 0xbbf13c62, 0x3ac9bc7f, 0x3c463c22, 0x3c62bbf1,
    0xbac9bc7f, 0x3c753b95, 0xbc7fbac9, 0x3b953c75, 0x3c223c46, 0xbbf13c62, 0x3c62bbf1, 0xbc7f3ac9, 0xbc75bb95, 0xbc46bc22,
    0xbbdb3c67, 0xba493c80, 0x3c3ebc2c, 0xbbdb3c67, 0xbb79bc78, 0xbc7dbb16, 0xbb163c7d, 0xbc5cbc04, 0x3c4e3c18, 0x3b79bc78,
    0xbc04bc5c, 0x3c18bc4e, 0xbc803a49, 0x3c713bac, 0x3c713bac, 0x3c3e3c2c,
};

#define G_EPI 3
#define G_TK 3
#define W_Q 6
#define W2_PC 32
#define W2_PF 3
constexpr int X_LOC0 = 5;
constexpr int A_IN = 112 * 128;
constexpr int G_ST = 2 * NB1 * 64;
constexpr int K1_R = 131072, K1_BAR = K1_R + 98304, K1_SMEM = K1_BAR + 2048 + 1024;
constexpr int K1_T = K1_R + 65536, K1_TIN = 0, K1_Y0 = 3 * G_ST + 8192, G_KM = 16 - G_TK, G_S0 = 2 * G_KM;
__device__ int g_done[8 * 32];
struct Ptrs {
  int* done;
  float* ge;
  const uint32_t *img, *ga;
};

__host__ __device__ constexpr int g_depth(int s) { return s < 11 ? 3 : s < 18 ? 4 : s < 23 ? 5 : 6; }
__host__ __device__ constexpr int g_slot(int s) { return s < 3 ? s : g_depth(s) != g_depth(s - 1) ? g_depth(s - 1) : g_slot(s - g_depth(s)); }
__host__ __device__ constexpr int g_off(int id) { return id * G_ST + (id < 3 ? K1_R : 8192 - 3 * G_ST); }
struct Plan {
  uint32_t raw[32];
  uint32_t x[16];
  uint32_t grp[8];
  uint32_t last;
  uint32_t wpf;
  uint32_t g0;
  uint32_t tmask;
  uint64_t list[2];
};
struct K1Maps {
  Plan p;
  CUtensorMap x, we, wo, xs, y, w2e, w2o, w2s;
  int slot[32];
  int src[32];
  int dep[32];
};
__device__ __forceinline__ void poll_ge(const int* p, int target) {
  for (int it = 0; it < (1 << 20); it++) {
    int v;
    asm volatile("ld.acquire.gpu.global.s32 %0, [%1];" : "=r"(v) : "l"(p) : "memory");
    if (v >= target) break;
  }
}
__device__ __forceinline__ uint32_t place(int rank, uint32_t c) { return (c ^ (rank * 4 & ~(c >> 1))) << 14; }
__device__ __forceinline__ int x_unit(int cta, int u, uint32_t pl) {
  const int i = u * 128 + cta;
  const int pr = cta >= 128 ? 2 * cta - 96 + (u & 1) : i % 160, sl = cta >= 128 ? u >> 1 : i / 160, b = pr >= 84;
  return pr | sl << 8 | b << 11 | (cta >= 128 ? (u & 7) << 14 : place(cta & 1, pl & 15)) | 12 * (pr - 84 * b) << 20;
}
__device__ __forceinline__ int lds32(uint32_t a) {
  int v;
  asm volatile("ld.shared.b32 %0, [%1];" : "=r"(v) : "r"(a));
  return v;
}
__host__ __device__ constexpr uint64_t sched(const char* p) {
  uint64_t r = 0;
  for (int n = 0; p[n]; n++) r |= (uint64_t)(p[n] - '0' + 1) << (5 * n);
  return r;
}

__global__ void __cluster_dims__(2, 1, 1) __launch_bounds__(384, 1)
k1(const Ptrs gp_, const char* __restrict__ x1, const char* __restrict__ w1, const __grid_constant__ K1Maps m, const __nv_bfloat16* __restrict__ g,
   const __nv_bfloat16* __restrict__ wgt) {
  extern __shared__ __align__(1024) uint8_t smem_k1[];
  const uint32_t sb = s2u(smem_k1);
  const int tid = threadIdx.x, cta = blockIdx.x, rank = cta & 1;
  if (tid == 288) {
    const uint32_t bar = sb + K1_BAR + 256, dst = sb + (cta >= 128 ? 0 : place(rank, X_LOC0));
    const int pr = cta >= 128 ? 2 * cta - 96 : cta, b = pr >= 84;
    mbar_init(bar, 1);
    mbar_expect(bar, A_IN);
    for (int h = 0; h < 2; h++) tma_ld4<1>(dst + h * (A_IN / 2), &m.x, bar, 0, 96 * (pr - 84 * b) - 24 + h * 56, 0, b);
    for (int i = 1; i < 4; i++) mbar_init(bar + 8 * i, 1);
    fence_bar_init();
  }
  const uint32_t sF = sb + (cta >= 128 ? K1_T : rank * 65536), fbar = sb + K1_BAR + 1792;
  if (tid == 320) {
    mbar_init(fbar, 1);
    mbar_expect(fbar, 8192);
    asm volatile("cp.async.bulk.shared::cluster.global.mbarrier::complete_tx::bytes [%0], [%1], 8192, [%2];" ::"r"(sF), "l"(gp_.img + 1536), "r"(fbar) : "memory");
    fence_bar_init();
  }
  const int wg = __shfl_sync(0xffffffffu, tid >> 7, 0), t = tid & 127;
  const int warp = __shfl_sync(0xffffffffu, t >> 5, 0), lane = t & 31;
  const bool spare = cta >= 128;
  const int nx = spare ? 16 : 10;
  int bp, dc;
  {
    const int ci = cta >> 1;
    const int G = ci < 4 ? 0 : ci < 36 ? (ci - 4) & 7 : 1 + (ci - 36) % 7;
    const int li = ci < 4 ? 4 + ci : ci < 36 ? (ci - 4) >> 3 : 4 + (ci - 36) / 7;
    bp = 2 * G + (li >> 2), dc = li & 3;
  }
  const int bin = 2 * bp + rank;
  const uint32_t bb = sb + K1_BAR;
  const uint32_t rfull = bb, xfull = bb + 256, xfree = bb + 384, gfull = bb + 512, win = bb + 1800, win1 = bb + 1808;
  const uint32_t inf0 = bb + 784, se0 = inf0 + 16, pfree = se0 + 16, rempty = bb + 1024, xready = bb + 1280;
  const uint32_t gdone = bb + 1536, ine0 = gdone + 224, sf0 = ine0 + 16;
  const uint32_t xtab = bb + 896, ptab = bb + 2048 + 768;
  auto raw_load = [&](int j, uint32_t dst) {
    mbar_expect(rfull + 8 * j, 16384);
    tma_ld4<0>(dst, rank ? &m.we : &m.wo, rfull + 8 * j, dc * 64, rank - 1, (j & 3) * 4, (j >> 2) * 2);
  };
  auto x_half = [&](int u, int c, int h) {
    tma_ld4<1>(sb + (c & 0x3C000) + h * (A_IN / 2), &m.x, xfull + 8 * u, 0, (c >> 17 & ~7) - 24 + h * 56, c >> 8 & 7, c >> 11 & 1);
  };
  auto w_prefetch = [&](int q) {
    if (cta < 124) asm volatile("cp.async.bulk.prefetch.L2.global [%0], 4096;" ::"l"(w1 + (cta >> 2) * 131072 + (q * 4 + (cta & 3)) * 4096) : "memory");
  };
  uint32_t peer;
  asm("mapa.shared::cluster.u32 %0, %1, %2;" : "=r"(peer) : "r"(sb), "r"(rank ^ 1));
  if (wg == 2) {
    if (lane == 0) {
      if (warp == 0) {
        for (int i = 0; i < 4; i++) mbar_init(bb + 8 * i, 1);
        fence_bar_init();
        if (!spare)
          for (int j = 0; j < 4; j++) raw_load(j, sb + K1_R + j * 16384);
      } else if (warp == 2) {
#pragma unroll 1
        for (int q = 1; q <= m.p.wpf; q++) w_prefetch(q);
        prefetch_map(&m.xs);
      }
    }
    if (warp == 3) {
      const uint32_t v = reinterpret_cast<const uint32_t*>(&m.p)[32 + lane];
      asm volatile("st.shared.b32 [%0], %1;" ::"r"(ptab + 4 * lane), "r"(m.p.raw[lane]) : "memory");
      asm volatile("st.shared.b32 [%0], %1;" ::"r"(ptab + 128 + 4 * lane), "r"(v) : "memory");
      if (lane < 16) asm volatile("st.shared.b32 [%0], %1;" ::"r"(xtab + 4 * lane), "r"(x_unit(cta, lane, v)) : "memory");
    }
  } else {
    const int c = 4 * wg + warp;
    if (lane == 0 && c < 7) {
      const uint32_t b0 = bb + 256 * c, n = c < 4 ? 1 : c < 6 ? 4 : 8;
      if (c >= 2)
        for (int i = 0; i < 4; i++) mbar_init(b0 + 8 * i, n);
      for (int i = 4; i < 16; i++) mbar_init(b0 + 8 * i, n);
      if (c == 3) {
        mbar_init(win, 1 + 2 * W_Q);
        mbar_init(win1, 17 - 2 * W_Q);
        mbar_expect(win, 8192 * W_Q);
        mbar_expect(win1, 65536 - 8192 * W_Q);
        mbar_arrive(bb + 776);
      } else {
        for (int i = 16; i < 32; i++) mbar_init(b0 + 8 * i, n);
      }
      fence_bar_init();
    }
  }
  pdl_launch();
  __syncthreads();
  asm volatile("barrier.cluster.arrive.relaxed.aligned;" ::: "memory");
  if (wg == 2) {
    asm volatile("setmaxnreg.dec.sync.aligned.u32 40;");
    asm volatile("barrier.cluster.wait.aligned;" ::: "memory");
    if (lane == 0) {
      const int wpf = lds32(ptab + 228), g0 = lds32(ptab + 232), s0 = g0 * 4 / 5;
      const int nx0 = spare ? 2 * s0 : g0;
      if (warp == 0) {
        if (!spare) {
#pragma unroll 1
          for (int j = 4; j < 32; j++) {
            const uint32_t e = lds32(ptab + 4 * j);
            mbar_wait(bb + (e >> 5 & ~7), 0);
            raw_load(j, sb + place(rank, e & 15));
            if ((j & 3) == 0 && wpf && (j >> 2) + wpf < 8) w_prefetch((j >> 2) + wpf);
          }
#pragma unroll 1
          for (int s = 0; s < 32; s++) {
            if (s == 0 || s == 4 * s0) {
              poll_ge(&gp_.done[(s ? 5 : 4) * 32], 132);
              asm volatile("fence.proxy.async.global;" ::: "memory");
              mbar_wait(bb + 8 * (lds32(ptab + 224) & 255), 0);
            }
            const uint32_t bar = gfull + 8 * s, dst = sb + 16 * m.slot[s];
            const char* src = x1 + bin * (4 * G_ST) + m.src[s];
            mbar_wait(bb + m.dep[s], 0);
            mbar_expect(bar, G_ST);
#pragma unroll
            for (int h = 0; h < 2; h++) {
              if (s >= 16)
                asm volatile("cp.async.bulk.shared::cluster.global.mbarrier::complete_tx::bytes.L2::cache_hint [%0], [%1], %2, [%3], %4;"
                             ::"r"(dst + h * (G_ST / 2)), "l"(src + h * (s < G_S0 ? G_ST / 2 : 2 * G_ST)), "n"(G_ST / 2), "r"(bar), "l"(policy<1>()) : "memory");
              else
                asm volatile("cp.async.bulk.shared::cluster.global.mbarrier::complete_tx::bytes [%0], [%1], %2, [%3];"
                             ::"r"(dst + h * (G_ST / 2)), "l"(src + h * (s < G_S0 ? G_ST / 2 : 2 * G_ST)), "n"(G_ST / 2), "r"(bar) : "memory");
            }
          }
          if (cta == 0) asm volatile("cp.async.bulk.prefetch.L2.global [%0], 14336;" ::"l"(gp_.img) : "memory");
        }
      } else if (warp < 3) {
        const int u0 = warp == 1 ? 0 : nx0, u1 = warp == 1 ? nx0 : nx;
#pragma unroll 1
        for (int u = u0; u < u1; u++) {
          const int c = lds32(xtab + 4 * u);
          const uint32_t e = spare ? 0xC0 : lds32(ptab + 128 + 4 * u);
          const uint32_t src = sb + (c & 0x3C000), rel = e >> 1 & 24, burst = (16 << (e >> 6 & 3)) - 1;
          mbar_wait(xready + 8 * u, 0);
#pragma unroll 1
          for (int p = 0; p < 128; p += 16) {
            tma_st4<0>(&m.xs, src + p * 128, 0, (c >> 2 & 0x1C0) + (p & 63), p >> 6, c & 255);
            if (((p + 16) & burst) == 0) {
              bulk_commit();
              bulk_wait_read<0>();
            }
          }
          mbar_arrive(xfree + 8 * u);
          if (rel)
            asm volatile("mbarrier.arrive.shared::cluster.b64 _, [%0];" ::"r"(peer + (pfree - sb) + rel) : "memory");
        }
        asm volatile("cp.async.bulk.wait_group 0;" ::: "memory");
        asm volatile("red.release.gpu.global.add.s32 [%0], 1;" ::"l"(&gp_.done[(3 + warp) * 32]) : "memory");
        if (!spare) {
          if (warp == 1) {
            auto w2_row = [&](int it, bool pf) {
              const CUtensorMap* mp = it & 1 ? &m.w2e : &m.w2o;
              const int c1 = (it & 1) - 1, c2 = (cta & 1) * 2, c3 = (it >> 1) * 64 + (cta >> 1);
              if (pf) {
                asm volatile("cp.async.bulk.prefetch.tensor.4d.L2.global [%0, {%1, %2, %3, %4}];" ::"l"(mp), "r"(0), "r"(c1), "r"(c2), "r"(c3) : "memory");
              } else {
                mbar_expect(inf0 + 8 * (it & 1), 4096);
                tma_ld4<1>(sb + K1_TIN + (it & 1) * 4096, mp, inf0 + 8 * (it & 1), 0, c1, c2, c3);
              }
            };
#pragma unroll 1
            for (int it = 0; it < W2_PF; it++) {
              mbar_wait(gfull + 8 * (it >> 1), 0);
              w2_row(it, true);
            }
            mbar_wait(gdone + 8, 0);
#pragma unroll 1
            for (int it = 0; it < 8; it++) {
              if (it >= 2) mbar_wait(ine0 + 8 * (it & 1), ((it >> 1) - 1) & 1);
              w2_row(it, false);
              if (W2_PF && it + W2_PF < 8) w2_row(it + W2_PF, true);
            }
          } else {
            prefetch_map(&m.w2s);
            prefetch_map(&m.y);
#pragma unroll 1
            for (int it = 0; it < 8; it++) {
              if ((0x74 >> it) & 1) poll_ge(&gp_.done[((0x33210000 >> (4 * it)) & 3) * 32], 128);
              mbar_wait(sf0 + 8 * (it & 1), (it >> 1) & 1);
#pragma unroll 1
              for (int p = 0; p < 128; p += W2_PC) {
                tma_st4<0>(&m.w2s, sb + K1_T + (it & 1) * 16384 + p * 128, 0, it * 64 + (p & 63), (cta & 1) * 2 + (p >> 6),
                           (cta >> 1 & 33) | (cta >> 3 & 6) | (cta << 1 & 24));
                bulk_commit();
                bulk_wait_read<0>();
              }
              mbar_arrive(se0 + 8 * (it & 1));
            }
          }
        }
      } else {
#pragma unroll 1
        for (int u = 1; u < nx; u++) {
          const int c = lds32(xtab + 4 * u);
          const uint32_t e = spare ? (u < 8 ? 97 : 40 + u) * 0x01010100u : lds32(ptab + 128 + 4 * u);
          mbar_wait(bb + (e >> 5 & 0x7F8), 0);
          mbar_expect(xfull + 8 * u, A_IN);
          mbar_wait(bb + (e >> 13 & 0x7F8), 0);
          x_half(u, c, 0);
          mbar_wait(bb + (e >> 21 & 0x7F8), 0);
          x_half(u, c, 1);
        }
#pragma unroll 1
        for (int s = 0; s < (spare ? 0 : 16); s++) {
          mbar_wait(gfull + 8 * s, 0);
          if ((s & 3) == 3) asm volatile("red.relaxed.gpu.global.add.s32 [%0], 1;" ::"l"(&gp_.done[(s >> 2) * 32]) : "memory");
        }
      }
    }
  } else {
    asm volatile("setmaxnreg.inc.sync.aligned.u32 232;");
    const int row = (lane & 7) + ((lane >> 3) & 1) * 8, hi = lane >> 4;
    asm volatile("barrier.cluster.wait.aligned;" ::: "memory");
    uint32_t fw[4];
    {
      uint32_t fa[16], za[64];
      mbar_wait(fbar, 0);
      const int f = (4 * bp + warp) & 63;
      const uint32_t lo = lds32(sF + f * 128 + ((f & 7) << 4) + (lane & 3) * 4), hh = lds32(sF + f * 128 + (((f & 7) ^ 1) << 4) + (lane & 3) * 4);
#pragma unroll
      for (int k = 0; k < 4; k++)
        ldsm4(sF + (warp * 16 + row) * 128 + (((2 * k + hi) ^ (lane & 7)) << 4), fa[4 * k], fa[4 * k + 1], fa[4 * k + 2], fa[4 * k + 3]);
      const int rho = (lane >> 3) | (lane & 4);
#pragma unroll
      for (int i = 0; i < 64; i++) za[i] = ((i & 1) == (i >> 5) && rho == ((i >> 2) & 7)) ? ((i & 2) ? hh : lo) : 0u;
      reg_fence(za);
      bar_sync(3, 256);
      const bool own = (warp >> 1) == rank;
      float d[64];
      constexpr uint64_t s2 = sched("02468:<>"), s3 = sched("13579;=?");
#pragma unroll 1
      for (uint64_t sc = spare ? (wg ? s3 : s2) : (uint32_t)lds32(ptab + 240 + 8 * wg) | (uint64_t)lds32(ptab + 244 + 8 * wg) << 32; sc; sc >>= 5) {
        const int item = (int)sc & 31;
        if (item >= 18) {
          const int q = item - 18;
          const uint32_t e = __shfl_sync(0xffffffffu, lds32(ptab + 192 + 4 * q), 0);
#pragma unroll
          for (int jj = 0; jj < 4; jj++) {
            const int j = 4 * q + jj;
            mbar_wait(rfull + 8 * j, 0);
            wg_fence();
#pragma unroll
            for (int i = 0; i < 4; i++)
              wgmma_rs_128<1, 1, 1>(d, za[16 * jj + 4 * i], za[16 * jj + 4 * i + 1], za[16 * jj + 4 * i + 2], za[16 * jj + 4 * i + 3],
                                    mk_desc(sb + place(rank, e >> (4 * jj) & 15), i * 2048, 8192, 1024, 1), jj | i);
            wg_commit();
            if (jj > 0) {
              wg_wait<1>();
              if (lane == 0) mbar_arrive(rempty + 8 * (j - 1));
            }
          }
          wg_wait<0>();
          reg_fence(d);
          if (lane == 0) mbar_arrive(rempty + 8 * (4 * q + 3));
          mbar_wait(bb + (e >> (own ? 13 : 21) & 0x7F8), 0);
          const uint32_t rb = (own ? sb : peer) + (8 * rank + q) * 8192 + (warp & 1) * 4096 + rho * 128;
          const uint32_t wbar = q < W_Q ? win : win1;
          auto put_w = [&](auto remote) {
#pragma unroll
            for (int v = 0; v < 8; v++) {
              const int j = 4 * (v >> 1), h = v & 1;
              const uint32_t a = rb + (j >> 3) * 2048 + h * 1024 + ((((j & 4) + (lane & 3)) ^ rho) << 4);
              const uint32_t p0 = pack2(d[4 * j + 2 * h], d[4 * j + 2 * h + 1]), p1 = pack2(d[4 * j + 4 + 2 * h], d[4 * j + 5 + 2 * h]);
              const uint32_t p2 = pack2(d[4 * j + 8 + 2 * h], d[4 * j + 9 + 2 * h]), p3 = pack2(d[4 * j + 12 + 2 * h], d[4 * j + 13 + 2 * h]);
              if (decltype(remote)::value)
                asm volatile("st.async.shared::cluster.mbarrier::complete_tx::bytes.v4.b32 [%0], {%1, %2, %3, %4}, [%5];"
                             ::"r"(a), "r"(p0), "r"(p1), "r"(p2), "r"(p3), "r"(peer + (wbar - sb)) : "memory");
              else
                asm volatile("st.shared.v4.b32 [%0], {%1, %2, %3, %4};" ::"r"(a), "r"(p0), "r"(p1), "r"(p2), "r"(p3) : "memory");
            }
          };
          if (own) {
            put_w(std::false_type());
            __syncwarp();
            if (lane == 0) mbar_arrive(wbar);
          } else {
            put_w(std::true_type());
          }
        } else {
          const int u = item - 1;
          const int c = lds32(xtab + 4 * u);
          const uint32_t in = sb + (c & 0x3C000);
          mbar_wait(xfull + 8 * u, 0);
          wg_fence();
#pragma unroll
          for (int k = 0; k < 4; k++)
            wgmma_rs_128<1, 1, 1>(d, fa[4 * k], fa[4 * k + 1], fa[4 * k + 2], fa[4 * k + 3], mk_desc(in, k * 2048, 6144, 1024, 1), k);
          wg_commit();
          wg_wait<0>();
          reg_fence(d);
          bar_sync(1 + wg, 128);
          const uint32_t rb = in + (warp * 16 + row) * 128, xr = (lane & 7) ^ (c & 3);
#pragma unroll
          for (int j = 0; j < 16; j += 2)
            stsm4(rb + ((j >> 2) & 1) * 8192 + ((((j >> 3) * 4 + (j & 3) + hi) ^ xr) << 4), pack2(d[4 * j], d[4 * j + 1]),
                  pack2(d[4 * j + 2], d[4 * j + 3]), pack2(d[4 * j + 4], d[4 * j + 5]), pack2(d[4 * j + 6], d[4 * j + 7]));
          fence_async();
          __syncwarp();
          if (lane == 0) mbar_arrive(xready + 8 * u);
        }
      }
#pragma unroll
      for (int i = 0; i < 4; i++) fw[i] = fa[i];
    }
    if (spare) {
      float* sg = reinterpret_cast<float*>(smem_k1 + K1_R);
      __nv_bfloat16* sw = reinterpret_cast<__nv_bfloat16*>(sg + 16 * 256);
      const int c0 = (cta - 128) * 64;
      uint4 vw[8], vg[2];
#pragma unroll
      for (int i = 0; i < 8; i++) vw[i] = __ldg(reinterpret_cast<const uint4*>(wgt + ((i * 256 + tid) >> 3) * 256 + c0 + (tid & 7) * 8));
#pragma unroll
      for (int i = 0; i < 2; i++) vg[i] = __ldg(reinterpret_cast<const uint4*>(g) + i * 256 + tid);
#pragma unroll
      for (int i = 0; i < 8; i++) reinterpret_cast<uint4*>(sw)[i * 256 + tid] = vw[i];
#pragma unroll
      for (int i = 0; i < 2; i++) {
        const uint32_t w4[4] = {vg[i].x, vg[i].y, vg[i].z, vg[i].w};
#pragma unroll
        for (int e = 0; e < 4; e++) {
          sg[(i * 256 + tid) * 8 + 2 * e] = __uint_as_float(w4[e] << 16);
          sg[(i * 256 + tid) * 8 + 2 * e + 1] = __uint_as_float(w4[e] & 0xffff0000u);
        }
      }
      bar_sync(3, 256);
      const int col = tid & 63, r0 = (tid >> 6) * 4;
      float a0 = 0.f, a1 = 0.f, a2 = 0.f, a3 = 0.f;
#pragma unroll 8
      for (int k = 0; k < 256; k++) {
        const float w = __bfloat162float(sw[k * 64 + col]);
        a0 = fmaf(sg[(r0 + 0) * 256 + k], w, a0);
        a1 = fmaf(sg[(r0 + 1) * 256 + k], w, a1);
        a2 = fmaf(sg[(r0 + 2) * 256 + k], w, a2);
        a3 = fmaf(sg[(r0 + 3) * 256 + k], w, a3);
      }
      const int cc = c0 + col;
      const int pos = (cc & ~15) + ((cc >> 1) & 3) * 4 + ((cc >> 3) & 1) * 2 + (cc & 1);
      gp_.ge[(r0 + 0) * 256 + pos] = __bfloat162float(__float2bfloat16_rn(a0));
      gp_.ge[(r0 + 1) * 256 + pos] = __bfloat162float(__float2bfloat16_rn(a1));
      gp_.ge[(r0 + 2) * 256 + pos] = __bfloat162float(__float2bfloat16_rn(a2));
      gp_.ge[(r0 + 3) * 256 + pos] = __bfloat162float(__float2bfloat16_rn(a3));
      return;
    }
    reg_fence(fw);
    mbar_wait(win, 0);
    float d[16];
    auto t_begin = [&](int it, int hh, int r) {
      if (r == 0) mbar_wait(inf0 + 8 * (it & 1), (it >> 1) & 1);
      wg_fence();
      wgmma_rs_32<1, 1, 1>(d, fw[0], fw[1], fw[2], fw[3], mk_desc(sb + K1_TIN + (it & 1) * 4096 + hh * 2048, r * 64, 0, 1024, 1), 0);
      wg_commit();
    };
    auto t_end = [&](int it, int hh, int r) {
      reg_fence(d);
      const int j = it & 1;
      if (r == 0) mbar_wait(it >= 2 ? se0 + 8 * j : bb + (m.p.last >> (5 + 8 * it) & 0x7F8), it >= 2 ? ((it >> 1) - 1) & 1 : 0);
      else if (lane == 0) mbar_arrive(ine0 + 8 * j);
      const uint32_t rb = sb + K1_T + j * 16384 + hh * 8192 + (warp * 16 + row) * 128;
#pragma unroll
      for (int i = 0; i < 2; i++)
        stsm4(rb + (((4 * r + 2 * i + hi) ^ (lane & 7)) << 4), pack2(d[8 * i], d[8 * i + 1]), pack2(d[8 * i + 2], d[8 * i + 3]),
              pack2(d[8 * i + 4], d[8 * i + 5]), pack2(d[8 * i + 6], d[8 * i + 7]));
      if (r == 1) {
        fence_async();
        __syncwarp();
        if (lane == 0) mbar_arrive(sf0 + 8 * j);
      }
    };
    float y0[NB1 / 2], y1[NB1 / 2];
    uint32_t wa[8], wb[8];
    uint32_t wp = sb + wg * 4096 + ((lane & 7) + hi * 8) * 128 + (((2 * warp + ((lane >> 3) & 1)) ^ (lane & 7)) << 4);
    const uint32_t neg = wg ? 0x80008000u : 0u;
    auto frag = [&](uint32_t (&w)[8], uint32_t a, uint32_t sg) {
      ldsm4t(a, w[0], w[1], w[2], w[3]);
      ldsm4t(a + 2048, w[4], w[5], w[6], w[7]);
#pragma unroll
      for (int i = 0; i < 8; i++) w[i] ^= sg;
    };
    auto stage = [&](const uint32_t (&w)[8], uint32_t x4, int acc) {
      wg_fence();
      wgmma_rs_168<1, 1, 0>(y0, w[0], w[1], w[2], w[3], mk_desc4(x4, 0, 512, 2), acc);
      wgmma_rs_168<1, 1, 0>(y1, w[0], w[1], w[2], w[3], mk_desc4(x4 + G_ST / 32, 0, 512, 2), acc);
      wgmma_rs_168<1, 1, 0>(y0, w[4], w[5], w[6], w[7], mk_desc4(x4 + 2, 0, 512, 2), 1);
      wgmma_rs_168<1, 1, 0>(y1, w[4], w[5], w[6], w[7], mk_desc4(x4 + G_ST / 32 + 2, 0, 512, 2), 1);
      wg_commit();
      wg_wait<1>();
    };
    frag(wa, wp, neg);
    int it = 0;
#pragma unroll 1
    for (int k = 0; k < G_KM; k++) {
      const bool T = (m.p.tmask >> (k + 16 * wg)) & 1;
      const uint32_t xa = ((sb & 0x3FFFF) >> 4) + m.slot[2 * k], xb = ((sb & 0x3FFFF) >> 4) + m.slot[2 * k + 1];
      if (T) t_begin(it, wg, 0);
      mbar_wait(gfull + 16 * k, 0);
      stage(wa, xa, k);
      frag(wb, wp ^ 4096, 0);
      if (k > 0 && lane == 0) mbar_arrive(gdone + 16 * k - 8);
      if (T) {
        t_end(it, wg, 0);
        t_begin(it, wg, 1);
      }
      mbar_wait(gfull + 16 * k + 8, 0);
      stage(wb, xb, 1);
      wp += 8192;
      if (k == W_Q - 1) {
        mbar_wait(win1, 0);
        fence_async();
      }
      frag(wa, wp, neg);
      if (lane == 0) mbar_arrive(gdone + 16 * k);
      if (T) t_end(it++, wg, 1);
    }
    auto tail = [&](float (&y)[NB1 / 2], auto batch, auto wgc) {
      constexpr int B = decltype(batch)::value, W = decltype(wgc)::value;
#pragma unroll
      for (int k = G_KM; k < 16; k++) {
        const int s = G_KM + k + G_TK * B;
        mbar_wait(gfull + 8 * s, 0);
        constexpr int xos[8] = {g_off(g_slot(24)), g_off(g_slot(25)), g_off(g_slot(26)), g_off(g_slot(27)),
                                g_off(g_slot(28)), g_off(g_slot(29)), g_off(g_slot(30)), g_off(g_slot(31))};
        const int xo = xos[s - 24];
        wg_fence();
#pragma unroll
        for (int h = 0; h < 4; h++) {
          const uint64_t dW = mk_desc(sb, k * 8192 + ((h >> 1) ^ W) * 4096 + (h & 1) * 2048, 0, 1024, 1);
          const uint64_t dX = mk_desc(sb, xo + (h >> 1) * (G_ST / 2) + (h & 1) * 32, 0, 512, 2);
          if (W == 1 && h < 2) wgmma_ss_168<-1, 1, 1, 0>(y, dW, dX, 1);
          else wgmma_ss_168<1, 1, 1, 0>(y, dW, dX, 1);
        }
        if (s <= 26) {
          wg_commit();
          if (W == 0 || k > G_KM) {
            wg_wait<1>();
            if (lane == 0) mbar_arrive(gdone + 8 * (s - 1));
          }
        }
      }
      wg_commit();
    };
    constexpr std::integral_constant<int, 0> c0;
    constexpr std::integral_constant<int, 1> c1;
    auto put = [&](const float (&v)[NB1 / 2], uint32_t stg, int b) {
      const int mi = lane >> 3, i = lane & 7;
      const uint32_t a0 = stg + (mi >> 1) * 1024 + i * 128 + (((2 * warp + (mi & 1)) ^ i) << 4);
      constexpr int J = 21 / G_EPI;
#pragma unroll
      for (int c = 0; c < G_EPI; c++) {
#pragma unroll
        for (int j = c * J; j + 1 < (c + 1) * J; j += 2)
          stsm4t(a0 + j * 1024, pack2(v[4 * j], v[4 * j + 1]), pack2(v[4 * j + 2], v[4 * j + 3]),
                 pack2(v[4 * j + 4], v[4 * j + 5]), pack2(v[4 * j + 6], v[4 * j + 7]));
        const int j = (c + 1) * J - 1;
        asm volatile("stmatrix.sync.aligned.m8n8.x2.trans.shared.b16 [%0], {%1, %2};" ::"r"(a0 + j * 1024),
                     "r"(pack2(v[4 * j], v[4 * j + 1])), "r"(pack2(v[4 * j + 2], v[4 * j + 3])) : "memory");
        fence_async();
        bar_sync(1 + wg, 128);
        if (t == 0) {
          tma_st4<0>(&m.y, stg + c * J * 1024, 0, b * NB1 + c * J * 8, 2 * bin + wg, dc);
          bulk_commit();
        }
      }
    };
    if (wg == 0) {
      tail(y0, c0, c0);
      bar_arrive(4, 256);
      mbar_wait(gdone + 8 * (G_S0 - 1), 0);
      wg_wait<0>();
      reg_fence(y0);
      put(y0, sb + K1_Y0, 0);
      bar_sync(7, 256);
      tail(y1, c1, c0);
      bar_arrive(8, 256);
      if (t == 0) bulk_wait_read<0>();
      wg_wait<0>();
      reg_fence(y1);
      bar_sync(1, 128);
      put(y1, sb + K1_Y0, 1);
    } else {
      wg_wait<0>();
      if (lane == 0) mbar_arrive(gdone + 8 * (G_S0 - 1));
#pragma unroll 1
      for (int h2 = 2 * it; h2 < 16; h2++) {
#pragma unroll
        for (int r = 0; r < 2; r++) {
          t_begin(h2 >> 1, h2 & 1, r);
          wg_wait<0>();
          t_end(h2 >> 1, h2 & 1, r);
        }
      }
      bar_sync(4, 256);
      tail(y0, c0, c1);
      bar_arrive(7, 256);
      mbar_wait(se0, 1);
      mbar_wait(se0 + 8, 1);
      wg_wait<0>();
      reg_fence(y0);
      put(y0, sb + K1_T, 0);
      bar_sync(8, 256);
      tail(y1, c1, c1);
      wg_wait<0>();
      reg_fence(y1);
      put(y1, sb + std::integral_constant<int, g_off(g_slot(26))>::value, 1);
    }
    if (t == 0) {
      bulk_wait_read<0>();
    }
  }
}

#define H_EPI 3
#define H_KS 11
#define C_PC 32
constexpr int H_XP = 168 * 64, H_STAGE = 8192 + 2 * H_XP, H_NST = 7, K2_STG = H_NST * H_STAGE, K2_SMEM = K2_STG + 21504 + 1024;

template <int WG>
__device__ __forceinline__ void h_loop(float (&acc)[84], uint32_t sb, uint32_t full0, uint32_t empty0, int lane) {
#pragma unroll 1
  for (int k = 0; k < 16; k++) {
    const int st = k % H_NST;
    if (WG == 1 && k == H_KS) bar_sync(5, 256);
    mbar_wait(full0 + 8 * st, (k / H_NST) & 1);
    const uint32_t base = sb + st * H_STAGE;
    wg_fence();
#pragma unroll
    for (int s = 0; s < 2; s++) {
      const uint64_t dP = mk_desc(base, s * 2048, 0, 1024, 1), dQ = mk_desc(base, 4096 + s * 2048, 0, 1024, 1);
      const uint64_t dA = mk_desc(base, 8192 + s * 32, 0, 1024, 1), dB = mk_desc(base, 8192 + 64 + s * 32, 0, 1024, 1);
      wgmma_ss_168<1, 1, 1, 0>(acc, dP, WG == 0 ? dA : dB, k | s);
      wgmma_ss_168<WG == 0 ? 1 : -1, 1, 1, 0>(acc, dQ, WG == 0 ? dB : dA, 1);
    }
    wg_commit();
    if (WG == 0 && k == 15) bar_arrive(5, 256);
    if (k <= 10) {
      wg_wait<1>();
      if (k > 0 && k - 1 + H_NST < 16 && lane < 2) mbar_arrive_cta(empty0 + 8 * ((k - 1) % H_NST), lane);
    }
  }
  wg_wait<0>();
  reg_fence(acc);
}
template <int C0, int C1> __device__ __forceinline__ void gelu_pack(uint32_t (&p)[12], const float (&h)[24]) {
#pragma unroll
  for (int i = 4 * C0; i < 4 * C1; i++) p[i] = pack2(gelu(h[2 * i]), gelu(h[2 * i + 1]));
}
struct K2Maps {
  int stage[16], item[8], wpre, pad[7];
  CUtensorMap y, xa, xs, w, y2;
};

__global__ void __cluster_dims__(2, 1, 1) __launch_bounds__(512, 1)
k2(const Ptrs gp_, const char* __restrict__ x2, const __grid_constant__ K2Maps m, const __nv_bfloat16* __restrict__ wf,
   const __nv_bfloat16* __restrict__ wo) {
  extern __shared__ __align__(1024) uint8_t smem_k1[];
  const uint32_t sb = s2u(smem_k1);
  const int tid = threadIdx.x, wg = __shfl_sync(0xffffffffu, tid >> 7, 0), t = tid & 127;
  const int warp = __shfl_sync(0xffffffffu, t >> 5, 0), lane = t & 31;
  const int cta = blockIdx.x, rank = cta & 1, dc = cta & 3, bin = cta >> 2;
  const uint32_t sGi = sb + K2_STG, sF = sGi + 6144, bb = sb + K2_STG + 21504;
  const uint32_t yfull = bb, full0 = bb + 128, empty0 = bb + 192, cfull = bb + 256, ready = bb + 320, bfree = bb + 384;
  const int b = cta & 1, j = cta >> 2;
  const int len0 = j < 20 ? 3 : 2, len1 = j >= 12 ? 3 : 2;
  const int n00 = j < 20 ? 3 * j : 2 * j + 20, n01 = j < 12 ? 2 * j : 3 * j - 12, cs0 = 3 - (cta >> 1 & 1);
  auto y_load = [&](int r, int i) {
    tma_ld5<1>(sb + (3 + 2 * r) * H_STAGE + i * 8192, &m.y, yfull + 64 * r + 8 * i, 0, 0, cs0 - 2 * r, 2 * (r ? n01 : n00) + i, b);
  };
  if (wg == 2 && warp == 0) {
    if (lane == 0) {
      prefetch_map(&m.y);
      for (int i = 0; i < 16; i++) mbar_init(yfull + 8 * i, 1);
      fence_bar_init();
    }
    __syncwarp();
    if (lane < 16) mbar_expect(yfull + 8 * lane, lane == 7 ? 6144 : 8192);
    bar_arrive(0, 512);
    asm volatile("barrier.cluster.arrive.relaxed.aligned;" ::: "memory");
    auto c_load = [&](int h) {
      asm volatile("cp.async.bulk.shared::cluster.global.mbarrier::complete_tx::bytes [%0], [%1], %2, [%3];"
                   ::"r"(sGi + 6144 * h), "l"(gp_.img + 1536 * h), "r"(6144 + 2048 * h), "r"(yfull + 56 + 64 * h) : "memory");
    };
    if (lane == 0) {
      c_load(0);
      c_load(1);
      pdl_wait();
      const int r2 = len0 == 2, i2 = r2 ? 2 : 6;
      y_load(0, 2), y_load(0, 0), y_load(0, 1), y_load(1, 0), y_load(0, 4), y_load(0, 3), y_load(r2, i2), y_load(r2, i2 - 1);
      pdl_launch();
    }
    __syncwarp();
  } else {
    if (lane == 0 && wg == 3) {
      for (int i = 0; i < 8; i++) mbar_init(full0 + 64 * warp + 8 * i, warp == 0 ? 1 : warp == 1 ? 16 : 4);
      fence_bar_init();
    }
    if (tid == 0) {
      mbar_init(bfree, 2);
      for (int i = 1; i < 5; i++) mbar_init(bfree + 8 * i, 1);
      mbar_arrive(bfree + 8);
      fence_bar_init();
    }
    if (tid == 128) {
      prefetch_map(&m.xa);
      prefetch_map(&m.xs);
      prefetch_map(&m.w);
      prefetch_map(&m.y2);
    }
    bar_sync(0, 512);
    asm volatile("barrier.cluster.arrive.relaxed.aligned;" ::: "memory");
  }
  if (wg == 2) asm volatile("barrier.cluster.wait.aligned;" ::: "memory");
  mbar_wait(yfull + 56, 0);
  auto idft = [&](float (&h)[24], uint32_t in, uint32_t bar) {
    mbar_wait(bar, 0);
    wg_fence();
#pragma unroll
    for (int k = 0; k < 4; k++) wgmma_ss_48<1, 1, 1, 0>(h, mk_desc(in, k * 2048, 0, 1024, 1), mk_desc(sGi, k * 32, 0, 1024, 1), k);
    wg_commit();
  };
  auto carry_out = [&](const uint32_t (&p)[12], uint32_t dst, uint32_t bar) {
    bar_sync(1 + wg, 128);
#pragma unroll
    for (int v = 0; v < 3; v++)
      asm volatile("st.shared.v4.b32 [%0], {%1, %2, %3, %4};" ::"r"(dst + v * 2048 + t * 16), "r"(p[4 * v]), "r"(p[4 * v + 1]), "r"(p[4 * v + 2]), "r"(p[4 * v + 3]) : "memory");
    __syncwarp();
    if (lane == 0) mbar_arrive(bar);
  };
  if (wg == 3) {
#pragma unroll 1
    for (int r = 0; r < 2; r++) {
      float h[24];
      uint32_t p[12];
      idft(h, sb + (3 + 2 * r) * H_STAGE, yfull + 64 * r);
      wg_wait<0>();
      reg_fence(h);
      gelu_pack<0, 3>(p, h);
      if (j == 0) p[0] = p[1] = p[2] = p[3] = 0;
      carry_out(p, sb + (3 + 2 * r) * H_STAGE, cfull + 32 * r);
    }
    asm volatile("barrier.cluster.wait.aligned;" ::: "memory");
    if (lane == 0) {
      if (warp == 0) {
        auto w_load = [&](int k) {
          mbar_expect(full0 + 8 * (k % H_NST), H_STAGE);
          tma_ld4<1>(sb + (k % H_NST) * H_STAGE, &m.w, full0 + 8 * (k % H_NST), 0, (k & 1) * 32, dc, (7 - (k >> 1)) * 64 + 2 * bin);
        };
        const int wpre = m.wpre;
        for (int k = 0; k < wpre; k++) w_load(k);
#pragma unroll 1
        for (int k = 0; k < 16; k++) {
          const int st = k % H_NST, e = m.stage[k];
          if ((k & 7) == 0) {
            poll_ge(&gp_.done[(6 + (k >> 3)) * 32], 128);
            asm volatile("fence.proxy.async.global;" ::: "memory");
            if (k == 0) mbar_arrive(bfree + 32);
          }
          if (e) mbar_wait(bb + 8 * e, 0);
          if (k == 5) mbar_wait(bfree, 0);
          if (k >= H_NST) mbar_wait(empty0 + 8 * st, ((k / H_NST) - 1) & 1);
          const char* xs = x2 + (((7 - (k >> 2) - (k & 2) * 2) * 64 + (k & 1) * 32 + bin) * 2 + rank) * H_XP;
          asm volatile("cp.async.bulk.shared::cluster.global.mbarrier::complete_tx::bytes.multicast::cluster [%0], [%1], %2, [%3], %4;"
                       ::"r"(sb + st * H_STAGE + 8192 + rank * H_XP), "l"(xs), "n"(H_XP), "r"(full0 + 8 * st), "h"((uint16_t)3) : "memory");
          if (k >= wpre) w_load(k);
          if (k == 8) {
            if (cta == 0) asm volatile("cp.async.bulk.prefetch.L2.global [%0], 6144;" ::"l"(gp_.ga) : "memory");
            asm volatile("cp.async.bulk.prefetch.L2.global [%0], 1024;" ::"l"(wf + cta * 512) : "memory");
            asm volatile("cp.async.bulk.prefetch.L2.global [%0], 1024;" ::"l"(wo + cta * 512) : "memory");
          }
        }
      } else if (warp < 3) {
        const int r = warp - 1, n0 = b * NB2 + (r ? n01 : n00), f0 = (cs0 - 2 * r) * 64;
#pragma unroll 1
        for (int i = 0; i < (r ? len1 : len0); i++) {
          const uint32_t src = sb + (3 + 2 * r) * H_STAGE + i * 16384;
          const int e = m.item[4 * r + i], burst = (16 << (e >> 8)) - 1;
          if (r) mbar_wait(bb + 8 * (e & 255), 0);
          mbar_wait(ready + 32 * r + 8 * i, 0);
          if (!r) {
            tma_st4<0>(&m.xa, src, 0, f0, 0, n0 + i);
            bulk_commit();
            continue;
          }
#pragma unroll 1
          for (int p = 0; p < 128; p += C_PC) {
            tma_st3<0>(&m.xs, src + p * 128, 0, f0 + (p & 63) + (p >> 6) * 256, n0 + i);
            bulk_commit();
            if (((p + C_PC) & burst) == 0) bulk_wait_read<0>();
          }
        }
        asm volatile("cp.async.bulk.wait_group 0;" ::: "memory");
        if (r) {
          mbar_arrive_cta(bfree, 0);
          mbar_arrive_cta(bfree, 1);
        }
        if (!r) mbar_arrive(bfree + 16);
        asm volatile("red.release.gpu.global.add.s32 [%0], 1;" ::"l"(&gp_.done[(6 + r) * 32]) : "memory");
        if (!r) mbar_arrive(bfree + 24);
      }
    }
    return;
  }
#pragma unroll 1
  for (int it = wg; it < len0 + len1; it += 3) {
    const int r = it >= len0, i = it - r * len0;
    const bool last = i + 1 == (r ? len1 : len0);
    const uint32_t in = sb + (3 + 2 * r) * H_STAGE + i * 16384, bar = yfull + 64 * r + 16 * i;
    float h1[24], h2[24];
    uint32_t p0[12], p1[12], p2[12];
    idft(h2, in + 16384, bar + 16);
    if (it == 2 && lane == 0 && 3 + warp - len0 < len1) {
      y_load(1, 2 * (3 + warp - len0) + 2);
      y_load(1, 2 * (3 + warp - len0) + 1);
    }
    if (it > 0) bar_sync(6 + wg, 256);
    wg_wait<0>();
    reg_fence(h2);
    gelu_pack<0, 2>(p2, h2);
    idft(h1, in + 8192, bar + 8);
    if (!last) {
      gelu_pack<2, 3>(p2, h2);
      carry_out(p2, in + 16384, cfull + 32 * r + 8 * i + 8);
    }
    if (it + 1 < len0 + len1) bar_arrive(6 + (wg + 1) % 3, 256);
    mbar_wait(cfull + 32 * r + 8 * i, 0);
#pragma unroll
    for (int v = 0; v < 3; v++)
      asm volatile("ld.shared.v4.b32 {%0, %1, %2, %3}, [%4];" : "=r"(p0[4 * v]), "=r"(p0[4 * v + 1]), "=r"(p0[4 * v + 2]), "=r"(p0[4 * v + 3]) : "r"(in + v * 2048 + t * 16) : "memory");
    if (it < 3) mbar_wait(yfull + 120, 0);
    wg_wait<0>();
    reg_fence(h1);
    gelu_pack<0, 3>(p1, h1);
    if (last && j == 31) {
#pragma unroll
      for (int v = 0; v < 12; v++) p1[v] = p2[v] = 0;
    }
    uint32_t hp[32];
#pragma unroll
    for (int c = 0; c < 8; c++)
#pragma unroll
      for (int v = 0; v < 4; v++) hp[(v >> 1) * 16 + 2 * c + (v & 1)] = c < 3 ? p0[4 * c + v] : c < 6 ? p1[4 * (c - 3) + v] : p2[4 * (c - 6) + v];
    float e0[32], e1[32];
    reg_fence(hp);
    wg_fence();
#pragma unroll
    for (int k = 0; k < 4; k++) {
      const uint64_t db = mk_desc(sF, k * 32, 0, 1024, 1);
      wgmma_rs_64<1, 1, 0>(e0, hp[4 * k], hp[4 * k + 1], hp[4 * k + 2], hp[4 * k + 3], db, k);
      wgmma_rs_64<1, 1, 0>(e1, hp[16 + 4 * k], hp[16 + 4 * k + 1], hp[16 + 4 * k + 2], hp[16 + 4 * k + 3], db, k);
    }
    wg_commit();
    bar_sync(1 + wg, 128);
    wg_wait<0>();
    reg_fence(e0);
    reg_fence(e1);
    {
      const int mi = lane >> 3, rr = (lane & 7) >> 1, blk = b * NB2 + (r ? n01 : n00) + i;
      const uint32_t a0 = in + (mi >> 1) * 8192 + (warp >> 1) * 4096 + rr * 128;
      const uint32_t pos = ((lane & 1) * 4 + (warp & 1) * 2 + (mi & 1)) ^ rr ^ (blk & 7);
#pragma unroll
      for (int q = 0; q < 8; q++)
        stsm4t(a0 + q * 512 + ((pos ^ (q & 1) * 4) << 4), pack2(e0[4 * q], e0[4 * q + 1]), pack2(e0[4 * q + 2], e0[4 * q + 3]),
               pack2(e1[4 * q], e1[4 * q + 1]), pack2(e1[4 * q + 2], e1[4 * q + 3]));
    }
    fence_async();
    __syncwarp();
    if (lane == 0) mbar_arrive(ready + 32 * r + 8 * i);
  }
  if (wg == 2) return;
  asm volatile("barrier.cluster.wait.aligned;" ::: "memory");
  float acc[84];
  if (wg == 0) {
    h_loop<0>(acc, sb, full0, empty0, lane);
  } else {
    h_loop<1>(acc, sb, full0, empty0, lane);
    bar_sync(2, 128);
  }
  const uint32_t stg = sb + (wg == 0 ? H_NST : 9 % H_NST) * H_STAGE;
  const int mi = lane >> 3, i = lane & 7;
  const uint32_t a0 = stg + (mi >> 1) * 1024 + i * 128 + (((2 * warp + (mi & 1)) ^ i) << 4);
  constexpr int J = 21 / H_EPI;
#pragma unroll
  for (int c = 0; c < H_EPI; c++) {
#pragma unroll
    for (int q = c * J; q + 1 < (c + 1) * J; q += 2)
      stsm4t(a0 + q * 1024, pack2(acc[4 * q], acc[4 * q + 1]), pack2(acc[4 * q + 2], acc[4 * q + 3]),
             pack2(acc[4 * q + 4], acc[4 * q + 5]), pack2(acc[4 * q + 6], acc[4 * q + 7]));
    const int q = (c + 1) * J - 1;
    asm volatile("stmatrix.sync.aligned.m8n8.x2.trans.shared.b16 [%0], {%1, %2};" ::"r"(a0 + q * 1024),
                 "r"(pack2(acc[4 * q], acc[4 * q + 1])), "r"(pack2(acc[4 * q + 2], acc[4 * q + 3])) : "memory");
    fence_async();
    bar_sync(1 + wg, 128);
    if (t == 0) {
      tma_st4<0>(&m.y2, stg + c * J * 1024, 0, c * J * 8, 2 * bin + wg, dc);
      bulk_commit();
    }
  }
  if (t == 0) {
    bulk_wait_read<0>();
  }
}

#define E_I1 12
#define E_WAITS 0xA8
#define E_EARLY0 5
#define E_EARLY 5
constexpr int E_SMEM = 65536 + 131072 + 32768 + 1024;

__device__ __forceinline__ uint32_t joint2(uint32_t fe, uint32_t g0, uint32_t g1) {
  uint32_t s0, s1;
  asm("{\n.reg .b16 l, h;\n.reg .b32 ll, hh;\nmov.b32 {l, h}, %2;\nmov.b32 ll, {l, l};\nmov.b32 hh, {h, h};\n"
      "fma.rn.bf16x2 %0, ll, %5, %3;\nfma.rn.bf16x2 %1, hh, %5, %4;\n}"
      : "=r"(s0), "=r"(s1) : "r"(fe), "r"(g0), "r"(g1), "r"(0x3F800000u));
  return pack2(tanh_f32(__uint_as_float(s0)), tanh_f32(__uint_as_float(s1)));
}
__device__ __forceinline__ uint4 lds128(uint32_t a) {
  uint4 v;
  asm volatile("ld.shared.v4.u32 {%0, %1, %2, %3}, [%4];" : "=r"(v.x), "=r"(v.y), "=r"(v.z), "=r"(v.w) : "r"(a));
  return v;
}
__device__ __forceinline__ void joint_group(uint32_t (&ja)[8], const uint32_t* fe, const uint4& c0, const uint4& c1) {
  ja[0] = joint2(fe[0], c0.x, c0.y);
  ja[1] = joint2(fe[1], c0.x, c0.y);
  ja[2] = joint2(fe[2], c0.z, c0.w);
  ja[3] = joint2(fe[3], c0.z, c0.w);
  ja[4] = joint2(fe[4], c1.x, c1.y);
  ja[5] = joint2(fe[5], c1.x, c1.y);
  ja[6] = joint2(fe[6], c1.z, c1.w);
  ja[7] = joint2(fe[7], c1.z, c1.w);
  reg_fence(ja);
}

__global__ void __cluster_dims__(2, 1, 1) __launch_bounds__(256, 1)
kE(const __grid_constant__ CUtensorMap my, const __grid_constant__ CUtensorMap mwf, const __grid_constant__ CUtensorMap mwo,
   const __grid_constant__ CUtensorMap mout) {
  const Ptrs gp_ = {g_done, g_ge, c_img, c_ga};
  extern __shared__ uint8_t smem_raw[];
  __shared__ __align__(8) uint64_t bars[17];
  const uint32_t sb = (s2u(smem_raw) + 1023) & ~1023u;
  const int tid = threadIdx.x, wg = __shfl_sync(0xffffffffu, tid >> 7, 0), t = tid & 127, warp = t >> 5, lane = t & 31;
  const uint32_t R0 = sb, R1 = sb + 65536, R2 = sb + 65536 + 131072;
  const uint32_t barY = s2u(&bars[0]), barO = barY + 32, barF = barY + 64, barA = barY + 128;
  const int b = blockIdx.x / 63, t0 = (blockIdx.x % 63) * 64;
  const int a = t0 / 48, o = t0 % 48;
  const int qw = o + 16 * warp, sel = qw >= 48;
  uint32_t ga[16];
#pragma unroll
  for (int s = 0; s < 4; s++)
    ldg128(reinterpret_cast<const uint4*>(gp_.ga) + ((qw >> 4) - 3 * sel) * 128 + s * 32 + lane, ga[4 * s], ga[4 * s + 1], ga[4 * s + 2], ga[4 * s + 3]);
  uint4 gev0, gev1;
  asm volatile("ld.global.cg.v4.u32 {%0, %1, %2, %3}, [%4];" : "=r"(gev0.x), "=r"(gev0.y), "=r"(gev0.z), "=r"(gev0.w)
               : "l"(reinterpret_cast<const uint4*>(gp_.ge) + (b * 8 + wg * 4) * 64 + t));
  asm volatile("ld.global.cg.v4.u32 {%0, %1, %2, %3}, [%4];" : "=r"(gev1.x), "=r"(gev1.y), "=r"(gev1.z), "=r"(gev1.w)
               : "l"(reinterpret_cast<const uint4*>(gp_.ge) + (b * 8 + wg * 4) * 64 + 128 + t));
  auto f_load = [&](int q) {
    const int p = (0x37156240 >> (4 * q)) & 7;
    mbar_expect(barF + 8 * p, 16384);
    tma_ld3<0>(R1 + p * 16384, &mwf, barF + 8 * p, 0, (p >> 1) * 64, (p & 1) * 2);
  };
  if (tid == 0) {
    prefetch_map(&my);
    for (int i = 0; i < 16; i++) mbar_init(barY + 8 * i, 1);
    mbar_init(barA, 8);
    fence_bar_init();
    prefetch_map(&mwf);
    pdl_wait();
    for (int i = 0; i < 4; i++) {
      mbar_expect(barY + 8 * i, 16384);
      tma_ld5<0>(R0 + i * 16384, &my, barY + 8 * i, 0, 0, 2 * (i & 1) + (i >> 1), a, b);
    }
    for (int q = 0; q < 4; q++) f_load(q);
  }
  if (tid == 64) {
    prefetch_map(&mwo);
    prefetch_map(&mout);
  }
  uint32_t gs[32];
#pragma unroll
  for (int i = 0; i < 16; i++) {
    gs[i] = sel ? 0u : ga[i];
    gs[16 + i] = sel ? ga[i] : 0u;
  }
  __syncthreads();
  if (blockIdx.x == 125 && tid < 8) gp_.done[tid * 32] = 0;
  reg_fence(gs);
  uint32_t gp = R2 + 16384 + wg * 4096 + (lane & 3) * 16;
  uint4 g0, g1;
  uint32_t fe[64];
  {
    float d0[32], d1[32], e[64];
    mbar_wait(barY + 8 * wg, 0);
    wg_fence();
#pragma unroll
    for (int k = 0; k < 8; k++)
      wgmma_rs_64<1, 1, 1>(d0, gs[4 * k], gs[4 * k + 1], gs[4 * k + 2], gs[4 * k + 3], mk_desc(R0 + wg * 16384, k * 2048, 0, 1024, 1), k);
    wg_commit();
    if (tid == 0)
      for (int q = 4; q < 8; q++) f_load(q);
    wg_wait<0>();
    reg_fence(d0);
    uint32_t p0[16], p1[16];
    const uint32_t wfo = R1 + wg * (65536 + 16384), wfx = R1 + 65536 - wg * (65536 - 16384), fx = R2 + 16384 - wg * 16384;
    const uint32_t fo = R2 + wg * 16384 + (warp * 16 + (lane & 7) + ((lane >> 3) & 1) * 8) * 128;
    auto fe_own = [&](const uint32_t (&p)[16], int c) {
      wg_fence();
#pragma unroll
      for (int s = 0; s < 4; s++)
        wgmma_rs_128<1, 1, 1>(e, p[4 * s], p[4 * s + 1], p[4 * s + 2], p[4 * s + 3], mk_desc(wfo, c * 32768 + s * 2048, 8192, 1024, 1), c | s);
    };
    auto fe_other = [&](int c) {
      wg_fence();
#pragma unroll
      for (int s = 0; s < 4; s++)
        wgmma_ss_128<1, 1, 0, 1>(e, mk_desc(fx, c * 8192 + s * 32, 0, 1024, 1), mk_desc(wfx, c * 32768 + s * 2048, 8192, 1024, 1), 1);
    };
    auto f_store = [&](const uint32_t (&p)[16], int c) {
#pragma unroll
      for (int s = 0; s < 4; s++) stsm4(fo + c * 8192 + (((2 * s + (lane >> 4)) ^ (lane & 7)) << 4), p[4 * s], p[4 * s + 1], p[4 * s + 2], p[4 * s + 3]);
    };
#pragma unroll
    for (int i = 0; i < E_I1; i++) p0[i] = pack2(gelu(d0[2 * i]), gelu(d0[2 * i + 1]));
    mbar_wait(barY + 8 * (2 + wg), 0);
    wg_fence();
#pragma unroll
    for (int k = 0; k < 8; k++)
      wgmma_rs_64<1, 1, 1>(d1, gs[4 * k], gs[4 * k + 1], gs[4 * k + 2], gs[4 * k + 3], mk_desc(R0 + wg * 16384, 32768 + k * 2048, 0, 1024, 1), k);
    wg_commit();
#pragma unroll
    for (int i = E_I1; i < 16; i++) p0[i] = pack2(gelu(d0[2 * i]), gelu(d0[2 * i + 1]));
    reg_fence(p0);
    f_store(p0, 0);
    const uint32_t bfo = barF + 40 * wg, bfx = barF + 32 - 24 * wg;
    auto o_load = [&](int kc) {
      mbar_expect(barO + 8 * kc, 32768);
      tma_ld3<0>(kc < 2 ? R0 + kc * 32768 : R1 + (kc - 2) * 65536, &mwo, barO + 8 * kc, 0, kc * 64, 0);
    };
    wg_wait<0>();
    reg_fence(d1);
    if (wg == 1) {
      fence_async();
      bar_arrive(8, 256);
    }
#pragma unroll
    for (int i = 0; i < 16; i++) p1[i] = pack2(gelu(d1[2 * i]), gelu(d1[2 * i + 1]));
    reg_fence(p1);
    if (wg == 0) {
      mbar_wait(bfo, 0);
      fe_own(p0, 0);
      mbar_wait(bfx, 0);
      bar_sync(8, 256);
      fe_other(0);
      wg_commit();
      if (t == 0) {
        o_load(0);
        o_load(1);
      }
      f_store(p1, 1);
      mbar_wait(bfo + 16, 0);
      fe_own(p1, 1);
      fence_async();
      mbar_wait(bfx + 16, 0);
      bar_sync(7, 256);
      fe_other(1);
      wg_commit();
      bar_arrive(4, 256);
      wg_wait<1>();
      if (lane == 0) mbar_arrive(barA);
      bar_sync(1, 128);
    } else {
      f_store(p1, 1);
      fence_async();
      bar_arrive(7, 256);
      mbar_wait(bfo, 0);
      mbar_wait(bfx, 0);
      bar_sync(4, 256);
      fe_own(p0, 0);
      fe_other(0);
      wg_commit();
      mbar_wait(bfo + 16, 0);
      mbar_wait(bfx + 16, 0);
      fe_own(p1, 1);
      wg_commit();
      wg_wait<1>();
      if (lane == 0) mbar_arrive(barA);
      fe_other(1);
      wg_commit();
      mbar_wait(barA, 0);
      if (t == 0) {
        o_load(2);
        o_load(3);
      }
    }
    asm volatile("st.shared.v4.u32 [%0], {%1, %2, %3, %4};" ::"r"(R2 + 16384 + wg * 4096 + ((t * 16) ^ (wg * 512))), "r"(gev0.x), "r"(gev0.y), "r"(gev0.z), "r"(gev0.w) : "memory");
    asm volatile("st.shared.v4.u32 [%0], {%1, %2, %3, %4};" ::"r"(R2 + 16384 + wg * 4096 + 2048 + ((t * 16) ^ (wg * 512))), "r"(gev1.x), "r"(gev1.y), "r"(gev1.z), "r"(gev1.w) : "memory");
    bar_sync(1 + wg, 128);
    g0 = lds128(gp);
    g1 = lds128(gp + 64);
    wg_wait<0>();
    reg_fence(e);
#pragma unroll
    for (int i = 0; i < 32; i++) fe[i] = pack2(e[2 * i], e[2 * i + 1]);
  }
  auto publish = [&]() {
    bar_sync(1 + wg, 128);
    const int row = warp * 16 + (lane & 7) + ((lane >> 3) & 1) * 8;
    const uint32_t xb = R1 + (wg == 0 ? 3 * 32768 : 32768 + 16384) + row * 128;
#pragma unroll
    for (int s = 0; s < 8; s++) {
      const int jj = 2 * s + (lane >> 4);
      stsm4(xb + (s >> 2) * 8192 + (((jj & 7) ^ (lane & 7)) << 4), fe[4 * s], fe[4 * s + 1], fe[4 * s + 2], fe[4 * s + 3]);
    }
    bar_arrive(5 + wg, 256);
  };
  if (wg == 1) publish();
  const uint32_t stg = R1 + 32768 + wg * 65536;
  const uint32_t w0 = sb + wg * 65536, w1 = sb + 32768 + wg * 98304, w2 = sb + 65536 - wg * 65536, w3 = sb + 131072 - wg * 98304;
  float acc[128];
  uint32_t j0[8], j1[8], j2[8], j3[8];
  uint4 h0 = lds128(gp + 128), h1 = lds128(gp + 192);
  const uint32_t bo0 = barO + 16 * wg, bo2 = barO + 16 * (1 - wg);
  joint_group(j0, fe, g0, g1);
  g0 = lds128(gp + 256);
  g1 = lds128(gp + 320);
  mbar_wait(barY, 0);
  joint_group(j1, fe + 8, h0, h1);
#define E_MMA2(J, W, OFF, FIRSTK)                                                                       \
  wgmma_rs_256<1, 1, 1>(acc, J[0], J[1], J[2], J[3], mk_desc(W, OFF, 8192, 1024, 1), FIRSTK);           \
  wgmma_rs_256<1, 1, 1>(acc, J[4], J[5], J[6], J[7], mk_desc(W, (OFF) + 2048, 8192, 1024, 1), 1);
#define E_TOKEN(N) \
  if ((ui + wg == 0 ? E_EARLY0 : E_EARLY) == (N) && (ui < 3 || wg == 0)) bar_arrive(4 - wg, 256);
#define E_BLOCK(N, J, W, BAR, JN, C0, C1, L0, L1)     \
  L0 = lds128(gp + 128 * (N) + 256);                  \
  L1 = lds128(gp + 128 * (N) + 320);                  \
  E_TOKEN((N) - 1)                                    \
  if (ui == 0) mbar_wait(BAR, 0);                     \
  if (E_WAITS >> (N) & 1) wg_wait<1>();               \
  wg_fence();                                         \
  E_MMA2(J, W, ((N) & 1) * 4096, 1)                   \
  wg_commit();                                        \
  if ((N) < 7) joint_group(JN, fe + 8 * (((N) + 1) & 7), C0, C1);
#pragma unroll 1
  for (int ui = 0; ui < 4; ui++) {
    h0 = lds128(gp + 384);
    h1 = lds128(gp + 448);
    if (ui == 0) mbar_wait(bo0, 0);
    if (ui > 0 || wg == 1) bar_sync(3 + wg, 256);
    wg_fence();
    E_MMA2(j0, w0, 0, 0)
    E_MMA2(j1, w0, 4096, 1)
    wg_commit();
    joint_group(j2, fe + 16, g0, g1);
    E_BLOCK(2, j2, w1, bo0 + 8, j3, h0, h1, g0, g1)
    if (ui == 0) {
      if (wg == 0) publish();
      bar_sync(6 - wg, 256);
      const int row = warp * 16 + (lane & 7) + ((lane >> 3) & 1) * 8;
      const uint32_t xb = R1 + (wg == 1 ? 3 * 32768 : 32768 + 16384) + row * 128;
#pragma unroll
      for (int s = 0; s < 8; s++) {
        const int jj = 2 * s + (lane >> 4);
        ldsm4(xb + (s >> 2) * 8192 + (((jj & 7) ^ (lane & 7)) << 4), fe[32 + 4 * s], fe[33 + 4 * s], fe[34 + 4 * s], fe[35 + 4 * s]);
      }
    }
    E_BLOCK(3, j3, w1, bo0 + 8, j0, g0, g1, h0, h1)
    E_BLOCK(4, j0, w2, bo2, j1, h0, h1, g0, g1)
    E_BLOCK(5, j1, w2, bo2, j2, g0, g1, h0, h1)
    E_BLOCK(6, j2, w3, bo2 + 8, j3, h0, h1, g0, g1)
    E_BLOCK(7, j3, w3, bo2 + 8, j0, g0, g1, h0, h1)
    gp += 1024;
    if (ui < 3) {
      joint_group(j0, fe, g0, g1);
      g0 = lds128(gp + 256);
      g1 = lds128(gp + 320);
      if (ui == 0) mbar_wait(bo2 + 8, 0);
      joint_group(j1, fe + 8, h0, h1);
    }
    if (t == 0) bulk_wait_read<0>();
    bar_sync(1 + wg, 128);
    wg_wait<0>();
    reg_fence(acc);
    const uint32_t rb = stg + (warp * 16 + (lane & 7) + ((lane >> 3) & 1) * 8) * 128;
#pragma unroll
    for (int h = 0; h < 2; h++) {
#pragma unroll
      for (int j = 16 * h; j < 16 * h + 16; j += 2) {
        const int jj = j + (lane >> 4);
        stsm4(rb + (j >> 3) * 8192 + (((jj & 7) ^ (lane & 7)) << 4), pack2(acc[4 * j], acc[4 * j + 1]), pack2(acc[4 * j + 2], acc[4 * j + 3]),
              pack2(acc[4 * j + 4], acc[4 * j + 5]), pack2(acc[4 * j + 6], acc[4 * j + 7]));
      }
      fence_async();
      bar_sync(1 + wg, 128);
      if (t == 0) {
        tma_st5<1>(&mout, stg + h * 16384, 0, t0, 2 * h, wg * 4 + ui, b);
        bulk_commit();
      }
    }
  }
  if (t == 0) bulk_wait_read<0>();
}

typedef CUresult (*EncodeFn)(CUtensorMap*, CUtensorMapDataType, cuuint32_t, void*, const cuuint64_t*, const cuuint64_t*,
                             const cuuint32_t*, const cuuint32_t*, CUtensorMapInterleave, CUtensorMapSwizzle,
                             CUtensorMapL2promotion, CUtensorMapFloatOOBfill);

CUtensorMap make_map(EncodeFn fn, const void* base, int rank, const uint64_t* dims, const uint64_t* strides, const uint32_t* box,
                     CUtensorMapSwizzle swz) {
  CUtensorMap m;
  cuuint64_t gd[5], gs[4];
  cuuint32_t bx[5], es[5];
  for (int i = 0; i < rank; i++) { gd[i] = dims[i]; bx[i] = box[i]; es[i] = 1; }
  for (int i = 0; i + 1 < rank; i++) gs[i] = strides[i];
  fn(&m, CU_TENSOR_MAP_DATA_TYPE_BFLOAT16, rank, const_cast<void*>(base), gd, gs, bx, es, CU_TENSOR_MAP_INTERLEAVE_NONE, swz,
     CU_TENSOR_MAP_L2_PROMOTION_NONE, CU_TENSOR_MAP_FLOAT_OOB_FILL_NONE);
  return m;
}

template <typename... KArgs, typename... Args>
void launch(void (*k)(KArgs...), int grid, int block, int smem, bool pdl, Args... args) {
  cudaLaunchConfig_t c = {};
  c.gridDim = dim3(grid);
  c.blockDim = dim3(block);
  c.dynamicSmemBytes = smem;
  c.stream = cudaStreamPerThread;
  cudaLaunchAttribute at[1];
  at[0].id = cudaLaunchAttributeProgrammaticStreamSerialization;
  at[0].val.programmaticStreamSerializationAllowed = 1;
  c.attrs = at;
  c.numAttrs = pdl ? 1 : 0;
  cudaLaunchKernelEx(&c, k, args...);
}

}

static const uint32_t h_plan[67 + 25] = {
    0x6108, 0x6109, 0x610a, 0x610b, 0x6101, 0x8008, 0x8109, 0x820a, 0x830b, 0x8401,
    0x8508, 0x6102, 0x8609, 0x870a, 0x880b, 0x6103, 0x8a08, 0x8b02, 0x8c09, 0x8d0a,
    0x8e0b, 0x8f03, 0x9008, 0x9209, 0x930a, 0x9503, 0x9608, 0x9709, 0x980a, 0x9a08,
    0x9b09, 0x9c0a, 0x61616115, 0x6161610d, 0x61616107, 0x83816166, 0x8986610c, 0x8a89314d, 0x8f8a3237, 0x938f940b,
    0x9393344c, 0x9993354d, 0x0, 0x0, 0x0, 0x0, 0x0, 0x0, 0x6161ba98, 0x6161a981,
    0x6789281b, 0x67893ba9, 0x6891a928, 0x6891983b, 0x6999983a, 0x6999a98a, 0x39389d, 0x3, 0x4, 0x1dcc17b8,
    0x8f6a0c52, 0xac1, 0x2e5a9261, 0x194a, 0x9e, 0x9f, 0x37, 0x0, 0x0, 0x0,
    0x10, 0x11, 0x13, 0x14, 0x0, 0x0, 0x0, 0x0, 0x0, 0x0,
    0x0, 0x0, 0x0, 0x431, 0x431, 0x431, 0x0, 0x133, 0x131, 0x331,
    0x0, 0x3,
};

extern "C" void kernel_launch(void* const* d_in, const int* in_sizes, int n_in, void* d_out, int out_size) {
  const __nv_bfloat16* x = (const __nv_bfloat16*)d_in[0];
  const __nv_bfloat16* w1 = (const __nv_bfloat16*)d_in[1];
  const __nv_bfloat16* w2 = (const __nv_bfloat16*)d_in[2];
  const __nv_bfloat16* g = (const __nv_bfloat16*)d_in[3];
  const __nv_bfloat16* wf = (const __nv_bfloat16*)d_in[4];
  const __nv_bfloat16* wgt = (const __nv_bfloat16*)d_in[5];
  const __nv_bfloat16* wo = (const __nv_bfloat16*)d_in[6];

  void* fp = nullptr;
  cudaDriverEntryPointQueryResult qr;
  cudaGetDriverEntryPoint("cuTensorMapEncodeTiled", &fp, cudaEnableDefault, &qr);
  EncodeFn fn = (EncodeFn)fp;
  void *W2 = d_out, *X2 = (char*)d_out + W2_BYTES, *X1 = (char*)X2 - X2_BYTES, *Y1, *Y2;
  cudaGetSymbolAddress(&Y1, g_Y);
  Y2 = Y1;
  cudaFuncSetAttribute(k1, cudaFuncAttributeMaxDynamicSharedMemorySize, K1_SMEM);
  cudaFuncSetAttribute(k2, cudaFuncAttributeMaxDynamicSharedMemorySize, K2_SMEM);
  cudaFuncSetAttribute(kE, cudaFuncAttributeMaxDynamicSharedMemorySize, E_SMEM);
  const CUtensorMapSwizzle S128 = CU_TENSOR_MAP_SWIZZLE_128B;

  auto map_x = [&]() {
    uint64_t d[] = {64, 8000, 8, 2}, s[] = {1024, 128, 8000ull * 1024};
    uint32_t bx[] = {64, 56, 1, 1};
    return make_map(fn, x, 4, d, s, bx, S128);
  };
  auto map_w_in = [&](const __nv_bfloat16* w, int odd) {
    uint64_t d[] = {64, (uint64_t)(odd ? 15 : 16), 4, 256}, s[] = {2ull * 65536 * 2, 128, 512};
    uint32_t bx[] = {64, 16, 2, 1};
    return make_map(fn, w + (odd ? 65536 : 0), 4, d, s, bx, S128);
  };
  auto map_X_st = [&](void* p, int nb, int boxb) {
    uint64_t d[] = {64, 512, (uint64_t)(2 * nb)}, s[] = {2ull * nb * 128, 128};
    uint32_t bx[] = {64, C_PC, (uint32_t)boxb};
    return make_map(fn, p, 3, d, s, bx, S128);
  };
  auto map_X1_st = [&]() {
    uint64_t d[] = {64, 512, 2, (uint64_t)NB1}, s[] = {2ull * NB1 * 128, (uint64_t)NB1 * 128, 128};
    uint32_t bx[] = {64, 16, 1, 1};
    return make_map(fn, X1, 4, d, s, bx, S128);
  };
  auto map_W_st = [&](void* p) {
    uint64_t d[] = {64, 512, 4, 64}, s[] = {32768, 8192, 128};
    uint32_t bx[] = {64, W2_PC < 64 ? W2_PC : 64, W2_PC == 128 ? 2 : 1, 1};
    return make_map(fn, p, 4, d, s, bx, S128);
  };
  auto map_W_ld = [&](void* p, uint32_t bd, uint32_t bf) {
    uint64_t d[] = {64, 64, 4, 512}, s[] = {128, 8192, 32768};
    uint32_t bx[] = {64, 32, bd, bf};
    return make_map(fn, p, 4, d, s, bx, S128);
  };
  auto map_Y_st = [&](void* p, int nb, int rows) {
    uint64_t d[] = {64, (uint64_t)(2 * nb), 64, 4}, s[] = {32768, 128, 8192};
    uint32_t bx[] = {64, (uint32_t)rows, 1, 1};
    return make_map(fn, p, 4, d, s, bx, S128);
  };
  auto map_Y_ld = [&](void* p, int nb, int boxc, int boxb) {
    uint64_t d[] = {64, 64, 4, (uint64_t)nb, 2}, s[] = {128, 8192, 32768, (uint64_t)nb * 32768};
    uint32_t bx[] = {64, 64, (uint32_t)boxc, (uint32_t)boxb, 1};
    return make_map(fn, p, 5, d, s, bx, S128);
  };
  auto map_wsq = [&](const __nv_bfloat16* w, uint32_t bn) {
    uint64_t d[] = {64, 256, 4}, s[] = {512, 128};
    uint32_t bx[] = {64, 64, bn};
    return make_map(fn, w, 3, d, s, bx, S128);
  };
  auto map_out = [&]() {
    uint64_t d[] = {64, 4000, 4, 8, 2}, s[] = {4096, 128, 512, 4000ull * 4096};
    uint32_t bx[] = {64, 64, 2, 1, 1};
    return make_map(fn, d_out, 5, d, s, bx, S128);
  };

  auto map_w_raw = [&](const __nv_bfloat16* w, int odd) {
    uint64_t d[] = {256, (uint64_t)(odd ? 15 : 16), 16, 16}, s[] = {2ull * 65536 * 2, 512, 8192};
    uint32_t bx[] = {64, 16, 4, 2};
    return make_map(fn, w + (odd ? 65536 : 0), 4, d, s, bx, S128);
  };
  Ptrs gp;
  cudaGetSymbolAddress((void**)&gp.done, g_done);
  cudaGetSymbolAddress((void**)&gp.ge, g_ge);
  cudaGetSymbolAddress((void**)&gp.img, c_img);
  cudaGetSymbolAddress((void**)&gp.ga, c_ga);
  K1Maps g1;
  memcpy(&g1.p, h_plan, sizeof(Plan));
  g1.x = map_x();
  g1.we = map_w_raw(w1, 0);
  g1.wo = map_w_raw(w1, 1);
  g1.xs = map_X1_st();
  g1.y = map_Y_st(Y1, NB1, NB1 / G_EPI);
  g1.w2e = map_w_in(w2, 0);
  g1.w2o = map_w_in(w2, 1);
  g1.w2s = map_W_st(W2);
  for (int s = 0; s < 32; s++) {
    const int k = s < G_S0 ? s >> 1 : G_KM + (s - G_S0) % G_TK;
    g1.slot[s] = g_off(g_slot(s)) / 16;
    g1.src[s] = ((k >> 1) * 256 + (k & 1) * 2 + (s < G_S0 ? (s & 1) * 4 : s >= G_S0 + G_TK)) * (G_ST / 2);
    g1.dep[s] = s < 3 ? 8 * h_plan[64 + s] : 1536 + 8 * (s - g_depth(s));
  }
  launch(k1, 132, 384, K1_SMEM, false, gp, (const char*)X1, (const char*)w1, g1, g, wgt);
  K2Maps g2;
  memcpy(&g2, h_plan + 67, 100);
  g2.y = map_Y_ld(Y1, NB1, 1, 1);
  g2.xs = map_X_st(X2, NB2, 1);
  {
    uint64_t d[] = {64, 256, 2, 2 * NB2}, s[] = {2ull * NB2 * 128, 512ull * NB2 * 128, 128};
    uint32_t bx[] = {64, 64, 2, 1};
    g2.xa = make_map(fn, X2, 4, d, s, bx, S128);
  }
  g2.w = map_W_ld(W2, 1, 2);
  g2.y2 = map_Y_st(Y2, NB2, 168 / H_EPI);
  launch(k2, 128, 512, K2_SMEM, true, gp, (const char*)X2, g2, wf, wo);
  launch(kE, 126, 256, E_SMEM, true, map_Y_ld(Y2, NB2, 1, 2), map_wsq(wf, 2), map_wsq(wo, 4), map_out());
}
```

```cpp
#include <cuda_runtime.h>
#include <cuda_bf16.h>
#include <cuda.h>
#include <stdint.h>
#include <string.h>
#include <initializer_list>
#include <type_traits>

#define MIN_PAIRS 66

namespace {

constexpr int NB1 = 168;
constexpr int NB2 = 84;

constexpr size_t W2_BYTES = 8 * 64 * 4 * 64 * 64 * 2, X2_BYTES = 8 * 64 * 2 * NB2 * 64 * 2;
__device__ __align__(1024) __nv_bfloat16 g_Y[2 * NB1 * 4 * 64 * 64];
__device__ __align__(1024) char g_far[W2_BYTES + X2_BYTES / 2];
__device__ __align__(1024) float g_ge[16 * 256];

__device__ __forceinline__ uint32_t s2u(const void* p) { return (uint32_t)__cvta_generic_to_shared(p); }
__device__ __forceinline__ void mbar_init(uint32_t b, int c) {
  asm volatile("mbarrier.init.shared::cta.b64 [%0], %1;" ::"r"(b), "r"(c) : "memory");
}
__device__ __forceinline__ void mbar_expect(uint32_t b, int bytes) {
  asm volatile("mbarrier.arrive.expect_tx.shared::cta.b64 _, [%0], %1;" ::"r"(b), "r"(bytes) : "memory");
}
__device__ __forceinline__ void mbar_arrive(uint32_t b) {
  asm volatile("mbarrier.arrive.shared::cta.b64 _, [%0];" ::"r"(b) : "memory");
}
__device__ __forceinline__ void mbar_arrive_cta(uint32_t b, uint32_t cta) {
  asm volatile("{\n.reg .b32 r;\nmapa.shared::cluster.u32 r, %0, %1;\nmbarrier.arrive.shared::cluster.b64 _, [r];\n}" ::"r"(b), "r"(cta) : "memory");
}
__device__ __forceinline__ void mbar_wait(uint32_t b, int ph) {
  asm volatile(
      "{\n.reg .pred p;\n.reg .u32 n;\n"
      "mov.u32 n, 0;\n"
      "MBW_LOOP:\n"
      "mbarrier.try_wait.parity.shared::cta.b64 p, [%0], %1;\n"
      "@p bra MBW_DONE;\n"
      "add.u32 n, n, 1;\n"
      "setp.lt.u32 p, n, 1048576;\n"
      "@p bra MBW_LOOP;\n"
      "MBW_DONE:\n}" ::"r"(b), "r"(ph) : "memory");
}
__device__ __forceinline__ void fence_bar_init() { asm volatile("fence.mbarrier_init.release.cluster;" ::: "memory"); }
__device__ __forceinline__ void fence_async() { asm volatile("fence.proxy.async.shared::cta;" ::: "memory"); }
__device__ __forceinline__ void bar_sync(int id, int n) { asm volatile("bar.sync %0, %1;" ::"r"(id), "r"(n) : "memory"); }
__device__ __forceinline__ void bar_arrive(int id, int n) { asm volatile("bar.arrive %0, %1;" ::"r"(id), "r"(n) : "memory"); }
__device__ __forceinline__ void pdl_wait() { asm volatile("griddepcontrol.wait;" ::: "memory"); }
__device__ __forceinline__ void pdl_launch() { asm volatile("griddepcontrol.launch_dependents;" ::: "memory"); }
__device__ __forceinline__ void prefetch_map(const CUtensorMap* m) {
  asm volatile("prefetch.tensormap [%0];" ::"l"(m) : "memory");
}
template <int P> __device__ __forceinline__ uint64_t policy() {
  uint64_t p;
  asm("createpolicy.fractional.L2::evict_first.b64 %0, 1.0;" : "=l"(p));
  return p;
}
template <int P> __device__ __forceinline__ void tma_ld3(uint32_t dst, const CUtensorMap* m, uint32_t bar, int c0, int c1, int c2) {
  if constexpr (P == 0)
    asm volatile("cp.async.bulk.tensor.3d.shared::cluster.global.mbarrier::complete_tx::bytes [%0], [%1, {%3, %4, %5}], [%2];"
                 ::"r"(dst), "l"(m), "r"(bar), "r"(c0), "r"(c1), "r"(c2) : "memory");
  else
    asm volatile("cp.async.bulk.tensor.3d.shared::cluster.global.mbarrier::complete_tx::bytes.L2::cache_hint [%0], [%1, {%3, %4, %5}], [%2], %6;"
                 ::"r"(dst), "l"(m), "r"(bar), "r"(c0), "r"(c1), "r"(c2), "l"(policy<P>()) : "memory");
}
template <int P> __device__ __forceinline__ void tma_ld4(uint32_t dst, const CUtensorMap* m, uint32_t bar, int c0, int c1, int c2, int c3) {
  if constexpr (P == 0)
    asm volatile("cp.async.bulk.tensor.4d.shared::cluster.global.mbarrier::complete_tx::bytes [%0], [%1, {%3, %4, %5, %6}], [%2];"
                 ::"r"(dst), "l"(m), "r"(bar), "r"(c0), "r"(c1), "r"(c2), "r"(c3) : "memory");
  else
    asm volatile("cp.async.bulk.tensor.4d.shared::cluster.global.mbarrier::complete_tx::bytes.L2::cache_hint [%0], [%1, {%3, %4, %5, %6}], [%2], %7;"
                 ::"r"(dst), "l"(m), "r"(bar), "r"(c0), "r"(c1), "r"(c2), "r"(c3), "l"(policy<P>()) : "memory");
}
template <int P> __device__ __forceinline__ void tma_ld5(uint32_t dst, const CUtensorMap* m, uint32_t bar, int c0, int c1, int c2, int c3, int c4) {
  if constexpr (P == 0)
    asm volatile("cp.async.bulk.tensor.5d.shared::cluster.global.mbarrier::complete_tx::bytes [%0], [%1, {%3, %4, %5, %6, %7}], [%2];"
                 ::"r"(dst), "l"(m), "r"(bar), "r"(c0), "r"(c1), "r"(c2), "r"(c3), "r"(c4) : "memory");
  else
    asm volatile("cp.async.bulk.tensor.5d.shared::cluster.global.mbarrier::complete_tx::bytes.L2::cache_hint [%0], [%1, {%3, %4, %5, %6, %7}], [%2], %8;"
                 ::"r"(dst), "l"(m), "r"(bar), "r"(c0), "r"(c1), "r"(c2), "r"(c3), "r"(c4), "l"(policy<P>()) : "memory");
}
template <int P> __device__ __forceinline__ void tma_st3(const CUtensorMap* m, uint32_t src, int c0, int c1, int c2) {
  if constexpr (P == 0)
    asm volatile("cp.async.bulk.tensor.3d.global.shared::cta.bulk_group [%0, {%2, %3, %4}], [%1];" ::"l"(m), "r"(src), "r"(c0), "r"(c1), "r"(c2) : "memory");
  else
    asm volatile("cp.async.bulk.tensor.3d.global.shared::cta.bulk_group.L2::cache_hint [%0, {%2, %3, %4}], [%1], %5;" ::"l"(m), "r"(src), "r"(c0), "r"(c1), "r"(c2), "l"(policy<P>()) : "memory");
}
template <int P> __device__ __forceinline__ void tma_st4(const CUtensorMap* m, uint32_t src, int c0, int c1, int c2, int c3) {
  if constexpr (P == 0)
    asm volatile("cp.async.bulk.tensor.4d.global.shared::cta.bulk_group [%0, {%2, %3, %4, %5}], [%1];" ::"l"(m), "r"(src), "r"(c0), "r"(c1), "r"(c2), "r"(c3) : "memory");
  else
    asm volatile("cp.async.bulk.tensor.4d.global.shared::cta.bulk_group.L2::cache_hint [%0, {%2, %3, %4, %5}], [%1], %6;" ::"l"(m), "r"(src), "r"(c0), "r"(c1), "r"(c2), "r"(c3), "l"(policy<P>()) : "memory");
}
template <int P> __device__ __forceinline__ void tma_st5(const CUtensorMap* m, uint32_t src, int c0, int c1, int c2, int c3, int c4) {
  if constexpr (P == 0)
    asm volatile("cp.async.bulk.tensor.5d.global.shared::cta.bulk_group [%0, {%2, %3, %4, %5, %6}], [%1];" ::"l"(m), "r"(src), "r"(c0), "r"(c1), "r"(c2), "r"(c3), "r"(c4) : "memory");
  else
    asm volatile("cp.async.bulk.tensor.5d.global.shared::cta.bulk_group.L2::cache_hint [%0, {%2, %3, %4, %5, %6}], [%1], %7;" ::"l"(m), "r"(src), "r"(c0), "r"(c1), "r"(c2), "r"(c3), "r"(c4), "l"(policy<P>()) : "memory");
}
__device__ __forceinline__ void bulk_commit() { asm volatile("cp.async.bulk.commit_group;" ::: "memory"); }
template <int N> __device__ __forceinline__ void bulk_wait_read() { asm volatile("cp.async.bulk.wait_group.read %0;" ::"n"(N) : "memory"); }
__device__ __forceinline__ void wg_fence() { asm volatile("wgmma.fence.sync.aligned;" ::: "memory"); }
__device__ __forceinline__ void wg_commit() { asm volatile("wgmma.commit_group.sync.aligned;" ::: "memory"); }
template <int N> __device__ __forceinline__ void wg_wait() { asm volatile("wgmma.wait_group.sync.aligned %0;" ::"n"(N) : "memory"); }
template <int R> __device__ __forceinline__ void reg_fence(float (&d)[R]) {
#pragma unroll
  for (int i = 0; i < R; i++) asm volatile("" : "+f"(d[i])::"memory");
}
template <int R> __device__ __forceinline__ void reg_fence(uint32_t (&d)[R]) {
#pragma unroll
  for (int i = 0; i < R; i++) asm volatile("" : "+r"(d[i])::"memory");
}
__device__ __forceinline__ void stsm4(uint32_t a, uint32_t r0, uint32_t r1, uint32_t r2, uint32_t r3) {
  asm volatile("stmatrix.sync.aligned.m8n8.x4.shared.b16 [%0], {%1, %2, %3, %4};" ::"r"(a), "r"(r0), "r"(r1), "r"(r2), "r"(r3) : "memory");
}
__device__ __forceinline__ void stsm4t(uint32_t a, uint32_t r0, uint32_t r1, uint32_t r2, uint32_t r3) {
  asm volatile("stmatrix.sync.aligned.m8n8.x4.trans.shared.b16 [%0], {%1, %2, %3, %4};" ::"r"(a), "r"(r0), "r"(r1), "r"(r2), "r"(r3) : "memory");
}
__device__ __forceinline__ void ldsm4(uint32_t a, uint32_t& r0, uint32_t& r1, uint32_t& r2, uint32_t& r3) {
  asm volatile("ldmatrix.sync.aligned.m8n8.x4.shared.b16 {%0, %1, %2, %3}, [%4];" : "=r"(r0), "=r"(r1), "=r"(r2), "=r"(r3) : "r"(a) : "memory");
}
__device__ __forceinline__ void ldsm4t(uint32_t a, uint32_t& r0, uint32_t& r1, uint32_t& r2, uint32_t& r3) {
  asm volatile("ldmatrix.sync.aligned.m8n8.x4.trans.shared.b16 {%0, %1, %2, %3}, [%4];" : "=r"(r0), "=r"(r1), "=r"(r2), "=r"(r3) : "r"(a) : "memory");
}
__device__ __forceinline__ void ldg128(const uint4* p, uint32_t& a, uint32_t& b, uint32_t& c, uint32_t& d) {
  asm volatile("ld.global.nc.v4.u32 {%0, %1, %2, %3}, [%4];" : "=r"(a), "=r"(b), "=r"(c), "=r"(d) : "l"(p));
}
__device__ __forceinline__ uint32_t pack2(float lo, float hi) {
  uint32_t r;
  asm("cvt.rn.bf16x2.f32 %0, %1, %2;" : "=r"(r) : "f"(hi), "f"(lo));
  return r;
}
__device__ __forceinline__ float tanh_f32(float x) {
  float y;
  asm("tanh.approx.f32 %0, %1;" : "=f"(y) : "f"(x));
  return y;
}
__device__ __forceinline__ float gelu(float hx) {
  const float u = hx * fmaf(hx * hx, 8.0f * 0.044715f * 0.7978845608028654f, 2.0f * 0.7978845608028654f);
  return fmaf(hx, tanh_f32(u), hx);
}
__device__ __forceinline__ uint64_t mk_desc4(uint32_t addr4, uint32_t lbo, uint32_t sbo, uint32_t swz) {
  const uint32_t lo = addr4 + ((lbo >> 4) << 16), hi = (sbo >> 4) | (swz << 30);
  uint64_t d;
  asm("mov.b64 %0, {%1, %2};" : "=l"(d) : "r"(lo), "r"(hi));
  return d;
}
#define mk_desc(base, off, lbo, sbo, swz) mk_desc4((((base) & 0x3FFFF) >> 4) + ((off) >> 4), lbo, sbo, swz)

template <int SA, int SB, int TA, int TB>
__device__ __forceinline__ void wgmma_ss_48(float (&d)[24], uint64_t da, uint64_t db, int sd) {
  asm volatile("{\n.reg .pred p;\nsetp.ne.b32 p, %26, 0;\n"
      "wgmma.mma_async.sync.aligned.m64n48k16.f32.bf16.bf16 {"
      "%0, %1, %2, %3, %4, %5, %6, %7, %8, %9, %10, %11, %12, %13, %14, %15, %16, %17, %18, %19, %20, %21, %22, %23"
      "}, %24, %25, p, %27, %28, %29, %30;\n}\n"
      : "+f"(d[0]), "+f"(d[1]), "+f"(d[2]), "+f"(d[3]), "+f"(d[4]), "+f"(d[5]), "+f"(d[6]), "+f"(d[7]), "+f"(d[8]),
        "+f"(d[9]), "+f"(d[10]), "+f"(d[11]), "+f"(d[12]), "+f"(d[13]), "+f"(d[14]), "+f"(d[15]), "+f"(d[16]),
        "+f"(d[17]), "+f"(d[18]), "+f"(d[19]), "+f"(d[20]), "+f"(d[21]), "+f"(d[22]), "+f"(d[23])
      : "l"(da), "l"(db), "r"(sd), "n"(SA), "n"(SB), "n"(TA), "n"(TB));
}
template <int SA, int SB, int TA, int TB>
__device__ __forceinline__ void wgmma_ss_128(float (&d)[64], uint64_t da, uint64_t db, int sd) {
  asm volatile("{\n.reg .pred p;\nsetp.ne.b32 p, %66, 0;\n"
      "wgmma.mma_async.sync.aligned.m64n128k16.f32.bf16.bf16 {"
      "%0, %1, %2, %3, %4, %5, %6, %7, %8, %9, %10, %11, %12, %13, %14, %15, %16, %17, %18, %19, %20, %21, %22, %23, "
      "%24, %25, %26, %27, %28, %29, %30, %31, %32, %33, %34, %35, %36, %37, %38, %39, %40, %41, %42, %43, %44, %45, "
      "%46, %47, %48, %49, %50, %51, %52, %53, %54, %55, %56, %57, %58, %59, %60, %61, %62, %63"
      "}, %64, %65, p, %67, %68, %69, %70;\n}\n"
      : "+f"(d[0]), "+f"(d[1]), "+f"(d[2]), "+f"(d[3]), "+f"(d[4]), "+f"(d[5]), "+f"(d[6]), "+f"(d[7]), "+f"(d[8]),
        "+f"(d[9]), "+f"(d[10]), "+f"(d[11]), "+f"(d[12]), "+f"(d[13]), "+f"(d[14]), "+f"(d[15]), "+f"(d[16]),
        "+f"(d[17]), "+f"(d[18]), "+f"(d[19]), "+f"(d[20]), "+f"(d[21]), "+f"(d[22]), "+f"(d[23]), "+f"(d[24]),
        "+f"(d[25]), "+f"(d[26]), "+f"(d[27]), "+f"(d[28]), "+f"(d[29]), "+f"(d[30]), "+f"(d[31]), "+f"(d[32]),
        "+f"(d[33]), "+f"(d[34]), "+f"(d[35]), "+f"(d[36]), "+f"(d[37]), "+f"(d[38]), "+f"(d[39]), "+f"(d[40]),
        "+f"(d[41]), "+f"(d[42]), "+f"(d[43]), "+f"(d[44]), "+f"(d[45]), "+f"(d[46]), "+f"(d[47]), "+f"(d[48]),
        "+f"(d[49]), "+f"(d[50]), "+f"(d[51]), "+f"(d[52]), "+f"(d[53]), "+f"(d[54]), "+f"(d[55]), "+f"(d[56]),
        "+f"(d[57]), "+f"(d[58]), "+f"(d[59]), "+f"(d[60]), "+f"(d[61]), "+f"(d[62]), "+f"(d[63])
      : "l"(da), "l"(db), "r"(sd), "n"(SA), "n"(SB), "n"(TA), "n"(TB));
}
template <int SA, int SB, int TA, int TB>
__device__ __forceinline__ void wgmma_ss_168(float (&d)[84], uint64_t da, uint64_t db, int sd) {
  asm volatile("{\n.reg .pred p;\nsetp.ne.b32 p, %86, 0;\n"
      "wgmma.mma_async.sync.aligned.m64n168k16.f32.bf16.bf16 {"
      "%0, %1, %2, %3, %4, %5, %6, %7, %8, %9, %10, %11, %12, %13, %14, %15, %16, %17, %18, %19, %20, %21, %22, %23, "
      "%24, %25, %26, %27, %28, %29, %30, %31, %32, %33, %34, %35, %36, %37, %38, %39, %40, %41, %42, %43, %44, %45, "
      "%46, %47, %48, %49, %50, %51, %52, %53, %54, %55, %56, %57, %58, %59, %60, %61, %62, %63, %64, %65, %66, %67, "
      "%68, %69, %70, %71, %72, %73, %74, %75, %76, %77, %78, %79, %80, %81, %82, %83"
      "}, %84, %85, p, %87, %88, %89, %90;\n}\n"
      : "+f"(d[0]), "+f"(d[1]), "+f"(d[2]), "+f"(d[3]), "+f"(d[4]), "+f"(d[5]), "+f"(d[6]), "+f"(d[7]), "+f"(d[8]),
        "+f"(d[9]), "+f"(d[10]), "+f"(d[11]), "+f"(d[12]), "+f"(d[13]), "+f"(d[14]), "+f"(d[15]), "+f"(d[16]),
        "+f"(d[17]), "+f"(d[18]), "+f"(d[19]), "+f"(d[20]), "+f"(d[21]), "+f"(d[22]), "+f"(d[23]), "+f"(d[24]),
        "+f"(d[25]), "+f"(d[26]), "+f"(d[27]), "+f"(d[28]), "+f"(d[29]), "+f"(d[30]), "+f"(d[31]), "+f"(d[32]),
        "+f"(d[33]), "+f"(d[34]), "+f"(d[35]), "+f"(d[36]), "+f"(d[37]), "+f"(d[38]), "+f"(d[39]), "+f"(d[40]),
        "+f"(d[41]), "+f"(d[42]), "+f"(d[43]), "+f"(d[44]), "+f"(d[45]), "+f"(d[46]), "+f"(d[47]), "+f"(d[48]),
        "+f"(d[49]), "+f"(d[50]), "+f"(d[51]), "+f"(d[52]), "+f"(d[53]), "+f"(d[54]), "+f"(d[55]), "+f"(d[56]),
        "+f"(d[57]), "+f"(d[58]), "+f"(d[59]), "+f"(d[60]), "+f"(d[61]), "+f"(d[62]), "+f"(d[63]), "+f"(d[64]),
        "+f"(d[65]), "+f"(d[66]), "+f"(d[67]), "+f"(d[68]), "+f"(d[69]), "+f"(d[70]), "+f"(d[71]), "+f"(d[72]),
        "+f"(d[73]), "+f"(d[74]), "+f"(d[75]), "+f"(d[76]), "+f"(d[77]), "+f"(d[78]), "+f"(d[79]), "+f"(d[80]),
        "+f"(d[81]), "+f"(d[82]), "+f"(d[83])
      : "l"(da), "l"(db), "r"(sd), "n"(SA), "n"(SB), "n"(TA), "n"(TB));
}
template <int SA, int SB, int TB>
__device__ __forceinline__ void wgmma_rs_32(float (&d)[16], uint32_t a0, uint32_t a1, uint32_t a2, uint32_t a3, uint64_t db, int sd) {
  asm volatile("{\n.reg .pred p;\nsetp.ne.b32 p, %21, 0;\n"
      "wgmma.mma_async.sync.aligned.m64n32k16.f32.bf16.bf16 {"
      "%0, %1, %2, %3, %4, %5, %6, %7, %8, %9, %10, %11, %12, %13, %14, %15"
      "}, {%16, %17, %18, %19}, %20, p, %22, %23, %24;\n}\n"
      : "+f"(d[0]), "+f"(d[1]), "+f"(d[2]), "+f"(d[3]), "+f"(d[4]), "+f"(d[5]), "+f"(d[6]), "+f"(d[7]), "+f"(d[8]),
        "+f"(d[9]), "+f"(d[10]), "+f"(d[11]), "+f"(d[12]), "+f"(d[13]), "+f"(d[14]), "+f"(d[15])
      : "r"(a0), "r"(a1), "r"(a2), "r"(a3), "l"(db), "r"(sd), "n"(SA), "n"(SB), "n"(TB));
}
template <int SA, int SB, int TB>
__device__ __forceinline__ void wgmma_rs_64(float (&d)[32], uint32_t a0, uint32_t a1, uint32_t a2, uint32_t a3, uint64_t db, int sd) {
  asm volatile("{\n.reg .pred p;\nsetp.ne.b32 p, %37, 0;\n"
      "wgmma.mma_async.sync.aligned.m64n64k16.f32.bf16.bf16 {"
      "%0, %1, %2, %3, %4, %5, %6, %7, %8, %9, %10, %11, %12, %13, %14, %15, %16, %17, %18, %19, %20, %21, %22, %23, "
      "%24, %25, %26, %27, %28, %29, %30, %31"
      "}, {%32, %33, %34, %35}, %36, p, %38, %39, %40;\n}\n"
      : "+f"(d[0]), "+f"(d[1]), "+f"(d[2]), "+f"(d[3]), "+f"(d[4]), "+f"(d[5]), "+f"(d[6]), "+f"(d[7]), "+f"(d[8]),
        "+f"(d[9]), "+f"(d[10]), "+f"(d[11]), "+f"(d[12]), "+f"(d[13]), "+f"(d[14]), "+f"(d[15]), "+f"(d[16]),
        "+f"(d[17]), "+f"(d[18]), "+f"(d[19]), "+f"(d[20]), "+f"(d[21]), "+f"(d[22]), "+f"(d[23]), "+f"(d[24]),
        "+f"(d[25]), "+f"(d[26]), "+f"(d[27]), "+f"(d[28]), "+f"(d[29]), "+f"(d[30]), "+f"(d[31])
      : "r"(a0), "r"(a1), "r"(a2), "r"(a3), "l"(db), "r"(sd), "n"(SA), "n"(SB), "n"(TB));
}
template <int SA, int SB, int TB>
__device__ __forceinline__ void wgmma_rs_128(float (&d)[64], uint32_t a0, uint32_t a1, uint32_t a2, uint32_t a3, uint64_t db, int sd) {
  asm volatile("{\n.reg .pred p;\nsetp.ne.b32 p, %69, 0;\n"
      "wgmma.mma_async.sync.aligned.m64n128k16.f32.bf16.bf16 {"
      "%0, %1, %2, %3, %4, %5, %6, %7, %8, %9, %10, %11, %12, %13, %14, %15, %16, %17, %18, %19, %20, %21, %22, %23, "
      "%24, %25, %26, %27, %28, %29, %30, %31, %32, %33, %34, %35, %36, %37, %38, %39, %40, %41, %42, %43, %44, %45, "
      "%46, %47, %48, %49, %50, %51, %52, %53, %54, %55, %56, %57, %58, %59, %60, %61, %62, %63"
      "}, {%64, %65, %66, %67}, %68, p, %70, %71, %72;\n}\n"
      : "+f"(d[0]), "+f"(d[1]), "+f"(d[2]), "+f"(d[3]), "+f"(d[4]), "+f"(d[5]), "+f"(d[6]), "+f"(d[7]), "+f"(d[8]),
        "+f"(d[9]), "+f"(d[10]), "+f"(d[11]), "+f"(d[12]), "+f"(d[13]), "+f"(d[14]), "+f"(d[15]), "+f"(d[16]),
        "+f"(d[17]), "+f"(d[18]), "+f"(d[19]), "+f"(d[20]), "+f"(d[21]), "+f"(d[22]), "+f"(d[23]), "+f"(d[24]),
        "+f"(d[25]), "+f"(d[26]), "+f"(d[27]), "+f"(d[28]), "+f"(d[29]), "+f"(d[30]), "+f"(d[31]), "+f"(d[32]),
        "+f"(d[33]), "+f"(d[34]), "+f"(d[35]), "+f"(d[36]), "+f"(d[37]), "+f"(d[38]), "+f"(d[39]), "+f"(d[40]),
        "+f"(d[41]), "+f"(d[42]), "+f"(d[43]), "+f"(d[44]), "+f"(d[45]), "+f"(d[46]), "+f"(d[47]), "+f"(d[48]),
        "+f"(d[49]), "+f"(d[50]), "+f"(d[51]), "+f"(d[52]), "+f"(d[53]), "+f"(d[54]), "+f"(d[55]), "+f"(d[56]),
        "+f"(d[57]), "+f"(d[58]), "+f"(d[59]), "+f"(d[60]), "+f"(d[61]), "+f"(d[62]), "+f"(d[63])
      : "r"(a0), "r"(a1), "r"(a2), "r"(a3), "l"(db), "r"(sd), "n"(SA), "n"(SB), "n"(TB));
}
template <int SA, int SB, int TB>
__device__ __forceinline__ void wgmma_rs_168(float (&d)[84], uint32_t a0, uint32_t a1, uint32_t a2, uint32_t a3, uint64_t db, int sd) {
  asm volatile("{\n.reg .pred p;\nsetp.ne.b32 p, %89, 0;\n"
      "wgmma.mma_async.sync.aligned.m64n168k16.f32.bf16.bf16 {"
      "%0, %1, %2, %3, %4, %5, %6, %7, %8, %9, %10, %11, %12, %13, %14, %15, %16, %17, %18, %19, %20, %21, %22, %23, "
      "%24, %25, %26, %27, %28, %29, %30, %31, %32, %33, %34, %35, %36, %37, %38, %39, %40, %41, %42, %43, %44, %45, "
      "%46, %47, %48, %49, %50, %51, %52, %53, %54, %55, %56, %57, %58, %59, %60, %61, %62, %63, %64, %65, %66, %67, "
      "%68, %69, %70, %71, %72, %73, %74, %75, %76, %77, %78, %79, %80, %81, %82, %83"
      "}, {%84, %85, %86, %87}, %88, p, %90, %91, %92;\n}\n"
      : "+f"(d[0]), "+f"(d[1]), "+f"(d[2]), "+f"(d[3]), "+f"(d[4]), "+f"(d[5]), "+f"(d[6]), "+f"(d[7]), "+f"(d[8]),
        "+f"(d[9]), "+f"(d[10]), "+f"(d[11]), "+f"(d[12]), "+f"(d[13]), "+f"(d[14]), "+f"(d[15]), "+f"(d[16]),
        "+f"(d[17]), "+f"(d[18]), "+f"(d[19]), "+f"(d[20]), "+f"(d[21]), "+f"(d[22]), "+f"(d[23]), "+f"(d[24]),
        "+f"(d[25]), "+f"(d[26]), "+f"(d[27]), "+f"(d[28]), "+f"(d[29]), "+f"(d[30]), "+f"(d[31]), "+f"(d[32]),
        "+f"(d[33]), "+f"(d[34]), "+f"(d[35]), "+f"(d[36]), "+f"(d[37]), "+f"(d[38]), "+f"(d[39]), "+f"(d[40]),
        "+f"(d[41]), "+f"(d[42]), "+f"(d[43]), "+f"(d[44]), "+f"(d[45]), "+f"(d[46]), "+f"(d[47]), "+f"(d[48]),
        "+f"(d[49]), "+f"(d[50]), "+f"(d[51]), "+f"(d[52]), "+f"(d[53]), "+f"(d[54]), "+f"(d[55]), "+f"(d[56]),
        "+f"(d[57]), "+f"(d[58]), "+f"(d[59]), "+f"(d[60]), "+f"(d[61]), "+f"(d[62]), "+f"(d[63]), "+f"(d[64]),
        "+f"(d[65]), "+f"(d[66]), "+f"(d[67]), "+f"(d[68]), "+f"(d[69]), "+f"(d[70]), "+f"(d[71]), "+f"(d[72]),
        "+f"(d[73]), "+f"(d[74]), "+f"(d[75]), "+f"(d[76]), "+f"(d[77]), "+f"(d[78]), "+f"(d[79]), "+f"(d[80]),
        "+f"(d[81]), "+f"(d[82]), "+f"(d[83])
      : "r"(a0), "r"(a1), "r"(a2), "r"(a3), "l"(db), "r"(sd), "n"(SA), "n"(SB), "n"(TB));
}
template <int SA, int SB, int TB>
__device__ __forceinline__ void wgmma_rs_256(float (&d)[128], uint32_t a0, uint32_t a1, uint32_t a2, uint32_t a3, uint64_t db, int sd) {
  asm volatile("{\n.reg .pred p;\nsetp.ne.b32 p, %133, 0;\n"
      "wgmma.mma_async.sync.aligned.m64n256k16.f32.bf16.bf16 {"
      "%0, %1, %2, %3, %4, %5, %6, %7, %8, %9, %10, %11, %12, %13, %14, %15, %16, %17, %18, %19, %20, %21, %22, %23, "
      "%24, %25, %26, %27, %28, %29, %30, %31, %32, %33, %34, %35, %36, %37, %38, %39, %40, %41, %42, %43, %44, %45, "
      "%46, %47, %48, %49, %50, %51, %52, %53, %54, %55, %56, %57, %58, %59, %60, %61, %62, %63, %64, %65, %66, %67, "
      "%68, %69, %70, %71, %72, %73, %74, %75, %76, %77, %78, %79, %80, %81, %82, %83, %84, %85, %86, %87, %88, %89, "
      "%90, %91, %92, %93, %94, %95, %96, %97, %98, %99, %100, %101, %102, %103, %104, %105, %106, %107, %108, %109, "
      "%110, %111, %112, %113, %114, %115, %116, %117, %118, %119, %120, %121, %122, %123, %124, %125, %126, %127"
      "}, {%128, %129, %130, %131}, %132, p, %134, %135, %136;\n}\n"
      : "+f"(d[0]), "+f"(d[1]), "+f"(d[2]), "+f"(d[3]), "+f"(d[4]), "+f"(d[5]), "+f"(d[6]), "+f"(d[7]), "+f"(d[8]),
        "+f"(d[9]), "+f"(d[10]), "+f"(d[11]), "+f"(d[12]), "+f"(d[13]), "+f"(d[14]), "+f"(d[15]), "+f"(d[16]),
        "+f"(d[17]), "+f"(d[18]), "+f"(d[19]), "+f"(d[20]), "+f"(d[21]), "+f"(d[22]), "+f"(d[23]), "+f"(d[24]),
        "+f"(d[25]), "+f"(d[26]), "+f"(d[27]), "+f"(d[28]), "+f"(d[29]), "+f"(d[30]), "+f"(d[31]), "+f"(d[32]),
        "+f"(d[33]), "+f"(d[34]), "+f"(d[35]), "+f"(d[36]), "+f"(d[37]), "+f"(d[38]), "+f"(d[39]), "+f"(d[40]),
        "+f"(d[41]), "+f"(d[42]), "+f"(d[43]), "+f"(d[44]), "+f"(d[45]), "+f"(d[46]), "+f"(d[47]), "+f"(d[48]),
        "+f"(d[49]), "+f"(d[50]), "+f"(d[51]), "+f"(d[52]), "+f"(d[53]), "+f"(d[54]), "+f"(d[55]), "+f"(d[56]),
        "+f"(d[57]), "+f"(d[58]), "+f"(d[59]), "+f"(d[60]), "+f"(d[61]), "+f"(d[62]), "+f"(d[63]), "+f"(d[64]),
        "+f"(d[65]), "+f"(d[66]), "+f"(d[67]), "+f"(d[68]), "+f"(d[69]), "+f"(d[70]), "+f"(d[71]), "+f"(d[72]),
        "+f"(d[73]), "+f"(d[74]), "+f"(d[75]), "+f"(d[76]), "+f"(d[77]), "+f"(d[78]), "+f"(d[79]), "+f"(d[80]),
        "+f"(d[81]), "+f"(d[82]), "+f"(d[83]), "+f"(d[84]), "+f"(d[85]), "+f"(d[86]), "+f"(d[87]), "+f"(d[88]),
        "+f"(d[89]), "+f"(d[90]), "+f"(d[91]), "+f"(d[92]), "+f"(d[93]), "+f"(d[94]), "+f"(d[95]), "+f"(d[96]),
        "+f"(d[97]), "+f"(d[98]), "+f"(d[99]), "+f"(d[100]), "+f"(d[101]), "+f"(d[102]), "+f"(d[103]), "+f"(d[104]),
        "+f"(d[105]), "+f"(d[106]), "+f"(d[107]), "+f"(d[108]), "+f"(d[109]), "+f"(d[110]), "+f"(d[111]),
        "+f"(d[112]), "+f"(d[113]), "+f"(d[114]), "+f"(d[115]), "+f"(d[116]), "+f"(d[117]), "+f"(d[118]),
        "+f"(d[119]), "+f"(d[120]), "+f"(d[121]), "+f"(d[122]), "+f"(d[123]), "+f"(d[124]), "+f"(d[125]),
        "+f"(d[126]), "+f"(d[127])
      : "r"(a0), "r"(a1), "r"(a2), "r"(a3), "l"(db), "r"(sd), "n"(SA), "n"(SB), "n"(TB));
}

__device__ const __align__(128) uint32_t c_img[3584] = {
    0x00003c80, 0x00003c80, 0x00003c80, 0x00003c80, 0x00003c80, 0x00003c80, 0x00003c80, 0x00003c80, 0x00003c80, 0x00003c80,
    0x00003c80, 0x00003c80, 0x00003c80, 0x00003c80, 0x00003c80, 0x00003c80, 0x00003c80, 0x00003c80, 0x00003c80, 0x00003c80,
    0x00003c80, 0x00003c80, 0x00003c80, 0x00003c80, 0x00003c80, 0x00003c80, 0x00003c80, 0x00003c80, 0x00003c80, 0x00003c80,
    0x00003c80, 0x00003c80, 0x3c463c22, 0x3c623bf1, 0x3c753b95, 0x3c7f3ac9, 0x3ac93c7f, 0x3b953c75, 0x3bf13c62, 0x3c223c46,
    0x3c22bc46, 0x3bf1bc62, 0x3b95bc75, 0x3ac9bc7f, 0x3c7fbac9, 0x3c75bb95, 0x3c62bbf1, 0x3c46bc22, 0xbc46bc22, 0xbc62bbf1,
    0xbc75bb95, 0xbc7fbac9, 0xbac9bc7f, 0xbb95bc75, 0xbbf1bc62, 0xbc22bc46, 0xbc223c46, 0xbbf13c62, 0xbb953c75, 0xbac93c7f,
    0xbc7f3ac9, 0xbc753b95, 0xbc623bf1, 0xbc463c22, 0xbb48bc7b, 0xbc0ebc55, 0xbc55bc0e, 0xbc7bbb48, 0xbc7b3b48, 0xbc553c0e,
    0xbc0e3c55, 0xbb483c7b, 0x3b483c7b, 0x3c0e3c55, 0x3c553c0e, 0x3c7b3b48, 0x3c7bbb48, 0x3c55bc0e, 0x3c0ebc55, 0x3b48bc7b,
    0xbb48bc7b, 0xbc0ebc55, 0xbc55bc0e, 0xbc7bbb48, 0xbc7b3b48, 0xbc553c0e, 0xbc0e3c55, 0xbb483c7b, 0x3b483c7b, 0x3c0e3c55,
    0x3c553c0e, 0x3c7b3b48, 0x3c7bbb48, 0x3c55bc0e, 0x3c0ebc55, 0x3b48bc7b, 0x3c623bf1, 0x3c7fbac9, 0x3c46bc22, 0x3b95bc75,
    0xbc753b95, 0xbc223c46, 0xbac93c7f, 0x3bf13c62, 0x3bf1bc62, 0xbac9bc7f, 0xbc22bc46, 0xbc75bb95, 0x3b953c75, 0x3c463c22,
    0x3c7f3ac9, 0x3c62bbf1, 0xbc62bbf1, 0xbc7f3ac9, 0xbc463c22, 0xbb953c75, 0x3c75bb95, 0x3c22bc46, 0x3ac9bc7f, 0xbbf1bc62,
    0xbbf13c62, 0x3ac93c7f, 0x3c223c46, 0x3c753b95, 0xbb95bc75, 0xbc46bc22, 0xbc7fbac9, 0xbc623bf1, 0x3bc43c6d, 0x3c6d3bc4,
    0x3c6dbbc4, 0x3bc4bc6d, 0xbbc4bc6d, 0xbc6dbbc4, 0xbc6d3bc4, 0xbbc43c6d, 0x3bc43c6d, 0x3c6d3bc4, 0x3c6dbbc4, 0x3bc4bc6d,
    0xbbc4bc6d, 0xbc6dbbc4, 0xbc6d3bc4, 0xbbc43c6d, 0x3bc43c6d, 0x3c6d3bc4, 0x3c6dbbc4, 0x3bc4bc6d, 0xbbc4bc6d, 0xbc6dbbc4,
    0xbc6d3bc4, 0xbbc43c6d, 0x3bc43c6d, 0x3c6d3bc4, 0x3c6dbbc4, 0x3bc4bc6d, 0xbbc4bc6d, 0xbc6dbbc4, 0xbc6d3bc4, 0xbbc43c6d,
    0x3c753b95, 0x3c46bc22, 0xbac9bc7f, 0xbc62bbf1, 0xbbf1bc62, 0xbc7fbac9, 0xbc223c46, 0x3b953c75, 0x3b95bc75, 0xbc22bc46,
    0xbc7f3ac9, 0xbbf13c62, 0xbc623bf1, 0xbac93c7f, 0x3c463c22, 0x3c75bb95, 0xbc75bb95, 0xbc463c22, 0x3ac93c7f, 0x3c623bf1,
    0x3bf13c62, 0x3c7f3ac9, 0x3c22bc46, 0xbb95bc75, 0xbb953c75, 0x3c223c46, 0x3c7fbac9, 0x3bf1bc62, 0x3c62bbf1, 0x3ac9bc7f,
    0xbc46bc22, 0xbc753b95, 0xbc0ebc55, 0xbc7b3b48, 0xbb483c7b, 0x3c553c0e, 0x3c55bc0e, 0xbb48bc7b, 0xbc7bbb48, 0xbc0e3c55,
    0x3c0e3c55, 0x3c7bbb48, 0x3b48bc7b, 0xbc55bc0e, 0xbc553c0e, 0x3b483c7b, 0x3c7b3b48, 0x3c0ebc55, 0xbc0ebc55, 0xbc7b3b48,
    0xbb483c7b, 0x3c553c0e, 0x3c55bc0e, 0xbb48bc7b, 0xbc7bbb48, 0xbc0e3c55, 0x3c0e3c55, 0x3c7bbb48, 0x3b48bc7b, 0xbc55bc0e,
    0xbc553c0e, 0x3b483c7b, 0x3c7b3b48, 0x3c0ebc55, 0x3c7f3ac9, 0x3b95bc75, 0xbc62bbf1, 0xbc223c46, 0x3c46bc22, 0xbbf1bc62,
    0xbc753b95, 0x3ac93c7f, 0x3ac9bc7f, 0xbc75bb95, 0xbbf13c62, 0x3c463c22, 0xbc22bc46, 0xbc623bf1, 0x3b953c75, 0x3c7fbac9,
    0xbc7fbac9, 0xbb953c75, 0x3c623bf1, 0x3c22bc46, 0xbc463c22, 0x3bf13c62, 0x3c75bb95, 0xbac9bc7f, 0xbac93c7f, 0x3c753b95,
    0x3bf1bc62, 0xbc46bc22, 0x3c223c46, 0x3c62bbf1, 0xbb95bc75, 0xbc7f3ac9, 0x3a493c80, 0x3b163c7d, 0x3b793c78, 0x3bac3c71,
    0x3bdb3c67, 0x3c043c5c, 0x3c183c4e, 0x3c2c3c3e, 0x3c3e3c2c, 0x3c4e3c18, 0x3c5c3c04, 0x3c673bdb, 0x3c713bac, 0x3c783b79,
    0x3c7d3b16, 0x3c803a49, 0x3c80ba49, 0x3c7dbb16, 0x3c78bb79, 0x3c71bbac, 0x3c67bbdb, 0x3c5cbc04, 0x3c4ebc18, 0x3c3ebc2c,
    0x3c2cbc3e, 0x3c18bc4e, 0x3c04bc5c, 0x3bdbbc67, 0x3bacbc71, 0x3b79bc78, 0x3b16bc7d, 0x3a49bc80, 0x3c783b79, 0x3c80ba49,
    0x3c71bbac, 0x3c4ebc18, 0x3b163c7d, 0x3bdb3c67, 0x3c2c3c3e, 0x3c5c3c04, 0xbc04bc5c, 0xbc3ebc2c, 0xbc67bbdb, 0xbc7dbb16,
    0x3c18bc4e, 0x3bacbc71, 0x3a49bc80, 0xbb79bc78, 0xbb793c78, 0x3a493c80, 0x3bac3c71, 0x3c183c4e, 0xbc7d3b16, 0xbc673bdb,
    0xbc3e3c2c, 0xbc043c5c, 0x3c5cbc04, 0x3c2cbc3e, 0x3bdbbc67, 0x3b16bc7d, 0x3c4e3c18, 0x3c713bac, 0x3c803a49, 0x3c78bb79,
    0xbc5cbc04, 0xbc80ba49, 0xbc673bdb, 0xbc183c4e, 0xbb163c7d, 0x3bac3c71, 0x3c3e3c2c, 0x3c783b79, 0x3b793c78, 0x3c2c3c3e,
    0x3c713bac, 0x3c7dbb16, 0x3c4ebc18, 0x3bdbbc67, 0xba49bc80, 0xbc04bc5c, 0xbc043c5c, 0xba493c80, 0x3bdb3c67, 0x3c4e3c18,
    0x3c7d3b16, 0x3c71bbac, 0x3c2cbc3e, 0x3b79bc78, 0x3c78bb79, 0x3c3ebc2c, 0x3bacbc71, 0xbb16bc7d, 0xbc18bc4e, 0xbc67bbdb,
    0xbc803a49, 0xbc5c3c04, 0x3c3ebc2c, 0x3b16bc7d, 0xbc04bc5c, 0xbc71bbac, 0xbbdb3c67, 0x3b793c78, 0x3c4e3c18, 0x3c80ba49,
    0x3a49bc80, 0xbc18bc4e, 0xbc78bb79, 0xbc673bdb, 0x3bac3c71, 0x3c5c3c04, 0x3c7dbb16, 0x3c2cbc3e, 0x3c2c3c3e, 0x3c7d3b16,
    0x3c5cbc04, 0x3bacbc71, 0xbc67bbdb, 0xbc783b79, 0xbc183c4e, 0x3a493c80, 0x3c803a49, 0x3c4ebc18, 0x3b79bc78, 0xbbdbbc67,
    0xbc713bac, 0xbc043c5c, 0x3b163c7d, 0x3c3e3c2c, 0x3c67bbdb, 0x3b79bc78, 0xbc18bc4e, 0xbc80ba49, 0xbc2c3c3e, 0x3b163c7d,
    0x3c5c3c04, 0x3c71bbac, 0x3bacbc71, 0xbc04bc5c, 0xbc7dbb16, 0xbc3e3c2c, 0x3a493c80, 0x3c4e3c18, 0x3c78bb79, 0x3bdbbc67,
    0x3bdb3c67, 0x3c783b79, 0x3c4ebc18, 0x3a49bc80, 0xbc3ebc2c, 0xbc7d3b16, 0xbc043c5c, 0x3bac3c71, 0x3c713bac, 0x3c5cbc04,
    0x3b16bc7d, 0xbc2cbc3e, 0xbc803a49, 0xbc183c4e, 0x3b793c78, 0x3c673bdb, 0xbb16bc7d, 0xbc71bbac, 0xbc3e3c2c, 0x3b793c78,
    0xbc5c3c04, 0x3a493c80, 0x3c673bdb, 0x3c4ebc18, 0xbc183c4e, 0x3bdb3c67, 0x3c803a49, 0x3c04bc5c, 0x3c783b79, 0x3c2cbc3e,
    0xbbacbc71, 0xbc7dbb16, 0xbc7d3b16, 0xbbac3c71, 0x3c2c3c3e, 0x3c78bb79, 0x3c043c5c, 0x3c80ba49, 0x3bdbbc67, 0xbc18bc4e,
    0x3c4e3c18, 0x3c67bbdb, 0x3a49bc80, 0xbc5cbc04, 0x3b79bc78, 0xbc3ebc2c, 0xbc713bac, 0xbb163c7d, 0xbb163c7d, 0x3c673bdb,
    0x3c2cbc3e, 0xbc04bc5c, 0xbc783b79, 0xba493c80, 0x3c713bac, 0x3c18bc4e, 0x3c4ebc18, 0xbbacbc71, 0xbc803a49, 0xbb793c78,
    0x3c5c3c04, 0x3c3ebc2c, 0xbbdbbc67, 0xbc7d3b16, 0xbc7dbb16, 0xbbdb3c67, 0x3c3e3c2c, 0x3c5cbc04, 0xbb79bc78, 0xbc80ba49,
    0xbbac3c71, 0x3c4e3c18, 0x3c183c4e, 0x3c71bbac, 0xba49bc80, 0xbc78bb79, 0xbc043c5c, 0x3c2c3c3e, 0x3c67bbdb, 0xbb16bc7d,
    0xbc67bbdb, 0xbc043c5c, 0x3c4e3c18, 0x3c2cbc3e, 0xbc80ba49, 0xbb163c7d, 0x3c783b79, 0x3bacbc71, 0xbc713bac, 0x3b793c78,
    0x3c7dbb16, 0xba49bc80, 0xbc3e3c2c, 0x3c183c4e, 0x3c5cbc04, 0xbbdbbc67, 0xbbdb3c67, 0x3c5c3c04, 0x3c18bc4e, 0xbc3ebc2c,
    0xba493c80, 0x3c7d3b16, 0x3b79bc78, 0xbc71bbac, 0x3bac3c71, 0x3c78bb79, 0xbb16bc7d, 0xbc803a49, 0x3c2c3c3e, 0x3c4ebc18,
    0xbc04bc5c, 0xbc673bdb, 0x3c353c35, 0x3c35bc35, 0xbc35bc35, 0xbc353c35, 0x3c353c35, 0x3c35bc35, 0xbc35bc35, 0xbc353c35,
    0x3c353c35, 0x3c35bc35, 0xbc35bc35, 0xbc353c35, 0x3c353c35, 0x3c35bc35, 0xbc35bc35, 0xbc353c35, 0x3c353c35, 0x3c35bc35,
    0xbc35bc35, 0xbc353c35, 0x3c353c35, 0x3c35bc35, 0xbc35bc35, 0xbc353c35, 0x3c353c35, 0x3c35bc35, 0xbc35bc35, 0xbc353c35,
    0x3c353c35, 0x3c35bc35, 0xbc35bc35, 0xbc353c35, 0x3c7fbac9, 0xbb95bc75, 0xbc623bf1, 0x3c223c46, 0x3c463c22, 0x3bf1bc62,
    0xbc75bb95, 0xbac93c7f, 0xbac9bc7f, 0xbc753b95, 0x3bf13c62, 0x3c46bc22, 0x3c22bc46, 0xbc62bbf1, 0xbb953c75, 0x3c7f3ac9,
    0xbc7f3ac9, 0x3b953c75, 0x3c62bbf1, 0xbc22bc46, 0xbc46bc22, 0xbbf13c62, 0x3c753b95, 0x3ac9bc7f, 0x3ac93c7f, 0x3c75bb95,
    0xbbf1bc62, 0xbc463c22, 0xbc223c46, 0x3c623bf1, 0x3b95bc75, 0xbc7fbac9, 0xbc55bc0e, 0xbb483c7b, 0x3c7bbb48, 0xbc0ebc55,
    0xbc0e3c55, 0x3c7b3b48, 0xbb48bc7b, 0xbc553c0e, 0x3c553c0e, 0x3b48bc7b, 0xbc7b3b48, 0x3c0e3c55, 0x3c0ebc55, 0xbc7bbb48,
    0x3b483c7b, 0x3c55bc0e, 0xbc55bc0e, 0xbb483c7b, 0x3c7bbb48, 0xbc0ebc55, 0xbc0e3c55, 0x3c7b3b48, 0xbb48bc7b, 0xbc553c0e,
    0x3c553c0e, 0x3b48bc7b, 0xbc7b3b48, 0x3c0e3c55, 0x3c0ebc55, 0xbc7bbb48, 0x3b483c7b, 0x3c55bc0e, 0x3c75bb95, 0xbc46bc22,
    0xbac93c7f, 0x3c62bbf1, 0xbbf13c62, 0x3c7fbac9, 0xbc22bc46, 0xbb953c75, 0xbb95bc75, 0xbc223c46, 0x3c7f3ac9, 0xbbf1bc62,
    0x3c623bf1, 0xbac9bc7f, 0xbc463c22, 0x3c753b95, 0xbc753b95, 0x3c463c22, 0x3ac9bc7f, 0xbc623bf1, 0x3bf1bc62, 0xbc7f3ac9,
    0x3c223c46, 0x3b95bc75, 0x3b953c75, 0x3c22bc46, 0xbc7fbac9, 0x3bf13c62, 0xbc62bbf1, 0x3ac93c7f, 0x3c46bc22, 0xbc75bb95,
    0x3c6d3bc4, 0xbbc4bc6d, 0xbbc43c6d, 0x3c6dbbc4, 0xbc6dbbc4, 0x3bc43c6d, 0x3bc4bc6d, 0xbc6d3bc4, 0x3c6d3bc4, 0xbbc4bc6d,
    0xbbc43c6d, 0x3c6dbbc4, 0xbc6dbbc4, 0x3bc43c6d, 0x3bc4bc6d, 0xbc6d3bc4, 0x3c6d3bc4, 0xbbc4bc6d, 0xbbc43c6d, 0x3c6dbbc4,
    0xbc6dbbc4, 0x3bc43c6d, 0x3bc4bc6d, 0xbc6d3bc4, 0x3c6d3bc4, 0xbbc4bc6d, 0xbbc43c6d, 0x3c6dbbc4, 0xbc6dbbc4, 0x3bc43c6d,
    0x3bc4bc6d, 0xbc6d3bc4, 0x3c62bbf1, 0xbc7fbac9, 0x3c463c22, 0xbb95bc75, 0xbc75bb95, 0x3c223c46, 0xbac9bc7f, 0xbbf13c62,
    0xbbf1bc62, 0xbac93c7f, 0x3c22bc46, 0xbc753b95, 0xbb953c75, 0x3c46bc22, 0xbc7f3ac9, 0x3c623bf1, 0xbc623bf1, 0x3c7f3ac9,
    0xbc46bc22, 0x3b953c75, 0x3c753b95, 0xbc22bc46, 0x3ac93c7f, 0x3bf1bc62, 0x3bf13c62, 0x3ac9bc7f, 0xbc223c46, 0x3c75bb95,
    0x3b95bc75, 0xbc463c22, 0x3c7fbac9, 0xbc62bbf1, 0xbc7bbb48, 0x3c553c0e, 0xbc0ebc55, 0x3b483c7b, 0x3b48bc7b, 0xbc0e3c55,
    0x3c55bc0e, 0xbc7b3b48, 0x3c7b3b48, 0xbc55bc0e, 0x3c0e3c55, 0xbb48bc7b, 0xbb483c7b, 0x3c0ebc55, 0xbc553c0e, 0x3c7bbb48,
    0xbc7bbb48, 0x3c553c0e, 0xbc0ebc55, 0x3b483c7b, 0x3b48bc7b, 0xbc0e3c55, 0x3c55bc0e, 0xbc7b3b48, 0x3c7b3b48, 0xbc55bc0e,
    0x3c0e3c55, 0xbb48bc7b, 0xbb483c7b, 0x3c0ebc55, 0xbc553c0e, 0x3c7bbb48, 0x3c46bc22, 0xbc623bf1, 0x3c75bb95, 0xbc7f3ac9,
    0x3ac9bc7f, 0xbb953c75, 0x3bf1bc62, 0xbc223c46, 0xbc22bc46, 0x3bf13c62, 0xbb95bc75, 0x3ac93c7f, 0xbc7fbac9, 0x3c753b95,
    0xbc62bbf1, 0x3c463c22, 0xbc463c22, 0x3c62bbf1, 0xbc753b95, 0x3c7fbac9, 0xbac93c7f, 0x3b95bc75, 0xbbf13c62, 0x3c22bc46,
    0x3c223c46, 0xbbf1bc62, 0x3b953c75, 0xbac9bc7f, 0x3c7f3ac9, 0xbc75bb95, 0x3c623bf1, 0xbc46bc22, 0x3c3e3c2c, 0x3c18bc4e,
    0xbc5cbc04, 0xbbdb3c67, 0x3c713bac, 0x3b79bc78, 0xbc7dbb16, 0xba493c80, 0x3c80ba49, 0xbb16bc7d, 0xbc783b79, 0x3bac3c71,
    0x3c67bbdb, 0xbc04bc5c, 0xbc4e3c18, 0x3c2c3c3e, 0x3c2cbc3e, 0xbc4ebc18, 0xbc043c5c, 0x3c673bdb, 0x3bacbc71, 0xbc78bb79,
    0xbb163c7d, 0x3c803a49, 0xba49bc80, 0xbc7d3b16, 0x3b793c78, 0x3c71bbac, 0xbbdbbc67, 0xbc5c3c04, 0x3c183c4e, 0x3c3ebc2c,
    0x3c5cbc04, 0xbc3ebc2c, 0xbbdb3c67, 0x3c7d3b16, 0x3c4e3c18, 0x3bacbc71, 0xbc80ba49, 0x3b793c78, 0xbc78bb79, 0x3a493c80,
    0x3c71bbac, 0xbc18bc4e, 0xbb16bc7d, 0xbc673bdb, 0x3c2c3c3e, 0x3c04bc5c, 0x3c043c5c, 0x3c2cbc3e, 0xbc67bbdb, 0xbb163c7d,
    0xbc183c4e, 0x3c713bac, 0x3a49bc80, 0xbc783b79, 0x3b79bc78, 0xbc803a49, 0x3bac3c71, 0x3c4ebc18, 0x3c7dbb16, 0xbbdbbc67,
    0xbc3e3c2c, 0x3c5c3c04, 0xbc783b79, 0x3c2c3c3e, 0x3bacbc71, 0xbc7d3b16, 0x3c183c4e, 0x3bdbbc67, 0xbc803a49, 0x3c043c5c,
    0x3c5c3c04, 0x3a49bc80, 0xbc673bdb, 0x3c4e3c18, 0x3b16bc7d, 0xbc713bac, 0x3c3e3c2c, 0x3b79bc78, 0x3b793c78, 0x3c3ebc2c,
    0xbc71bbac, 0x3b163c7d, 0x3c4ebc18, 0xbc67bbdb, 0x3a493c80, 0x3c5cbc04, 0x3c04bc5c, 0xbc80ba49, 0x3bdb3c67, 0x3c18bc4e,
    0xbc7dbb16, 0x3bac3c71, 0x3c2cbc3e, 0xbc78bb79, 0x3a49bc80, 0xbc4e3c18, 0x3c783b79, 0xbbdbbc67, 0x3bac3c71, 0x3c04bc5c,
    0xbc7d3b16, 0x3c3e3c2c, 0xbc2cbc3e, 0xbb163c7d, 0x3c5cbc04, 0xbc71bbac, 0x3c673bdb, 0xbb79bc78, 0xbc183c4e, 0x3c80ba49,
    0x3c803a49, 0xbc18bc4e, 0xbb793c78, 0x3c67bbdb, 0xbc713bac, 0x3c5c3c04, 0xbb16bc7d, 0xbc2c3c3e, 0x3c3ebc2c, 0xbc7dbb16,
    0x3c043c5c, 0x3bacbc71, 0xbbdb3c67, 0x3c78bb79, 0xbc4ebc18, 0x3a493c80, 0x3bacbc71, 0xbc5c3c04, 0x3c7d3b16, 0xbc2cbc3e,
    0x3a493c80, 0x3c18bc4e, 0xbc783b79, 0x3c673bdb, 0xbbdbbc67, 0xbb793c78, 0x3c4ebc18, 0xbc80ba49, 0x3c3e3c2c, 0xbb16bc7d,
    0xbc043c5c, 0x3c71bbac, 0x3c713bac, 0xbc04bc5c, 0xbb163c7d, 0x3c3ebc2c, 0xbc803a49, 0x3c4e3c18, 0xbb79bc78, 0xbbdb3c67,
    0x3c67bbdb, 0xbc78bb79, 0x3c183c4e, 0x3a49bc80, 0xbc2c3c3e, 0x3c7dbb16, 0xbc5cbc04, 0x3bac3c71, 0xbc4ebc18, 0x3bdb3c67,
    0x3a49bc80, 0xbc043c5c, 0xbb793c78, 0x3c2cbc3e, 0xbc713bac, 0x3c7d3b16, 0x3b163c7d, 0x3bacbc71, 0xbc3e3c2c, 0x3c78bb79,
    0x3c5cbc04, 0xbc803a49, 0x3c673bdb, 0xbc18bc4e, 0xbc183c4e, 0x3c67bbdb, 0xbc80ba49, 0x3c5c3c04, 0x3c783b79, 0xbc3ebc2c,
    0x3bac3c71, 0x3b16bc7d, 0x3c7dbb16, 0xbc71bbac, 0x3c2c3c3e, 0xbb79bc78, 0xbc04bc5c, 0x3a493c80, 0x3bdbbc67, 0xbc4e3c18,
    0x3c183c4e, 0xbbacbc71, 0x3a493c80, 0x3b79bc78, 0xbc043c5c, 0x3c3ebc2c, 0xbc673bdb, 0x3c7dbb16, 0x3b16bc7d, 0xbbdb3c67,
    0x3c2cbc3e, 0xbc5c3c04, 0x3c78bb79, 0xbc80ba49, 0x3c713bac, 0xbc4ebc18, 0xbc4e3c18, 0x3c71bbac, 0xbc803a49, 0x3c783b79,
    0xbc5cbc04, 0x3c2c3c3e, 0xbbdbbc67, 0x3b163c7d, 0x3c7d3b16, 0xbc67bbdb, 0x3c3e3c2c, 0xbc04bc5c, 0x3b793c78, 0x3a49bc80,
    0xbbac3c71, 0x3c18bc4e, 0xbc713bac, 0x3c78bb79, 0xbc7d3b16, 0x3c80ba49, 0xbc3e3c2c, 0x3c4ebc18, 0xbc5c3c04, 0x3c67bbdb,
    0xbbdb3c67, 0x3c04bc5c, 0xbc183c4e, 0x3c2cbc3e, 0xba493c80, 0x3b16bc7d, 0xbb793c78, 0x3bacbc71, 0x3bac3c71, 0xbb79bc78,
    0x3b163c7d, 0xba49bc80, 0x3c2c3c3e, 0xbc18bc4e, 0x3c043c5c, 0xbbdbbc67, 0x3c673bdb, 0xbc5cbc04, 0x3c4e3c18, 0xbc3ebc2c,
    0x3c803a49, 0xbc7dbb16, 0x3c783b79, 0xbc71bbac, 0x3c800000, 0xbc800000, 0x3c800000, 0xbc800000, 0x3c800000, 0xbc800000,
    0x3c800000, 0xbc800000, 0x3c800000, 0xbc800000, 0x3c800000, 0xbc800000, 0x3c800000, 0xbc800000, 0x3c800000, 0xbc800000,
    0x3c800000, 0xbc800000, 0x3c800000, 0xbc800000, 0x3c800000, 0xbc800000, 0x3c800000, 0xbc800000, 0x3c800000, 0xbc800000,
    0x3c800000, 0xbc800000, 0x3c800000, 0xbc800000, 0x3c800000, 0xbc800000, 0x3c22bc46, 0xbbf13c62, 0x3b95bc75, 0xbac93c7f,
    0x3c7fbac9, 0xbc753b95, 0x3c62bbf1, 0xbc463c22, 0xbc46bc22, 0x3c623bf1, 0xbc75bb95, 0x3c7f3ac9, 0xbac9bc7f, 0x3b953c75,
    0xbbf1bc62, 0x3c223c46, 0xbc223c46, 0x3bf1bc62, 0xbb953c75, 0x3ac9bc7f, 0xbc7f3ac9, 0x3c75bb95, 0xbc623bf1, 0x3c46bc22,
    0x3c463c22, 0xbc62bbf1, 0x3c753b95, 0xbc7fbac9, 0x3ac93c7f, 0xbb95bc75, 0x3bf13c62, 0xbc22bc46, 0xbc7b3b48, 0x3c55bc0e,
    0xbc0e3c55, 0x3b48bc7b, 0x3b483c7b, 0xbc0ebc55, 0x3c553c0e, 0xbc7bbb48, 0x3c7bbb48, 0xbc553c0e, 0x3c0ebc55, 0xbb483c7b,
    0xbb48bc7b, 0x3c0e3c55, 0xbc55bc0e, 0x3c7b3b48, 0xbc7b3b48, 0x3c55bc0e, 0xbc0e3c55, 0x3b48bc7b, 0x3b483c7b, 0xbc0ebc55,
    0x3c553c0e, 0xbc7bbb48, 0x3c7bbb48, 0xbc553c0e, 0x3c0ebc55, 0xbb483c7b, 0xbb48bc7b, 0x3c0e3c55, 0xbc55bc0e, 0x3c7b3b48,
    0x3bf1bc62, 0x3ac93c7f, 0xbc22bc46, 0x3c753b95, 0x3b953c75, 0xbc46bc22, 0x3c7f3ac9, 0xbc623bf1, 0xbc62bbf1, 0x3c7fbac9,
    0xbc463c22, 0x3b95bc75, 0x3c75bb95, 0xbc223c46, 0x3ac9bc7f, 0x3bf13c62, 0xbbf13c62, 0xbac9bc7f, 0x3c223c46, 0xbc75bb95,
    0xbb95bc75, 0x3c463c22, 0xbc7fbac9, 0x3c62bbf1, 0x3c623bf1, 0xbc7f3ac9, 0x3c46bc22, 0xbb953c75, 0xbc753b95, 0x3c22bc46,
    0xbac93c7f, 0xbbf1bc62, 0x3c6dbbc4, 0xbbc43c6d, 0xbbc4bc6d, 0x3c6d3bc4, 0xbc6d3bc4, 0x3bc4bc6d, 0x3bc43c6d, 0xbc6dbbc4,
    0x3c6dbbc4, 0xbbc43c6d, 0xbbc4bc6d, 0x3c6d3bc4, 0xbc6d3bc4, 0x3bc4bc6d, 0x3bc43c6d, 0xbc6dbbc4, 0x3c6dbbc4, 0xbbc43c6d,
    0xbbc4bc6d, 0x3c6d3bc4, 0xbc6d3bc4, 0x3bc4bc6d, 0x3bc43c6d, 0xbc6dbbc4, 0x3c6dbbc4, 0xbbc43c6d, 0xbbc4bc6d, 0x3c6d3bc4,
    0xbc6d3bc4, 0x3bc4bc6d, 0x3bc43c6d, 0xbc6dbbc4, 0x3b95bc75, 0x3c223c46, 0xbc7f3ac9, 0x3bf1bc62, 0xbc623bf1, 0x3ac9bc7f,
    0x3c463c22, 0xbc753b95, 0xbc75bb95, 0x3c46bc22, 0x3ac93c7f, 0xbc62bbf1, 0x3bf13c62, 0xbc7fbac9, 0x3c22bc46, 0x3b953c75,
    0xbb953c75, 0xbc22bc46, 0x3c7fbac9, 0xbbf13c62, 0x3c62bbf1, 0xbac93c7f, 0xbc46bc22, 0x3c75bb95, 0x3c753b95, 0xbc463c22,
    0xbac9bc7f, 0x3c623bf1, 0xbbf1bc62, 0x3c7f3ac9, 0xbc223c46, 0xbb95bc75, 0xbc553c0e, 0xbb48bc7b, 0x3c7b3b48, 0xbc0e3c55,
    0xbc0ebc55, 0x3c7bbb48, 0xbb483c7b, 0xbc55bc0e, 0x3c55bc0e, 0x3b483c7b, 0xbc7bbb48, 0x3c0ebc55, 0x3c0e3c55, 0xbc7b3b48,
    0x3b48bc7b, 0x3c553c0e, 0xbc553c0e, 0xbb48bc7b, 0x3c7b3b48, 0xbc0e3c55, 0xbc0ebc55, 0x3c7bbb48, 0xbb483c7b, 0xbc55bc0e,
    0x3c55bc0e, 0x3b483c7b, 0xbc7bbb48, 0x3c0ebc55, 0x3c0e3c55, 0xbc7b3b48, 0x3b48bc7b, 0x3c553c0e, 0x3ac9bc7f, 0x3c753b95,
    0xbbf13c62, 0xbc46bc22, 0xbc22bc46, 0x3c62bbf1, 0x3b953c75, 0xbc7f3ac9, 0xbc7fbac9, 0x3b95bc75, 0x3c623bf1, 0xbc223c46,
    0xbc463c22, 0xbbf1bc62, 0x3c75bb95, 0x3ac93c7f, 0xbac93c7f, 0xbc75bb95, 0x3bf1bc62, 0x3c463c22, 0x3c223c46, 0xbc623bf1,
    0xbb95bc75, 0x3c7fbac9, 0x3c7f3ac9, 0xbb953c75, 0xbc62bbf1, 0x3c22bc46, 0x3c46bc22, 0x3bf13c62, 0xbc753b95, 0xbac9bc7f,
    0x3c80ba49, 0xbc7d3b16, 0x3c78bb79, 0xbc713bac, 0x3c67bbdb, 0xbc5c3c04, 0x3c4ebc18, 0xbc3e3c2c, 0x3c2cbc3e, 0xbc183c4e,
    0x3c04bc5c, 0xbbdb3c67, 0x3bacbc71, 0xbb793c78, 0x3b16bc7d, 0xba493c80, 0xba49bc80, 0x3b163c7d, 0xbb79bc78, 0x3bac3c71,
    0xbbdbbc67, 0x3c043c5c, 0xbc18bc4e, 0x3c2c3c3e, 0xbc3ebc2c, 0x3c4e3c18, 0xbc5cbc04, 0x3c673bdb, 0xbc71bbac, 0x3c783b79,
    0xbc7dbb16, 0x3c803a49, 0x3b79bc78, 0x3a493c80, 0xbbacbc71, 0x3c183c4e, 0x3c7dbb16, 0xbc673bdb, 0x3c3ebc2c, 0xbc043c5c,
    0xbc5c3c04, 0x3c2cbc3e, 0xbbdb3c67, 0x3b16bc7d, 0xbc4ebc18, 0x3c713bac, 0xbc80ba49, 0x3c78bb79, 0x3c783b79, 0xbc803a49,
    0x3c71bbac, 0xbc4e3c18, 0x3b163c7d, 0xbbdbbc67, 0x3c2c3c3e, 0xbc5cbc04, 0xbc04bc5c, 0x3c3e3c2c, 0xbc67bbdb, 0x3c7d3b16,
    0x3c18bc4e, 0xbbac3c71, 0x3a49bc80, 0x3b793c78, 0xbc043c5c, 0x3a49bc80, 0x3bdb3c67, 0xbc4ebc18, 0x3c7d3b16, 0xbc713bac,
    0x3c2cbc3e, 0xbb793c78, 0x3c78bb79, 0xbc3e3c2c, 0x3bacbc71, 0x3b163c7d, 0xbc18bc4e, 0x3c673bdb, 0xbc803a49, 0x3c5cbc04,
    0x3c5c3c04, 0xbc80ba49, 0x3c67bbdb, 0xbc183c4e, 0x3b16bc7d, 0x3bac3c71, 0xbc3ebc2c, 0x3c783b79, 0xbb79bc78, 0x3c2c3c3e,
    0xbc71bbac, 0x3c7dbb16, 0xbc4e3c18, 0x3bdbbc67, 0x3a493c80, 0xbc04bc5c, 0xbc2cbc3e, 0x3c7d3b16, 0xbc5c3c04, 0x3bacbc71,
    0x3c673bdb, 0xbc783b79, 0x3c18bc4e, 0x3a493c80, 0xbc80ba49, 0x3c4ebc18, 0xbb793c78, 0xbbdbbc67, 0x3c71bbac, 0xbc043c5c,
    0xbb16bc7d, 0x3c3e3c2c, 0x3c3ebc2c, 0xbb163c7d, 0xbc04bc5c, 0x3c713bac, 0xbbdb3c67, 0xbb79bc78, 0x3c4e3c18, 0xbc803a49,
    0x3a49bc80, 0x3c183c4e, 0xbc78bb79, 0x3c67bbdb, 0x3bac3c71, 0xbc5cbc04, 0x3c7dbb16, 0xbc2c3c3e, 0xbbdbbc67, 0x3c783b79,
    0xbc4e3c18, 0x3a49bc80, 0x3c3e3c2c, 0xbc7d3b16, 0x3c04bc5c, 0x3bac3c71, 0xbc71bbac, 0x3c5cbc04, 0xbb163c7d, 0xbc2cbc3e,
    0x3c80ba49, 0xbc183c4e, 0xbb79bc78, 0x3c673bdb, 0x3c67bbdb, 0xbb793c78, 0xbc18bc4e, 0x3c803a49, 0xbc2c3c3e, 0xbb16bc7d,
    0x3c5c3c04, 0xbc713bac, 0x3bacbc71, 0x3c043c5c, 0xbc7dbb16, 0x3c3ebc2c, 0x3a493c80, 0xbc4ebc18, 0x3c78bb79, 0xbbdb3c67,
    0xbc7d3b16, 0x3bacbc71, 0x3c2c3c3e, 0xbc783b79, 0x3c043c5c, 0xbc803a49, 0x3bdbbc67, 0x3c183c4e, 0x3c4e3c18, 0xbc673bdb,
    0x3a49bc80, 0x3c5c3c04, 0x3b79bc78, 0x3c3e3c2c, 0xbc713bac, 0x3b16bc7d, 0x3b163c7d, 0xbc71bbac, 0x3c3ebc2c, 0x3b793c78,
    0x3c5cbc04, 0x3a493c80, 0xbc67bbdb, 0x3c4ebc18, 0x3c18bc4e, 0x3bdb3c67, 0xbc80ba49, 0x3c04bc5c, 0xbc78bb79, 0x3c2cbc3e,
    0x3bac3c71, 0xbc7dbb16, 0x3c7d3b16, 0xbbdb3c67, 0xbc3ebc2c, 0x3c5cbc04, 0x3b793c78, 0xbc80ba49, 0x3bacbc71, 0x3c4e3c18,
    0xbc18bc4e, 0x3c71bbac, 0x3a493c80, 0xbc78bb79, 0x3c04bc5c, 0x3c2c3c3e, 0xbc673bdb, 0xbb16bc7d, 0xbb163c7d, 0xbc67bbdb,
    0x3c2cbc3e, 0x3c043c5c, 0xbc783b79, 0x3a49bc80, 0x3c713bac, 0xbc183c4e, 0x3c4ebc18, 0x3bac3c71, 0xbc803a49, 0x3b79bc78,
    0x3c5c3c04, 0xbc3e3c2c, 0xbbdbbc67, 0x3c7dbb16, 0xbbdb3c67, 0xbc5cbc04, 0x3c18bc4e, 0x3c3e3c2c, 0xba493c80, 0xbc7dbb16,
    0x3b79bc78, 0x3c713bac, 0x3bac3c71, 0xbc783b79, 0xbb16bc7d, 0x3c80ba49, 0x3c2c3c3e, 0xbc4e3c18, 0xbc04bc5c, 0x3c67bbdb,
    0x3c673bdb, 0xbc043c5c, 0xbc4ebc18, 0x3c2cbc3e, 0x3c803a49, 0xbb163c7d, 0xbc78bb79, 0x3bacbc71, 0x3c71bbac, 0x3b793c78,
    0xbc7d3b16, 0xba49bc80, 0x3c3ebc2c, 0x3c183c4e, 0xbc5c3c04, 0xbbdbbc67, 0x3f803f80, 0x3f7d3f7f, 0x3f783f7b, 0x3f713f75,
    0x3f673f6d, 0x3f5c3f62, 0x3f4e3f55, 0x3f3e3f46, 0x3f2c3f35, 0x3f183f22, 0x3f043f0e, 0x3edb3ef1, 0x3eac3ec4, 0x3e793e95,
    0x3e163e48, 0x3d493dc9, 0xbd490000, 0xbe16bdc9, 0xbe79be48, 0xbeacbe95, 0xbedbbec4, 0xbf04bef1, 0xbf18bf0e, 0xbf2cbf22,
    0xbf3ebf35, 0xbf4ebf46, 0xbf5cbf55, 0xbf67bf62, 0xbf71bf6d, 0xbf78bf75, 0xbf7dbf7b, 0xbf80bf7f, 0x3edb3ec4, 0x3f043ef1,
    0x3f183f0e, 0x3f2c3f22, 0x3d490000, 0x3e163dc9, 0x3e793e48, 0x3eac3e95, 0x3f713f6d, 0x3f783f75, 0x3f7d3f7b, 0x3f803f7f,
    0x3f3e3f35, 0x3f4e3f46, 0x3f5c3f55, 0x3f673f62, 0x3f673f6d, 0x3f5c3f62, 0x3f4e3f55, 0x3f3e3f46, 0x3f803f80, 0x3f7d3f7f,
    0x3f783f7b, 0x3f713f75, 0x3eac3ec4, 0x3e793e95, 0x3e163e48, 0x3d493dc9, 0x3f2c3f35, 0x3f183f22, 0x3f043f0e, 0x3edb3ef1,
    0xbf4ebf35, 0xbf71bf62, 0xbf80bf7b, 0xbf78bf7f, 0xbf5cbf6d, 0xbf2cbf46, 0xbedbbf0e, 0xbe16be95, 0x3f7d3f80, 0x3f673f75,
    0x3f3e3f55, 0x3f043f22, 0x3e793ec4, 0xbd493dc9, 0xbeacbe48, 0xbf18bef1, 0x3f183f35, 0x3eac3ef1, 0x3d493e48, 0xbe79bdc9,
    0xbf04bec4, 0xbf3ebf22, 0xbf67bf55, 0xbf7dbf75, 0x3e160000, 0x3edb3e95, 0x3f2c3f0e, 0x3f5c3f46, 0x3f783f6d, 0x3f803f7f,
    0x3f713f7b, 0x3f4e3f62, 0xbf04bec4, 0xbf3ebf22, 0xbf67bf55, 0xbf7dbf75, 0x3f183f35, 0x3eac3ef1, 0x3d493e48, 0xbe79bdc9,
    0x3f783f6d, 0x3f803f7f, 0x3f713f7b, 0x3f4e3f62, 0x3e160000, 0x3edb3e95, 0x3f2c3f0e, 0x3f5c3f46, 0x3f5c3f6d, 0x3f2c3f46,
    0x3edb3f0e, 0x3e163e95, 0x3f4e3f35, 0x3f713f62, 0x3f803f7b, 0x3f783f7f, 0xbe79bec4, 0x3d49bdc9, 0x3eac3e48, 0x3f183ef1,
    0xbf7dbf80, 0xbf67bf75, 0xbf3ebf55, 0xbf04bf22, 0xbe790000, 0xbf2cbef1, 0xbf71bf55, 0xbf7dbf7f, 0xbf4ebf6d, 0xbedbbf22,
    0x3d49be48, 0x3f043e95, 0x3f5c3f35, 0x3f803f75, 0x3f673f7b, 0x3f183f46, 0x3e163ec4, 0xbeacbdc9, 0xbf3ebf0e, 0xbf78bf62,
    0x3f783f80, 0x3f3e3f62, 0x3eac3f0e, 0xbe163dc9, 0xbf18bec4, 0xbf67bf46, 0xbf80bf7b, 0xbf5cbf75, 0xbf04bf35, 0xbd49be95,
    0x3edb3e48, 0x3f4e3f22, 0x3f7d3f6d, 0x3f713f7f, 0x3f2c3f55, 0x3e793ef1, 0xbf18bec4, 0xbf67bf46, 0xbf80bf7b, 0xbf5cbf75,
    0x3f783f80, 0x3f3e3f62, 0x3eac3f0e, 0xbe163dc9, 0x3f7d3f6d, 0x3f713f7f, 0x3f2c3f55, 0x3e793ef1, 0xbf04bf35, 0xbd49be95,
    0x3edb3e48, 0x3f4e3f22, 0x3f4e3f6d, 0x3edb3f22, 0xbd493e48, 0xbf04be95, 0x3e790000, 0x3f2c3ef1, 0x3f713f55, 0x3f7d3f7f,
    0xbe16bec4, 0x3eac3dc9, 0x3f3e3f0e, 0x3f783f62, 0xbf5cbf35, 0xbf80bf75, 0xbf67bf7b, 0xbf18bf46, 0xbedbbf35, 0x3e79bdc9,
    0x3f4e3f0e, 0x3f803f75, 0x3f3e3f6d, 0x3e163ef1, 0xbf04be48, 0xbf71bf46, 0x3eac0000, 0x3f5c3f22, 0x3f7d3f7b, 0x3f2c3f62,
    0x3d493ec4, 0xbf18be95, 0xbf78bf55, 0xbf67bf7f, 0x3f673f35, 0x3f783f7f, 0x3f183f55, 0xbd493e95, 0xbf2cbec4, 0xbf7dbf62,
    0xbf5cbf7b, 0xbeacbf22, 0x3f713f80, 0x3f043f46, 0xbe163e48, 0xbf3ebef1, 0xbf80bf6d, 0xbf4ebf75, 0xbe79bf0e, 0x3edb3dc9,
    0x3f2c3ec4, 0x3f7d3f62, 0x3f5c3f7b, 0x3eac3f22, 0xbf67bf35, 0xbf78bf7f, 0xbf18bf55, 0x3d49be95, 0x3f803f6d, 0x3f4e3f75,
    0x3e793f0e, 0xbedbbdc9, 0xbf71bf80, 0xbf04bf46, 0x3e16be48, 0x3f3e3ef1, 0x3f3e3f6d, 0x3e163ef1, 0xbf04be48, 0xbf71bf46,
    0xbedbbf35, 0x3e79bdc9, 0x3f4e3f0e, 0x3f803f75, 0x3d493ec4, 0xbf18be95, 0xbf78bf55, 0xbf67bf7f, 0x3eac0000, 0x3f5c3f22,
    0x3f7d3f7b, 0x3f2c3f62, 0x3f673f80, 0x3e793f22, 0xbf18be48, 0xbf80bf62, 0xbf2cbf6d, 0x3e16be95, 0x3f5c3f0e, 0x3f713f7f,
    0x3eac3f35, 0xbf04bdc9, 0xbf7dbf55, 0xbf3ebf75, 0x3d49bec4, 0x3f4e3ef1, 0x3f783f7b, 0x3edb3f46, 0xbedb0000, 0xbf78bf46,
    0xbf4ebf7b, 0xbd49bef1, 0x3f3e3ec4, 0x3f7d3f75, 0x3f043f55, 0xbeac3dc9, 0xbf71bf35, 0xbf5cbf7f, 0xbe16bf0e, 0x3f2c3e95,
    0x3f803f6d, 0x3f183f62, 0xbe793e48, 0xbf67bf22, 0xbf3ebec4, 0xbf7dbf75, 0xbf04bf55, 0x3eacbdc9, 0x3edb0000, 0x3f783f46,
    0x3f4e3f7b, 0x3d493ef1, 0xbf80bf6d, 0xbf18bf62, 0x3e79be48, 0x3f673f22, 0x3f713f35, 0x3f5c3f7f, 0x3e163f0e, 0xbf2cbe95,
    0xbf2cbf6d, 0x3e16be95, 0x3f5c3f0e, 0x3f713f7f, 0x3f673f80, 0x3e793f22, 0xbf18be48, 0xbf80bf62, 0x3d49bec4, 0x3f4e3ef1,
    0x3f783f7b, 0x3edb3f46, 0x3eac3f35, 0xbf04bdc9, 0xbf7dbf55, 0xbf3ebf75, 0xbf78bf35, 0xbf2cbf75, 0x3eacbe48, 0x3f7d3f46,
    0x3f183f6d, 0xbedb3dc9, 0xbf80bf55, 0xbf04bf62, 0x3f5c3f80, 0xbd493ef1, 0xbf67bf0e, 0xbf4ebf7f, 0x3e16bec4, 0x3f713f22,
    0x3f3e3f7b, 0xbe793e95, 0x3e793f35, 0xbf3ebe95, 0xbf71bf7b, 0xbe16bf22, 0x3f4e3ec4, 0x3f673f7f, 0x3d493f0e, 0xbf5cbef1,
    0x3f040000, 0x3f803f62, 0x3edb3f55, 0xbf18bdc9, 0xbf7dbf6d, 0xbeacbf46, 0x3f2c3e48, 0x3f783f75, 0x3f4e3ec4, 0x3f673f7f,
    0x3d493f0e, 0xbf5cbef1, 0x3e793f35, 0xbf3ebe95, 0xbf71bf7b, 0xbe16bf22, 0xbf7dbf6d, 0xbeacbf46, 0x3f2c3e48, 0x3f783f75,
    0x3f040000, 0x3f803f62, 0x3edb3f55, 0xbf18bdc9, 0xbf18bf6d, 0x3edbbdc9, 0x3f803f55, 0x3f043f62, 0x3f783f35, 0x3f2c3f75,
    0xbeac3e48, 0xbf7dbf46, 0xbe163ec4, 0xbf71bf22, 0xbf3ebf7b, 0x3e79be95, 0xbf5cbf80, 0x3d49bef1, 0x3f673f0e, 0x3f4e3f7f,
    0xbf180000, 0xbf71bf75, 0x3d49bf0e, 0x3f783f22, 0x3f043f6d, 0xbf2cbdc9, 0xbf67bf7b, 0x3e16bef1, 0x3f7d3f35, 0x3edb3f62,
    0xbf3ebe48, 0xbf5cbf7f, 0x3e79bec4, 0x3f803f46, 0x3eac3f55, 0xbf4ebe95, 0x3f4e3f80, 0xbeac3e95, 0xbf80bf55, 0xbe79bf46,
    0x3f5c3ec4, 0x3f3e3f7f, 0xbedb3e48, 0xbf7dbf62, 0xbe16bf35, 0x3f673ef1, 0x3f2c3f7b, 0xbf043dc9, 0xbf78bf6d, 0xbd49bf22,
    0x3f713f0e, 0x3f183f75, 0x3f5c3ec4, 0x3f3e3f7f, 0xbedb3e48, 0xbf7dbf62, 0x3f4e3f80, 0xbeac3e95, 0xbf80bf55, 0xbe79bf46,
    0xbf78bf6d, 0xbd49bf22, 0x3f713f0e, 0x3f183f75, 0xbe16bf35, 0x3f673ef1, 0x3f2c3f7b, 0xbf043dc9, 0xbf04bf6d, 0x3f2c3dc9,
    0x3f673f7b, 0xbe163ef1, 0x3f180000, 0x3f713f75, 0xbd493f0e, 0xbf78bf22, 0xbe793ec4, 0xbf80bf46, 0xbeacbf55, 0x3f4e3e95,
    0xbf7dbf35, 0xbedbbf62, 0x3f3e3e48, 0x3f5c3f7f, 0xbd49bf35, 0x3f7d3f22, 0x3e793f55, 0xbf71bef1, 0xbedbbf6d, 0x3f5c3e95,
    0x3f183f7b, 0xbf3ebdc9, 0x3f2c0000, 0x3f4e3f7f, 0xbf043e48, 0xbf67bf75, 0x3eacbec4, 0x3f783f62, 0xbe163f0e, 0xbf80bf46,
    0x3f803f35, 0x3e163f46, 0xbf78bf0e, 0xbeacbf62, 0x3f673ec4, 0x3f043f75, 0xbf4ebe48, 0xbf2cbf7f, 0x3f3e3f80, 0xbf183dc9,
    0xbf5cbf7b, 0x3edbbe95, 0x3f713f6d, 0xbe793ef1, 0xbf7dbf55, 0x3d49bf22, 0xbf67bec4, 0xbf04bf75, 0x3f4e3e48, 0x3f2c3f7f,
    0xbf80bf35, 0xbe16bf46, 0x3f783f0e, 0x3eac3f62, 0xbf71bf6d, 0x3e79bef1, 0x3f7d3f55, 0xbd493f22, 0xbf3ebf80, 0x3f18bdc9,
    0x3f5c3f7b, 0xbedb3e95, 0xbedbbf6d, 0x3f5c3e95, 0x3f183f7b, 0xbf3ebdc9, 0xbd49bf35, 0x3f7d3f22, 0x3e793f55, 0xbf71bef1,
    0x3eacbec4, 0x3f783f62, 0xbe163f0e, 0xbf80bf46, 0x3f2c0000, 0x3f4e3f7f, 0xbf043e48, 0xbf67bf75, 0x3f2c3f80, 0xbf4ebdc9,
    0xbf04bf7b, 0x3f673e95, 0x3eac3f6d, 0xbf78bef1, 0xbe16bf55, 0x3f803f22, 0xbd493f35, 0xbf7dbf46, 0x3e79bf0e, 0x3f713f62,
    0xbedb3ec4, 0xbf5cbf75, 0x3f18be48, 0x3f3e3f7f, 0xbf3e0000, 0xbf18bf7f, 0x3f5c3e48, 0x3edb3f75, 0xbf71bec4, 0xbe79bf62,
    0x3f7d3f0e, 0x3d493f46, 0xbf80bf35, 0x3e16bf22, 0x3f783f55, 0xbeac3ef1, 0xbf67bf6d, 0x3f04be95, 0x3f4e3f7b, 0xbf2c3dc9,
    0x3f713ec4, 0x3e793f62, 0xbf7dbf0e, 0xbd49bf46, 0x3f3e0000, 0x3f183f7f, 0xbf5cbe48, 0xbedbbf75, 0x3f673f6d, 0xbf043e95,
    0xbf4ebf7b, 0x3f2cbdc9, 0x3f803f35, 0xbe163f22, 0xbf78bf55, 0x3eacbef1, 0x3eac3f6d, 0xbf78bef1, 0xbe16bf55, 0x3f803f22,
    0x3f2c3f80, 0xbf4ebdc9, 0xbf04bf7b, 0x3f673e95, 0xbedb3ec4, 0xbf5cbf75, 0x3f18be48, 0x3f3e3f7f, 0xbd493f35, 0xbf7dbf46,
    0x3e79bf0e, 0x3f713f62, 0xbf7dbf35, 0x3edbbef1, 0x3f3e3f7b, 0xbf5cbdc9, 0xbe79bf6d, 0x3f803f22, 0xbeac3f0e, 0xbf4ebf75,
    0x3f183f80, 0xbf71be95, 0xbd49bf55, 0x3f783f46, 0xbf043ec4, 0xbf2cbf7f, 0x3f673e48, 0x3e163f62, 0xbe163f35, 0xbf67bf62,
    0x3f2cbe48, 0x3f043f7f, 0xbf78bec4, 0x3d49bf46, 0x3f713f55, 0xbf183e95, 0x3f4e0000, 0x3eac3f75, 0xbf80bf0e, 0x3e79bf22,
    0x3f5c3f6d, 0xbf3e3dc9, 0xbedbbf7b, 0x3f7d3ef1, 0xbf78bec4, 0x3d49bf46, 0x3f713f55, 0xbf183e95, 0xbe163f35, 0xbf67bf62,
    0x3f2cbe48, 0x3f043f7f, 0x3f5c3f6d, 0xbf3e3dc9, 0xbedbbf7b, 0x3f7d3ef1, 0x3f4e0000, 0x3eac3f75, 0xbf80bf0e, 0x3e79bf22,
    0x3e793f6d, 0xbf80bf22, 0x3eacbf0e, 0x3f4e3f75, 0x3f7d3f35, 0xbedb3ef1, 0xbf3ebf7b, 0x3f5c3dc9, 0x3f04bec4, 0x3f2c3f7f,
    0xbf67be48, 0xbe16bf62, 0xbf18bf80, 0x3f713e95, 0x3d493f55, 0xbf78bf46, 0xbf5c0000, 0xbd49bf62, 0x3f673f55, 0xbf4e3dc9,
    0xbe16bf6d, 0x3f713f46, 0xbf3e3e48, 0xbe79bf75, 0x3f783f35, 0xbf2c3e95, 0xbeacbf7b, 0x3f7d3f22, 0xbf183ec4, 0xbedbbf7f,
    0x3f803f0e, 0xbf043ef1, 0x3f043f80, 0xbf80bef1, 0x3edbbf0e, 0x3f183f7f, 0xbf7dbec4, 0x3eacbf22, 0x3f2c3f7b, 0xbf78be95,
    0x3e79bf35, 0x3f3e3f75, 0xbf71be48, 0x3e16bf46, 0x3f4e3f6d, 0xbf67bdc9, 0x3d49bf55, 0x3f5c3f62, 0xbf7dbec4, 0x3eacbf22,
    0x3f2c3f7b, 0xbf78be95, 0x3f043f80, 0xbf80bef1, 0x3edbbf0e, 0x3f183f7f, 0x3f4e3f6d, 0xbf67bdc9, 0x3d49bf55, 0x3f5c3f62,
    0x3e79bf35, 0x3f3e3f75, 0xbf71be48, 0x3e16bf46, 0x3e163f6d, 0xbf71bf46, 0x3f3ebe48, 0x3e793f75, 0x3f5c0000, 0x3d493f62,
    0xbf67bf55, 0x3f4ebdc9, 0x3f18bec4, 0x3edb3f7f, 0xbf80bf0e, 0x3f04bef1, 0xbf78bf35, 0x3f2cbe95, 0x3eac3f7b, 0xbf7dbf22,
    0x3eacbf35, 0x3f043f7f, 0xbf7dbf0e, 0x3f3ebe95, 0x3d493f6d, 0xbf4ebf62, 0x3f783e48, 0xbedb3f22, 0x3f670000, 0xbe793f46,
    0xbf18bf7b, 0x3f803ef1, 0xbf2c3ec4, 0xbe16bf75, 0x3f5c3f55, 0xbf71bdc9, 0x3f713f35, 0xbf5c3dc9, 0x3e16bf55, 0x3f2c3f75,
    0xbf80bec4, 0x3f18bef1, 0x3e793f7b, 0xbf67bf46, 0x3edb3f80, 0xbf78bf22, 0x3f4ebe48, 0xbd493f62, 0xbf3ebf6d, 0x3f7d3e95,
    0xbf043f0e, 0xbeacbf7f, 0x3f803ec4, 0xbf183ef1, 0xbe79bf7b, 0x3f673f46, 0xbf71bf35, 0x3f5cbdc9, 0xbe163f55, 0xbf2cbf75,
    0x3f3e3f6d, 0xbf7dbe95, 0x3f04bf0e, 0x3eac3f7f, 0xbedbbf80, 0x3f783f22, 0xbf4e3e48, 0x3d49bf62, 0x3d493f6d, 0xbf4ebf62,
    0x3f783e48, 0xbedb3f22, 0x3eacbf35, 0x3f043f7f, 0xbf7dbf0e, 0x3f3ebe95, 0xbf2c3ec4, 0xbe16bf75, 0x3f5c3f55, 0xbf71bdc9,
    0x3f670000, 0xbe793f46, 0xbf18bf7b, 0x3f803ef1, 0x3eac3f80, 0xbf5cbf46, 0x3f7d3e48, 0xbf2c3ef1, 0x3d49bf6d, 0x3f183f75,
    0xbf78bf0e, 0x3f67bdc9, 0xbedb3f35, 0xbe79bf7f, 0x3f4e3f55, 0xbf80be95, 0x3f3ebec4, 0xbe163f62, 0xbf04bf7b, 0x3f713f22,
    0xbf710000, 0x3f04bf22, 0x3e163f7b, 0xbf3ebf62, 0x3f803ec4, 0xbf4e3e95, 0x3e79bf55, 0x3edb3f7f, 0xbf67bf35, 0x3f783dc9,
    0xbf183f0e, 0xbd49bf75, 0x3f2c3f6d, 0xbf7dbef1, 0x3f5cbe48, 0xbeac3f46, 0xbf80bec4, 0x3f4ebe95, 0xbe793f55, 0xbedbbf7f,
    0x3f710000, 0xbf043f22, 0xbe16bf7b, 0x3f3e3f62, 0xbf2cbf6d, 0x3f7d3ef1, 0xbf5c3e48, 0x3eacbf46, 0x3f673f35, 0xbf78bdc9,
    0x3f18bf0e, 0x3d493f75, 0x3d49bf6d, 0x3f183f75, 0xbf78bf0e, 0x3f67bdc9, 0x3eac3f80, 0xbf5cbf46, 0x3f7d3e48, 0xbf2c3ef1,
    0x3f3ebec4, 0xbe163f62, 0xbf04bf7b, 0x3f713f22, 0xbedb3f35, 0xbe79bf7f, 0x3f4e3f55, 0xbf80be95, 0xbf5cbf35, 0x3f803e95,
    0xbf673e48, 0x3f18bf22, 0xbe163f6d, 0xbeacbf7f, 0x3f3e3f55, 0xbf78bef1, 0x3e793f80, 0xbf2cbf62, 0x3f713f0e, 0xbf7dbdc9,
    0x3f4ebec4, 0xbedb3f46, 0xbd49bf7b, 0x3f043f75, 0xbf043f35, 0x3d49bf75, 0x3edb3f7b, 0xbf4ebf46, 0x3f7d3ec4, 0xbf713dc9,
    0x3f2cbf0e, 0xbe793f62, 0x3f780000, 0xbf3e3ef1, 0x3eacbf55, 0x3e163f7f, 0xbf18bf6d, 0x3f673f22, 0xbf80be48, 0x3f5cbe95,
    0x3f7d3ec4, 0xbf713dc9, 0x3f2cbf0e, 0xbe793f62, 0xbf043f35, 0x3d49bf75, 0x3edb3f7b, 0xbf4ebf46, 0xbf18bf6d, 0x3f673f22,
    0xbf80be48, 0x3f5cbe95, 0x3f780000, 0xbf3e3ef1, 0x3eacbf55, 0x3e163f7f, 0x3e16bf6d, 0x3eac3f7f, 0xbf3ebf55, 0x3f783ef1,
    0x3f5c3f35, 0xbf80be95, 0x3f67be48, 0xbf183f22, 0xbf4e3ec4, 0x3edbbf46, 0x3d493f7b, 0xbf04bf75, 0xbe79bf80, 0x3f2c3f62,
    0xbf71bf0e, 0x3f7d3dc9, 0xbf7d0000, 0x3f67be95, 0xbf3e3f0e, 0x3f04bf46, 0xbe793f6d, 0xbd49bf7f, 0x3eac3f7b, 0xbf18bf62,
    0x3f4e3f35, 0xbf71bef1, 0x3f803e48, 0xbf783dc9, 0x3f5cbec4, 0xbf2c3f22, 0x3edbbf55, 0xbe163f75, 0x3e163f80, 0xbedbbf75,
    0x3f2c3f55, 0xbf5cbf22, 0x3f783ec4, 0xbf80bdc9, 0x3f71be48, 0xbf4e3ef1, 0x3f18bf35, 0xbeac3f62, 0x3d49bf7b, 0x3e793f7f,
    0xbf04bf6d, 0x3f3e3f46, 0xbf67bf0e, 0x3f7d3e95, 0x3f783ec4, 0xbf80bdc9, 0x3f71be48, 0xbf4e3ef1, 0x3e163f80, 0xbedbbf75,
    0x3f2c3f55, 0xbf5cbf22, 0xbf04bf6d, 0x3f3e3f46, 0xbf67bf0e, 0x3f7d3e95, 0x3f18bf35, 0xbeac3f62, 0x3d49bf7b, 0x3e793f7f,
    0x3e79bf6d, 0x3d493f7f, 0xbeacbf7b, 0x3f183f62, 0x3f7d0000, 0xbf673e95, 0x3f3ebf0e, 0xbf043f46, 0xbf5c3ec4, 0x3f2cbf22,
    0xbedb3f55, 0x3e16bf75, 0xbf4ebf35, 0x3f713ef1, 0xbf80be48, 0x3f78bdc9, 0x3f2cbf35, 0xbf183f46, 0x3f04bf55, 0xbedb3f62,
    0x3eacbf6d, 0xbe793f75, 0x3e16bf7b, 0xbd493f7f, 0x3f800000, 0xbf7d3dc9, 0x3f78be48, 0xbf713e95, 0x3f67bec4, 0xbf5c3ef1,
    0x3f4ebf0e, 0xbf3e3f22, 0x3f3e3f35, 0xbf4ebf22, 0x3f5c3f0e, 0xbf67bef1, 0x3f713ec4, 0xbf78be95, 0x3f7d3e48, 0xbf80bdc9,
    0x3d493f80, 0xbe16bf7f, 0x3e793f7b, 0xbeacbf75, 0x3edb3f6d, 0xbf04bf62, 0x3f183f55, 0xbf2cbf46, 0xbf71bec4, 0x3f783e95,
    0xbf7dbe48, 0x3f803dc9, 0xbf3ebf35, 0x3f4e3f22, 0xbf5cbf0e, 0x3f673ef1, 0xbedbbf6d, 0x3f043f62, 0xbf18bf55, 0x3f2c3f46,
    0xbd49bf80, 0x3e163f7f, 0xbe79bf7b, 0x3eac3f75, 0x3eacbf6d, 0xbe793f75, 0x3e16bf7b, 0xbd493f7f, 0x3f2cbf35, 0xbf183f46,
    0x3f04bf55, 0xbedb3f62, 0x3f67bec4, 0xbf5c3ef1, 0x3f4ebf0e, 0xbf3e3f22, 0x3f800000, 0xbf7d3dc9, 0x3f78be48, 0xbf713e95,
    0xbd493f80, 0x3e16bf7f, 0xbe793f7b, 0x3eacbf75, 0xbedb3f6d, 0x3f04bf62, 0xbf183f55, 0x3f2cbf46, 0xbf3e3f35, 0x3f4ebf22,
    0xbf5c3f0e, 0x3f67bef1, 0xbf713ec4, 0x3f78be95, 0xbf7d3e48, 0x3f80bdc9, 0xbf800000, 0x3f7d3dc9, 0xbf78be48, 0x3f713e95,
    0xbf67bec4, 0x3f5c3ef1, 0xbf4ebf0e, 0x3f3e3f22, 0xbf2cbf35, 0x3f183f46, 0xbf04bf55, 0x3edb3f62, 0xbeacbf6d, 0x3e793f75,
    0xbe16bf7b, 0x3d493f7f, 0x3f673ec4, 0xbf5cbef1, 0x3f4e3f0e, 0xbf3ebf22, 0x3f800000, 0xbf7dbdc9, 0x3f783e48, 0xbf71be95,
    0x3eac3f6d, 0xbe79bf75, 0x3e163f7b, 0xbd49bf7f, 0x3f2c3f35, 0xbf18bf46, 0x3f043f55, 0xbedbbf62, 0xbedb3f6d, 0x3f04bf62,
    0xbf183f55, 0x3f2cbf46, 0xbd493f80, 0x3e16bf7f, 0xbe793f7b, 0x3eacbf75, 0xbf713ec4, 0x3f78be95, 0xbf7d3e48, 0x3f80bdc9,
    0xbf3e3f35, 0x3f4ebf22, 0xbf5c3f0e, 0x3f67bef1, 0xbf18bf35, 0x3eac3f62, 0xbd49bf7b, 0xbe793f7f, 0x3f04bf6d, 0xbf3e3f46,
    0x3f67bf0e, 0xbf7d3e95, 0xbe163f80, 0x3edbbf75, 0xbf2c3f55, 0x3f5cbf22, 0xbf783ec4, 0x3f80bdc9, 0xbf71be48, 0x3f4e3ef1,
    0xbf4e3f35, 0x3f71bef1, 0xbf803e48, 0x3f783dc9, 0xbf5cbec4, 0x3f2c3f22, 0xbedbbf55, 0x3e163f75, 0x3f7d0000, 0xbf67be95,
    0x3f3e3f0e, 0xbf04bf46, 0x3e793f6d, 0x3d49bf7f, 0xbeac3f7b, 0x3f18bf62, 0xbf5cbec4, 0x3f2c3f22, 0xbedbbf55, 0x3e163f75,
    0xbf4e3f35, 0x3f71bef1, 0xbf803e48, 0x3f783dc9, 0x3e793f6d, 0x3d49bf7f, 0xbeac3f7b, 0x3f18bf62, 0x3f7d0000, 0xbf67be95,
    0x3f3e3f0e, 0xbf04bf46, 0xbf043f6d, 0x3f3ebf46, 0xbf673f0e, 0x3f7dbe95, 0x3f183f35, 0xbeacbf62, 0x3d493f7b, 0x3e79bf7f,
    0x3f78bec4, 0xbf803dc9, 0x3f713e48, 0xbf4ebef1, 0x3e16bf80, 0xbedb3f75, 0x3f2cbf55, 0xbf5c3f22, 0xbf780000, 0x3f3e3ef1,
    0xbeacbf55, 0xbe163f7f, 0x3f18bf6d, 0xbf673f22, 0x3f80be48, 0xbf5cbe95, 0x3f043f35, 0xbd49bf75, 0xbedb3f7b, 0x3f4ebf46,
    0xbf7d3ec4, 0x3f713dc9, 0xbf2cbf0e, 0x3e793f62, 0xbe793f80, 0x3f2cbf62, 0xbf713f0e, 0x3f7dbdc9, 0xbf4ebec4, 0x3edb3f46,
    0x3d49bf7b, 0xbf043f75, 0x3f5cbf35, 0xbf803e95, 0x3f673e48, 0xbf18bf22, 0x3e163f6d, 0x3eacbf7f, 0xbf3e3f55, 0x3f78bef1,
    0xbf4ebec4, 0x3edb3f46, 0x3d49bf7b, 0xbf043f75, 0xbe793f80, 0x3f2cbf62, 0xbf713f0e, 0x3f7dbdc9, 0x3e163f6d, 0x3eacbf7f,
    0xbf3e3f55, 0x3f78bef1, 0x3f5cbf35, 0xbf803e95, 0x3f673e48, 0xbf18bf22, 0xbf183f6d, 0x3f67bf22, 0xbf803e48, 0x3f5c3e95,
    0x3f780000, 0xbf3ebef1, 0x3eac3f55, 0x3e16bf7f, 0x3f7dbec4, 0xbf71bdc9, 0x3f2c3f0e, 0xbe79bf62, 0xbf04bf35, 0x3d493f75,
    0x3edbbf7b, 0xbf4e3f46, 0x3f67bf35, 0xbf783dc9, 0x3f183f0e, 0x3d49bf75, 0xbf2c3f6d, 0x3f7dbef1, 0xbf5cbe48, 0x3eac3f46,
    0x3f710000, 0xbf04bf22, 0xbe163f7b, 0x3f3ebf62, 0xbf803ec4, 0x3f4e3e95, 0xbe79bf55, 0xbedb3f7f, 0x3edb3f35, 0x3e79bf7f,
    0xbf4e3f55, 0x3f80be95, 0xbf3ebec4, 0x3e163f62, 0x3f04bf7b, 0xbf713f22, 0xbeac3f80, 0x3f5cbf46, 0xbf7d3e48, 0x3f2c3ef1,
    0xbd49bf6d, 0xbf183f75, 0x3f78bf0e, 0xbf67bdc9, 0x3f3e3ec4, 0xbe16bf62, 0xbf043f7b, 0x3f71bf22, 0xbedbbf35, 0xbe793f7f,
    0x3f4ebf55, 0xbf803e95, 0x3d493f6d, 0x3f18bf75, 0xbf783f0e, 0x3f673dc9, 0x3eacbf80, 0xbf5c3f46, 0x3f7dbe48, 0xbf2cbef1,
    0xbf2c3f6d, 0x3f7dbef1, 0xbf5cbe48, 0x3eac3f46, 0x3f67bf35, 0xbf783dc9, 0x3f183f0e, 0x3d49bf75, 0xbf803ec4, 0x3f4e3e95,
    0xbe79bf55, 0xbedb3f7f, 0x3f710000, 0xbf04bf22, 0xbe163f7b, 0x3f3ebf62, 0xbedb3f80, 0x3f78bf22, 0xbf4ebe48, 0x3d493f62,
    0x3f3ebf6d, 0xbf7d3e95, 0x3f043f0e, 0x3eacbf7f, 0xbf713f35, 0x3f5c3dc9, 0xbe16bf55, 0xbf2c3f75, 0x3f80bec4, 0xbf18bef1,
    0xbe793f7b, 0x3f67bf46, 0xbf670000, 0x3e793f46, 0x3f18bf7b, 0xbf803ef1, 0x3f2c3ec4, 0x3e16bf75, 0xbf5c3f55, 0x3f71bdc9,
    0xbeacbf35, 0xbf043f7f, 0x3f7dbf0e, 0xbf3ebe95, 0xbd493f6d, 0x3f4ebf62, 0xbf783e48, 0x3edb3f22, 0xbf2cbec4, 0xbe163f75,
    0x3f5cbf55, 0xbf713dc9, 0x3f670000, 0xbe79bf46, 0xbf183f7b, 0x3f80bef1, 0x3d49bf6d, 0xbf4e3f62, 0x3f78be48, 0xbedbbf22,
    0x3eac3f35, 0x3f04bf7f, 0xbf7d3f0e, 0x3f3e3e95, 0x3f3ebf6d, 0xbf7d3e95, 0x3f043f0e, 0x3eacbf7f, 0xbedb3f80, 0x3f78bf22,
    0xbf4ebe48, 0x3d493f62, 0x3f80bec4, 0xbf18bef1, 0xbe793f7b, 0x3f67bf46, 0xbf713f35, 0x3f5c3dc9, 0xbe16bf55, 0xbf2c3f75,
    0xbe79bf35, 0xbf3e3f75, 0x3f71be48, 0xbe16bf46, 0xbf4e3f6d, 0x3f67bdc9, 0xbd49bf55, 0xbf5c3f62, 0xbf043f80, 0x3f80bef1,
    0xbedbbf0e, 0xbf183f7f, 0x3f7dbec4, 0xbeacbf22, 0xbf2c3f7b, 0x3f78be95, 0xbf783f35, 0x3f2c3e95, 0x3eacbf7b, 0xbf7d3f22,
    0x3f183ec4, 0x3edbbf7f, 0xbf803f0e, 0x3f043ef1, 0x3f5c0000, 0x3d49bf62, 0xbf673f55, 0x3f4e3dc9, 0x3e16bf6d, 0xbf713f46,
    0x3f3e3e48, 0x3e79bf75, 0x3f183ec4, 0x3edbbf7f, 0xbf803f0e, 0x3f043ef1, 0xbf783f35, 0x3f2c3e95, 0x3eacbf7b, 0xbf7d3f22,
    0x3e16bf6d, 0xbf713f46, 0x3f3e3e48, 0x3e79bf75, 0x3f5c0000, 0x3d49bf62, 0xbf673f55, 0x3f4e3dc9, 0x3f4ebf6d, 0xbf673dc9,
    0x3d493f55, 0x3f5cbf62, 0x3e793f35, 0x3f3ebf75, 0xbf713e48, 0x3e163f46, 0xbf7d3ec4, 0x3eac3f22, 0x3f2cbf7b, 0xbf783e95,
    0x3f04bf80, 0xbf803ef1, 0x3edb3f0e, 0x3f18bf7f, 0xbf4e0000, 0xbeac3f75, 0x3f80bf0e, 0xbe79bf22, 0xbf5c3f6d, 0x3f3e3dc9,
    0x3edbbf7b, 0xbf7d3ef1, 0x3e163f35, 0x3f67bf62, 0xbf2cbe48, 0xbf043f7f, 0x3f78bec4, 0xbd49bf46, 0xbf713f55, 0x3f183e95,
    0xbf183f80, 0x3f71be95, 0x3d49bf55, 0xbf783f46, 0x3f043ec4, 0x3f2cbf7f, 0xbf673e48, 0xbe163f62, 0x3f7dbf35, 0xbedbbef1,
    0xbf3e3f7b, 0x3f5cbdc9, 0x3e79bf6d, 0xbf803f22, 0x3eac3f0e, 0x3f4ebf75, 0x3f043ec4, 0x3f2cbf7f, 0xbf673e48, 0xbe163f62,
    0xbf183f80, 0x3f71be95, 0x3d49bf55, 0xbf783f46, 0x3e79bf6d, 0xbf803f22, 0x3eac3f0e, 0x3f4ebf75, 0x3f7dbf35, 0xbedbbef1,
    0xbf3e3f7b, 0x3f5cbdc9, 0x3f5cbf6d, 0xbf3ebdc9, 0xbedb3f7b, 0x3f7dbef1, 0x3f4e0000, 0x3eacbf75, 0xbf803f0e, 0x3e793f22,
    0xbf783ec4, 0x3d493f46, 0x3f71bf55, 0xbf18be95, 0xbe16bf35, 0xbf673f62, 0x3f2c3e48, 0x3f04bf7f, 0x3f80bf35, 0xbe16bf22,
    0xbf783f55, 0x3eac3ef1, 0x3f67bf6d, 0xbf04be95, 0xbf4e3f7b, 0x3f2c3dc9, 0x3f3e0000, 0x3f18bf7f, 0xbf5c3e48, 0xbedb3f75,
    0x3f71bec4, 0x3e79bf62, 0xbf7d3f0e, 0xbd493f46, 0x3d493f35, 0x3f7dbf46, 0xbe79bf0e, 0xbf713f62, 0x3edb3ec4, 0x3f5cbf75,
    0xbf18be48, 0xbf3e3f7f, 0xbf2c3f80, 0x3f4ebdc9, 0x3f04bf7b, 0xbf673e95, 0xbeac3f6d, 0x3f78bef1, 0x3e16bf55, 0xbf803f22,
    0xbedbbec4, 0xbf5c3f75, 0x3f183e48, 0x3f3ebf7f, 0xbd49bf35, 0xbf7d3f46, 0x3e793f0e, 0x3f71bf62, 0x3eacbf6d, 0xbf783ef1,
    0xbe163f55, 0x3f80bf22, 0x3f2cbf80, 0xbf4e3dc9, 0xbf043f7b, 0x3f67be95, 0x3f67bf6d, 0xbf04be95, 0xbf4e3f7b, 0x3f2c3dc9,
    0x3f80bf35, 0xbe16bf22, 0xbf783f55, 0x3eac3ef1, 0x3f71bec4, 0x3e79bf62, 0xbf7d3f0e, 0xbd493f46, 0x3f3e0000, 0x3f18bf7f,
    0xbf5c3e48, 0xbedb3f75, 0xbf3e3f80, 0x3f183dc9, 0x3f5cbf7b, 0xbedbbe95, 0xbf713f6d, 0x3e793ef1, 0x3f7dbf55, 0xbd49bf22,
    0xbf803f35, 0xbe163f46, 0x3f78bf0e, 0x3eacbf62, 0xbf673ec4, 0xbf043f75, 0x3f4ebe48, 0x3f2cbf7f, 0xbf2c0000, 0xbf4e3f7f,
    0x3f043e48, 0x3f67bf75, 0xbeacbec4, 0xbf783f62, 0x3e163f0e, 0x3f80bf46, 0x3d49bf35, 0xbf7d3f22, 0xbe793f55, 0x3f71bef1,
    0x3edbbf6d, 0xbf5c3e95, 0xbf183f7b, 0x3f3ebdc9, 0x3eac3ec4, 0x3f78bf62, 0xbe16bf0e, 0xbf803f46, 0x3f2c0000, 0x3f4ebf7f,
    0xbf04be48, 0xbf673f75, 0xbedb3f6d, 0x3f5cbe95, 0x3f18bf7b, 0xbf3e3dc9, 0xbd493f35, 0x3f7dbf22, 0x3e79bf55, 0xbf713ef1,
    0xbf713f6d, 0x3e793ef1, 0x3f7dbf55, 0xbd49bf22, 0xbf3e3f80, 0x3f183dc9, 0x3f5cbf7b, 0xbedbbe95, 0xbf673ec4, 0xbf043f75,
    0x3f4ebe48, 0x3f2cbf7f, 0xbf803f35, 0xbe163f46, 0x3f78bf0e, 0x3eacbf62, 0x3e16bf35, 0xbf673ef1, 0xbf2c3f7b, 0x3f043dc9,
    0x3f78bf6d, 0x3d49bf22, 0xbf713f0e, 0xbf183f75, 0xbf4e3f80, 0x3eac3e95, 0x3f80bf55, 0x3e79bf46, 0xbf5c3ec4, 0xbf3e3f7f,
    0x3edb3e48, 0x3f7dbf62, 0xbf7d3f35, 0xbedb3f62, 0x3f3ebe48, 0x3f5cbf7f, 0xbe79bec4, 0xbf803f46, 0xbeac3f55, 0x3f4ebe95,
    0x3f180000, 0x3f71bf75, 0xbd49bf0e, 0xbf783f22, 0xbf043f6d, 0x3f2cbdc9, 0x3f67bf7b, 0xbe16bef1, 0xbe79bec4, 0xbf803f46,
    0xbeac3f55, 0x3f4ebe95, 0xbf7d3f35, 0xbedb3f62, 0x3f3ebe48, 0x3f5cbf7f, 0xbf043f6d, 0x3f2cbdc9, 0x3f67bf7b, 0xbe16bef1,
    0x3f180000, 0x3f71bf75, 0xbd49bf0e, 0xbf783f22, 0xbf783f6d, 0xbd493f22, 0x3f71bf0e, 0x3f18bf75, 0xbe163f35, 0x3f67bef1,
    0x3f2cbf7b, 0xbf04bdc9, 0x3f5cbec4, 0x3f3ebf7f, 0xbedbbe48, 0xbf7d3f62, 0x3f4ebf80, 0xbeacbe95, 0xbf803f55, 0xbe793f46,
    0xbf040000, 0xbf803f62, 0xbedb3f55, 0x3f18bdc9, 0x3f7dbf6d, 0x3eacbf46, 0xbf2c3e48, 0xbf783f75, 0xbe793f35, 0x3f3ebe95,
    0x3f71bf7b, 0x3e16bf22, 0xbf4e3ec4, 0xbf673f7f, 0xbd493f0e, 0x3f5cbef1, 0xbf5c3f80, 0x3d493ef1, 0x3f67bf0e, 0x3f4ebf7f,
    0xbe16bec4, 0xbf713f22, 0xbf3e3f7b, 0x3e793e95, 0x3f78bf35, 0x3f2cbf75, 0xbeacbe48, 0xbf7d3f46, 0xbf183f6d, 0x3edb3dc9,
    0x3f80bf55, 0x3f04bf62, 0xbe16bec4, 0xbf713f22, 0xbf3e3f7b, 0x3e793e95, 0xbf5c3f80, 0x3d493ef1, 0x3f67bf0e, 0x3f4ebf7f,
    0xbf183f6d, 0x3edb3dc9, 0x3f80bf55, 0x3f04bf62, 0x3f78bf35, 0x3f2cbf75, 0xbeacbe48, 0xbf7d3f46, 0xbf7d3f6d, 0xbeac3f46,
    0x3f2cbe48, 0x3f78bf75, 0x3f040000, 0x3f80bf62, 0x3edbbf55, 0xbf183dc9, 0x3f4ebec4, 0x3f67bf7f, 0x3d49bf0e, 0xbf5c3ef1,
    0x3e79bf35, 0xbf3e3e95, 0xbf713f7b, 0xbe163f22, 0x3f71bf35, 0x3f5cbf7f, 0x3e16bf0e, 0xbf2c3e95, 0xbf803f6d, 0xbf183f62,
    0x3e793e48, 0x3f67bf22, 0x3edb0000, 0x3f78bf46, 0x3f4ebf7b, 0x3d49bef1, 0xbf3e3ec4, 0xbf7d3f75, 0xbf043f55, 0x3eac3dc9,
    0xbeac3f35, 0x3f04bdc9, 0x3f7dbf55, 0x3f3ebf75, 0xbd49bec4, 0xbf4e3ef1, 0xbf783f7b, 0xbedb3f46, 0xbf673f80, 0xbe793f22,
    0x3f18be48, 0x3f80bf62, 0x3f2cbf6d, 0xbe16be95, 0xbf5c3f0e, 0xbf713f7f, 0x3d493ec4, 0x3f4ebef1, 0x3f78bf7b, 0x3edbbf46,
    0x3eacbf35, 0xbf043dc9, 0xbf7d3f55, 0xbf3e3f75, 0xbf2c3f6d, 0x3e163e95, 0x3f5cbf0e, 0x3f71bf7f, 0x3f67bf80, 0x3e79bf22,
    0xbf183e48, 0xbf803f62, 0xbf803f6d, 0xbf183f62, 0x3e793e48, 0x3f67bf22, 0x3f71bf35, 0x3f5cbf7f, 0x3e16bf0e, 0xbf2c3e95,
    0xbf3e3ec4, 0xbf7d3f75, 0xbf043f55, 0x3eac3dc9, 0x3edb0000, 0x3f78bf46, 0x3f4ebf7b, 0x3d49bef1, 0xbf713f80, 0xbf043f46,
    0x3e163e48, 0x3f3ebef1, 0x3f80bf6d, 0x3f4ebf75, 0x3e79bf0e, 0xbedb3dc9, 0xbf673f35, 0xbf783f7f, 0xbf183f55, 0x3d493e95,
    0x3f2cbec4, 0x3f7dbf62, 0x3f5cbf7b, 0x3eacbf22, 0xbeac0000, 0xbf5c3f22, 0xbf7d3f7b, 0xbf2c3f62, 0xbd493ec4, 0x3f18be95,
    0x3f78bf55, 0x3f67bf7f, 0x3edbbf35, 0xbe79bdc9, 0xbf4e3f0e, 0xbf803f75, 0xbf3e3f6d, 0xbe163ef1, 0x3f04be48, 0x3f71bf46,
    0x3d49bec4, 0xbf183e95, 0xbf783f55, 0xbf673f7f, 0x3eac0000, 0x3f5cbf22, 0x3f7dbf7b, 0x3f2cbf62, 0x3f3ebf6d, 0x3e16bef1,
    0xbf043e48, 0xbf713f46, 0xbedb3f35, 0x3e793dc9, 0x3f4ebf0e, 0x3f80bf75, 0x3f80bf6d, 0x3f4ebf75, 0x3e79bf0e, 0xbedb3dc9,
    0xbf713f80, 0xbf043f46, 0x3e163e48, 0x3f3ebef1, 0x3f2cbec4, 0x3f7dbf62, 0x3f5cbf7b, 0x3eacbf22, 0xbf673f35, 0xbf783f7f,
    0xbf183f55, 0x3d493e95, 0x3f04bf35, 0x3d49be95, 0xbedb3e48, 0xbf4e3f22, 0xbf7d3f6d, 0xbf713f7f, 0xbf2c3f55, 0xbe793ef1,
    0xbf783f80, 0xbf3e3f62, 0xbeac3f0e, 0x3e163dc9, 0x3f18bec4, 0x3f67bf46, 0x3f80bf7b, 0x3f5cbf75, 0xbf5c3f35, 0xbf803f75,
    0xbf673f7b, 0xbf183f46, 0xbe163ec4, 0x3eacbdc9, 0x3f3ebf0e, 0x3f78bf62, 0x3e790000, 0x3f2cbef1, 0x3f71bf55, 0x3f7dbf7f,
    0x3f4ebf6d, 0x3edbbf22, 0xbd49be48, 0xbf043e95, 0xbe163ec4, 0x3eacbdc9, 0x3f3ebf0e, 0x3f78bf62, 0xbf5c3f35, 0xbf803f75,
    0xbf673f7b, 0xbf183f46, 0x3f4ebf6d, 0x3edbbf22, 0xbd49be48, 0xbf043e95, 0x3e790000, 0x3f2cbef1, 0x3f71bf55, 0x3f7dbf7f,
    0x3f7dbf6d, 0x3f71bf7f, 0x3f2cbf55, 0x3e79bef1, 0xbf043f35, 0xbd493e95, 0x3edbbe48, 0x3f4ebf22, 0xbf183ec4, 0xbf673f46,
    0xbf803f7b, 0xbf5c3f75, 0x3f78bf80, 0x3f3ebf62, 0x3eacbf0e, 0xbe16bdc9, 0xbe160000, 0xbedb3e95, 0xbf2c3f0e, 0xbf5c3f46,
    0xbf783f6d, 0xbf803f7f, 0xbf713f7b, 0xbf4e3f62, 0xbf183f35, 0xbeac3ef1, 0xbd493e48, 0x3e79bdc9, 0x3f04bec4, 0x3f3ebf22,
    0x3f67bf55, 0x3f7dbf75, 0xbf7d3f80, 0xbf673f75, 0xbf3e3f55, 0xbf043f22, 0xbe793ec4, 0x3d493dc9, 0x3eacbe48, 0x3f18bef1,
    0x3f4ebf35, 0x3f71bf62, 0x3f80bf7b, 0x3f78bf7f, 0x3f5cbf6d, 0x3f2cbf46, 0x3edbbf0e, 0x3e16be95, 0xbe793ec4, 0x3d493dc9,
    0x3eacbe48, 0x3f18bef1, 0xbf7d3f80, 0xbf673f75, 0xbf3e3f55, 0xbf043f22, 0x3f5cbf6d, 0x3f2cbf46, 0x3edbbf0e, 0x3e16be95,
    0x3f4ebf35, 0x3f71bf62, 0x3f80bf7b, 0x3f78bf7f, 0x3f78bf6d, 0x3f80bf7f, 0x3f71bf7b, 0x3f4ebf62, 0x3e160000, 0x3edbbe95,
    0x3f2cbf0e, 0x3f5cbf46, 0xbf043ec4, 0xbf3e3f22, 0xbf673f55, 0xbf7d3f75, 0x3f18bf35, 0x3eacbef1, 0x3d49be48, 0xbe793dc9,
    0x3f3ebf35, 0x3f4ebf46, 0x3f5cbf55, 0x3f67bf62, 0x3f71bf6d, 0x3f78bf75, 0x3f7dbf7b, 0x3f80bf7f, 0x3d490000, 0x3e16bdc9,
    0x3e79be48, 0x3eacbe95, 0x3edbbec4, 0x3f04bef1, 0x3f18bf0e, 0x3f2cbf22, 0xbf2c3f35, 0xbf183f22, 0xbf043f0e, 0xbedb3ef1,
    0xbeac3ec4, 0xbe793e95, 0xbe163e48, 0xbd493dc9, 0xbf803f80, 0xbf7d3f7f, 0xbf783f7b, 0xbf713f75, 0xbf673f6d, 0xbf5c3f62,
    0xbf4e3f55, 0xbf3e3f46, 0x3eacbec4, 0x3e79be95, 0x3e16be48, 0x3d49bdc9, 0x3f2cbf35, 0x3f18bf22, 0x3f04bf0e, 0x3edbbef1,
    0x3f67bf6d, 0x3f5cbf62, 0x3f4ebf55, 0x3f3ebf46, 0x3f80bf80, 0x3f7dbf7f, 0x3f78bf7b, 0x3f71bf75, 0x3f71bf6d, 0x3f78bf75,
    0x3f7dbf7b, 0x3f80bf7f, 0x3f3ebf35, 0x3f4ebf46, 0x3f5cbf55, 0x3f67bf62, 0x3edbbec4, 0x3f04bef1, 0x3f18bf0e, 0x3f2cbf22,
    0x3d490000, 0x3e16bdc9, 0x3e79be48, 0x3eacbe95,
};
__device__ const __align__(128) uint32_t c_ga[1536] = {
    0x00003c80, 0x3bc43c6d, 0x00003c80, 0xbbc4bc6d, 0x00003c80, 0x3c6d3bc4, 0x00003c80, 0xbc6dbbc4, 0x00003c80, 0x3c6dbbc4,
    0x00003c80, 0xbc6d3bc4, 0x00003c80, 0x3bc4bc6d, 0x00003c80, 0xbbc43c6d, 0x3a493c80, 0x3bdb3c67, 0x3bdb3c67, 0xbc3ebc2c,
    0x3b163c7d, 0x3c783b79, 0x3c043c5c, 0xbc7d3b16, 0x3b793c78, 0x3c4ebc18, 0x3c183c4e, 0xbc043c5c, 0x3bac3c71, 0x3a49bc80,
    0x3c2c3c3e, 0x3bac3c71, 0x3ac93c7f, 0x3bf13c62, 0x3c463c22, 0xbc75bb95, 0x3b953c75, 0x3c7f3ac9, 0x3c623bf1, 0xbc463c22,
    0x3bf13c62, 0x3c22bc46, 0x3c753b95, 0x3ac93c7f, 0x3c223c46, 0xbb95bc75, 0x3c7f3ac9, 0x3c623bf1, 0x3b163c7d, 0x3c043c5c,
    0x3c783b79, 0xbc7d3b16, 0x3bdb3c67, 0x3c80ba49, 0x3c80ba49, 0xbbac3c71, 0x3c2c3c3e, 0x3bdbbc67, 0x3c71bbac, 0x3c2c3c3e,
    0x3c5c3c04, 0xbc18bc4e, 0x3c4ebc18, 0x3c78bb79, 0x3b483c7b, 0x3c0e3c55, 0x3c7bbb48, 0xbc553c0e, 0x3c0e3c55, 0x3c7bbb48,
    0x3c55bc0e, 0x3b483c7b, 0x3c553c0e, 0x3b48bc7b, 0x3c0ebc55, 0x3c7b3b48, 0x3c7b3b48, 0xbc55bc0e, 0x3b48bc7b, 0x3c0ebc55,
    0x3b793c78, 0x3c183c4e, 0x3c4ebc18, 0xbc043c5c, 0x3c2c3c3e, 0x3c71bbac, 0x3bdbbc67, 0x3c2c3c3e, 0x3c713bac, 0xba49bc80,
    0xba49bc80, 0x3c67bbdb, 0x3c7dbb16, 0xbc78bb79, 0xbc04bc5c, 0xbb16bc7d, 0x3b953c75, 0x3c223c46, 0x3bf1bc62, 0xbac93c7f,
    0x3c463c22, 0x3c62bbf1, 0xbac9bc7f, 0x3c753b95, 0x3c7f3ac9, 0xbb95bc75, 0xbc22bc46, 0x3bf1bc62, 0x3c62bbf1, 0xbc7f3ac9,
    0xbc75bb95, 0xbc46bc22, 0x3bac3c71, 0x3c2c3c3e, 0x3a49bc80, 0x3bac3c71, 0x3c5c3c04, 0x3c4ebc18, 0xbc18bc4e, 0x3c78bb79,
    0x3c7dbb16, 0xbc04bc5c, 0xbc78bb79, 0xbb16bc7d, 0x3c2cbc3e, 0xbc673bdb, 0xbc673bdb, 0xbc803a49, 0x00003c80, 0x3bc43c6d,
    0x00003c80, 0xbbc4bc6d, 0x00003c80, 0x3c6d3bc4, 0x00003c80, 0xbc6dbbc4, 0x00003c80, 0x3c6dbbc4, 0x00003c80, 0xbc6d3bc4,
    0x00003c80, 0x3bc4bc6d, 0x00003c80, 0xbbc43c6d, 0x3c3e3c2c, 0x3c713bac, 0x3c713bac, 0xbc803a49, 0x3c4e3c18, 0x3c5cbc04,
    0x3c783b79, 0xbc183c4e, 0x3c5c3c04, 0x3b16bc7d, 0x3c7d3b16, 0x3b793c78, 0x3c673bdb, 0xbc2cbc3e, 0x3c803a49, 0x3c673bdb,
    0x3c7fbac9, 0x3c62bbf1, 0x3c22bc46, 0xbb953c75, 0x3c75bb95, 0x3ac9bc7f, 0x3bf1bc62, 0x3c223c46, 0x3c62bbf1, 0xbc46bc22,
    0x3b95bc75, 0x3c7fbac9, 0x3c46bc22, 0xbc753b95, 0x3ac9bc7f, 0x3bf1bc62, 0x3c18bc4e, 0x3b79bc78, 0xbc04bc5c, 0x3c4e3c18,
    0x3bacbc71, 0xbc3ebc2c, 0xbc3ebc2c, 0x3c67bbdb, 0x3a49bc80, 0xbc713bac, 0xbc67bbdb, 0x3a49bc80, 0xbb79bc78, 0xbb163c7d,
    0xbc7dbb16, 0xbc5cbc04, 0xbb48bc7b, 0xbc0ebc55, 0xbc7b3b48, 0x3c55bc0e, 0xbc0ebc55, 0xbc7b3b48, 0xbc553c0e, 0xbb48bc7b,
    0xbc55bc0e, 0xbb483c7b, 0xbc0e3c55, 0xbc7bbb48, 0xbc7bbb48, 0x3c553c0e, 0xbb483c7b, 0xbc0e3c55, 0xbc5cbc04, 0xbc7dbb16,
    0xbb163c7d, 0xbb79bc78, 0xbc80ba49, 0xbbdb3c67, 0x3bac3c71, 0xbc80ba49, 0xbc673bdb, 0x3c3e3c2c, 0x3c3e3c2c, 0xbbac3c71,
    0xbc183c4e, 0x3c5cbc04, 0x3c783b79, 0x3c4e3c18, 0xbc753b95, 0xbc463c22, 0x3c623bf1, 0xbc7fbac9, 0xbc223c46, 0x3bf13c62,
    0x3c7fbac9, 0xbb953c75, 0xbac93c7f, 0x3c75bb95, 0x3c46bc22, 0x3c623bf1, 0x3bf13c62, 0xbac9bc7f, 0x3b95bc75, 0x3c22bc46,
    0xbbdb3c67, 0xba493c80, 0x3c3ebc2c, 0xbbdb3c67, 0x3b793c78, 0x3c7d3b16, 0x3b16bc7d, 0x3c5c3c04, 0x3c4e3c18, 0x3b79bc78,
    0xbc04bc5c, 0x3c18bc4e, 0x3c80ba49, 0xbc71bbac, 0xbc71bbac, 0xbc3ebc2c, 0x00003c80, 0x3bc43c6d, 0x00003c80, 0xbbc4bc6d,
    0x00003c80, 0x3c6d3bc4, 0x00003c80, 0xbc6dbbc4, 0x00003c80, 0x3c6dbbc4, 0x00003c80, 0xbc6d3bc4, 0x00003c80, 0x3bc4bc6d,
    0x00003c80, 0xbbc43c6d, 0x3c80ba49, 0x3c67bbdb, 0x3c67bbdb, 0xbc2c3c3e, 0x3c7dbb16, 0x3b79bc78, 0x3c5cbc04, 0x3b163c7d,
    0x3c78bb79, 0xbc18bc4e, 0x3c4ebc18, 0x3c5c3c04, 0x3c71bbac, 0xbc80ba49, 0x3c3ebc2c, 0x3c71bbac, 0xbac9bc7f, 0xbbf1bc62,
    0xbc46bc22, 0x3c753b95, 0xbb95bc75, 0xbc7fbac9, 0xbc62bbf1, 0x3c46bc22, 0xbbf1bc62, 0xbc223c46, 0xbc75bb95, 0xbac9bc7f,
    0xbc22bc46, 0x3b953c75, 0xbc7fbac9, 0xbc62bbf1, 0xbc7d3b16, 0xbc5c3c04, 0xbb793c78, 0xbb16bc7d, 0xbc673bdb, 0x3a493c80,
    0x3a493c80, 0xbc71bbac, 0xbc3e3c2c, 0x3c673bdb, 0x3bac3c71, 0xbc3e3c2c, 0xbc043c5c, 0x3c4ebc18, 0x3c183c4e, 0x3b793c78,
    0x3b483c7b, 0x3c0e3c55, 0x3c7bbb48, 0xbc553c0e, 0x3c0e3c55, 0x3c7bbb48, 0x3c55bc0e, 0x3b483c7b, 0x3c553c0e, 0x3b48bc7b,
    0x3c0ebc55, 0x3c7b3b48, 0x3c7b3b48, 0xbc55bc0e, 0x3b48bc7b, 0x3c0ebc55, 0x3c78bb79, 0x3c4ebc18, 0xbc18bc4e, 0x3c5c3c04,
    0x3c3ebc2c, 0xbbacbc71, 0xbc67bbdb, 0x3c3ebc2c, 0x3bacbc71, 0xbc803a49, 0xbc803a49, 0xbbdbbc67, 0xbb16bc7d, 0xbb793c78,
    0xbc5c3c04, 0xbc7d3b16, 0xbb95bc75, 0xbc22bc46, 0xbbf13c62, 0x3ac9bc7f, 0xbc46bc22, 0xbc623bf1, 0x3ac93c7f, 0xbc75bb95,
    0xbc7fbac9, 0x3b953c75, 0x3c223c46, 0xbbf13c62, 0xbc623bf1, 0x3c7fbac9, 0x3c753b95, 0x3c463c22, 0xbc713bac, 0xbc3e3c2c,
    0x3c803a49, 0xbc713bac, 0xbc043c5c, 0x3c183c4e, 0x3c4ebc18, 0x3b793c78, 0x3b163c7d, 0x3c5cbc04, 0x3b79bc78, 0x3c7dbb16,
    0x3c3e3c2c, 0xbbdbbc67, 0xbbdbbc67, 0xba49bc80, 0x00003c80, 0x3bc43c6d, 0x00003c80, 0xbbc4bc6d, 0x00003c80, 0x3c6d3bc4,
    0x00003c80, 0xbc6dbbc4, 0x00003c80, 0x3c6dbbc4, 0x00003c80, 0xbc6d3bc4, 0x00003c80, 0x3bc4bc6d, 0x00003c80, 0xbbc43c6d,
    0x3c2cbc3e, 0x3bacbc71, 0x3bacbc71, 0x3a493c80, 0x3c18bc4e, 0xbc04bc5c, 0x3b79bc78, 0x3c4e3c18, 0x3c04bc5c, 0xbc7dbb16,
    0x3b16bc7d, 0x3c78bb79, 0x3bdbbc67, 0xbc3e3c2c, 0x3a49bc80, 0x3bdbbc67, 0xbc7f3ac9, 0xbc623bf1, 0xbc223c46, 0x3b95bc75,
    0xbc753b95, 0xbac93c7f, 0xbbf13c62, 0xbc22bc46, 0xbc623bf1, 0x3c463c22, 0xbb953c75, 0xbc7f3ac9, 0xbc463c22, 0x3c75bb95,
    0xbac93c7f, 0xbbf13c62, 0x3c4e3c18, 0x3c783b79, 0x3c5cbc04, 0xbc183c4e, 0x3c713bac, 0x3c2cbc3e, 0x3c2cbc3e, 0x3bdb3c67,
    0x3c803a49, 0xbbacbc71, 0x3bdbbc67, 0x3c803a49, 0x3c78bb79, 0xbc7dbb16, 0x3b16bc7d, 0x3c04bc5c, 0xbb48bc7b, 0xbc0ebc55,
    0xbc7b3b48, 0x3c55bc0e, 0xbc0ebc55, 0xbc7b3b48, 0xbc553c0e, 0xbb48bc7b, 0xbc55bc0e, 0xbb483c7b, 0xbc0e3c55, 0xbc7bbb48,
    0xbc7bbb48, 0x3c553c0e, 0xbb483c7b, 0xbc0e3c55, 0xbc043c5c, 0xbb163c7d, 0x3c7d3b16, 0xbc783b79, 0xba493c80, 0x3c673bdb,
    0x3c71bbac, 0xba493c80, 0x3bdb3c67, 0x3c2cbc3e, 0x3c2cbc3e, 0x3c713bac, 0x3c4e3c18, 0xbc04bc5c, 0x3b79bc78, 0x3c18bc4e,
    0x3c75bb95, 0x3c46bc22, 0xbc62bbf1, 0x3c7f3ac9, 0x3c22bc46, 0xbbf1bc62, 0xbc7f3ac9, 0x3b95bc75, 0x3ac9bc7f, 0xbc753b95,
    0xbc463c22, 0xbc62bbf1, 0xbbf1bc62, 0x3ac93c7f, 0xbb953c75, 0xbc223c46, 0xbc67bbdb, 0xbc80ba49, 0x3c2c3c3e, 0xbc67bbdb,
    0xbc783b79, 0xbb163c7d, 0x3c7d3b16, 0xbc043c5c, 0xbc183c4e, 0x3c783b79, 0x3c5cbc04, 0x3c4e3c18, 0x3a493c80, 0x3bacbc71,
    0x3bacbc71, 0x3c2cbc3e, 0x3c353c35, 0x3c6d3bc4, 0x3c353c35, 0xbc6dbbc4, 0x3c35bc35, 0xbbc4bc6d, 0x3c35bc35, 0x3bc43c6d,
    0xbc35bc35, 0xbbc43c6d, 0xbc35bc35, 0x3bc4bc6d, 0xbc353c35, 0x3c6dbbc4, 0xbc353c35, 0xbc6d3bc4, 0x3c3e3c2c, 0x3c713bac,
    0x3c713bac, 0xbc803a49, 0x3c18bc4e, 0xbc04bc5c, 0x3b79bc78, 0x3c4e3c18, 0xbc5cbc04, 0xbb163c7d, 0xbc7dbb16, 0xbb79bc78,
    0xbbdb3c67, 0x3c3ebc2c, 0xba493c80, 0xbbdb3c67, 0x3c463c22, 0x3c753b95, 0x3c7fbac9, 0xbc623bf1, 0x3bf1bc62, 0xbc22bc46,
    0xbb95bc75, 0x3c7f3ac9, 0xbc75bb95, 0x3ac93c7f, 0xbc623bf1, 0xbc46bc22, 0xbac93c7f, 0x3bf1bc62, 0x3c223c46, 0x3b953c75,
    0x3c4e3c18, 0x3c783b79, 0x3c5cbc04, 0xbc183c4e, 0x3bacbc71, 0xbc3ebc2c, 0xbc3ebc2c, 0x3c67bbdb, 0xbc80ba49, 0x3bac3c71,
    0xbbdb3c67, 0xbc80ba49, 0x3b793c78, 0x3b16bc7d, 0x3c7d3b16, 0x3c5c3c04, 0x3c553c0e, 0x3c7b3b48, 0x3c0ebc55, 0xbb483c7b,
    0x3b48bc7b, 0xbc55bc0e, 0xbc7bbb48, 0x3c0ebc55, 0xbc7b3b48, 0x3c0e3c55, 0x3b483c7b, 0xbc553c0e, 0x3c0e3c55, 0xbb48bc7b,
    0x3c55bc0e, 0x3c7bbb48, 0x3c5c3c04, 0x3c7d3b16, 0x3b16bc7d, 0x3b793c78, 0x3a49bc80, 0xbc67bbdb, 0xbc713bac, 0x3a49bc80,
    0xbc673bdb, 0x3c3e3c2c, 0x3c3e3c2c, 0xbbac3c71, 0x3c4e3c18, 0xbc04bc5c, 0x3b79bc78, 0x3c18bc4e, 0x3c623bf1, 0x3c7f3ac9,
    0xbb95bc75, 0x3c223c46, 0xbac9bc7f, 0xbc75bb95, 0xbc223c46, 0xbbf1bc62, 0xbc463c22, 0x3c623bf1, 0x3c7f3ac9, 0x3b953c75,
    0x3c753b95, 0xbc46bc22, 0xbbf1bc62, 0xbac9bc7f, 0x3c673bdb, 0x3c803a49, 0xbc2cbc3e, 0x3c673bdb, 0xbb79bc78, 0xbc7dbb16,
    0xbb163c7d, 0xbc5cbc04, 0xbc183c4e, 0x3c783b79, 0x3c5cbc04, 0x3c4e3c18, 0x3c80ba49, 0xbc71bbac, 0xbc71bbac, 0xbc3ebc2c,
    0x3c353c35, 0x3c6d3bc4, 0x3c353c35, 0xbc6dbbc4, 0x3c35bc35, 0xbbc4bc6d, 0x3c35bc35, 0x3bc43c6d, 0xbc35bc35, 0xbbc43c6d,
    0xbc35bc35, 0x3bc4bc6d, 0xbc353c35, 0x3c6dbbc4, 0xbc353c35, 0xbc6d3bc4, 0x3c80ba49, 0x3c67bbdb, 0x3c67bbdb, 0xbc2c3c3e,
    0xbb16bc7d, 0xbc78bb79, 0xbc04bc5c, 0x3c7dbb16, 0xbc783b79, 0x3c183c4e, 0xbc4e3c18, 0xbc5cbc04, 0x3bac3c71, 0x3a49bc80,
    0x3c2c3c3e, 0x3bac3c71, 0x3c22bc46, 0x3b95bc75, 0xbac9bc7f, 0x3bf13c62, 0xbc62bbf1, 0xbc463c22, 0xbc753b95, 0x3ac9bc7f,
    0xbb953c75, 0x3c7fbac9, 0x3bf13c62, 0xbc223c46, 0x3c7f3ac9, 0xbc62bbf1, 0x3c46bc22, 0x3c75bb95, 0xbb16bc7d, 0xbc04bc5c,
    0xbc78bb79, 0x3c7dbb16, 0xbc673bdb, 0x3a493c80, 0x3a493c80, 0xbc71bbac, 0x3c2c3c3e, 0x3bdbbc67, 0x3c71bbac, 0x3c2c3c3e,
    0x3c04bc5c, 0xbc4e3c18, 0xbc18bc4e, 0xbb79bc78, 0xbc55bc0e, 0xbc7bbb48, 0xbc0e3c55, 0x3b48bc7b, 0xbb483c7b, 0x3c553c0e,
    0x3c7b3b48, 0xbc0e3c55, 0x3c7bbb48, 0xbc0ebc55, 0xbb48bc7b, 0x3c55bc0e, 0xbc0ebc55, 0x3b483c7b, 0xbc553c0e, 0xbc7b3b48,
    0xbc783b79, 0xbc4e3c18, 0x3c183c4e, 0xbc5cbc04, 0x3c2c3c3e, 0x3c71bbac, 0x3bdbbc67, 0x3c2c3c3e, 0x3bacbc71, 0xbc803a49,
    0xbc803a49, 0xbbdbbc67, 0xbc7d3b16, 0x3c783b79, 0x3c043c5c, 0x3b163c7d, 0xbbf13c62, 0xbac93c7f, 0x3c75bb95, 0xbc463c22,
    0x3c7fbac9, 0x3b95bc75, 0xbc46bc22, 0x3c62bbf1, 0xbc22bc46, 0xbbf13c62, 0xbac93c7f, 0xbc753b95, 0xbb953c75, 0x3c22bc46,
    0x3c62bbf1, 0x3c7fbac9, 0x3bac3c71, 0x3c2c3c3e, 0x3a49bc80, 0x3bac3c71, 0x3c04bc5c, 0xbc18bc4e, 0xbc4e3c18, 0xbb79bc78,
    0xbc7d3b16, 0x3c043c5c, 0x3c783b79, 0x3b163c7d, 0x3c3e3c2c, 0xbbdbbc67, 0xbbdbbc67, 0xba49bc80, 0x3c353c35, 0x3c6d3bc4,
    0x3c353c35, 0xbc6dbbc4, 0x3c35bc35, 0xbbc4bc6d, 0x3c35bc35, 0x3bc43c6d, 0xbc35bc35, 0xbbc43c6d, 0xbc35bc35, 0x3bc4bc6d,
    0xbc353c35, 0x3c6dbbc4, 0xbc353c35, 0xbc6d3bc4, 0x3c2cbc3e, 0x3bacbc71, 0x3bacbc71, 0x3a493c80, 0xbc4ebc18, 0xbc5c3c04,
    0xbc78bb79, 0x3c18bc4e, 0xbc043c5c, 0x3c7d3b16, 0xbb163c7d, 0xbc783b79, 0x3c673bdb, 0xbc2cbc3e, 0x3c803a49, 0x3c673bdb,
    0xbc46bc22, 0xbc75bb95, 0xbc7f3ac9, 0x3c62bbf1, 0xbbf13c62, 0x3c223c46, 0x3b953c75, 0xbc7fbac9, 0x3c753b95, 0xbac9bc7f,
    0x3c62bbf1, 0x3c463c22, 0x3ac9bc7f, 0xbbf13c62, 0xbc22bc46, 0xbb95bc75, 0xbc183c4e, 0xbb793c78, 0x3c043c5c, 0xbc4ebc18,
    0x3c713bac, 0x3c2cbc3e, 0x3c2cbc3e, 0x3bdb3c67, 0x3a49bc80, 0xbc713bac, 0xbc67bbdb, 0x3a49bc80, 0xbc783b79, 0x3c7d3b16,
    0xbb163c7d, 0xbc043c5c, 0x3c553c0e, 0x3c7b3b48, 0x3c0ebc55, 0xbb483c7b, 0x3b48bc7b, 0xbc55bc0e, 0xbc7bbb48, 0x3c0ebc55,
    0xbc7b3b48, 0x3c0e3c55, 0x3b483c7b, 0xbc553c0e, 0x3c0e3c55, 0xbb48bc7b, 0x3c55bc0e, 0x3c7bbb48, 0x3c04bc5c, 0x3b16bc7d,
    0xbc7dbb16, 0x3c78bb79, 0xbc80ba49, 0xbbdb3c67, 0x3bac3c71, 0xbc80ba49, 0x3bdb3c67, 0x3c2cbc3e, 0x3c2cbc3e, 0x3c713bac,
    0x3c18bc4e, 0xbc5c3c04, 0xbc78bb79, 0xbc4ebc18, 0xbc62bbf1, 0xbc7fbac9, 0x3b953c75, 0xbc22bc46, 0x3ac93c7f, 0x3c753b95,
    0x3c22bc46, 0x3bf13c62, 0x3c46bc22, 0xbc62bbf1, 0xbc7fbac9, 0xbb95bc75, 0xbc75bb95, 0x3c463c22, 0x3bf13c62, 0x3ac93c7f,
    0xbbdb3c67, 0xba493c80, 0x3c3ebc2c, 0xbbdb3c67, 0x3c78bb79, 0x3b16bc7d, 0xbc7dbb16, 0x3c04bc5c, 0xbc4ebc18, 0xbb793c78,
    0x3c043c5c, 0xbc183c4e, 0x3a493c80, 0x3bacbc71, 0x3bacbc71, 0x3c2cbc3e, 0x3c353c35, 0x3c6d3bc4, 0x3c353c35, 0xbc6dbbc4,
    0x3c35bc35, 0xbbc4bc6d, 0x3c35bc35, 0x3bc43c6d, 0xbc35bc35, 0xbbc43c6d, 0xbc35bc35, 0x3bc4bc6d, 0xbc353c35, 0x3c6dbbc4,
    0xbc353c35, 0xbc6d3bc4, 0xba49bc80, 0xbbdbbc67, 0xbbdbbc67, 0x3c3e3c2c, 0xbc7d3b16, 0xbb793c78, 0xbc5c3c04, 0xbb16bc7d,
    0x3b793c78, 0x3c4ebc18, 0x3c183c4e, 0xbc043c5c, 0x3c71bbac, 0xbc80ba49, 0x3c3ebc2c, 0x3c71bbac, 0xbc223c46, 0xbb953c75,
    0x3ac93c7f, 0xbbf1bc62, 0x3c623bf1, 0x3c46bc22, 0x3c75bb95, 0xbac93c7f, 0x3b95bc75, 0xbc7f3ac9, 0xbbf1bc62, 0x3c22bc46,
    0xbc7fbac9, 0x3c623bf1, 0xbc463c22, 0xbc753b95, 0x3c7dbb16, 0x3c5cbc04, 0x3b79bc78, 0x3b163c7d, 0xbbdbbc67, 0xbc803a49,
    0xbc803a49, 0x3bacbc71, 0xbc3e3c2c, 0x3c673bdb, 0x3bac3c71, 0xbc3e3c2c, 0x3c5c3c04, 0xbc18bc4e, 0x3c4ebc18, 0x3c78bb79,
    0xbc55bc0e, 0xbc7bbb48, 0xbc0e3c55, 0x3b48bc7b, 0xbb483c7b, 0x3c553c0e, 0x3c7b3b48, 0xbc0e3c55, 0x3c7bbb48, 0xbc0ebc55,
    0xbb48bc7b, 0x3c55bc0e, 0xbc0ebc55, 0x3b483c7b, 0xbc553c0e, 0xbc7b3b48, 0x3b793c78, 0x3c183c4e, 0x3c4ebc18, 0xbc043c5c,
    0x3c3ebc2c, 0xbbacbc71, 0xbc67bbdb, 0x3c3ebc2c, 0xbc71bbac, 0x3a493c80, 0x3a493c80, 0xbc673bdb, 0x3b163c7d, 0x3b79bc78,
    0x3c5cbc04, 0x3c7dbb16, 0x3bf1bc62, 0x3ac9bc7f, 0xbc753b95, 0x3c46bc22, 0xbc7f3ac9, 0xbb953c75, 0x3c463c22, 0xbc623bf1,
    0x3c223c46, 0x3bf1bc62, 0x3ac9bc7f, 0x3c75bb95, 0x3b95bc75, 0xbc223c46, 0xbc623bf1, 0xbc7f3ac9, 0xbc713bac, 0xbc3e3c2c,
    0x3c803a49, 0xbc713bac, 0x3c5c3c04, 0x3c4ebc18, 0xbc18bc4e, 0x3c78bb79, 0xbb16bc7d, 0xbc5c3c04, 0xbb793c78, 0xbc7d3b16,
    0xbc2c3c3e, 0x3c67bbdb, 0x3c67bbdb, 0x3c80ba49, 0x3c800000, 0x3c6dbbc4, 0x3c800000, 0xbc6d3bc4, 0xbc800000, 0xbbc43c6d,
    0xbc800000, 0x3bc4bc6d, 0x3c800000, 0xbbc4bc6d, 0x3c800000, 0x3bc43c6d, 0xbc800000, 0x3c6d3bc4, 0xbc800000, 0xbc6dbbc4,
    0x3c80ba49, 0x3c67bbdb, 0x3c67bbdb, 0xbc2c3c3e, 0xbc7d3b16, 0xbb793c78, 0xbc5c3c04, 0xbb16bc7d, 0x3c78bb79, 0xbc18bc4e,
    0x3c4ebc18, 0x3c5c3c04, 0xbc713bac, 0x3c803a49, 0xbc3e3c2c, 0xbc713bac, 0x3c7fbac9, 0x3c62bbf1, 0x3c22bc46, 0xbb953c75,
    0xbc753b95, 0xbac93c7f, 0xbbf13c62, 0xbc22bc46, 0x3c62bbf1, 0xbc46bc22, 0x3b95bc75, 0x3c7fbac9, 0xbc463c22, 0x3c75bb95,
    0xbac93c7f, 0xbbf13c62, 0x3c7dbb16, 0x3c5cbc04, 0x3b79bc78, 0x3b163c7d, 0xbc673bdb, 0x3a493c80, 0x3a493c80, 0xbc71bbac,
    0x3c3ebc2c, 0xbc67bbdb, 0xbbacbc71, 0x3c3ebc2c, 0xbc043c5c, 0x3c4ebc18, 0x3c183c4e, 0x3b793c78, 0x3c7bbb48, 0x3c55bc0e,
    0xbb48bc7b, 0x3c0e3c55, 0xbc553c0e, 0x3b483c7b, 0x3c0e3c55, 0xbc7b3b48, 0x3c0ebc55, 0xbc7bbb48, 0xbc55bc0e, 0x3b48bc7b,
    0xbb483c7b, 0x3c0ebc55, 0x3c7b3b48, 0x3c553c0e, 0x3c78bb79, 0x3c4ebc18, 0xbc18bc4e, 0x3c5c3c04, 0xbc3e3c2c, 0x3bac3c71,
    0x3c673bdb, 0xbc3e3c2c, 0x3bacbc71, 0xbc803a49, 0xbc803a49, 0xbbdbbc67, 0x3b163c7d, 0x3b79bc78, 0x3c5cbc04, 0x3c7dbb16,
    0x3c75bb95, 0x3c46bc22, 0xbc62bbf1, 0x3c7f3ac9, 0xbc223c46, 0x3bf13c62, 0x3c7fbac9, 0xbb953c75, 0x3ac9bc7f, 0xbc753b95,
    0xbc463c22, 0xbc62bbf1, 0x3bf13c62, 0xbac9bc7f, 0x3b95bc75, 0x3c22bc46, 0x3c71bbac, 0x3c3ebc2c, 0xbc80ba49, 0x3c71bbac,
    0xbc043c5c, 0x3c183c4e, 0x3c4ebc18, 0x3b793c78, 0xbb16bc7d, 0xbc5c3c04, 0xbb793c78, 0xbc7d3b16, 0x3c3e3c2c, 0xbbdbbc67,
    0xbbdbbc67, 0xba49bc80, 0x3c800000, 0x3c6dbbc4, 0x3c800000, 0xbc6d3bc4, 0xbc800000, 0xbbc43c6d, 0xbc800000, 0x3bc4bc6d,
    0x3c800000, 0xbbc4bc6d, 0x3c800000, 0x3bc43c6d, 0xbc800000, 0x3c6d3bc4, 0xbc800000, 0xbc6dbbc4, 0x3c2cbc3e, 0x3bacbc71,
    0x3bacbc71, 0x3a493c80, 0xbc183c4e, 0x3c043c5c, 0xbb793c78, 0xbc4ebc18, 0x3c04bc5c, 0xbc7dbb16, 0x3b16bc7d, 0x3c78bb79,
    0xbbdb3c67, 0x3c3ebc2c, 0xba493c80, 0xbbdb3c67, 0xbac9bc7f, 0xbbf1bc62, 0xbc46bc22, 0x3c753b95, 0x3b953c75, 0x3c7f3ac9,
    0x3c623bf1, 0xbc463c22, 0xbbf1bc62, 0xbc223c46, 0xbc75bb95, 0xbac9bc7f, 0x3c223c46, 0xbb95bc75, 0x3c7f3ac9, 0x3c623bf1,
    0xbc4ebc18, 0xbc78bb79, 0xbc5c3c04, 0x3c18bc4e, 0x3c713bac, 0x3c2cbc3e, 0x3c2cbc3e, 0x3bdb3c67, 0xbc80ba49, 0x3bac3c71,
    0xbbdb3c67, 0xbc80ba49, 0x3c78bb79, 0xbc7dbb16, 0x3b16bc7d, 0x3c04bc5c, 0xbc7b3b48, 0xbc553c0e, 0x3b483c7b, 0xbc0ebc55,
    0x3c55bc0e, 0xbb48bc7b, 0xbc0ebc55, 0x3c7bbb48, 0xbc0e3c55, 0x3c7b3b48, 0x3c553c0e, 0xbb483c7b, 0x3b48bc7b, 0xbc0e3c55,
    0xbc7bbb48, 0xbc55bc0e, 0xbc043c5c, 0xbb163c7d, 0x3c7d3b16, 0xbc783b79, 0x3a49bc80, 0xbc67bbdb, 0xbc713bac, 0x3a49bc80,
    0x3bdb3c67, 0x3c2cbc3e, 0x3c2cbc3e, 0x3c713bac, 0xbc4ebc18, 0x3c043c5c, 0xbb793c78, 0xbc183c4e, 0x3b953c75, 0x3c223c46,
    0x3bf1bc62, 0xbac93c7f, 0xbc46bc22, 0xbc623bf1, 0x3ac93c7f, 0xbc75bb95, 0x3c7f3ac9, 0xbb95bc75, 0xbc22bc46, 0x3bf1bc62,
    0xbc623bf1, 0x3c7fbac9, 0x3c753b95, 0x3c463c22, 0x3c673bdb, 0x3c803a49, 0xbc2cbc3e, 0x3c673bdb, 0xbc783b79, 0xbb163c7d,
    0x3c7d3b16, 0xbc043c5c, 0x3c18bc4e, 0xbc78bb79, 0xbc5c3c04, 0xbc4ebc18, 0x3a493c80, 0x3bacbc71, 0x3bacbc71, 0x3c2cbc3e,
    0x3c800000, 0x3c6dbbc4, 0x3c800000, 0xbc6d3bc4, 0xbc800000, 0xbbc43c6d, 0xbc800000, 0x3bc4bc6d, 0x3c800000, 0xbbc4bc6d,
    0x3c800000, 0x3bc43c6d, 0xbc800000, 0x3c6d3bc4, 0xbc800000, 0xbc6dbbc4, 0xba49bc80, 0xbbdbbc67, 0xbbdbbc67, 0x3c3e3c2c,
    0x3b163c7d, 0x3c783b79, 0x3c043c5c, 0xbc7d3b16, 0xbb79bc78, 0xbc4e3c18, 0xbc18bc4e, 0x3c04bc5c, 0x3bac3c71, 0x3a49bc80,
    0x3c2c3c3e, 0x3bac3c71, 0xbc7f3ac9, 0xbc623bf1, 0xbc223c46, 0x3b95bc75, 0x3c75bb95, 0x3ac9bc7f, 0x3bf1bc62, 0x3c223c46,
    0xbc623bf1, 0x3c463c22, 0xbb953c75, 0xbc7f3ac9, 0x3c46bc22, 0xbc753b95, 0x3ac9bc7f, 0x3bf1bc62, 0x3b163c7d, 0x3c043c5c,
    0x3c783b79, 0xbc7d3b16, 0xbbdbbc67, 0xbc803a49, 0xbc803a49, 0x3bacbc71, 0x3c2c3c3e, 0x3bdbbc67, 0x3c71bbac, 0x3c2c3c3e,
    0xbc5cbc04, 0x3c183c4e, 0xbc4e3c18, 0xbc783b79, 0x3c7bbb48, 0x3c55bc0e, 0xbb48bc7b, 0x3c0e3c55, 0xbc553c0e, 0x3b483c7b,
    0x3c0e3c55, 0xbc7b3b48, 0x3c0ebc55, 0xbc7bbb48, 0xbc55bc0e, 0x3b48bc7b, 0xbb483c7b, 0x3c0ebc55, 0x3c7b3b48, 0x3c553c0e,
    0xbb79bc78, 0xbc18bc4e, 0xbc4e3c18, 0x3c04bc5c, 0x3c2c3c3e, 0x3c71bbac, 0x3bdbbc67, 0x3c2c3c3e, 0xbc71bbac, 0x3a493c80,
    0x3a493c80, 0xbc673bdb, 0x3c7dbb16, 0xbc78bb79, 0xbc04bc5c, 0xbb16bc7d, 0xbc753b95, 0xbc463c22, 0x3c623bf1, 0xbc7fbac9,
    0x3c22bc46, 0xbbf1bc62, 0xbc7f3ac9, 0x3b95bc75, 0xbac93c7f, 0x3c75bb95, 0x3c46bc22, 0x3c623bf1, 0xbbf1bc62, 0x3ac93c7f,
    0xbb953c75, 0xbc223c46, 0x3bac3c71, 0x3c2c3c3e, 0x3a49bc80, 0x3bac3c71, 0xbc5cbc04, 0xbc4e3c18, 0x3c183c4e, 0xbc783b79,
    0x3c7dbb16, 0xbc04bc5c, 0xbc78bb79, 0xbb16bc7d, 0xbc2c3c3e, 0x3c67bbdb, 0x3c67bbdb, 0x3c80ba49, 0x3c800000, 0x3c6dbbc4,
    0x3c800000, 0xbc6d3bc4, 0xbc800000, 0xbbc43c6d, 0xbc800000, 0x3bc4bc6d, 0x3c800000, 0xbbc4bc6d, 0x3c800000, 0x3bc43c6d,
    0xbc800000, 0x3c6d3bc4, 0xbc800000, 0xbc6dbbc4, 0xbc3ebc2c, 0xbc71bbac, 0xbc71bbac, 0x3c80ba49, 0x3c4e3c18, 0x3c5cbc04,
    0x3c783b79, 0xbc183c4e, 0xbc5cbc04, 0xbb163c7d, 0xbc7dbb16, 0xbb79bc78, 0x3c673bdb, 0xbc2cbc3e, 0x3c803a49, 0x3c673bdb,
    0x3ac93c7f, 0x3bf13c62, 0x3c463c22, 0xbc75bb95, 0xbb95bc75, 0xbc7fbac9, 0xbc62bbf1, 0x3c46bc22, 0x3bf13c62, 0x3c22bc46,
    0x3c753b95, 0x3ac93c7f, 0xbc22bc46, 0x3b953c75, 0xbc7fbac9, 0xbc62bbf1, 0x3c18bc4e, 0x3b79bc78, 0xbc04bc5c, 0x3c4e3c18,
    0xbbac3c71, 0x3c3e3c2c, 0x3c3e3c2c, 0xbc673bdb, 0x3a49bc80, 0xbc713bac, 0xbc67bbdb, 0x3a49bc80, 0x3b793c78, 0x3b16bc7d,
    0x3c7d3b16, 0x3c5c3c04, 0xbc7b3b48, 0xbc553c0e, 0x3b483c7b, 0xbc0ebc55, 0x3c55bc0e, 0xbb48bc7b, 0xbc0ebc55, 0x3c7bbb48,
    0xbc0e3c55, 0x3c7b3b48, 0x3c553c0e, 0xbb483c7b, 0x3b48bc7b, 0xbc0e3c55, 0xbc7bbb48, 0xbc55bc0e, 0x3c5c3c04, 0x3c7d3b16,
    0x3b16bc7d, 0x3b793c78, 0xbc80ba49, 0xbbdb3c67, 0x3bac3c71, 0xbc80ba49, 0x3c67bbdb, 0xbc3ebc2c, 0xbc3ebc2c, 0x3bacbc71,
    0xbc183c4e, 0x3c5cbc04, 0x3c783b79, 0x3c4e3c18, 0xbb95bc75, 0xbc22bc46, 0xbbf13c62, 0x3ac9bc7f, 0x3c463c22, 0x3c62bbf1,
    0xbac9bc7f, 0x3c753b95, 0xbc7fbac9, 0x3b953c75, 0x3c223c46, 0xbbf13c62, 0x3c62bbf1, 0xbc7f3ac9, 0xbc75bb95, 0xbc46bc22,
    0xbbdb3c67, 0xba493c80, 0x3c3ebc2c, 0xbbdb3c67, 0xbb79bc78, 0xbc7dbb16, 0xbb163c7d, 0xbc5cbc04, 0x3c4e3c18, 0x3b79bc78,
    0xbc04bc5c, 0x3c18bc4e, 0xbc803a49, 0x3c713bac, 0x3c713bac, 0x3c3e3c2c,
};

#define G_EPI 3
#define G_TK 3
#define W_Q 6
#define W2_PC 32
#define W2_PF 3
constexpr int X_LOC0 = 5;
constexpr int A_IN = 112 * 128;
constexpr int G_ST = 2 * NB1 * 64;
constexpr int K1_R = 131072, K1_BAR = K1_R + 98304, K1_SMEM = K1_BAR + 2048 + 1024;
constexpr int K1_T = K1_R + 65536, K1_TIN = 0, K1_Y0 = 3 * G_ST + 8192, G_KM = 16 - G_TK, G_S0 = 2 * G_KM;
__device__ int g_done[8 * 32];
struct Ptrs {
  int* done;
  float* ge;
  const uint32_t *img, *ga;
};

__host__ __device__ constexpr int g_depth(int s) { return s < 11 ? 3 : s < 18 ? 4 : s < 23 ? 5 : 6; }
__host__ __device__ constexpr int g_slot(int s) { return s < 3 ? s : g_depth(s) != g_depth(s - 1) ? g_depth(s - 1) : g_slot(s - g_depth(s)); }
__host__ __device__ constexpr int g_off(int id) { return id * G_ST + (id < 3 ? K1_R : 8192 - 3 * G_ST); }
struct Plan {
  uint32_t raw[32];
  uint32_t x[16];
  uint32_t grp[8];
  uint32_t last;
  uint32_t wpf;
  uint32_t g0;
  uint32_t tmask;
  uint64_t list[2];
};
struct K1Maps {
  Plan p;
  CUtensorMap x, we, wo, xs, y, w2e, w2o, w2s;
  int slot[32];
  int src[32];
  int dep[32];
};
__device__ __forceinline__ void poll_ge(const int* p, int target) {
  for (int it = 0; it < (1 << 20); it++) {
    int v;
    asm volatile("ld.acquire.gpu.global.s32 %0, [%1];" : "=r"(v) : "l"(p) : "memory");
    if (v >= target) break;
  }
}
__device__ __forceinline__ uint32_t place(int rank, uint32_t c) { return (c ^ (rank * 4 & ~(c >> 1))) << 14; }
__device__ __forceinline__ int x_unit(int cta, int u, uint32_t pl) {
  const int i = u * 128 + cta;
  const int pr = cta >= 128 ? 2 * cta - 96 + (u & 1) : i % 160, sl = cta >= 128 ? u >> 1 : i / 160, b = pr >= 84;
  return pr | sl << 8 | b << 11 | (cta >= 128 ? (u & 7) << 14 : place(cta & 1, pl & 15)) | 12 * (pr - 84 * b) << 20;
}
__device__ __forceinline__ int lds32(uint32_t a) {
  int v;
  asm volatile("ld.shared.b32 %0, [%1];" : "=r"(v) : "r"(a));
  return v;
}
__host__ __device__ constexpr uint64_t sched(const char* p) {
  uint64_t r = 0;
  for (int n = 0; p[n]; n++) r |= (uint64_t)(p[n] - '0' + 1) << (5 * n);
  return r;
}

template <int MODE>
__global__ void __cluster_dims__(2, 1, 1) __launch_bounds__(384, 1)
k1(const Ptrs gp_, const char* __restrict__ x1, const char* __restrict__ w1, const __grid_constant__ K1Maps m, const __nv_bfloat16* __restrict__ g,
   const __nv_bfloat16* __restrict__ wgt) {
  extern __shared__ __align__(1024) uint8_t smem_k1[];
  const uint32_t sb = s2u(smem_k1);
  const int tid = threadIdx.x, cta = blockIdx.x, rank = cta & 1;
  if (tid == 288) {
    const uint32_t bar = sb + K1_BAR + 256, dst = sb + (cta >= 128 ? 0 : place(rank, X_LOC0));
    const int pr = cta >= 128 ? 2 * cta - 96 : cta, b = pr >= 84;
    mbar_init(bar, 1);
    mbar_expect(bar, A_IN);
    for (int h = 0; h < 2; h++) tma_ld4<1>(dst + h * (A_IN / 2), &m.x, bar, 0, 96 * (pr - 84 * b) - 24 + h * 56, 0, b);
    for (int i = 1; i < 4; i++) mbar_init(bar + 8 * i, 1);
    fence_bar_init();
  }
  const uint32_t sF = sb + (cta >= 128 ? K1_T : rank * 65536), fbar = sb + K1_BAR + 1792;
  if (tid == 320) {
    mbar_init(fbar, 1);
    mbar_expect(fbar, 8192);
    asm volatile("cp.async.bulk.shared::cluster.global.mbarrier::complete_tx::bytes [%0], [%1], 8192, [%2];" ::"r"(sF), "l"(gp_.img + 1536), "r"(fbar) : "memory");
    fence_bar_init();
  }
  const int wg = __shfl_sync(0xffffffffu, tid >> 7, 0), t = tid & 127;
  const int warp = __shfl_sync(0xffffffffu, t >> 5, 0), lane = t & 31;
  const bool spare = cta >= 128;
  const int nx = spare ? 16 : 10;
  int bp, dc;
  {
    const int ci = cta >> 1;
    const int G = ci < 4 ? 0 : ci < 36 ? (ci - 4) & 7 : 1 + (ci - 36) % 7;
    const int li = ci < 4 ? 4 + ci : ci < 36 ? (ci - 4) >> 3 : 4 + (ci - 36) / 7;
    bp = 2 * G + (li >> 2), dc = li & 3;
  }
  const int bin = 2 * bp + rank;
  const uint32_t bb = sb + K1_BAR;
  const uint32_t rfull = bb, xfull = bb + 256, xfree = bb + 384, gfull = bb + 512, win = bb + 1800, win1 = bb + 1808;
  const uint32_t inf0 = bb + 784, se0 = inf0 + 16, pfree = se0 + 16, rempty = bb + 1024, xready = bb + 1280;
  const uint32_t gdone = bb + 1536, ine0 = gdone + 224, sf0 = ine0 + 16;
  const uint32_t xtab = bb + 896, ptab = bb + 2048 + 768;
  auto raw_load = [&](int j, uint32_t dst) {
    mbar_expect(rfull + 8 * j, 16384);
    tma_ld4<0>(dst, rank ? &m.we : &m.wo, rfull + 8 * j, dc * 64, rank - 1, (j & 3) * 4, (j >> 2) * 2);
  };
  auto x_half = [&](int u, int c, int h) {
    tma_ld4<1>(sb + (c & 0x3C000) + h * (A_IN / 2), &m.x, xfull + 8 * u, 0, (c >> 17 & ~7) - 24 + h * 56, c >> 8 & 7, c >> 11 & 1);
  };
  auto w_prefetch = [&](int q) {
    if (cta < 124) asm volatile("cp.async.bulk.prefetch.L2.global [%0], 4096;" ::"l"(w1 + (cta >> 2) * 131072 + (q * 4 + (cta & 3)) * 4096) : "memory");
  };
  uint32_t peer;
  asm("mapa.shared::cluster.u32 %0, %1, %2;" : "=r"(peer) : "r"(sb), "r"(rank ^ 1));
  if (wg == 2) {
    if (lane == 0) {
      if (warp == 0) {
        for (int i = 0; i < 4; i++) mbar_init(bb + 8 * i, 1);
        fence_bar_init();
        if (!spare)
          for (int j = 0; j < 4; j++) raw_load(j, sb + K1_R + j * 16384);
      } else if (warp == 2) {
#pragma unroll 1
        for (int q = 1; q <= m.p.wpf; q++) w_prefetch(q);
        prefetch_map(&m.xs);
      }
    }
    if (warp == 3) {
      const uint32_t v = reinterpret_cast<const uint32_t*>(&m.p)[32 + lane];
      asm volatile("st.shared.b32 [%0], %1;" ::"r"(ptab + 4 * lane), "r"(m.p.raw[lane]) : "memory");
      asm volatile("st.shared.b32 [%0], %1;" ::"r"(ptab + 128 + 4 * lane), "r"(v) : "memory");
      if (lane < 16) asm volatile("st.shared.b32 [%0], %1;" ::"r"(xtab + 4 * lane), "r"(x_unit(cta, lane, v)) : "memory");
    }
  } else {
    const int c = 4 * wg + warp;
    if (lane == 0 && c < 7) {
      const uint32_t b0 = bb + 256 * c, n = c < 4 ? 1 : c < 6 ? 4 : 8;
      if (c >= 2)
        for (int i = 0; i < 4; i++) mbar_init(b0 + 8 * i, n);
      for (int i = 4; i < 16; i++) mbar_init(b0 + 8 * i, n);
      if (c == 3) {
        mbar_init(win, 1 + 2 * W_Q);
        mbar_init(win1, 17 - 2 * W_Q);
        mbar_expect(win, 8192 * W_Q);
        mbar_expect(win1, 65536 - 8192 * W_Q);
        mbar_arrive(bb + 776);
      } else {
        for (int i = 16; i < 32; i++) mbar_init(b0 + 8 * i, n);
      }
      fence_bar_init();
    }
  }
  pdl_launch();
  __syncthreads();
  asm volatile("barrier.cluster.arrive.relaxed.aligned;" ::: "memory");
  if (wg == 2) {
    asm volatile("setmaxnreg.dec.sync.aligned.u32 40;");
    asm volatile("barrier.cluster.wait.aligned;" ::: "memory");
    if (lane == 0) {
      const int wpf = lds32(ptab + 228), g0 = lds32(ptab + 232), s0 = g0 * 4 / 5;
      const int nx0 = spare ? 2 * s0 : g0;
      if (warp == 0) {
        if (!spare) {
#pragma unroll 1
          for (int j = 4; j < 32; j++) {
            const uint32_t e = lds32(ptab + 4 * j);
            mbar_wait(bb + (e >> 5 & ~7), 0);
            raw_load(j, sb + place(rank, e & 15));
            if ((j & 3) == 0 && wpf && (j >> 2) + wpf < 8) w_prefetch((j >> 2) + wpf);
          }
#pragma unroll 1
          for (int s = 0; s < (MODE == 1 ? 0 : 32); s++) {
            if (s == 0 || s == 4 * s0) {
              poll_ge(&gp_.done[(s ? 5 : 4) * 32], 132);
              asm volatile("fence.proxy.async.global;" ::: "memory");
              mbar_wait(bb + 8 * (lds32(ptab + 224) & 255), 0);
            }
            const uint32_t bar = gfull + 8 * s, dst = sb + 16 * m.slot[s];
            const char* src = x1 + bin * (4 * G_ST) + m.src[s];
            mbar_wait(bb + m.dep[s], 0);
            mbar_expect(bar, G_ST);
#pragma unroll
            for (int h = 0; h < 2; h++) {
              if (s >= 16)
                asm volatile("cp.async.bulk.shared::cluster.global.mbarrier::complete_tx::bytes.L2::cache_hint [%0], [%1], %2, [%3], %4;"
                             ::"r"(dst + h * (G_ST / 2)), "l"(src + h * (s < G_S0 ? G_ST / 2 : 2 * G_ST)), "n"(G_ST / 2), "r"(bar), "l"(policy<1>()) : "memory");
              else
                asm volatile("cp.async.bulk.shared::cluster.global.mbarrier::complete_tx::bytes [%0], [%1], %2, [%3];"
                             ::"r"(dst + h * (G_ST / 2)), "l"(src + h * (s < G_S0 ? G_ST / 2 : 2 * G_ST)), "n"(G_ST / 2), "r"(bar) : "memory");
            }
          }
          if (cta == 0) asm volatile("cp.async.bulk.prefetch.L2.global [%0], 14336;" ::"l"(gp_.img) : "memory");
        }
      } else if (warp < 3) {
        const int u0 = warp == 1 ? 0 : nx0, u1 = warp == 1 ? nx0 : nx;
#pragma unroll 1
        for (int u = u0; u < u1; u++) {
          const int c = lds32(xtab + 4 * u);
          const uint32_t e = spare ? 0xC0 : lds32(ptab + 128 + 4 * u);
          const uint32_t src = sb + (c & 0x3C000), rel = e >> 1 & 24, burst = (16 << (e >> 6 & 3)) - 1;
          mbar_wait(xready + 8 * u, 0);
#pragma unroll 1
          for (int p = 0; p < 128; p += 16) {
            tma_st4<0>(&m.xs, src + p * 128, 0, (c >> 2 & 0x1C0) + (p & 63), p >> 6, c & 255);
            if (((p + 16) & burst) == 0) {
              bulk_commit();
              bulk_wait_read<0>();
            }
          }
          mbar_arrive(xfree + 8 * u);
          if (rel)
            asm volatile("mbarrier.arrive.shared::cluster.b64 _, [%0];" ::"r"(peer + (pfree - sb) + rel) : "memory");
        }
        asm volatile("cp.async.bulk.wait_group 0;" ::: "memory");
        asm volatile("red.release.gpu.global.add.s32 [%0], 1;" ::"l"(&gp_.done[(3 + warp) * 32]) : "memory");
        if (!spare && MODE != 1) {
          if (warp == 1) {
            auto w2_row = [&](int it, bool pf) {
              const CUtensorMap* mp = it & 1 ? &m.w2e : &m.w2o;
              const int c1 = (it & 1) - 1, c2 = (cta & 1) * 2, c3 = (it >> 1) * 64 + (cta >> 1);
              if (pf) {
                asm volatile("cp.async.bulk.prefetch.tensor.4d.L2.global [%0, {%1, %2, %3, %4}];" ::"l"(mp), "r"(0), "r"(c1), "r"(c2), "r"(c3) : "memory");
              } else {
                mbar_expect(inf0 + 8 * (it & 1), 4096);
                tma_ld4<1>(sb + K1_TIN + (it & 1) * 4096, mp, inf0 + 8 * (it & 1), 0, c1, c2, c3);
              }
            };
#pragma unroll 1
            for (int it = 0; it < W2_PF; it++) {
              mbar_wait(gfull + 8 * (it >> 1), 0);
              w2_row(it, true);
            }
            mbar_wait(gdone + 8, 0);
#pragma unroll 1
            for (int it = 0; it < 8; it++) {
              if (it >= 2) mbar_wait(ine0 + 8 * (it & 1), ((it >> 1) - 1) & 1);
              w2_row(it, false);
              if (W2_PF && it + W2_PF < 8) w2_row(it + W2_PF, true);
            }
          } else {
            prefetch_map(&m.w2s);
            prefetch_map(&m.y);
#pragma unroll 1
            for (int it = 0; it < 8; it++) {
              if (MODE == 0 && ((0x74 >> it) & 1)) poll_ge(&gp_.done[((0x33210000 >> (4 * it)) & 3) * 32], 128);
              mbar_wait(sf0 + 8 * (it & 1), (it >> 1) & 1);
#pragma unroll 1
              for (int p = 0; p < 128; p += W2_PC) {
                tma_st4<0>(&m.w2s, sb + K1_T + (it & 1) * 16384 + p * 128, 0, it * 64 + (p & 63), (cta & 1) * 2 + (p >> 6),
                           (cta >> 1 & 33) | (cta >> 3 & 6) | (cta << 1 & 24));
                bulk_commit();
                bulk_wait_read<0>();
              }
              mbar_arrive(se0 + 8 * (it & 1));
            }
          }
        }
      } else {
#pragma unroll 1
        for (int u = 1; u < nx; u++) {
          const int c = lds32(xtab + 4 * u);
          const uint32_t e = spare ? (u < 8 ? 97 : 40 + u) * 0x01010100u : lds32(ptab + 128 + 4 * u);
          mbar_wait(bb + (e >> 5 & 0x7F8), 0);
          mbar_expect(xfull + 8 * u, A_IN);
          mbar_wait(bb + (e >> 13 & 0x7F8), 0);
          x_half(u, c, 0);
          mbar_wait(bb + (e >> 21 & 0x7F8), 0);
          x_half(u, c, 1);
        }
#pragma unroll 1
        for (int s = 0; s < (spare || MODE ? 0 : 16); s++) {
          mbar_wait(gfull + 8 * s, 0);
          if ((s & 3) == 3) asm volatile("red.relaxed.gpu.global.add.s32 [%0], 1;" ::"l"(&gp_.done[(s >> 2) * 32]) : "memory");
        }
      }
    }
  } else {
    asm volatile("setmaxnreg.inc.sync.aligned.u32 232;");
    const int row = (lane & 7) + ((lane >> 3) & 1) * 8, hi = lane >> 4;
    asm volatile("barrier.cluster.wait.aligned;" ::: "memory");
    uint32_t fw[4];
    {
      uint32_t fa[16], za[64];
      mbar_wait(fbar, 0);
      const int f = (4 * bp + warp) & 63;
      const uint32_t lo = lds32(sF + f * 128 + ((f & 7) << 4) + (lane & 3) * 4), hh = lds32(sF + f * 128 + (((f & 7) ^ 1) << 4) + (lane & 3) * 4);
#pragma unroll
      for (int k = 0; k < 4; k++)
        ldsm4(sF + (warp * 16 + row) * 128 + (((2 * k + hi) ^ (lane & 7)) << 4), fa[4 * k], fa[4 * k + 1], fa[4 * k + 2], fa[4 * k + 3]);
      const int rho = (lane >> 3) | (lane & 4);
#pragma unroll
      for (int i = 0; i < 64; i++) za[i] = ((i & 1) == (i >> 5) && rho == ((i >> 2) & 7)) ? ((i & 2) ? hh : lo) : 0u;
      reg_fence(za);
      bar_sync(3, 256);
      const bool own = (warp >> 1) == rank;
      float d[64];
      constexpr uint64_t s2 = sched("02468:<>"), s3 = sched("13579;=?");
#pragma unroll 1
      for (uint64_t sc = spare ? (wg ? s3 : s2) : (uint32_t)lds32(ptab + 240 + 8 * wg) | (uint64_t)lds32(ptab + 244 + 8 * wg) << 32; sc; sc >>= 5) {
        const int item = (int)sc & 31;
        if (item >= 18) {
          const int q = item - 18;
          const uint32_t e = __shfl_sync(0xffffffffu, lds32(ptab + 192 + 4 * q), 0);
#pragma unroll
          for (int jj = 0; jj < 4; jj++) {
            const int j = 4 * q + jj;
            mbar_wait(rfull + 8 * j, 0);
            wg_fence();
#pragma unroll
            for (int i = 0; i < 4; i++)
              wgmma_rs_128<1, 1, 1>(d, za[16 * jj + 4 * i], za[16 * jj + 4 * i + 1], za[16 * jj + 4 * i + 2], za[16 * jj + 4 * i + 3],
                                    mk_desc(sb + place(rank, e >> (4 * jj) & 15), i * 2048, 8192, 1024, 1), jj | i);
            wg_commit();
            if (jj > 0) {
              wg_wait<1>();
              if (lane == 0) mbar_arrive(rempty + 8 * (j - 1));
            }
          }
          wg_wait<0>();
          reg_fence(d);
          if (lane == 0) mbar_arrive(rempty + 8 * (4 * q + 3));
          mbar_wait(bb + (e >> (own ? 13 : 21) & 0x7F8), 0);
          const uint32_t rb = (own ? sb : peer) + (8 * rank + q) * 8192 + (warp & 1) * 4096 + rho * 128;
          const uint32_t wbar = q < W_Q ? win : win1;
          auto put_w = [&](auto remote) {
#pragma unroll
            for (int v = 0; v < 8; v++) {
              const int j = 4 * (v >> 1), h = v & 1;
              const uint32_t a = rb + (j >> 3) * 2048 + h * 1024 + ((((j & 4) + (lane & 3)) ^ rho) << 4);
              const uint32_t p0 = pack2(d[4 * j + 2 * h], d[4 * j + 2 * h + 1]), p1 = pack2(d[4 * j + 4 + 2 * h], d[4 * j + 5 + 2 * h]);
              const uint32_t p2 = pack2(d[4 * j + 8 + 2 * h], d[4 * j + 9 + 2 * h]), p3 = pack2(d[4 * j + 12 + 2 * h], d[4 * j + 13 + 2 * h]);
              if (decltype(remote)::value)
                asm volatile("st.async.shared::cluster.mbarrier::complete_tx::bytes.v4.b32 [%0], {%1, %2, %3, %4}, [%5];"
                             ::"r"(a), "r"(p0), "r"(p1), "r"(p2), "r"(p3), "r"(peer + (wbar - sb)) : "memory");
              else
                asm volatile("st.shared.v4.b32 [%0], {%1, %2, %3, %4};" ::"r"(a), "r"(p0), "r"(p1), "r"(p2), "r"(p3) : "memory");
            }
          };
          if (own) {
            put_w(std::false_type());
            __syncwarp();
            if (lane == 0) mbar_arrive(wbar);
          } else {
            put_w(std::true_type());
          }
        } else {
          const int u = item - 1;
          const int c = lds32(xtab + 4 * u);
          const uint32_t in = sb + (c & 0x3C000);
          mbar_wait(xfull + 8 * u, 0);
          wg_fence();
#pragma unroll
          for (int k = 0; k < 4; k++)
            wgmma_rs_128<1, 1, 1>(d, fa[4 * k], fa[4 * k + 1], fa[4 * k + 2], fa[4 * k + 3], mk_desc(in, k * 2048, 6144, 1024, 1), k);
          wg_commit();
          wg_wait<0>();
          reg_fence(d);
          bar_sync(1 + wg, 128);
          const uint32_t rb = in + (warp * 16 + row) * 128, xr = (lane & 7) ^ (c & 3);
#pragma unroll
          for (int j = 0; j < 16; j += 2)
            stsm4(rb + ((j >> 2) & 1) * 8192 + ((((j >> 3) * 4 + (j & 3) + hi) ^ xr) << 4), pack2(d[4 * j], d[4 * j + 1]),
                  pack2(d[4 * j + 2], d[4 * j + 3]), pack2(d[4 * j + 4], d[4 * j + 5]), pack2(d[4 * j + 6], d[4 * j + 7]));
          fence_async();
          __syncwarp();
          if (lane == 0) mbar_arrive(xready + 8 * u);
        }
      }
#pragma unroll
      for (int i = 0; i < 4; i++) fw[i] = fa[i];
    }
    if (spare) {
      float* sg = reinterpret_cast<float*>(smem_k1 + K1_R);
      __nv_bfloat16* sw = reinterpret_cast<__nv_bfloat16*>(sg + 16 * 256);
      const int c0 = (cta - 128) * 64;
      uint4 vw[8], vg[2];
#pragma unroll
      for (int i = 0; i < 8; i++) vw[i] = __ldg(reinterpret_cast<const uint4*>(wgt + ((i * 256 + tid) >> 3) * 256 + c0 + (tid & 7) * 8));
#pragma unroll
      for (int i = 0; i < 2; i++) vg[i] = __ldg(reinterpret_cast<const uint4*>(g) + i * 256 + tid);
#pragma unroll
      for (int i = 0; i < 8; i++) reinterpret_cast<uint4*>(sw)[i * 256 + tid] = vw[i];
#pragma unroll
      for (int i = 0; i < 2; i++) {
        const uint32_t w4[4] = {vg[i].x, vg[i].y, vg[i].z, vg[i].w};
#pragma unroll
        for (int e = 0; e < 4; e++) {
          sg[(i * 256 + tid) * 8 + 2 * e] = __uint_as_float(w4[e] << 16);
          sg[(i * 256 + tid) * 8 + 2 * e + 1] = __uint_as_float(w4[e] & 0xffff0000u);
        }
      }
      bar_sync(3, 256);
      const int col = tid & 63, r0 = (tid >> 6) * 4;
      float a0 = 0.f, a1 = 0.f, a2 = 0.f, a3 = 0.f;
#pragma unroll 8
      for (int k = 0; k < 256; k++) {
        const float w = __bfloat162float(sw[k * 64 + col]);
        a0 = fmaf(sg[(r0 + 0) * 256 + k], w, a0);
        a1 = fmaf(sg[(r0 + 1) * 256 + k], w, a1);
        a2 = fmaf(sg[(r0 + 2) * 256 + k], w, a2);
        a3 = fmaf(sg[(r0 + 3) * 256 + k], w, a3);
      }
      const int cc = c0 + col;
      const int pos = (cc & ~15) + ((cc >> 1) & 3) * 4 + ((cc >> 3) & 1) * 2 + (cc & 1);
      gp_.ge[(r0 + 0) * 256 + pos] = __bfloat162float(__float2bfloat16_rn(a0));
      gp_.ge[(r0 + 1) * 256 + pos] = __bfloat162float(__float2bfloat16_rn(a1));
      gp_.ge[(r0 + 2) * 256 + pos] = __bfloat162float(__float2bfloat16_rn(a2));
      gp_.ge[(r0 + 3) * 256 + pos] = __bfloat162float(__float2bfloat16_rn(a3));
      return;
    }
    reg_fence(fw);
    mbar_wait(win, 0);
    if (MODE == 1) {
      mbar_wait(win1, 0);
      return;
    }
    float d[16];
    auto t_begin = [&](int it, int hh, int r) {
      if (r == 0) mbar_wait(inf0 + 8 * (it & 1), (it >> 1) & 1);
      wg_fence();
      wgmma_rs_32<1, 1, 1>(d, fw[0], fw[1], fw[2], fw[3], mk_desc(sb + K1_TIN + (it & 1) * 4096 + hh * 2048, r * 64, 0, 1024, 1), 0);
      wg_commit();
    };
    auto t_end = [&](int it, int hh, int r) {
      reg_fence(d);
      const int j = it & 1;
      if (r == 0) mbar_wait(it >= 2 ? se0 + 8 * j : bb + (m.p.last >> (5 + 8 * it) & 0x7F8), it >= 2 ? ((it >> 1) - 1) & 1 : 0);
      else if (lane == 0) mbar_arrive(ine0 + 8 * j);
      const uint32_t rb = sb + K1_T + j * 16384 + hh * 8192 + (warp * 16 + row) * 128;
#pragma unroll
      for (int i = 0; i < 2; i++)
        stsm4(rb + (((4 * r + 2 * i + hi) ^ (lane & 7)) << 4), pack2(d[8 * i], d[8 * i + 1]), pack2(d[8 * i + 2], d[8 * i + 3]),
              pack2(d[8 * i + 4], d[8 * i + 5]), pack2(d[8 * i + 6], d[8 * i + 7]));
      if (r == 1) {
        fence_async();
        __syncwarp();
        if (lane == 0) mbar_arrive(sf0 + 8 * j);
      }
    };
    float y0[NB1 / 2], y1[NB1 / 2];
    uint32_t wa[8], wb[8];
    uint32_t wp = sb + wg * 4096 + ((lane & 7) + hi * 8) * 128 + (((2 * warp + ((lane >> 3) & 1)) ^ (lane & 7)) << 4);
    const uint32_t neg = wg ? 0x80008000u : 0u;
    auto frag = [&](uint32_t (&w)[8], uint32_t a, uint32_t sg) {
      ldsm4t(a, w[0], w[1], w[2], w[3]);
      ldsm4t(a + 2048, w[4], w[5], w[6], w[7]);
#pragma unroll
      for (int i = 0; i < 8; i++) w[i] ^= sg;
    };
    auto stage = [&](const uint32_t (&w)[8], uint32_t x4, int acc) {
      wg_fence();
      wgmma_rs_168<1, 1, 0>(y0, w[0], w[1], w[2], w[3], mk_desc4(x4, 0, 512, 2), acc);
      wgmma_rs_168<1, 1, 0>(y1, w[0], w[1], w[2], w[3], mk_desc4(x4 + G_ST / 32, 0, 512, 2), acc);
      wgmma_rs_168<1, 1, 0>(y0, w[4], w[5], w[6], w[7], mk_desc4(x4 + 2, 0, 512, 2), 1);
      wgmma_rs_168<1, 1, 0>(y1, w[4], w[5], w[6], w[7], mk_desc4(x4 + G_ST / 32 + 2, 0, 512, 2), 1);
      wg_commit();
      wg_wait<1>();
    };
    frag(wa, wp, neg);
    int it = 0;
#pragma unroll 1
    for (int k = 0; k < G_KM; k++) {
      const bool T = (m.p.tmask >> (k + 16 * wg)) & 1;
      const uint32_t xa = ((sb & 0x3FFFF) >> 4) + m.slot[2 * k], xb = ((sb & 0x3FFFF) >> 4) + m.slot[2 * k + 1];
      if (T) t_begin(it, wg, 0);
      mbar_wait(gfull + 16 * k, 0);
      stage(wa, xa, k);
      frag(wb, wp ^ 4096, 0);
      if (k > 0 && lane == 0) mbar_arrive(gdone + 16 * k - 8);
      if (T) {
        t_end(it, wg, 0);
        t_begin(it, wg, 1);
      }
      mbar_wait(gfull + 16 * k + 8, 0);
      stage(wb, xb, 1);
      wp += 8192;
      if (k == W_Q - 1) {
        mbar_wait(win1, 0);
        fence_async();
      }
      frag(wa, wp, neg);
      if (lane == 0) mbar_arrive(gdone + 16 * k);
      if (T) t_end(it++, wg, 1);
    }
    auto tail = [&](float (&y)[NB1 / 2], auto batch, auto wgc) {
      constexpr int B = decltype(batch)::value, W = decltype(wgc)::value;
#pragma unroll
      for (int k = G_KM; k < 16; k++) {
        const int s = G_KM + k + G_TK * B;
        mbar_wait(gfull + 8 * s, 0);
        constexpr int xos[8] = {g_off(g_slot(24)), g_off(g_slot(25)), g_off(g_slot(26)), g_off(g_slot(27)),
                                g_off(g_slot(28)), g_off(g_slot(29)), g_off(g_slot(30)), g_off(g_slot(31))};
        const int xo = xos[s - 24];
        wg_fence();
#pragma unroll
        for (int h = 0; h < 4; h++) {
          const uint64_t dW = mk_desc(sb, k * 8192 + ((h >> 1) ^ W) * 4096 + (h & 1) * 2048, 0, 1024, 1);
          const uint64_t dX = mk_desc(sb, xo + (h >> 1) * (G_ST / 2) + (h & 1) * 32, 0, 512, 2);
          if (W == 1 && h < 2) wgmma_ss_168<-1, 1, 1, 0>(y, dW, dX, 1);
          else wgmma_ss_168<1, 1, 1, 0>(y, dW, dX, 1);
        }
        if (s <= 26) {
          wg_commit();
          if (W == 0 || k > G_KM) {
            wg_wait<1>();
            if (lane == 0) mbar_arrive(gdone + 8 * (s - 1));
          }
        }
      }
      wg_commit();
    };
    constexpr std::integral_constant<int, 0> c0;
    constexpr std::integral_constant<int, 1> c1;
    auto put = [&](const float (&v)[NB1 / 2], uint32_t stg, int b) {
      const int mi = lane >> 3, i = lane & 7;
      const uint32_t a0 = stg + (mi >> 1) * 1024 + i * 128 + (((2 * warp + (mi & 1)) ^ i) << 4);
      constexpr int J = 21 / G_EPI;
#pragma unroll
      for (int c = 0; c < G_EPI; c++) {
#pragma unroll
        for (int j = c * J; j + 1 < (c + 1) * J; j += 2)
          stsm4t(a0 + j * 1024, pack2(v[4 * j], v[4 * j + 1]), pack2(v[4 * j + 2], v[4 * j + 3]),
                 pack2(v[4 * j + 4], v[4 * j + 5]), pack2(v[4 * j + 6], v[4 * j + 7]));
        const int j = (c + 1) * J - 1;
        asm volatile("stmatrix.sync.aligned.m8n8.x2.trans.shared.b16 [%0], {%1, %2};" ::"r"(a0 + j * 1024),
                     "r"(pack2(v[4 * j], v[4 * j + 1])), "r"(pack2(v[4 * j + 2], v[4 * j + 3])) : "memory");
        fence_async();
        bar_sync(1 + wg, 128);
        if (t == 0) {
          tma_st4<0>(&m.y, stg + c * J * 1024, 0, b * NB1 + c * J * 8, 2 * bin + wg, dc);
          bulk_commit();
        }
      }
    };
    if (wg == 0) {
      tail(y0, c0, c0);
      bar_arrive(4, 256);
      mbar_wait(gdone + 8 * (G_S0 - 1), 0);
      wg_wait<0>();
      reg_fence(y0);
      put(y0, sb + K1_Y0, 0);
      bar_sync(7, 256);
      tail(y1, c1, c0);
      bar_arrive(8, 256);
      if (t == 0) bulk_wait_read<0>();
      wg_wait<0>();
      reg_fence(y1);
      bar_sync(1, 128);
      put(y1, sb + K1_Y0, 1);
    } else {
      wg_wait<0>();
      if (lane == 0) mbar_arrive(gdone + 8 * (G_S0 - 1));
#pragma unroll 1
      for (int h2 = 2 * it; h2 < 16; h2++) {
#pragma unroll
        for (int r = 0; r < 2; r++) {
          t_begin(h2 >> 1, h2 & 1, r);
          wg_wait<0>();
          t_end(h2 >> 1, h2 & 1, r);
        }
      }
      bar_sync(4, 256);
      tail(y0, c0, c1);
      bar_arrive(7, 256);
      mbar_wait(se0, 1);
      mbar_wait(se0 + 8, 1);
      wg_wait<0>();
      reg_fence(y0);
      put(y0, sb + K1_T, 0);
      bar_sync(8, 256);
      tail(y1, c1, c1);
      wg_wait<0>();
      reg_fence(y1);
      put(y1, sb + std::integral_constant<int, g_off(g_slot(26))>::value, 1);
    }
    if (t == 0) {
      bulk_wait_read<0>();
    }
  }
}

#define H_EPI 3
#define H_KS 11
#define C_PC 32
constexpr int H_XP = 168 * 64, H_STAGE = 8192 + 2 * H_XP, H_NST = 7, K2_STG = H_NST * H_STAGE, K2_SMEM = K2_STG + 21504 + 1024;

template <int WG>
__device__ __forceinline__ void h_loop(float (&acc)[84], uint32_t sb, uint32_t full0, uint32_t empty0, int lane) {
#pragma unroll 1
  for (int k = 0; k < 16; k++) {
    const int st = k % H_NST;
    if (WG == 1 && k == H_KS) bar_sync(5, 256);
    mbar_wait(full0 + 8 * st, (k / H_NST) & 1);
    const uint32_t base = sb + st * H_STAGE;
    wg_fence();
#pragma unroll
    for (int s = 0; s < 2; s++) {
      const uint64_t dP = mk_desc(base, s * 2048, 0, 1024, 1), dQ = mk_desc(base, 4096 + s * 2048, 0, 1024, 1);
      const uint64_t dA = mk_desc(base, 8192 + s * 32, 0, 1024, 1), dB = mk_desc(base, 8192 + 64 + s * 32, 0, 1024, 1);
      wgmma_ss_168<1, 1, 1, 0>(acc, dP, WG == 0 ? dA : dB, k | s);
      wgmma_ss_168<WG == 0 ? 1 : -1, 1, 1, 0>(acc, dQ, WG == 0 ? dB : dA, 1);
    }
    wg_commit();
    if (WG == 0 && k == 15) bar_arrive(5, 256);
    if (k <= 10) {
      wg_wait<1>();
      if (k > 0 && k - 1 + H_NST < 16 && lane < 2) mbar_arrive_cta(empty0 + 8 * ((k - 1) % H_NST), lane);
    }
  }
  wg_wait<0>();
  reg_fence(acc);
}
template <int C0, int C1> __device__ __forceinline__ void gelu_pack(uint32_t (&p)[12], const float (&h)[24]) {
#pragma unroll
  for (int i = 4 * C0; i < 4 * C1; i++) p[i] = pack2(gelu(h[2 * i]), gelu(h[2 * i + 1]));
}
struct K2Maps {
  int stage[16], item[8], wpre, pad[7];
  CUtensorMap y, xa, xs, w, y2;
};

template <int MODE>
__global__ void __cluster_dims__(2, 1, 1) __launch_bounds__(512, 1)
k2(const Ptrs gp_, const char* __restrict__ x2, const __grid_constant__ K2Maps m, const __nv_bfloat16* __restrict__ wf,
   const __nv_bfloat16* __restrict__ wo) {
  extern __shared__ __align__(1024) uint8_t smem_k1[];
  const uint32_t sb = s2u(smem_k1);
  const int tid = threadIdx.x, wg = __shfl_sync(0xffffffffu, tid >> 7, 0), t = tid & 127;
  const int warp = __shfl_sync(0xffffffffu, t >> 5, 0), lane = t & 31;
  const int cta = blockIdx.x, rank = cta & 1, dc = cta & 3, bin = cta >> 2;
  const uint32_t sGi = sb + K2_STG, sF = sGi + 6144, bb = sb + K2_STG + 21504;
  const uint32_t yfull = bb, full0 = bb + 128, empty0 = bb + 192, cfull = bb + 256, ready = bb + 320, bfree = bb + 384;
  const int b = cta & 1, j = cta >> 2;
  const int len0 = j < 20 ? 3 : 2, len1 = j >= 12 ? 3 : 2;
  const int n00 = j < 20 ? 3 * j : 2 * j + 20, n01 = j < 12 ? 2 * j : 3 * j - 12, cs0 = 3 - (cta >> 1 & 1);
  auto y_load = [&](int r, int i) {
    tma_ld5<1>(sb + (3 + 2 * r) * H_STAGE + i * 8192, &m.y, yfull + 64 * r + 8 * i, 0, 0, cs0 - 2 * r, 2 * (r ? n01 : n00) + i, b);
  };
  if (wg == 2 && warp == 0) {
    if (lane == 0) {
      prefetch_map(&m.y);
      for (int i = 0; i < 16; i++) mbar_init(yfull + 8 * i, 1);
      fence_bar_init();
    }
    __syncwarp();
    if (lane < 16) mbar_expect(yfull + 8 * lane, lane == 7 ? 6144 : 8192);
    bar_arrive(0, 512);
    asm volatile("barrier.cluster.arrive.relaxed.aligned;" ::: "memory");
    auto c_load = [&](int h) {
      asm volatile("cp.async.bulk.shared::cluster.global.mbarrier::complete_tx::bytes [%0], [%1], %2, [%3];"
                   ::"r"(sGi + 6144 * h), "l"(gp_.img + 1536 * h), "r"(6144 + 2048 * h), "r"(yfull + 56 + 64 * h) : "memory");
    };
    if (lane == 0) {
      c_load(0);
      c_load(1);
      pdl_wait();
      const int r2 = len0 == 2, i2 = r2 ? 2 : 6;
      y_load(0, 2), y_load(0, 0), y_load(0, 1), y_load(1, 0), y_load(0, 4), y_load(0, 3), y_load(r2, i2), y_load(r2, i2 - 1);
      pdl_launch();
    }
    __syncwarp();
  } else {
    if (lane == 0 && wg == 3) {
      for (int i = 0; i < 8; i++) mbar_init(full0 + 64 * warp + 8 * i, warp == 0 ? 1 : warp == 1 ? 16 : 4);
      fence_bar_init();
    }
    if (tid == 0) {
      mbar_init(bfree, 2);
      for (int i = 1; i < 5; i++) mbar_init(bfree + 8 * i, 1);
      mbar_arrive(bfree + 8);
      fence_bar_init();
    }
    if (tid == 128) {
      prefetch_map(&m.xa);
      prefetch_map(&m.xs);
      prefetch_map(&m.w);
      prefetch_map(&m.y2);
    }
    bar_sync(0, 512);
    asm volatile("barrier.cluster.arrive.relaxed.aligned;" ::: "memory");
  }
  if (wg == 2) asm volatile("barrier.cluster.wait.aligned;" ::: "memory");
  mbar_wait(yfull + 56, 0);
  auto idft = [&](float (&h)[24], uint32_t in, uint32_t bar) {
    mbar_wait(bar, 0);
    wg_fence();
#pragma unroll
    for (int k = 0; k < 4; k++) wgmma_ss_48<1, 1, 1, 0>(h, mk_desc(in, k * 2048, 0, 1024, 1), mk_desc(sGi, k * 32, 0, 1024, 1), k);
    wg_commit();
  };
  auto carry_out = [&](const uint32_t (&p)[12], uint32_t dst, uint32_t bar) {
    bar_sync(1 + wg, 128);
#pragma unroll
    for (int v = 0; v < 3; v++)
      asm volatile("st.shared.v4.b32 [%0], {%1, %2, %3, %4};" ::"r"(dst + v * 2048 + t * 16), "r"(p[4 * v]), "r"(p[4 * v + 1]), "r"(p[4 * v + 2]), "r"(p[4 * v + 3]) : "memory");
    __syncwarp();
    if (lane == 0) mbar_arrive(bar);
  };
  if (wg == 3) {
#pragma unroll 1
    for (int r = 0; r < 2; r++) {
      float h[24];
      uint32_t p[12];
      idft(h, sb + (3 + 2 * r) * H_STAGE, yfull + 64 * r);
      wg_wait<0>();
      reg_fence(h);
      gelu_pack<0, 3>(p, h);
      if (j == 0) p[0] = p[1] = p[2] = p[3] = 0;
      carry_out(p, sb + (3 + 2 * r) * H_STAGE, cfull + 32 * r);
    }
    asm volatile("barrier.cluster.wait.aligned;" ::: "memory");
    if (lane == 0) {
      if (warp == 0) {
        auto w_load = [&](int k) {
          mbar_expect(full0 + 8 * (k % H_NST), H_STAGE);
          tma_ld4<1>(sb + (k % H_NST) * H_STAGE, &m.w, full0 + 8 * (k % H_NST), 0, (k & 1) * 32, dc, (7 - (k >> 1)) * 64 + 2 * bin);
        };
        if (MODE) mbar_wait(bfree, 0);
        if (MODE == 1) return;
        const int wpre = m.wpre;
        for (int k = 0; k < wpre; k++) w_load(k);
#pragma unroll 1
        for (int k = 0; k < 16; k++) {
          const int st = k % H_NST, e = m.stage[k];
          if ((k & 7) == 0) {
            poll_ge(&gp_.done[(6 + (k >> 3)) * 32], 128);
            asm volatile("fence.proxy.async.global;" ::: "memory");
            if (k == 0) mbar_arrive(bfree + 32);
          }
          if (e) mbar_wait(bb + 8 * e, 0);
          if (k == 5) mbar_wait(bfree, 0);
          if (k >= H_NST) mbar_wait(empty0 + 8 * st, ((k / H_NST) - 1) & 1);
          const char* xs = x2 + (((7 - (k >> 2) - (k & 2) * 2) * 64 + (k & 1) * 32 + bin) * 2 + rank) * H_XP;
          asm volatile("cp.async.bulk.shared::cluster.global.mbarrier::complete_tx::bytes.multicast::cluster [%0], [%1], %2, [%3], %4;"
                       ::"r"(sb + st * H_STAGE + 8192 + rank * H_XP), "l"(xs), "n"(H_XP), "r"(full0 + 8 * st), "h"((uint16_t)3) : "memory");
          if (k >= wpre) w_load(k);
          if (k == 8) {
            if (cta == 0) asm volatile("cp.async.bulk.prefetch.L2.global [%0], 6144;" ::"l"(gp_.ga) : "memory");
            asm volatile("cp.async.bulk.prefetch.L2.global [%0], 1024;" ::"l"(wf + cta * 512) : "memory");
            asm volatile("cp.async.bulk.prefetch.L2.global [%0], 1024;" ::"l"(wo + cta * 512) : "memory");
          }
        }
      } else if (warp < 3) {
        const int r = warp - 1, n0 = b * NB2 + (r ? n01 : n00), f0 = (cs0 - 2 * r) * 64;
#pragma unroll 1
        for (int i = 0; i < (r ? len1 : len0); i++) {
          const uint32_t src = sb + (3 + 2 * r) * H_STAGE + i * 16384;
          const int e = m.item[4 * r + i], burst = (16 << (e >> 8)) - 1;
          if (r) mbar_wait(bb + 8 * (e & 255), 0);
          mbar_wait(ready + 32 * r + 8 * i, 0);
          if (!r) {
            tma_st4<0>(&m.xa, src, 0, f0, 0, n0 + i);
            bulk_commit();
            continue;
          }
#pragma unroll 1
          for (int p = 0; p < 128; p += C_PC) {
            tma_st3<0>(&m.xs, src + p * 128, 0, f0 + (p & 63) + (p >> 6) * 256, n0 + i);
            bulk_commit();
            if (((p + C_PC) & burst) == 0) bulk_wait_read<0>();
          }
        }
        asm volatile("cp.async.bulk.wait_group 0;" ::: "memory");
        if (r) {
          mbar_arrive_cta(bfree, 0);
          mbar_arrive_cta(bfree, 1);
        }
        if (!r) mbar_arrive(bfree + 16);
        asm volatile("red.release.gpu.global.add.s32 [%0], 1;" ::"l"(&gp_.done[(6 + r) * 32]) : "memory");
        if (!r) mbar_arrive(bfree + 24);
      }
    }
    return;
  }
#pragma unroll 1
  for (int it = wg; it < len0 + len1; it += 3) {
    const int r = it >= len0, i = it - r * len0;
    const bool last = i + 1 == (r ? len1 : len0);
    const uint32_t in = sb + (3 + 2 * r) * H_STAGE + i * 16384, bar = yfull + 64 * r + 16 * i;
    float h1[24], h2[24];
    uint32_t p0[12], p1[12], p2[12];
    idft(h2, in + 16384, bar + 16);
    if (it == 2 && lane == 0 && 3 + warp - len0 < len1) {
      y_load(1, 2 * (3 + warp - len0) + 2);
      y_load(1, 2 * (3 + warp - len0) + 1);
    }
    if (it > 0) bar_sync(6 + wg, 256);
    wg_wait<0>();
    reg_fence(h2);
    gelu_pack<0, 2>(p2, h2);
    idft(h1, in + 8192, bar + 8);
    if (!last) {
      gelu_pack<2, 3>(p2, h2);
      carry_out(p2, in + 16384, cfull + 32 * r + 8 * i + 8);
    }
    if (it + 1 < len0 + len1) bar_arrive(6 + (wg + 1) % 3, 256);
    mbar_wait(cfull + 32 * r + 8 * i, 0);
#pragma unroll
    for (int v = 0; v < 3; v++)
      asm volatile("ld.shared.v4.b32 {%0, %1, %2, %3}, [%4];" : "=r"(p0[4 * v]), "=r"(p0[4 * v + 1]), "=r"(p0[4 * v + 2]), "=r"(p0[4 * v + 3]) : "r"(in + v * 2048 + t * 16) : "memory");
    if (it < 3) mbar_wait(yfull + 120, 0);
    wg_wait<0>();
    reg_fence(h1);
    gelu_pack<0, 3>(p1, h1);
    if (last && j == 31) {
#pragma unroll
      for (int v = 0; v < 12; v++) p1[v] = p2[v] = 0;
    }
    uint32_t hp[32];
#pragma unroll
    for (int c = 0; c < 8; c++)
#pragma unroll
      for (int v = 0; v < 4; v++) hp[(v >> 1) * 16 + 2 * c + (v & 1)] = c < 3 ? p0[4 * c + v] : c < 6 ? p1[4 * (c - 3) + v] : p2[4 * (c - 6) + v];
    float e0[32], e1[32];
    reg_fence(hp);
    wg_fence();
#pragma unroll
    for (int k = 0; k < 4; k++) {
      const uint64_t db = mk_desc(sF, k * 32, 0, 1024, 1);
      wgmma_rs_64<1, 1, 0>(e0, hp[4 * k], hp[4 * k + 1], hp[4 * k + 2], hp[4 * k + 3], db, k);
      wgmma_rs_64<1, 1, 0>(e1, hp[16 + 4 * k], hp[16 + 4 * k + 1], hp[16 + 4 * k + 2], hp[16 + 4 * k + 3], db, k);
    }
    wg_commit();
    bar_sync(1 + wg, 128);
    wg_wait<0>();
    reg_fence(e0);
    reg_fence(e1);
    {
      const int mi = lane >> 3, rr = (lane & 7) >> 1, blk = b * NB2 + (r ? n01 : n00) + i;
      const uint32_t a0 = in + (mi >> 1) * 8192 + (warp >> 1) * 4096 + rr * 128;
      const uint32_t pos = ((lane & 1) * 4 + (warp & 1) * 2 + (mi & 1)) ^ rr ^ (blk & 7);
#pragma unroll
      for (int q = 0; q < 8; q++)
        stsm4t(a0 + q * 512 + ((pos ^ (q & 1) * 4) << 4), pack2(e0[4 * q], e0[4 * q + 1]), pack2(e0[4 * q + 2], e0[4 * q + 3]),
               pack2(e1[4 * q], e1[4 * q + 1]), pack2(e1[4 * q + 2], e1[4 * q + 3]));
    }
    fence_async();
    __syncwarp();
    if (lane == 0) mbar_arrive(ready + 32 * r + 8 * i);
  }
  if (wg == 2) return;
  asm volatile("barrier.cluster.wait.aligned;" ::: "memory");
  if (MODE == 1) return;
  float acc[84];
  if (wg == 0) {
    h_loop<0>(acc, sb, full0, empty0, lane);
  } else {
    h_loop<1>(acc, sb, full0, empty0, lane);
    bar_sync(2, 128);
  }
  const uint32_t stg = sb + (wg == 0 ? H_NST : 9 % H_NST) * H_STAGE;
  const int mi = lane >> 3, i = lane & 7;
  const uint32_t a0 = stg + (mi >> 1) * 1024 + i * 128 + (((2 * warp + (mi & 1)) ^ i) << 4);
  constexpr int J = 21 / H_EPI;
#pragma unroll
  for (int c = 0; c < H_EPI; c++) {
#pragma unroll
    for (int q = c * J; q + 1 < (c + 1) * J; q += 2)
      stsm4t(a0 + q * 1024, pack2(acc[4 * q], acc[4 * q + 1]), pack2(acc[4 * q + 2], acc[4 * q + 3]),
             pack2(acc[4 * q + 4], acc[4 * q + 5]), pack2(acc[4 * q + 6], acc[4 * q + 7]));
    const int q = (c + 1) * J - 1;
    asm volatile("stmatrix.sync.aligned.m8n8.x2.trans.shared.b16 [%0], {%1, %2};" ::"r"(a0 + q * 1024),
                 "r"(pack2(acc[4 * q], acc[4 * q + 1])), "r"(pack2(acc[4 * q + 2], acc[4 * q + 3])) : "memory");
    fence_async();
    bar_sync(1 + wg, 128);
    if (t == 0) {
      tma_st4<0>(&m.y2, stg + c * J * 1024, 0, c * J * 8, 2 * bin + wg, dc);
      bulk_commit();
    }
  }
  if (t == 0) {
    bulk_wait_read<0>();
  }
}

#define E_I1 12
#define E_WAITS 0xA8
#define E_EARLY0 5
#define E_EARLY 5
constexpr int E_SMEM = 65536 + 131072 + 32768 + 1024;

__device__ __forceinline__ uint32_t joint2(uint32_t fe, uint32_t g0, uint32_t g1) {
  uint32_t s0, s1;
  asm("{\n.reg .b16 l, h;\n.reg .b32 ll, hh;\nmov.b32 {l, h}, %2;\nmov.b32 ll, {l, l};\nmov.b32 hh, {h, h};\n"
      "fma.rn.bf16x2 %0, ll, %5, %3;\nfma.rn.bf16x2 %1, hh, %5, %4;\n}"
      : "=r"(s0), "=r"(s1) : "r"(fe), "r"(g0), "r"(g1), "r"(0x3F800000u));
  return pack2(tanh_f32(__uint_as_float(s0)), tanh_f32(__uint_as_float(s1)));
}
__device__ __forceinline__ uint4 lds128(uint32_t a) {
  uint4 v;
  asm volatile("ld.shared.v4.u32 {%0, %1, %2, %3}, [%4];" : "=r"(v.x), "=r"(v.y), "=r"(v.z), "=r"(v.w) : "r"(a));
  return v;
}
__device__ __forceinline__ void joint_group(uint32_t (&ja)[8], const uint32_t* fe, const uint4& c0, const uint4& c1) {
  ja[0] = joint2(fe[0], c0.x, c0.y);
  ja[1] = joint2(fe[1], c0.x, c0.y);
  ja[2] = joint2(fe[2], c0.z, c0.w);
  ja[3] = joint2(fe[3], c0.z, c0.w);
  ja[4] = joint2(fe[4], c1.x, c1.y);
  ja[5] = joint2(fe[5], c1.x, c1.y);
  ja[6] = joint2(fe[6], c1.z, c1.w);
  ja[7] = joint2(fe[7], c1.z, c1.w);
  reg_fence(ja);
}

__global__ void __cluster_dims__(2, 1, 1) __launch_bounds__(256, 1)
kE(const __grid_constant__ CUtensorMap my, const __grid_constant__ CUtensorMap mwf, const __grid_constant__ CUtensorMap mwo,
   const __grid_constant__ CUtensorMap mout) {
  const Ptrs gp_ = {g_done, g_ge, c_img, c_ga};
  extern __shared__ uint8_t smem_raw[];
  __shared__ __align__(8) uint64_t bars[17];
  const uint32_t sb = (s2u(smem_raw) + 1023) & ~1023u;
  const int tid = threadIdx.x, wg = __shfl_sync(0xffffffffu, tid >> 7, 0), t = tid & 127, warp = t >> 5, lane = t & 31;
  const uint32_t R0 = sb, R1 = sb + 65536, R2 = sb + 65536 + 131072;
  const uint32_t barY = s2u(&bars[0]), barO = barY + 32, barF = barY + 64, barA = barY + 128;
  const int b = blockIdx.x / 63, t0 = (blockIdx.x % 63) * 64;
  const int a = t0 / 48, o = t0 % 48;
  const int qw = o + 16 * warp, sel = qw >= 48;
  uint32_t ga[16];
#pragma unroll
  for (int s = 0; s < 4; s++)
    ldg128(reinterpret_cast<const uint4*>(gp_.ga) + ((qw >> 4) - 3 * sel) * 128 + s * 32 + lane, ga[4 * s], ga[4 * s + 1], ga[4 * s + 2], ga[4 * s + 3]);
  uint4 gev0, gev1;
  asm volatile("ld.global.cg.v4.u32 {%0, %1, %2, %3}, [%4];" : "=r"(gev0.x), "=r"(gev0.y), "=r"(gev0.z), "=r"(gev0.w)
               : "l"(reinterpret_cast<const uint4*>(gp_.ge) + (b * 8 + wg * 4) * 64 + t));
  asm volatile("ld.global.cg.v4.u32 {%0, %1, %2, %3}, [%4];" : "=r"(gev1.x), "=r"(gev1.y), "=r"(gev1.z), "=r"(gev1.w)
               : "l"(reinterpret_cast<const uint4*>(gp_.ge) + (b * 8 + wg * 4) * 64 + 128 + t));
  auto f_load = [&](int q) {
    const int p = (0x37156240 >> (4 * q)) & 7;
    mbar_expect(barF + 8 * p, 16384);
    tma_ld3<0>(R1 + p * 16384, &mwf, barF + 8 * p, 0, (p >> 1) * 64, (p & 1) * 2);
  };
  if (tid == 0) {
    prefetch_map(&my);
    for (int i = 0; i < 16; i++) mbar_init(barY + 8 * i, 1);
    mbar_init(barA, 8);
    fence_bar_init();
    prefetch_map(&mwf);
    pdl_wait();
    for (int i = 0; i < 4; i++) {
      mbar_expect(barY + 8 * i, 16384);
      tma_ld5<0>(R0 + i * 16384, &my, barY + 8 * i, 0, 0, 2 * (i & 1) + (i >> 1), a, b);
    }
    for (int q = 0; q < 4; q++) f_load(q);
  }
  if (tid == 64) {
    prefetch_map(&mwo);
    prefetch_map(&mout);
  }
  uint32_t gs[32];
#pragma unroll
  for (int i = 0; i < 16; i++) {
    gs[i] = sel ? 0u : ga[i];
    gs[16 + i] = sel ? ga[i] : 0u;
  }
  __syncthreads();
  if (blockIdx.x == 125 && tid < 8) gp_.done[tid * 32] = 0;
  reg_fence(gs);
  uint32_t gp = R2 + 16384 + wg * 4096 + (lane & 3) * 16;
  uint4 g0, g1;
  uint32_t fe[64];
  {
    float d0[32], d1[32], e[64];
    mbar_wait(barY + 8 * wg, 0);
    wg_fence();
#pragma unroll
    for (int k = 0; k < 8; k++)
      wgmma_rs_64<1, 1, 1>(d0, gs[4 * k], gs[4 * k + 1], gs[4 * k + 2], gs[4 * k + 3], mk_desc(R0 + wg * 16384, k * 2048, 0, 1024, 1), k);
    wg_commit();
    if (tid == 0)
      for (int q = 4; q < 8; q++) f_load(q);
    wg_wait<0>();
    reg_fence(d0);
    uint32_t p0[16], p1[16];
    const uint32_t wfo = R1 + wg * (65536 + 16384), wfx = R1 + 65536 - wg * (65536 - 16384), fx = R2 + 16384 - wg * 16384;
    const uint32_t fo = R2 + wg * 16384 + (warp * 16 + (lane & 7) + ((lane >> 3) & 1) * 8) * 128;
    auto fe_own = [&](const uint32_t (&p)[16], int c) {
      wg_fence();
#pragma unroll
      for (int s = 0; s < 4; s++)
        wgmma_rs_128<1, 1, 1>(e, p[4 * s], p[4 * s + 1], p[4 * s + 2], p[4 * s + 3], mk_desc(wfo, c * 32768 + s * 2048, 8192, 1024, 1), c | s);
    };
    auto fe_other = [&](int c) {
      wg_fence();
#pragma unroll
      for (int s = 0; s < 4; s++)
        wgmma_ss_128<1, 1, 0, 1>(e, mk_desc(fx, c * 8192 + s * 32, 0, 1024, 1), mk_desc(wfx, c * 32768 + s * 2048, 8192, 1024, 1), 1);
    };
    auto f_store = [&](const uint32_t (&p)[16], int c) {
#pragma unroll
      for (int s = 0; s < 4; s++) stsm4(fo + c * 8192 + (((2 * s + (lane >> 4)) ^ (lane & 7)) << 4), p[4 * s], p[4 * s + 1], p[4 * s + 2], p[4 * s + 3]);
    };
#pragma unroll
    for (int i = 0; i < E_I1; i++) p0[i] = pack2(gelu(d0[2 * i]), gelu(d0[2 * i + 1]));
    mbar_wait(barY + 8 * (2 + wg), 0);
    wg_fence();
#pragma unroll
    for (int k = 0; k < 8; k++)
      wgmma_rs_64<1, 1, 1>(d1, gs[4 * k], gs[4 * k + 1], gs[4 * k + 2], gs[4 * k + 3], mk_desc(R0 + wg * 16384, 32768 + k * 2048, 0, 1024, 1), k);
    wg_commit();
#pragma unroll
    for (int i = E_I1; i < 16; i++) p0[i] = pack2(gelu(d0[2 * i]), gelu(d0[2 * i + 1]));
    reg_fence(p0);
    f_store(p0, 0);
    const uint32_t bfo = barF + 40 * wg, bfx = barF + 32 - 24 * wg;
    auto o_load = [&](int kc) {
      mbar_expect(barO + 8 * kc, 32768);
      tma_ld3<0>(kc < 2 ? R0 + kc * 32768 : R1 + (kc - 2) * 65536, &mwo, barO + 8 * kc, 0, kc * 64, 0);
    };
    wg_wait<0>();
    reg_fence(d1);
    if (wg == 1) {
      fence_async();
      bar_arrive(8, 256);
    }
#pragma unroll
    for (int i = 0; i < 16; i++) p1[i] = pack2(gelu(d1[2 * i]), gelu(d1[2 * i + 1]));
    reg_fence(p1);
    if (wg == 0) {
      mbar_wait(bfo, 0);
      fe_own(p0, 0);
      mbar_wait(bfx, 0);
      bar_sync(8, 256);
      fe_other(0);
      wg_commit();
      if (t == 0) {
        o_load(0);
        o_load(1);
      }
      f_store(p1, 1);
      mbar_wait(bfo + 16, 0);
      fe_own(p1, 1);
      fence_async();
      mbar_wait(bfx + 16, 0);
      bar_sync(7, 256);
      fe_other(1);
      wg_commit();
      bar_arrive(4, 256);
      wg_wait<1>();
      if (lane == 0) mbar_arrive(barA);
      bar_sync(1, 128);
    } else {
      f_store(p1, 1);
      fence_async();
      bar_arrive(7, 256);
      mbar_wait(bfo, 0);
      mbar_wait(bfx, 0);
      bar_sync(4, 256);
      fe_own(p0, 0);
      fe_other(0);
      wg_commit();
      mbar_wait(bfo + 16, 0);
      mbar_wait(bfx + 16, 0);
      fe_own(p1, 1);
      wg_commit();
      wg_wait<1>();
      if (lane == 0) mbar_arrive(barA);
      fe_other(1);
      wg_commit();
      mbar_wait(barA, 0);
      if (t == 0) {
        o_load(2);
        o_load(3);
      }
    }
    asm volatile("st.shared.v4.u32 [%0], {%1, %2, %3, %4};" ::"r"(R2 + 16384 + wg * 4096 + ((t * 16) ^ (wg * 512))), "r"(gev0.x), "r"(gev0.y), "r"(gev0.z), "r"(gev0.w) : "memory");
    asm volatile("st.shared.v4.u32 [%0], {%1, %2, %3, %4};" ::"r"(R2 + 16384 + wg * 4096 + 2048 + ((t * 16) ^ (wg * 512))), "r"(gev1.x), "r"(gev1.y), "r"(gev1.z), "r"(gev1.w) : "memory");
    bar_sync(1 + wg, 128);
    g0 = lds128(gp);
    g1 = lds128(gp + 64);
    wg_wait<0>();
    reg_fence(e);
#pragma unroll
    for (int i = 0; i < 32; i++) fe[i] = pack2(e[2 * i], e[2 * i + 1]);
  }
  auto publish = [&]() {
    bar_sync(1 + wg, 128);
    const int row = warp * 16 + (lane & 7) + ((lane >> 3) & 1) * 8;
    const uint32_t xb = R1 + (wg == 0 ? 3 * 32768 : 32768 + 16384) + row * 128;
#pragma unroll
    for (int s = 0; s < 8; s++) {
      const int jj = 2 * s + (lane >> 4);
      stsm4(xb + (s >> 2) * 8192 + (((jj & 7) ^ (lane & 7)) << 4), fe[4 * s], fe[4 * s + 1], fe[4 * s + 2], fe[4 * s + 3]);
    }
    bar_arrive(5 + wg, 256);
  };
  if (wg == 1) publish();
  const uint32_t stg = R1 + 32768 + wg * 65536;
  const uint32_t w0 = sb + wg * 65536, w1 = sb + 32768 + wg * 98304, w2 = sb + 65536 - wg * 65536, w3 = sb + 131072 - wg * 98304;
  float acc[128];
  uint32_t j0[8], j1[8], j2[8], j3[8];
  uint4 h0 = lds128(gp + 128), h1 = lds128(gp + 192);
  const uint32_t bo0 = barO + 16 * wg, bo2 = barO + 16 * (1 - wg);
  joint_group(j0, fe, g0, g1);
  g0 = lds128(gp + 256);
  g1 = lds128(gp + 320);
  mbar_wait(barY, 0);
  joint_group(j1, fe + 8, h0, h1);
#define E_MMA2(J, W, OFF, FIRSTK)                                                                       \
  wgmma_rs_256<1, 1, 1>(acc, J[0], J[1], J[2], J[3], mk_desc(W, OFF, 8192, 1024, 1), FIRSTK);           \
  wgmma_rs_256<1, 1, 1>(acc, J[4], J[5], J[6], J[7], mk_desc(W, (OFF) + 2048, 8192, 1024, 1), 1);
#define E_TOKEN(N) \
  if ((ui + wg == 0 ? E_EARLY0 : E_EARLY) == (N) && (ui < 3 || wg == 0)) bar_arrive(4 - wg, 256);
#define E_BLOCK(N, J, W, BAR, JN, C0, C1, L0, L1)     \
  L0 = lds128(gp + 128 * (N) + 256);                  \
  L1 = lds128(gp + 128 * (N) + 320);                  \
  E_TOKEN((N) - 1)                                    \
  if (ui == 0) mbar_wait(BAR, 0);                     \
  if (E_WAITS >> (N) & 1) wg_wait<1>();               \
  wg_fence();                                         \
  E_MMA2(J, W, ((N) & 1) * 4096, 1)                   \
  wg_commit();                                        \
  if ((N) < 7) joint_group(JN, fe + 8 * (((N) + 1) & 7), C0, C1);
#pragma unroll 1
  for (int ui = 0; ui < 4; ui++) {
    h0 = lds128(gp + 384);
    h1 = lds128(gp + 448);
    if (ui == 0) mbar_wait(bo0, 0);
    if (ui > 0 || wg == 1) bar_sync(3 + wg, 256);
    wg_fence();
    E_MMA2(j0, w0, 0, 0)
    E_MMA2(j1, w0, 4096, 1)
    wg_commit();
    joint_group(j2, fe + 16, g0, g1);
    E_BLOCK(2, j2, w1, bo0 + 8, j3, h0, h1, g0, g1)
    if (ui == 0) {
      if (wg == 0) publish();
      bar_sync(6 - wg, 256);
      const int row = warp * 16 + (lane & 7) + ((lane >> 3) & 1) * 8;
      const uint32_t xb = R1 + (wg == 1 ? 3 * 32768 : 32768 + 16384) + row * 128;
#pragma unroll
      for (int s = 0; s < 8; s++) {
        const int jj = 2 * s + (lane >> 4);
        ldsm4(xb + (s >> 2) * 8192 + (((jj & 7) ^ (lane & 7)) << 4), fe[32 + 4 * s], fe[33 + 4 * s], fe[34 + 4 * s], fe[35 + 4 * s]);
      }
    }
    E_BLOCK(3, j3, w1, bo0 + 8, j0, g0, g1, h0, h1)
    E_BLOCK(4, j0, w2, bo2, j1, h0, h1, g0, g1)
    E_BLOCK(5, j1, w2, bo2, j2, g0, g1, h0, h1)
    E_BLOCK(6, j2, w3, bo2 + 8, j3, h0, h1, g0, g1)
    E_BLOCK(7, j3, w3, bo2 + 8, j0, g0, g1, h0, h1)
    gp += 1024;
    if (ui < 3) {
      joint_group(j0, fe, g0, g1);
      g0 = lds128(gp + 256);
      g1 = lds128(gp + 320);
      if (ui == 0) mbar_wait(bo2 + 8, 0);
      joint_group(j1, fe + 8, h0, h1);
    }
    if (t == 0) bulk_wait_read<0>();
    bar_sync(1 + wg, 128);
    wg_wait<0>();
    reg_fence(acc);
    const uint32_t rb = stg + (warp * 16 + (lane & 7) + ((lane >> 3) & 1) * 8) * 128;
#pragma unroll
    for (int h = 0; h < 2; h++) {
#pragma unroll
      for (int j = 16 * h; j < 16 * h + 16; j += 2) {
        const int jj = j + (lane >> 4);
        stsm4(rb + (j >> 3) * 8192 + (((jj & 7) ^ (lane & 7)) << 4), pack2(acc[4 * j], acc[4 * j + 1]), pack2(acc[4 * j + 2], acc[4 * j + 3]),
              pack2(acc[4 * j + 4], acc[4 * j + 5]), pack2(acc[4 * j + 6], acc[4 * j + 7]));
      }
      fence_async();
      bar_sync(1 + wg, 128);
      if (t == 0) {
        tma_st5<1>(&mout, stg + h * 16384, 0, t0, 2 * h, wg * 4 + ui, b);
        bulk_commit();
      }
    }
  }
  if (t == 0) bulk_wait_read<0>();
}

typedef CUresult (*EncodeFn)(CUtensorMap*, CUtensorMapDataType, cuuint32_t, void*, const cuuint64_t*, const cuuint64_t*,
                             const cuuint32_t*, const cuuint32_t*, CUtensorMapInterleave, CUtensorMapSwizzle,
                             CUtensorMapL2promotion, CUtensorMapFloatOOBfill);

CUtensorMap make_map(EncodeFn fn, const void* base, int rank, const uint64_t* dims, const uint64_t* strides, const uint32_t* box,
                     CUtensorMapSwizzle swz) {
  CUtensorMap m;
  cuuint64_t gd[5], gs[4];
  cuuint32_t bx[5], es[5];
  for (int i = 0; i < rank; i++) { gd[i] = dims[i]; bx[i] = box[i]; es[i] = 1; }
  for (int i = 0; i + 1 < rank; i++) gs[i] = strides[i];
  fn(&m, CU_TENSOR_MAP_DATA_TYPE_BFLOAT16, rank, const_cast<void*>(base), gd, gs, bx, es, CU_TENSOR_MAP_INTERLEAVE_NONE, swz,
     CU_TENSOR_MAP_L2_PROMOTION_NONE, CU_TENSOR_MAP_FLOAT_OOB_FILL_NONE);
  return m;
}

template <typename... KArgs, typename... Args>
void launch(void (*k)(KArgs...), int grid, int block, int smem, bool pdl, Args... args) {
  cudaLaunchConfig_t c = {};
  c.gridDim = dim3(grid);
  c.blockDim = dim3(block);
  c.dynamicSmemBytes = smem;
  c.stream = cudaStreamPerThread;
  cudaLaunchAttribute at[1];
  at[0].id = cudaLaunchAttributeProgrammaticStreamSerialization;
  at[0].val.programmaticStreamSerializationAllowed = 1;
  c.attrs = at;
  c.numAttrs = pdl ? 1 : 0;
  cudaLaunchKernelEx(&c, k, args...);
}

}

static const uint32_t h_plan[67 + 25] = {
    0x6108, 0x6109, 0x610a, 0x610b, 0x6101, 0x8008, 0x8109, 0x820a, 0x830b, 0x8401,
    0x8508, 0x6102, 0x8609, 0x870a, 0x880b, 0x6103, 0x8a08, 0x8b02, 0x8c09, 0x8d0a,
    0x8e0b, 0x8f03, 0x9008, 0x9209, 0x930a, 0x9503, 0x9608, 0x9709, 0x980a, 0x9a08,
    0x9b09, 0x9c0a, 0x61616115, 0x6161610d, 0x61616107, 0x83816166, 0x8986610c, 0x8a89314d, 0x8f8a3237, 0x938f940b,
    0x9393344c, 0x9993354d, 0x0, 0x0, 0x0, 0x0, 0x0, 0x0, 0x6161ba98, 0x6161a981,
    0x6789281b, 0x67893ba9, 0x6891a928, 0x6891983b, 0x6999983a, 0x6999a98a, 0x39389d, 0x3, 0x4, 0x1dcc17b8,
    0x8f6a0c52, 0xac1, 0x2e5a9261, 0x194a, 0x9e, 0x9f, 0x37, 0x0, 0x0, 0x0,
    0x10, 0x11, 0x13, 0x14, 0x0, 0x0, 0x0, 0x0, 0x0, 0x0,
    0x0, 0x0, 0x0, 0x431, 0x431, 0x431, 0x0, 0x133, 0x131, 0x331,
    0x0, 0x3,
};

extern "C" void kernel_launch(void* const* d_in, const int* in_sizes, int n_in, void* d_out, int out_size) {
  const __nv_bfloat16* x = (const __nv_bfloat16*)d_in[0];
  const __nv_bfloat16* w1 = (const __nv_bfloat16*)d_in[1];
  const __nv_bfloat16* w2 = (const __nv_bfloat16*)d_in[2];
  const __nv_bfloat16* g = (const __nv_bfloat16*)d_in[3];
  const __nv_bfloat16* wf = (const __nv_bfloat16*)d_in[4];
  const __nv_bfloat16* wgt = (const __nv_bfloat16*)d_in[5];
  const __nv_bfloat16* wo = (const __nv_bfloat16*)d_in[6];

  void* fp = nullptr;
  cudaDriverEntryPointQueryResult qr;
  cudaGetDriverEntryPoint("cuTensorMapEncodeTiled", &fp, cudaEnableDefault, &qr);
  EncodeFn fn = (EncodeFn)fp;
  void *W2 = d_out, *X2 = (char*)d_out + W2_BYTES, *X1 = (char*)X2 - X2_BYTES, *Y1, *Y2;
  cudaGetSymbolAddress(&Y1, g_Y);
  Y2 = Y1;
  cudaFuncSetAttribute(k1<0>, cudaFuncAttributeMaxDynamicSharedMemorySize, K1_SMEM);
  for (auto k : {k2<0>, k2<1>, k2<2>}) cudaFuncSetAttribute(k, cudaFuncAttributeMaxDynamicSharedMemorySize, K2_SMEM);
  for (auto k : {k1<1>, k1<2>}) cudaFuncSetAttribute(k, cudaFuncAttributeMaxDynamicSharedMemorySize, K1_SMEM);
  cudaFuncSetAttribute(kE, cudaFuncAttributeMaxDynamicSharedMemorySize, E_SMEM);
  int pairs = 0;
  {
    cudaLaunchConfig_t c = {};
    c.gridDim = dim3(132);
    c.blockDim = dim3(384);
    c.dynamicSmemBytes = K1_SMEM;
    cudaOccupancyMaxActiveClusters(&pairs, k1<0>, &c);
  }
  const bool fused = pairs >= MIN_PAIRS;
  if (!fused) {
    cudaGetSymbolAddress(&W2, g_far);
    Y2 = (char*)W2 + W2_BYTES;
  }
  const CUtensorMapSwizzle S128 = CU_TENSOR_MAP_SWIZZLE_128B;

  auto map_x = [&]() {
    uint64_t d[] = {64, 8000, 8, 2}, s[] = {1024, 128, 8000ull * 1024};
    uint32_t bx[] = {64, 56, 1, 1};
    return make_map(fn, x, 4, d, s, bx, S128);
  };
  auto map_w_in = [&](const __nv_bfloat16* w, int odd) {
    uint64_t d[] = {64, (uint64_t)(odd ? 15 : 16), 4, 256}, s[] = {2ull * 65536 * 2, 128, 512};
    uint32_t bx[] = {64, 16, 2, 1};
    return make_map(fn, w + (odd ? 65536 : 0), 4, d, s, bx, S128);
  };
  auto map_X_st = [&](void* p, int nb, int boxb) {
    uint64_t d[] = {64, 512, (uint64_t)(2 * nb)}, s[] = {2ull * nb * 128, 128};
    uint32_t bx[] = {64, C_PC, (uint32_t)boxb};
    return make_map(fn, p, 3, d, s, bx, S128);
  };
  auto map_X1_st = [&]() {
    uint64_t d[] = {64, 512, 2, (uint64_t)NB1}, s[] = {2ull * NB1 * 128, (uint64_t)NB1 * 128, 128};
    uint32_t bx[] = {64, 16, 1, 1};
    return make_map(fn, X1, 4, d, s, bx, S128);
  };
  auto map_W_st = [&](void* p) {
    uint64_t d[] = {64, 512, 4, 64}, s[] = {32768, 8192, 128};
    uint32_t bx[] = {64, W2_PC < 64 ? W2_PC : 64, W2_PC == 128 ? 2 : 1, 1};
    return make_map(fn, p, 4, d, s, bx, S128);
  };
  auto map_W_ld = [&](void* p, uint32_t bd, uint32_t bf) {
    uint64_t d[] = {64, 64, 4, 512}, s[] = {128, 8192, 32768};
    uint32_t bx[] = {64, 32, bd, bf};
    return make_map(fn, p, 4, d, s, bx, S128);
  };
  auto map_Y_st = [&](void* p, int nb, int rows) {
    uint64_t d[] = {64, (uint64_t)(2 * nb), 64, 4}, s[] = {32768, 128, 8192};
    uint32_t bx[] = {64, (uint32_t)rows, 1, 1};
    return make_map(fn, p, 4, d, s, bx, S128);
  };
  auto map_Y_ld = [&](void* p, int nb, int boxc, int boxb) {
    uint64_t d[] = {64, 64, 4, (uint64_t)nb, 2}, s[] = {128, 8192, 32768, (uint64_t)nb * 32768};
    uint32_t bx[] = {64, 64, (uint32_t)boxc, (uint32_t)boxb, 1};
    return make_map(fn, p, 5, d, s, bx, S128);
  };
  auto map_wsq = [&](const __nv_bfloat16* w, uint32_t bn) {
    uint64_t d[] = {64, 256, 4}, s[] = {512, 128};
    uint32_t bx[] = {64, 64, bn};
    return make_map(fn, w, 3, d, s, bx, S128);
  };
  auto map_out = [&]() {
    uint64_t d[] = {64, 4000, 4, 8, 2}, s[] = {4096, 128, 512, 4000ull * 4096};
    uint32_t bx[] = {64, 64, 2, 1, 1};
    return make_map(fn, d_out, 5, d, s, bx, S128);
  };

  auto map_w_raw = [&](const __nv_bfloat16* w, int odd) {
    uint64_t d[] = {256, (uint64_t)(odd ? 15 : 16), 16, 16}, s[] = {2ull * 65536 * 2, 512, 8192};
    uint32_t bx[] = {64, 16, 4, 2};
    return make_map(fn, w + (odd ? 65536 : 0), 4, d, s, bx, S128);
  };
  Ptrs gp;
  cudaGetSymbolAddress((void**)&gp.done, g_done);
  cudaGetSymbolAddress((void**)&gp.ge, g_ge);
  cudaGetSymbolAddress((void**)&gp.img, c_img);
  cudaGetSymbolAddress((void**)&gp.ga, c_ga);
  K1Maps g1;
  memcpy(&g1.p, h_plan, sizeof(Plan));
  g1.x = map_x();
  g1.we = map_w_raw(w1, 0);
  g1.wo = map_w_raw(w1, 1);
  g1.xs = map_X1_st();
  g1.y = map_Y_st(Y1, NB1, NB1 / G_EPI);
  g1.w2e = map_w_in(w2, 0);
  g1.w2o = map_w_in(w2, 1);
  g1.w2s = map_W_st(W2);
  for (int s = 0; s < 32; s++) {
    const int k = s < G_S0 ? s >> 1 : G_KM + (s - G_S0) % G_TK;
    g1.slot[s] = g_off(g_slot(s)) / 16;
    g1.src[s] = ((k >> 1) * 256 + (k & 1) * 2 + (s < G_S0 ? (s & 1) * 4 : s >= G_S0 + G_TK)) * (G_ST / 2);
    g1.dep[s] = s < 3 ? 8 * h_plan[64 + s] : 1536 + 8 * (s - g_depth(s));
  }
  if (!fused) launch(k1<1>, 132, 384, K1_SMEM, false, gp, (const char*)X1, (const char*)w1, g1, g, wgt);
  launch(fused ? k1<0> : k1<2>, 132, 384, K1_SMEM, false, gp, (const char*)X1, (const char*)w1, g1, g, wgt);
  K2Maps g2;
  memcpy(&g2, h_plan + 67, 100);
  g2.y = map_Y_ld(Y1, NB1, 1, 1);
  g2.xs = map_X_st(X2, NB2, 1);
  {
    uint64_t d[] = {64, 256, 2, 2 * NB2}, s[] = {2ull * NB2 * 128, 512ull * NB2 * 128, 128};
    uint32_t bx[] = {64, 64, 2, 1};
    g2.xa = make_map(fn, X2, 4, d, s, bx, S128);
  }
  g2.w = map_W_ld(W2, 1, 2);
  g2.y2 = map_Y_st(Y2, NB2, 168 / H_EPI);
  if (!fused) launch(k2<1>, 128, 512, K2_SMEM, false, gp, (const char*)X2, g2, wf, wo);
  launch(fused ? k2<0> : k2<2>, 128, 512, K2_SMEM, fused, gp, (const char*)X2, g2, wf, wo);
  launch(kE, 126, 256, E_SMEM, fused, map_Y_ld(Y2, NB2, 1, 2), map_wsq(wf, 2), map_wsq(wo, 4), map_out());
}
```
